```python
import torch

def _softmax(x, axis=-1):
    return torch.softmax(x, dim=axis)
def _gelu(x):
    return torch.nn.functional.gelu(x, approximate="tanh")
def _silu(x):
    return torch.nn.functional.silu(x)
def _sigmoid(x):
    return torch.sigmoid(x)
def _layernorm(x, axis=-1, eps=1e-5):
    m = x.mean(dim=axis, keepdim=True)
    v = x.var(dim=axis, keepdim=True, unbiased=False)
    return (x - m) / torch.sqrt(v + eps)
def _scatter_add(tgt, idx, src, axis=0):
    return tgt.clone().index_add_(axis, idx, src)
def _segment_sum(src, seg, n):
    out = torch.zeros((n,) + src.shape[1:], dtype=src.dtype)
    return out.index_add_(0, seg, src)
def _pad(x, pw):
    flat = tuple(v for pair in reversed(pw) for v in pair)
    return torch.nn.functional.pad(x, flat)

kernel_name = 'gated_mix__linear_kernel_hedgehog__grouped_kv_mqa__prompt'

def setup_inputs():

    _w = (lambda a: (lambda t: t.to(torch.bfloat16) if t.is_floating_point() else t)(torch.as_tensor(a)))
    def _A_setup():
        B, S, D, H = 1, 2048, 448, 16
        Dh = D // H
        return {
            "x": _w((lambda *s: torch.randn(*s, dtype=torch.bfloat16) * 0.05)(B, S, D)),
            "wqkv": _w((lambda *s: torch.randn(*s, dtype=torch.bfloat16) * 1.6)(D, 3 * D)),
            "w_phi": _w((lambda *s: torch.randn(*s, dtype=torch.bfloat16) * 1.6)(H, Dh, Dh) * (Dh ** -0.5)),
            "wo": _w((lambda *s: torch.randn(*s, dtype=torch.bfloat16) * 0.05)(D, D)),
        }
    _A_in = _A_setup()

    def _B_setup():
        B, S, D, H = 1, 2048, 448, 16
        Dh = D // H
        return {
            "x": _w((lambda *s: torch.randn(*s, dtype=torch.bfloat16) * 0.05)(B, S, D)),
            "wq": _w((lambda *s: torch.randn(*s, dtype=torch.bfloat16) * 1.6)(D, H * Dh)),
            "wk": _w((lambda *s: torch.randn(*s, dtype=torch.bfloat16) * 1.6)(D, Dh)),
            "wv": _w((lambda *s: torch.randn(*s, dtype=torch.bfloat16) * 0.05)(D, Dh)),
            "wo": _w((lambda *s: torch.randn(*s, dtype=torch.bfloat16) * 0.05)(H * Dh, D)),
        }
    _B_in = _B_setup()

    return {
        "A_x": _A_in["x"],
        "A_wqkv": _A_in["wqkv"],
        "A_w_phi": _A_in["w_phi"],
        "A_wo": _A_in["wo"],
        "B_x": _B_in["x"],
        "B_wq": _B_in["wq"],
        "B_wk": _B_in["wk"],
        "B_wv": _B_in["wv"],
        "B_wo": _B_in["wo"],
        "gate_w": _w((lambda *s: torch.randn(*s, dtype=torch.bfloat16) * 0.05)(448) * 16.0),
    }

def reference(A_x, A_wqkv, A_w_phi, A_wo, B_x, B_wq, B_wk, B_wv, B_wo, gate_w):
    def _A_ref(x, wqkv, w_phi, wo):
        B, S, D = x.shape
        H = 16; Dh = D // H
        qkv = (lambda x, *d: x.permute(*d))((x @ wqkv).reshape(B, S, 3, H, Dh), 2, 0, 3, 1, 4)
        q, k, v = qkv[0], qkv[1], qkv[2]
        pq = torch.einsum("bhsd,hdf->bhsf", q, w_phi)
        pk = torch.einsum("bhsd,hdf->bhsf", k, w_phi)
        phi_q = torch.concatenate([_softmax(pq, axis=-1), _softmax(-pq, axis=-1)], axis=-1)
        phi_k = torch.concatenate([_softmax(pk, axis=-1), _softmax(-pk, axis=-1)], axis=-1)
        kv = torch.einsum("bhsf,bhsd->bhfd", phi_k, v)
        z  = torch.einsum("bhsf->bhf", phi_k)
        num = torch.einsum("bhqf,bhfd->bhqd", phi_q, kv)
        den = torch.einsum("bhqf,bhf->bhq", phi_q, z)[..., None] + 1e-6
        o = num / den
        return (lambda x, *d: x.permute(*d))(o, 0, 2, 1, 3).reshape(B, S, D) @ wo

    def _B_ref(x, wq, wk, wv, wo):
        B, S, D = x.shape
        H = 16
        Dh = D // H
        q = (lambda x, *d: x.permute(*d))((x @ wq).reshape(B, S, H, Dh), 0, 2, 1, 3)
        k = x @ wk
        v = x @ wv
        scores = torch.einsum("bhqd,bkd->bhqk", q, k) * (Dh ** -0.5)
        p = _softmax(scores, axis=-1)
        o = torch.einsum("bhqk,bkd->bhqd", p, v)
        return (lambda x, *d: x.permute(*d))(o, 0, 2, 1, 3).reshape(B, S, H * Dh) @ wo

    x = A_x
    g = _sigmoid((x * gate_w).sum(-1, keepdims=True))
    a = _A_ref(x, A_wqkv, A_w_phi, A_wo)
    b = _B_ref(x, B_wq, B_wk, B_wv, B_wo)
    return g * a + (1 - g) * b
```

```cpp
#include <cuda_runtime.h>
#include <cuda_bf16.h>
#include <cuda.h>
#include <stdint.h>

namespace {

constexpr int S_LEN = 2048, DM = 448, DH = 28;
constexpr int NCTA = 128;
constexpr int NTHREADS = 640;
constexpr int RING = 12;
constexpr uint32_t POLY_PAT = 0x57;

constexpr int OFF_X = 0;
constexpr int OFF_PHIK = 0;
constexpr int OFF_VA = 32768;
constexpr int OFF_WOA = 0;
constexpr int OFF_PHIQ = 57344;
constexpr int OFF_KVR = 90112;
constexpr int OFF_QP = 98304;
constexpr int OFF_WOB = 57344;
constexpr int OFF_RING = 114688;
constexpr int OFF_WBD = 212992;
constexpr int OFF_SLC = 221184;
constexpr int OFF_QSQ = 228352;
constexpr int OFF_RED = 229376;
constexpr int OFF_BAR = 229632;
constexpr int SMEM_BYTES = 230400 + 1024;

constexpr int B_FULL = 0, B_EMPTY = RING, B_X = 2 * RING, B_WOA = B_X + 7, B_WOB = B_WOA + 1, B_KVR = B_WOA + 2,
              B_X0FREE = B_WOA + 3, B_X1FREE = B_WOA + 4, B_B1 = B_WOA + 5, B_SLOW = B_WOA + 6;

constexpr int C_KV = 0, C_PART = 1, C_RED = 2, C_DONE = 3, C_OA = 4, C_OB = 20, C_N = 36;

__device__ __align__(1024) uint8_t g_kv_img[32 * 8192];
__device__ float g_ksq[512];
__device__ float g_vmx[512];
__device__ float g_gate[S_LEN];
__device__ __align__(16) float g_kvpart[16 * 16 * 64 * 32];
__device__ __align__(1024) uint8_t g_kvr_img[16 * 4096];
__device__ __align__(1024) uint8_t g_o_img[2 * 16 * 14 * 8192];
__device__ unsigned g_cnt[C_N * 32];

__device__ __forceinline__ uint32_t smem_u32(const void* p) { return (uint32_t)__cvta_generic_to_shared(p); }
__device__ __forceinline__ void mbar_init(uint32_t a, int cnt) {
  asm volatile("mbarrier.init.shared::cta.b64 [%0], %1;" ::"r"(a), "r"(cnt) : "memory");
}
__device__ __forceinline__ void mbar_expect_tx(uint32_t a, uint32_t bytes) {
  asm volatile("mbarrier.arrive.expect_tx.shared::cta.b64 _, [%0], %1;" ::"r"(a), "r"(bytes) : "memory");
}
__device__ __forceinline__ void mbar_arrive(uint32_t a, uint32_t cnt) {
  asm volatile("mbarrier.arrive.shared::cta.b64 _, [%0], %1;" ::"r"(a), "r"(cnt) : "memory");
}
__device__ __forceinline__ bool mbar_try(uint32_t a, uint32_t parity) {
  uint32_t ok;
  asm volatile("{\n.reg .pred p;\nmbarrier.try_wait.parity.shared::cta.b64 p, [%1], %2;\nselp.u32 %0, 1, 0, p;\n}"
               : "=r"(ok) : "r"(a), "r"(parity) : "memory");
  return ok != 0;
}
__device__ __forceinline__ void mbar_wait(uint32_t a, uint32_t parity) {
  if (mbar_try(a, parity)) return;
  uint32_t n = 0;
  while (!mbar_try(a, parity)) {
    if (++n > (1u << 24)) break;
  }
}
__device__ __forceinline__ void tma_2d(uint32_t dst, const CUtensorMap* tm, int c0, int c1, uint32_t bar) {
  asm volatile("cp.async.bulk.tensor.2d.shared::cluster.global.mbarrier::complete_tx::bytes [%0], [%1, {%3, %4}], [%2];"
               ::"r"(dst), "l"(tm), "r"(bar), "r"(c0), "r"(c1) : "memory");
}
__device__ __forceinline__ void bulk_g2s(uint32_t dst, const void* src, uint32_t bytes, uint32_t bar) {
  asm volatile("cp.async.bulk.shared::cluster.global.mbarrier::complete_tx::bytes [%0], [%1], %2, [%3];"
               ::"r"(dst), "l"(src), "r"(bytes), "r"(bar) : "memory");
}
__device__ __forceinline__ void fence_async_smem() { asm volatile("fence.proxy.async.shared::cta;" ::: "memory"); }
__device__ __forceinline__ void fence_async_all() { asm volatile("fence.proxy.async;" ::: "memory"); }
__device__ __forceinline__ void bar_sync(int id, int n) { asm volatile("bar.sync %0, %1;" ::"r"(id), "r"(n) : "memory"); }
__device__ __forceinline__ bool bar_or(int id, int n, bool v) {
  uint32_t r;
  asm volatile("{\n.reg .pred p, q;\nsetp.ne.u32 p, %3, 0;\nbar.red.or.pred q, %1, %2, p;\nselp.u32 %0, 1, 0, q;\n}"
               : "=r"(r) : "r"(id), "r"(n), "r"((uint32_t)v) : "memory");
  return r != 0;
}
__device__ __forceinline__ void cnt_arrive(int idx) {
  asm volatile("red.release.gpu.global.add.u32 [%0], 1;" ::"l"(&g_cnt[idx * 32]) : "memory");
}
__device__ __forceinline__ void cnt_wait(int idx, unsigned target) {
  unsigned v, n = 0;
  while (true) {
    asm volatile("ld.acquire.gpu.global.u32 %0, [%1];" : "=r"(v) : "l"(&g_cnt[idx * 32]) : "memory");
    if (v >= target) break;
    if (++n > (1u << 22)) break;
  }
}
__device__ __forceinline__ void wg_fence() { asm volatile("wgmma.fence.sync.aligned;" ::: "memory"); }
__device__ __forceinline__ void wg_commit() { asm volatile("wgmma.commit_group.sync.aligned;" ::: "memory"); }
template <int N> __device__ __forceinline__ void wg_wait() { asm volatile("wgmma.wait_group.sync.aligned %0;" ::"n"(N) : "memory"); }
template <int N> __device__ __forceinline__ void fence_regs(float (&d)[N]) {
#pragma unroll
  for (int i = 0; i < N; i++) asm volatile("" : "+f"(d[i])::"memory");
}
__device__ __forceinline__ uint64_t make_desc(uint32_t saddr, uint32_t lbo, uint32_t sbo, uint32_t swz) {
  return (uint64_t)((saddr & 0x3FFFF) >> 4) | ((uint64_t)(lbo >> 4) << 16) | ((uint64_t)(sbo >> 4) << 32) | ((uint64_t)swz << 62);
}
__device__ __forceinline__ float ex2f(float x) { float y; asm("ex2.approx.ftz.f32 %0, %1;" : "=f"(y) : "f"(x)); return y; }
__device__ __forceinline__ float rcpf(float x) { float y; asm("rcp.approx.ftz.f32 %0, %1;" : "=f"(y) : "f"(x)); return y; }
__device__ __forceinline__ uint32_t pack_bf16(float lo, float hi) {
  uint32_t r; asm("cvt.rn.bf16x2.f32 %0, %1, %2;" : "=r"(r) : "f"(hi), "f"(lo)); return r;
}
__device__ __forceinline__ uint32_t lop_and_or(uint32_t a, uint32_t m, uint32_t c) {
  uint32_t r; asm("lop3.b32 %0, %1, %2, %3, 0xEA;" : "=r"(r) : "r"(a), "r"(m), "r"(c)); return r;
}
__device__ __forceinline__ void sts32(uint32_t a, uint32_t v) { asm volatile("st.shared.b32 [%0], %1;" ::"r"(a), "r"(v) : "memory"); }
__device__ __forceinline__ void sts64(uint32_t a, uint32_t v0, uint32_t v1) { asm volatile("st.shared.v2.b32 [%0], {%1, %2};" ::"r"(a), "r"(v0), "r"(v1) : "memory"); }
__device__ __forceinline__ void sts128(uint32_t a, uint4 v) {
  asm volatile("st.shared.v4.b32 [%0], {%1, %2, %3, %4};" ::"r"(a), "r"(v.x), "r"(v.y), "r"(v.z), "r"(v.w) : "memory");
}
__device__ __forceinline__ float ldcg_f(const float* p) { float v; asm volatile("ld.global.cg.f32 %0, [%1];" : "=f"(v) : "l"(p) : "memory"); return v; }
__device__ __forceinline__ float4 ldcg_f4(const float* p) {
  float4 v; asm volatile("ld.global.cg.v4.f32 {%0, %1, %2, %3}, [%4];" : "=f"(v.x), "=f"(v.y), "=f"(v.z), "=f"(v.w) : "l"(p) : "memory"); return v;
}
__device__ __forceinline__ float quad_sum(float v) { v += __shfl_xor_sync(~0u, v, 1); v += __shfl_xor_sync(~0u, v, 2); return v; }
__device__ __forceinline__ float quad_max(float v) { v = fmaxf(v, __shfl_xor_sync(~0u, v, 1)); v = fmaxf(v, __shfl_xor_sync(~0u, v, 2)); return v; }
__device__ __forceinline__ float quad_min(float v) { v = fminf(v, __shfl_xor_sync(~0u, v, 1)); v = fminf(v, __shfl_xor_sync(~0u, v, 2)); return v; }

template <int SD> __device__ __forceinline__ void wgmma_ss_n56_ta0_tb1(float (&d)[28], uint64_t da, uint64_t db) {
  asm volatile("wgmma.mma_async.sync.aligned.m64n56k16.f32.bf16.bf16 {%0, %1, %2, %3, %4, %5, %6, %7, %8, %9, %10, %11, %12, %13, %14, %15, %16, %17, %18, %19, %20, %21, %22, %23, %24, %25, %26, %27}, %28, %29, %30, 1, 1, 0, 1;\n"
    : "+f"(d[0]), "+f"(d[1]), "+f"(d[2]), "+f"(d[3]), "+f"(d[4]), "+f"(d[5]), "+f"(d[6]), "+f"(d[7]), "+f"(d[8]), "+f"(d[9]), "+f"(d[10]), "+f"(d[11]), "+f"(d[12]), "+f"(d[13]), "+f"(d[14]), "+f"(d[15]), "+f"(d[16]), "+f"(d[17]), "+f"(d[18]), "+f"(d[19]), "+f"(d[20]), "+f"(d[21]), "+f"(d[22]), "+f"(d[23]), "+f"(d[24]), "+f"(d[25]), "+f"(d[26]), "+f"(d[27])
    : "l"(da), "l"(db), "n"(SD));
}
template <int SD> __device__ __forceinline__ void wgmma_ss_n8_ta0_tb1(float (&d)[4], uint64_t da, uint64_t db) {
  asm volatile("wgmma.mma_async.sync.aligned.m64n8k16.f32.bf16.bf16 {%0, %1, %2, %3}, %4, %5, %6, 1, 1, 0, 1;\n"
    : "+f"(d[0]), "+f"(d[1]), "+f"(d[2]), "+f"(d[3])
    : "l"(da), "l"(db), "n"(SD));
}
template <int SD> __device__ __forceinline__ void wgmma_rs_n64_tb1(float (&d)[32], uint32_t a0, uint32_t a1, uint32_t a2, uint32_t a3, uint64_t db) {
  asm volatile("wgmma.mma_async.sync.aligned.m64n64k16.f32.bf16.bf16 {%0, %1, %2, %3, %4, %5, %6, %7, %8, %9, %10, %11, %12, %13, %14, %15, %16, %17, %18, %19, %20, %21, %22, %23, %24, %25, %26, %27, %28, %29, %30, %31}, {%32, %33, %34, %35}, %36, %37, 1, 1, 1;\n"
    : "+f"(d[0]), "+f"(d[1]), "+f"(d[2]), "+f"(d[3]), "+f"(d[4]), "+f"(d[5]), "+f"(d[6]), "+f"(d[7]), "+f"(d[8]), "+f"(d[9]), "+f"(d[10]), "+f"(d[11]), "+f"(d[12]), "+f"(d[13]), "+f"(d[14]), "+f"(d[15]), "+f"(d[16]), "+f"(d[17]), "+f"(d[18]), "+f"(d[19]), "+f"(d[20]), "+f"(d[21]), "+f"(d[22]), "+f"(d[23]), "+f"(d[24]), "+f"(d[25]), "+f"(d[26]), "+f"(d[27]), "+f"(d[28]), "+f"(d[29]), "+f"(d[30]), "+f"(d[31])
    : "r"(a0), "r"(a1), "r"(a2), "r"(a3), "l"(db), "n"(SD));
}
template <int SD> __device__ __forceinline__ void wgmma_ss_n32_ta1_tb1(float (&d)[16], uint64_t da, uint64_t db) {
  asm volatile("wgmma.mma_async.sync.aligned.m64n32k16.f32.bf16.bf16 {%0, %1, %2, %3, %4, %5, %6, %7, %8, %9, %10, %11, %12, %13, %14, %15}, %16, %17, %18, 1, 1, 1, 1;\n"
    : "+f"(d[0]), "+f"(d[1]), "+f"(d[2]), "+f"(d[3]), "+f"(d[4]), "+f"(d[5]), "+f"(d[6]), "+f"(d[7]), "+f"(d[8]), "+f"(d[9]), "+f"(d[10]), "+f"(d[11]), "+f"(d[12]), "+f"(d[13]), "+f"(d[14]), "+f"(d[15])
    : "l"(da), "l"(db), "n"(SD));
}
template <int SD> __device__ __forceinline__ void wgmma_ss_n32_ta0_tb1(float (&d)[16], uint64_t da, uint64_t db) {
  asm volatile("wgmma.mma_async.sync.aligned.m64n32k16.f32.bf16.bf16 {%0, %1, %2, %3, %4, %5, %6, %7, %8, %9, %10, %11, %12, %13, %14, %15}, %16, %17, %18, 1, 1, 0, 1;\n"
    : "+f"(d[0]), "+f"(d[1]), "+f"(d[2]), "+f"(d[3]), "+f"(d[4]), "+f"(d[5]), "+f"(d[6]), "+f"(d[7]), "+f"(d[8]), "+f"(d[9]), "+f"(d[10]), "+f"(d[11]), "+f"(d[12]), "+f"(d[13]), "+f"(d[14]), "+f"(d[15])
    : "l"(da), "l"(db), "n"(SD));
}
template <int SD> __device__ __forceinline__ void wgmma_rs_n64_tb0(float (&d)[32], uint32_t a0, uint32_t a1, uint32_t a2, uint32_t a3, uint64_t db) {
  asm volatile("wgmma.mma_async.sync.aligned.m64n64k16.f32.bf16.bf16 {%0, %1, %2, %3, %4, %5, %6, %7, %8, %9, %10, %11, %12, %13, %14, %15, %16, %17, %18, %19, %20, %21, %22, %23, %24, %25, %26, %27, %28, %29, %30, %31}, {%32, %33, %34, %35}, %36, %37, 1, 1, 0;\n"
    : "+f"(d[0]), "+f"(d[1]), "+f"(d[2]), "+f"(d[3]), "+f"(d[4]), "+f"(d[5]), "+f"(d[6]), "+f"(d[7]), "+f"(d[8]), "+f"(d[9]), "+f"(d[10]), "+f"(d[11]), "+f"(d[12]), "+f"(d[13]), "+f"(d[14]), "+f"(d[15]), "+f"(d[16]), "+f"(d[17]), "+f"(d[18]), "+f"(d[19]), "+f"(d[20]), "+f"(d[21]), "+f"(d[22]), "+f"(d[23]), "+f"(d[24]), "+f"(d[25]), "+f"(d[26]), "+f"(d[27]), "+f"(d[28]), "+f"(d[29]), "+f"(d[30]), "+f"(d[31])
    : "r"(a0), "r"(a1), "r"(a2), "r"(a3), "l"(db), "n"(SD));
}
template <int SD> __device__ __forceinline__ void wgmma_rs_n32_tb1(float (&d)[16], uint32_t a0, uint32_t a1, uint32_t a2, uint32_t a3, uint64_t db) {
  asm volatile("wgmma.mma_async.sync.aligned.m64n32k16.f32.bf16.bf16 {%0, %1, %2, %3, %4, %5, %6, %7, %8, %9, %10, %11, %12, %13, %14, %15}, {%16, %17, %18, %19}, %20, %21, 1, 1, 1;\n"
    : "+f"(d[0]), "+f"(d[1]), "+f"(d[2]), "+f"(d[3]), "+f"(d[4]), "+f"(d[5]), "+f"(d[6]), "+f"(d[7]), "+f"(d[8]), "+f"(d[9]), "+f"(d[10]), "+f"(d[11]), "+f"(d[12]), "+f"(d[13]), "+f"(d[14]), "+f"(d[15])
    : "r"(a0), "r"(a1), "r"(a2), "r"(a3), "l"(db), "n"(SD));
}


__device__ __forceinline__ uint32_t sw64_off(int row, int d) { return row * 64 + ((((d >> 3) ^ (row >> 1)) & 3) << 4) + (d & 7) * 2; }

__device__ __forceinline__ uint32_t exp2_pair_fma(float t0, float t1, uint32_t c_half, uint32_t c_3) {
  uint32_t y0, y;
  asm("prmt.b32 %0, %1, %2, 0x6521;" : "=r"(y0) : "r"(__float_as_uint(t0)), "r"(__float_as_uint(t1)));
  uint32_t h = lop_and_or(y0, 0x007F007Fu, c_half);
  uint32_t e = lop_and_or(y0, 0xFF80FF80u, c_3);
  asm("fma.rn.bf16x2 %0, %1, %2, %3;" : "=r"(y) : "r"(y0), "r"(h), "r"(e));
  return y;
}

template <bool TO_SMEM>
__device__ __forceinline__ void feature_map(const float (&p)[32], uint32_t (&ph)[32], int lq, uint32_t base, int row0) {
  const float L2E = 1.4426950408889634f;
  const bool tail_ok = lq < 2;
#pragma unroll
  for (int e = 0; e < 2; e++) {
#pragma unroll
    for (int rr = 0; rr < 2; rr++) {
      float v[8];
#pragma unroll
      for (int jj = 0; jj < 4; jj++) { v[2 * jj] = p[16 * e + 4 * jj + 2 * rr]; v[2 * jj + 1] = p[16 * e + 4 * jj + 2 * rr + 1]; }
      if (!tail_ok) { v[6] = v[0]; v[7] = v[0]; }
      float mx = v[0], mn = v[0];
#pragma unroll
      for (int i = 1; i < 8; i++) { mx = fmaxf(mx, v[i]); mn = fminf(mn, v[i]); }
      mx = quad_max(mx) * L2E; mn = quad_min(mn) * L2E;
      float a[8], b[8];
#pragma unroll
      for (int i = 0; i < 8; i++) { a[i] = ex2f(fmaf(v[i], L2E, -mx)); b[i] = ex2f(fmaf(v[i], -L2E, mn)); }
      if (!tail_ok) { a[6] = a[7] = b[6] = b[7] = 0.f; }
      float sa = ((a[0] + a[1]) + (a[2] + a[3])) + ((a[4] + a[5]) + (a[6] + a[7]));
      float sb = ((b[0] + b[1]) + (b[2] + b[3])) + ((b[4] + b[5]) + (b[6] + b[7]));
      float ra = rcpf(quad_sum(sa)), rb = rcpf(quad_sum(sb));
      const int row = row0 + 8 * rr;
      const uint32_t rbase = base + e * 16384 + row * 128 + lq * 4;
#pragma unroll
      for (int jj = 0; jj < 4; jj++) {
        uint32_t pa = pack_bf16(a[2 * jj] * ra, a[2 * jj + 1] * ra), pb = pack_bf16(b[2 * jj] * rb, b[2 * jj + 1] * rb);
        if (TO_SMEM) {
          sts32(rbase + ((jj ^ (row & 7)) << 4), pa);
          sts32(rbase + (((4 + jj) ^ (row & 7)) << 4), pb);
        } else {
          ph[e * 16 + jj * 2 + rr] = pa;
          ph[e * 16 + (4 + jj) * 2 + rr] = pb;
        }
      }
    }
  }
}

template <bool TO_SMEM>
__device__ __forceinline__ void phi_from_acc(const float (&acc)[28], uint32_t sb, uint32_t (&ph)[32], int lq, uint32_t base, int row0) {
  uint32_t a[16];
#pragma unroll
  for (int i = 0; i < 14; i++) a[i] = pack_bf16(acc[2 * i], acc[2 * i + 1]);
  a[14] = pack_bf16(acc[1], acc[0]);
  a[15] = pack_bf16(acc[3], acc[2]);
  float p[32];
  const uint64_t dWbd = make_desc(sb + OFF_WBD, 1024, 1024, 1);
  wg_fence();
  wgmma_rs_n64_tb1<0>(p, a[0], a[1], a[2], a[3], dWbd);
  wgmma_rs_n64_tb1<1>(p, a[4], a[5], a[6], a[7], dWbd + 128);
  wgmma_rs_n64_tb1<1>(p, a[8], a[9], a[10], a[11], dWbd + 256);
  wgmma_rs_n64_tb1<1>(p, a[12], a[13], a[14], a[15], dWbd + 384);
  wg_commit();
  wg_wait<0>();
  fence_regs(p);
  feature_map<TO_SMEM>(p, ph, lq, base, row0);
}

__device__ __forceinline__ void store_phi(uint32_t base, const uint32_t (&ph)[32], int row0, int lq) {
#pragma unroll
  for (int e = 0; e < 2; e++)
#pragma unroll
    for (int ch = 0; ch < 8; ch++)
#pragma unroll
      for (int rr = 0; rr < 2; rr++) {
        int row = row0 + 8 * rr;
        sts32(base + e * 16384 + row * 128 + ((ch ^ (row & 7)) << 4) + lq * 4, ph[e * 16 + ch * 2 + rr]);
      }
}

__device__ __forceinline__ void store_heads(uint32_t base, uint32_t head_stride, const uint32_t (&a)[14], int row0, int lq) {
#pragma unroll
  for (int j = 0; j < 7; j++) {
    int col = 8 * j + 2 * lq;
    int e = col >= DH;
    int d = col - DH * e;
#pragma unroll
    for (int rr = 0; rr < 2; rr++) sts32(base + e * head_stride + sw64_off(row0 + 8 * rr, d), a[2 * j + rr]);
  }
}

__device__ __forceinline__ void store_o(const float (&o)[16], float s0, float s1, float eps, int branch, int pt, int mh, int head,
                                        int rowl, int lane) {
  const int lq = lane & 3;
  float d0 = __shfl_sync(~0u, o[12], (lane & ~3) | 2), d1 = __shfl_sync(~0u, o[14], (lane & ~3) | 2);
  float r0 = s0 / (d0 + eps), r1 = s1 / (d1 + eps);
  uint8_t* img = g_o_img + (size_t)((branch * 16 + pt) * 14 + mh) * 8192;
#pragma unroll
  for (int j = 0; j < 4; j++) {
    int d = 8 * j + 2 * lq;
    if (d < DH) {
      int col = head * DH + d;
      int c = col >> 6, cc = col & 63;
      uint8_t* p = img + c * 16384 + rowl * 128 + (((cc >> 3) ^ (rowl & 7)) << 4) + (cc & 7) * 2;
      *(uint32_t*)p = pack_bf16(o[4 * j] * r0, o[4 * j + 1] * r0);
      *(uint32_t*)(p + 1024) = pack_bf16(o[4 * j + 2] * r1, o[4 * j + 3] * r1);
    }
  }
}

template <bool SLICE>
__device__ __forceinline__ void round0(float (&acc)[28], float (&accs)[4], uint64_t dX, uint64_t dRingN, uint64_t dSlc,
                                       uint32_t bars, int nh, int lane) {
#pragma unroll
  for (int c = 0; c < 7; c++) {
    const int slot = (c < 6) ? 2 * c + nh : nh;
    mbar_wait(bars + 8u * (B_X + c), 0);
    mbar_wait(bars + 8u * (B_FULL + slot), c < 6 ? 0 : 1);
    wg_fence();
#pragma unroll
    for (int ks = 0; ks < 4; ks++) {
      if (c == 0 && ks == 0) wgmma_ss_n56_ta0_tb1<0>(acc, dX, dRingN + slot * 512);
      else wgmma_ss_n56_ta0_tb1<1>(acc, dX + c * 1024 + ks * 2, dRingN + slot * 512 + ks * 128);
    }
    if (SLICE) {
#pragma unroll
      for (int ks = 0; ks < 4; ks++) {
        if (c == 0 && ks == 0) wgmma_ss_n8_ta0_tb1<0>(accs, dX, dSlc);
        else wgmma_ss_n8_ta0_tb1<1>(accs, dX + c * 1024 + ks * 2, dSlc + (c * 4 + ks) * 16);
      }
    }
    wg_commit();
    if (c > 0) {
      wg_wait<1>();
      if (lane == 0) mbar_arrive(bars + 8u * (B_EMPTY + 2 * (c - 1) + nh), 2);
    }
  }
  wg_wait<0>();
  fence_regs(acc);
  if (SLICE) fence_regs(accs);
  if (lane == 0) mbar_arrive(bars + 8u * (B_EMPTY + nh), 2);
}

struct Params {
  const __nv_bfloat16* w_phi;
  const __nv_bfloat16* wk;
  const __nv_bfloat16* wv;
  const __nv_bfloat16* gate_w;
  __nv_bfloat16* out;
};

__global__ void __launch_bounds__(NTHREADS, 1)
fused_kernel(const __grid_constant__ CUtensorMap tm_x, const __grid_constant__ CUtensorMap tm_wqkv,
             const __grid_constant__ CUtensorMap tm_wq, const __grid_constant__ CUtensorMap tm_woa,
             const __grid_constant__ CUtensorMap tm_wob, const Params prm) {
  extern __shared__ uint8_t smem_raw[];
  const uint32_t sb = (smem_u32(smem_raw) + 1023u) & ~1023u;
  uint8_t* sgen = smem_raw + (sb - smem_u32(smem_raw));
  const int tid = threadIdx.x, lane = tid & 31;
  const int warp = __shfl_sync(~0u, tid >> 5, 0), wg = warp >> 2;
  const int pt = blockIdx.x >> 3, hp = blockIdx.x & 7;
  const uint32_t bars = sb + OFF_BAR;
  auto BAR = [&](int i) { return bars + 8u * i; };

  if (tid == 512) {
    for (int i = 0; i < RING; i++) { mbar_init(BAR(B_FULL + i), 1); mbar_init(BAR(B_EMPTY + i), 16); }
    for (int i = 0; i < 7; i++) mbar_init(BAR(B_X + i), 1);
    mbar_init(BAR(B_WOA), 1); mbar_init(BAR(B_WOB), 1); mbar_init(BAR(B_KVR), 1);
    mbar_init(BAR(B_X0FREE), 8); mbar_init(BAR(B_X1FREE), 16); mbar_init(BAR(B_B1), 1); mbar_init(BAR(B_SLOW), 1);
    asm volatile("fence.mbarrier_init.release.cluster;" ::: "memory");
    fence_async_smem();
    for (int c = 0; c < 6; c++) {
      mbar_expect_tx(BAR(B_X + c), 16384);
      tma_2d(sb + OFF_X + c * 16384, &tm_x, c * 64, pt * 128, BAR(B_X + c));
      mbar_expect_tx(BAR(B_FULL + 2 * c), 8192);
      tma_2d(sb + OFF_RING + (2 * c) * 8192, &tm_wq, hp * 56, c * 64, BAR(B_FULL + 2 * c));
      mbar_expect_tx(BAR(B_FULL + 2 * c + 1), 8192);
      tma_2d(sb + OFF_RING + (2 * c + 1) * 8192, &tm_wqkv, DM + hp * 56, c * 64, BAR(B_FULL + 2 * c + 1));
    }
    mbar_expect_tx(BAR(B_X + 6), 16384);
    tma_2d(sb + OFF_X + 6 * 16384, &tm_x, 6 * 64, pt * 128, BAR(B_X + 6));
  }
  if (tid < 512) {
    const int k = tid >> 3, cn = tid & 7, e = cn >> 2, ek = k >= DH, d = k - DH * ek;
    uint32_t w[4] = {0, 0, 0, 0};
    if (k < 56 && ek == e) {
      const unsigned short* src = (const unsigned short*)prm.w_phi + ((2 * hp + e) * DH + d) * DH + (cn & 3) * 8;
#pragma unroll
      for (int i = 0; i < 4; i++)
        if ((cn & 3) * 8 + 2 * i < DH) w[i] = *(const uint32_t*)(src + 2 * i);
    }
    sts128(sb + OFF_WBD + k * 128 + ((cn ^ (k & 7)) << 4), make_uint4(w[0], w[1], w[2], w[3]));
    if (tid < DM) {
      const __nv_bfloat16* src = (hp < 4 ? prm.wk : prm.wv) + tid * DH + (hp & 3) * 8;
      uint2 lo = *(const uint2*)src, hi = make_uint2(0, 0);
      if ((hp & 3) != 3) hi = *(const uint2*)(src + 4);
      else if (hp == 3) hi.x = ((const unsigned short*)prm.gate_w)[tid];
      sts128(sb + OFF_SLC + tid * 16, make_uint4(lo.x, lo.y, hi.x, hi.y));
    }
    fence_async_smem();
  }
  __syncthreads();

  if (wg == 4) {
    asm volatile("setmaxnreg.dec.sync.aligned.u32 32;");
    if (warp == 16 && lane == 0) {
      int item = 12;
      auto acquire = [&](int it) -> uint32_t {
        int slot = it % RING;
        mbar_wait(BAR(B_EMPTY + slot), ((it / RING) - 1) & 1);
        mbar_expect_tx(BAR(B_FULL + slot), 8192);
        return slot;
      };
      for (; item < 28; item++) {
        uint32_t slot = acquire(item);
        int r = item / 14, c = (item % 14) >> 1, nh = item & 1;
        if (r == 0 && nh == 0) tma_2d(sb + OFF_RING + slot * 8192, &tm_wq, hp * 56, c * 64, BAR(B_FULL + slot));
        else {
          int part = (r == 0) ? 1 : (nh == 0 ? 0 : 2);
          tma_2d(sb + OFF_RING + slot * 8192, &tm_wqkv, part * DM + hp * 56, c * 64, BAR(B_FULL + slot));
        }
      }
      cnt_wait(C_KV, NCTA);
      fence_async_all();
      mbar_arrive(BAR(B_B1), 1);
      for (int j = 0; j < 32; j++, item++) {
        uint32_t slot = acquire(item);
        bulk_g2s(sb + OFF_RING + slot * 8192, g_kv_img + j * 8192, 8192, BAR(B_FULL + slot));
      }
      mbar_wait(BAR(B_SLOW), 0);
      if (*(volatile int*)(sgen + OFF_RED + 128)) {
        for (int j = 0; j < 32; j++, item++) {
          uint32_t slot = acquire(item);
          bulk_g2s(sb + OFF_RING + slot * 8192, g_kv_img + j * 8192, 8192, BAR(B_FULL + slot));
        }
      }
      for (int br = 0; br < 2; br++) {
        cnt_wait((br ? C_OB : C_OA) + pt, 8);
        fence_async_all();
        for (int j = 0; j < 14; j++, item++) {
          uint32_t slot = acquire(item);
          bulk_g2s(sb + OFF_RING + slot * 8192, g_o_img + (size_t)((br * 16 + pt) * 14 + j) * 8192, 8192, BAR(B_FULL + slot));
        }
      }
    } else if (warp == 17) {
    if (lane == 0) {
      mbar_wait(BAR(B_X0FREE), 0);
      mbar_expect_tx(BAR(B_WOA), 57344);
      for (int c = 0; c < 7; c++) tma_2d(sb + OFF_WOA + c * 8192, &tm_woa, hp * 56, c * 64, BAR(B_WOA));
      cnt_wait(C_PART, NCTA);
    }
    __syncwarp();
    {
      const int head = blockIdx.x >> 3, f = (blockIdx.x & 7) * 8 + (lane >> 2), d0 = (lane & 3) * 8;
      const float* src = g_kvpart + ((size_t)head * 64 + f) * 32 + d0;
      float4 s0 = make_float4(0, 0, 0, 0), s1 = s0;
#pragma unroll 2
      for (int t = 0; t < 16; t++) {
        float4 a = ldcg_f4(src + (size_t)t * 16 * 64 * 32), b = ldcg_f4(src + (size_t)t * 16 * 64 * 32 + 4);
        s0.x += a.x; s0.y += a.y; s0.z += a.z; s0.w += a.w; s1.x += b.x; s1.y += b.y; s1.z += b.z; s1.w += b.w;
      }
      uint4 v = make_uint4(pack_bf16(s0.x, s0.y), pack_bf16(s0.z, s0.w), pack_bf16(s1.x, s1.y), pack_bf16(s1.z, s1.w));
      *(uint4*)(g_kvr_img + head * 4096 + sw64_off(f, d0)) = v;
      fence_async_all();
    }
    __syncwarp();
    if (lane == 0) {
      cnt_arrive(C_RED);
      cnt_wait(C_RED, NCTA);
      fence_async_all();
      mbar_expect_tx(BAR(B_KVR), 8192);
      bulk_g2s(sb + OFF_KVR, g_kvr_img + hp * 8192, 8192, BAR(B_KVR));
      mbar_wait(BAR(B_X1FREE), 0);
      mbar_expect_tx(BAR(B_WOB), 57344);
      for (int c = 0; c < 7; c++) tma_2d(sb + OFF_WOB + c * 8192, &tm_wob, hp * 56, c * 64, BAR(B_WOB));
    }
    }
  } else {
    asm volatile("setmaxnreg.inc.sync.aligned.u32 112;");
    const int mh = wg & 1, nh = wg >> 1, wq = warp & 3, lq = lane & 3;
    const int rowl = wq * 16 + (lane >> 2);
    const int row0 = mh * 64 + rowl;
    const uint64_t dX = make_desc(sb + OFF_X + mh * 8192, 16, 1024, 1);
    const uint64_t dRingN = make_desc(sb + OFF_RING, 1024, 1024, 1);
    const uint64_t dSlc = make_desc(sb + OFF_SLC, 128, 128, 0);
    float acc[28], accs[4];
    uint32_t keep[32];

    if (nh == 0) round0<true>(acc, accs, dX, dRingN, dSlc, bars, 0, lane);
    else round0<false>(acc, accs, dX, dRingN, dSlc, bars, 1, lane);

    if (nh == 0) {
      const int sl = hp & 3;
      float mxv = 0.f;
#pragma unroll
      for (int rr = 0; rr < 2; rr++) {
        const int pos = pt * 128 + row0 + 8 * rr, kr = pos & 63;
        float v0 = accs[2 * rr], v1 = accs[2 * rr + 1];
        const bool real = (sl < 3) || (lq < 2);
        uint32_t outv;
        if (hp < 4) {
          const bool poly = (POLY_PAT >> (kr >> 3)) & 1;
          float sq = quad_sum(real ? v0 * v0 + v1 * v1 : 0.f);
          mxv = fmaxf(mxv, sq);
          if (real) outv = poly ? pack_bf16(2.f * v0, 2.f * v1) : pack_bf16(v0, v1);
          else if (lq == 2) {
            g_gate[pos] = 1.f / (1.f + __expf(-v0));
            outv = poly ? 0x443F4000u : 0x00003F80u;
          } else outv = poly ? 0x3AB03F4Du : 0u;
        } else {
          mxv = fmaxf(mxv, real ? fmaxf(fabsf(v0), fabsf(v1)) : 0.f);
          if (!(fabsf(v0) <= 3.0e38f) || !(fabsf(v1) <= 3.0e38f)) mxv = __int_as_float(0x7f800000);
          outv = real ? pack_bf16(v0, v1) : (lq == 2 ? 0x00003F80u : 0u);
        }
        *(uint32_t*)(g_kv_img + (pos >> 6) * 8192 + (hp < 4 ? 0 : 4096) + sw64_off(kr, sl * 8 + 2 * lq)) = outv;
      }
      if (!(mxv <= 3.0e38f)) mxv = __int_as_float(0x7f800000);
#pragma unroll
      for (int o = 16; o > 0; o >>= 1) mxv = fmaxf(mxv, __shfl_xor_sync(~0u, mxv, o));
      if (lane == 0) (hp < 4 ? g_ksq : g_vmx)[sl * 128 + pt * 8 + mh * 4 + wq] = mxv;
      fence_async_all();
      bar_sync(2, 256);
      if (tid == 0) cnt_arrive(C_KV);
      const float QS = 0.18898223650461362f * 1.4426950408889634f;
      float sq[4] = {0.f, 0.f, 0.f, 0.f};
#pragma unroll
      for (int j = 0; j < 7; j++) {
#pragma unroll
        for (int rr = 0; rr < 2; rr++) {
          float v0 = acc[4 * j + 2 * rr] * QS, v1 = acc[4 * j + 2 * rr + 1] * QS;
          keep[2 * j + rr] = pack_bf16(v0, v1);
          float s2 = v0 * v0 + v1 * v1;
          if (j < 3) sq[rr] += s2;
          else if (j > 3) sq[2 + rr] += s2;
          else { sq[rr] += (lq < 2) ? s2 : 0.f; sq[2 + rr] += (lq < 2) ? 0.f : s2; }
        }
      }
#pragma unroll
      for (int i = 0; i < 4; i++) sq[i] = quad_sum(sq[i]);
      float* qsq = (float*)(sgen + OFF_QSQ);
      if (lq == 0) {
        qsq[(mh + 0) * 64 + rowl] = sq[0]; qsq[(mh + 0) * 64 + rowl + 8] = sq[1];
        qsq[(mh + 2) * 64 + rowl] = sq[2]; qsq[(mh + 2) * 64 + rowl + 8] = sq[3];
      }
    } else {
      phi_from_acc<false>(acc, sb, keep, lq, 0, 0);
    }

#pragma unroll
    for (int c = 0; c < 7; c++) {
      const int item = 14 + 2 * c + nh;
      const int slot = (c < 5) ? item - 12 : item - 24;
      mbar_wait(BAR(B_FULL + slot), c < 5 ? 1 : 0);
      wg_fence();
#pragma unroll
      for (int ks = 0; ks < 4; ks++) {
        if (c == 0 && ks == 0) wgmma_ss_n56_ta0_tb1<0>(acc, dX, dRingN + slot * 512);
        else wgmma_ss_n56_ta0_tb1<1>(acc, dX + c * 1024 + ks * 2, dRingN + slot * 512 + ks * 128);
      }
      wg_commit();
      if (c > 0) {
        wg_wait<1>();
        const int pslot = (c - 1 < 5) ? item - 2 - 12 : item - 2 - 24;
        if (lane == 0) mbar_arrive(BAR(B_EMPTY + pslot), 2);
      }
    }
    wg_wait<0>();
    fence_regs(acc);
    if (lane == 0) mbar_arrive(BAR(B_EMPTY + 2 + nh), 2);
    bar_sync(1, 512);

    if (nh == 0) {
      uint32_t q14[14];
#pragma unroll
      for (int i = 0; i < 14; i++) q14[i] = keep[i];
      store_heads(sb + OFF_QP + mh * 4096, 8192, q14, rowl, lq);
      phi_from_acc<true>(acc, sb, keep, lq, sb + OFF_PHIQ, row0);
      fence_async_smem();
    } else {
      store_phi(sb + OFF_PHIK, keep, row0, lq);
      uint32_t va[14];
#pragma unroll
      for (int j = 0; j < 7; j++) { va[2 * j] = pack_bf16(acc[4 * j], acc[4 * j + 1]); va[2 * j + 1] = pack_bf16(acc[4 * j + 2], acc[4 * j + 3]); }
      store_heads(sb + OFF_VA, 8192, va, row0, lq);
      sts64(sb + OFF_VA + (lq & 1) * 8192 + sw64_off(row0 + 8 * (lq >> 1), 28), 0x00003F80u, 0u);
      fence_async_smem();
      bar_sync(3, 256);
      float kv[16];
      const uint64_t dA = make_desc(sb + OFF_PHIK + mh * 16384, 1024, 1024, 1);
      const uint64_t dB = make_desc(sb + OFF_VA + mh * 8192, 512, 512, 2);
      wg_fence();
      wgmma_ss_n32_ta1_tb1<0>(kv, dA, dB);
#pragma unroll
      for (int ks = 1; ks < 8; ks++) wgmma_ss_n32_ta1_tb1<1>(kv, dA + ks * 128, dB + ks * 64);
      wg_commit();
      wg_wait<0>();
      fence_regs(kv);
      if (lane == 0) mbar_arrive(BAR(B_X0FREE), 1);
      float* dst = g_kvpart + ((size_t)(pt * 16 + 2 * hp + mh) * 64 + rowl) * 32 + 2 * lq;
#pragma unroll
      for (int j = 0; j < 4; j++) {
        *(float2*)(dst + 8 * j) = make_float2(kv[4 * j], kv[4 * j + 1]);
        *(float2*)(dst + 8 * 32 + 8 * j) = make_float2(kv[4 * j + 2], kv[4 * j + 3]);
      }
      bar_sync(3, 256);
      if (tid == 256) cnt_arrive(C_PART);
    }

    mbar_wait(BAR(B_B1), 0);
    float* red = (float*)(sgen + OFF_RED);
    {
      float a = ldcg_f(g_ksq + tid), b = ldcg_f(g_vmx + tid);
#pragma unroll
      for (int o = 16; o > 0; o >>= 1) { a = fmaxf(a, __shfl_xor_sync(~0u, a, o)); b = fmaxf(b, __shfl_xor_sync(~0u, b, o)); }
      if (lane == 0) { red[warp] = a; red[16 + warp] = b; }
    }
    const float g0 = ldcg_f(g_gate + pt * 128 + row0), g1 = ldcg_f(g_gate + pt * 128 + row0 + 8);
    bar_sync(1, 512);
    float ksq = 0.f, vmx = 0.f;
#pragma unroll
    for (int s = 0; s < 4; s++) {
      ksq += fmaxf(fmaxf(red[4 * s], red[4 * s + 1]), fmaxf(red[4 * s + 2], red[4 * s + 3]));
      vmx = fmaxf(vmx, fmaxf(fmaxf(red[16 + 4 * s], red[16 + 4 * s + 1]), fmaxf(red[16 + 4 * s + 2], red[16 + 4 * s + 3])));
    }
    const float* qsq = (const float*)(sgen + OFF_QSQ);
    const float b0 = sqrtf(qsq[wg * 64 + rowl] * ksq) * 1.02f, b1 = sqrtf(qsq[wg * 64 + rowl + 8] * ksq) * 1.02f;
    const bool bad = !(b0 <= 92.f) || !(b1 <= 92.f) || !(vmx <= 1.0e12f);
    const bool slow = bar_or(1, 512, bad);
    if (tid == 0) { *(volatile int*)(sgen + OFF_RED + 128) = slow; mbar_arrive(BAR(B_SLOW), 1); }

    uint32_t q[8];
    {
      const uint32_t qa = sb + OFF_QP + wg * 4096;
      const int r = wq * 16 + (lane & 7) + ((lane >> 3) & 1) * 8;
#pragma unroll
      for (int ks = 0; ks < 2; ks++)
        asm volatile("ldmatrix.sync.aligned.m8n8.x4.shared.b16 {%0, %1, %2, %3}, [%4];"
                     : "=r"(q[4 * ks]), "=r"(q[4 * ks + 1]), "=r"(q[4 * ks + 2]), "=r"(q[4 * ks + 3])
                     : "r"(qa + sw64_off(r, ks * 16 + (lane >> 4) * 8)) : "memory");
      if (lq >= 2) {
        q[6] = slow ? 0u : (lq == 2 ? pack_bf16(64.f - b0, 1.f) : 0x3F803F80u);
        q[7] = slow ? 0u : (lq == 2 ? pack_bf16(64.f - b1, 1.f) : 0x3F803F80u);
      }
    }

    const uint64_t dK = make_desc(sb + OFF_RING, 16, 512, 2);
    const uint64_t dV = make_desc(sb + OFF_RING + 4096, 512, 512, 2);
    float o[16];
#pragma unroll
    for (int i = 0; i < 16; i++) o[i] = 0.f;
    int item = 28;

    auto a_final = [&]() {
      float num[16];
      mbar_wait(BAR(B_KVR), 0);
      const uint64_t dA = make_desc(sb + OFF_PHIQ + nh * 16384 + mh * 8192, 16, 1024, 1);
      const uint64_t dB = make_desc(sb + OFF_KVR + nh * 4096, 512, 512, 2);
      wg_fence();
      wgmma_ss_n32_ta0_tb1<0>(num, dA, dB);
#pragma unroll
      for (int ks = 1; ks < 4; ks++) wgmma_ss_n32_ta0_tb1<1>(num, dA + ks * 2, dB + ks * 64);
      wg_commit();
      wg_wait<0>();
      fence_regs(num);
      if (lane == 0) mbar_arrive(BAR(B_X1FREE), 1);
      store_o(num, g0, g1, 1e-6f, 0, pt, mh, 2 * hp + nh, rowl, lane);
      fence_async_all();
      bar_sync(1, 512);
      if (tid == 0) cnt_arrive(C_OA + pt);
    };

    if (!slow) {
      uint32_t c_half = 0x3F003F00u, c_3 = 0x00030003u;
      asm volatile("" : "+r"(c_half), "+r"(c_3));
#pragma unroll 1
      for (int it = 0; it < 8; it++) {
        if (it == 4) a_final();
        const int slot0 = item % RING;
        const uint32_t par = (item / RING) & 1;
        float s[32];
        mbar_wait(BAR(B_FULL + slot0), par);
        wg_fence();
        wgmma_rs_n64_tb0<0>(s, q[0], q[1], q[2], q[3], dK + slot0 * 512);
        wgmma_rs_n64_tb0<1>(s, q[4], q[5], q[6], q[7], dK + slot0 * 512 + 2);
        wg_commit();
#pragma unroll
        for (int u = 0; u < 4; u++) {
          wg_wait<0>();
          fence_regs(s);
          if (lane == 0 && (u > 0 || it > 0)) mbar_arrive(BAR(B_EMPTY + (u > 0 ? slot0 + u - 1 : (slot0 + RING - 1) % RING)), 1);
          uint32_t p[16];
#pragma unroll
          for (int j = 0; j < 8; j++) {
            if ((POLY_PAT >> j) & 1) {
              p[2 * j] = exp2_pair_fma(s[4 * j], s[4 * j + 1], c_half, c_3);
              p[2 * j + 1] = exp2_pair_fma(s[4 * j + 2], s[4 * j + 3], c_half, c_3);
            } else {
              p[2 * j] = pack_bf16(ex2f(s[4 * j]), ex2f(s[4 * j + 1]));
              p[2 * j + 1] = pack_bf16(ex2f(s[4 * j + 2]), ex2f(s[4 * j + 3]));
            }
          }
          if (u < 3) mbar_wait(BAR(B_FULL + slot0 + u + 1), par);
          wg_fence();
#pragma unroll
          for (int ks = 0; ks < 4; ks++)
            wgmma_rs_n32_tb1<1>(o, p[4 * ks], p[4 * ks + 1], p[4 * ks + 2], p[4 * ks + 3], dV + (slot0 + u) * 512 + ks * 64);
          if (u < 3) {
            wgmma_rs_n64_tb0<0>(s, q[0], q[1], q[2], q[3], dK + (slot0 + u + 1) * 512);
            wgmma_rs_n64_tb0<1>(s, q[4], q[5], q[6], q[7], dK + (slot0 + u + 1) * 512 + 2);
          }
          wg_commit();
        }
        item += 4;
      }
      wg_wait<0>();
      fence_regs(o);
      if (lane == 0) mbar_arrive(BAR(B_EMPTY + (item - 1) % RING), 1);
    } else {
      float m0 = -3.0e38f, m1 = -3.0e38f;
#pragma unroll 1
      for (int j64 = 0; j64 < 32; j64++, item++) {
        const int slot = item % RING;
        float s[32];
        mbar_wait(BAR(B_FULL + slot), (item / RING) & 1);
        wg_fence();
        wgmma_rs_n64_tb0<0>(s, q[0], q[1], q[2], q[3], dK + slot * 512);
        wgmma_rs_n64_tb0<1>(s, q[4], q[5], q[6], q[7], dK + slot * 512 + 2);
        wg_commit();
        wg_wait<0>();
        fence_regs(s);
#pragma unroll
        for (int j = 0; j < 8; j++) {
          const float sc = ((POLY_PAT >> j) & 1) ? 0.5f : 1.f;
          m0 = fmaxf(m0, fmaxf(s[4 * j], s[4 * j + 1]) * sc);
          m1 = fmaxf(m1, fmaxf(s[4 * j + 2], s[4 * j + 3]) * sc);
        }
        if (lane == 0) mbar_arrive(BAR(B_EMPTY + slot), 1);
      }
      m0 = quad_max(m0); m1 = quad_max(m1);
      a_final();
      float o2[16];
#pragma unroll
      for (int i = 0; i < 16; i++) o2[i] = 0.f;
#pragma unroll 1
      for (int j64 = 0; j64 < 32; j64++, item++) {
        const int slot = item % RING;
        float s[32];
        mbar_wait(BAR(B_FULL + slot), (item / RING) & 1);
        wg_fence();
        wgmma_rs_n64_tb0<0>(s, q[0], q[1], q[2], q[3], dK + slot * 512);
        wgmma_rs_n64_tb0<1>(s, q[4], q[5], q[6], q[7], dK + slot * 512 + 2);
        wg_commit();
        wg_wait<0>();
        fence_regs(s);
        uint32_t p[16];
#pragma unroll
        for (int j = 0; j < 8; j++) {
          const float sc = ((POLY_PAT >> j) & 1) ? 0.5f : 1.f;
          p[2 * j] = pack_bf16(ex2f(fmaf(s[4 * j], sc, -m0)), ex2f(fmaf(s[4 * j + 1], sc, -m0)));
          p[2 * j + 1] = pack_bf16(ex2f(fmaf(s[4 * j + 2], sc, -m1)), ex2f(fmaf(s[4 * j + 3], sc, -m1)));
        }
        wg_fence();
#pragma unroll
        for (int ks = 0; ks < 4; ks++)
          wgmma_rs_n32_tb1<1>(o2, p[4 * ks], p[4 * ks + 1], p[4 * ks + 2], p[4 * ks + 3], dV + slot * 512 + ks * 64);
        wg_commit();
        wg_wait<0>();
        fence_regs(o2);
        if (lane == 0) mbar_arrive(BAR(B_EMPTY + slot), 1);
      }
#pragma unroll
      for (int i = 0; i < 16; i++) o[i] = o2[i];
    }

    store_o(o, 1.f - g0, 1.f - g1, 0.f, 1, pt, mh, 2 * hp + nh, rowl, lane);
    fence_async_all();
    bar_sync(1, 512);
    if (tid == 0) cnt_arrive(C_OB + pt);

    if (nh == 0) {
      const uint64_t dRingK = make_desc(sb + OFF_RING, 16, 1024, 1);
      const uint64_t dWo = make_desc(sb + OFF_WOA, 1024, 1024, 1);
      int prev = -1;
#pragma unroll
      for (int bc = 0; bc < 14; bc++) {
        const int itm = item + 2 * bc + mh, slot = itm % RING;
        if (bc == 0) mbar_wait(BAR(B_WOA), 0);
        if (bc == 7) mbar_wait(BAR(B_WOB), 0);
        mbar_wait(BAR(B_FULL + slot), (itm / RING) & 1);
        wg_fence();
#pragma unroll
        for (int ks = 0; ks < 4; ks++) {
          if (bc == 0 && ks == 0) wgmma_ss_n56_ta0_tb1<0>(acc, dRingK + slot * 512, dWo);
          else wgmma_ss_n56_ta0_tb1<1>(acc, dRingK + slot * 512 + ks * 2, dWo + bc * 512 + ks * 128);
        }
        wg_commit();
        if (bc > 0) {
          wg_wait<1>();
          if (lane == 0) mbar_arrive(BAR(B_EMPTY + prev), 4);
        }
        prev = slot;
      }
      wg_wait<0>();
      fence_regs(acc);
      __nv_bfloat16* op = prm.out + (size_t)(pt * 128 + row0) * DM + hp * 56 + 2 * lq;
#pragma unroll
      for (int j = 0; j < 7; j++) {
        *(uint32_t*)(op + 8 * j) = pack_bf16(acc[4 * j], acc[4 * j + 1]);
        *(uint32_t*)(op + 8 * DM + 8 * j) = pack_bf16(acc[4 * j + 2], acc[4 * j + 3]);
      }
      if (tid == 0) {
        unsigned prevd = atomicAdd(&g_cnt[C_DONE * 32], 1u);
        if (prevd == NCTA - 1) {
          for (int i = 0; i < C_N; i++) g_cnt[i * 32] = 0;
        }
      }
    }
  }
}

typedef CUresult (*EncodeFn)(CUtensorMap*, CUtensorMapDataType, cuuint32_t, void*, const cuuint64_t*, const cuuint64_t*,
                             const cuuint32_t*, const cuuint32_t*, CUtensorMapInterleave, CUtensorMapSwizzle,
                             CUtensorMapL2promotion, CUtensorMapFloatOOBfill);

void make_map(EncodeFn enc, CUtensorMap* tm, const void* ptr, uint64_t cols, uint64_t rows, uint32_t box_rows) {
  cuuint64_t dims[2] = {cols, rows};
  cuuint64_t strides[1] = {cols * 2};
  cuuint32_t box[2] = {64, box_rows};
  cuuint32_t es[2] = {1, 1};
  enc(tm, CU_TENSOR_MAP_DATA_TYPE_BFLOAT16, 2, const_cast<void*>(ptr), dims, strides, box, es, CU_TENSOR_MAP_INTERLEAVE_NONE,
      CU_TENSOR_MAP_SWIZZLE_128B, CU_TENSOR_MAP_L2_PROMOTION_L2_128B, CU_TENSOR_MAP_FLOAT_OOB_FILL_NONE);
}

}

extern "C" void kernel_launch(void* const* d_in, const int* in_sizes, int n_in, void* d_out, int out_size) {
  (void)in_sizes; (void)n_in; (void)out_size;
  static EncodeFn enc = nullptr;
  if (!enc) {
    void* fn = nullptr;
    cudaDriverEntryPointQueryResult qr;
    cudaGetDriverEntryPoint("cuTensorMapEncodeTiled", &fn, cudaEnableDefault, &qr);
    enc = (EncodeFn)fn;
    cudaFuncSetAttribute(fused_kernel, cudaFuncAttributeMaxDynamicSharedMemorySize, SMEM_BYTES);
  }
  CUtensorMap tm_x, tm_wqkv, tm_wq, tm_woa, tm_wob;
  make_map(enc, &tm_x, d_in[0], DM, S_LEN, 128);
  make_map(enc, &tm_wqkv, d_in[1], 3 * DM, DM, 64);
  make_map(enc, &tm_wq, d_in[5], DM, DM, 64);
  make_map(enc, &tm_woa, d_in[3], DM, DM, 64);
  make_map(enc, &tm_wob, d_in[8], DM, DM, 64);
  Params prm;
  prm.w_phi = (const __nv_bfloat16*)d_in[2];
  prm.wk = (const __nv_bfloat16*)d_in[6];
  prm.wv = (const __nv_bfloat16*)d_in[7];
  prm.gate_w = (const __nv_bfloat16*)d_in[9];
  prm.out = (__nv_bfloat16*)d_out;
  fused_kernel<<<NCTA, NTHREADS, SMEM_BYTES>>>(tm_x, tm_wqkv, tm_wq, tm_woa, tm_wob, prm);
}
```

```cpp
#include <cuda_runtime.h>
#include <cuda_bf16.h>
#include <cuda.h>
#include <stdint.h>

namespace {

constexpr int S_LEN = 2048, DM = 448, DH = 28;
constexpr int NCTA = 128;
constexpr int NTHREADS = 640;
constexpr int RING = 12;
constexpr uint32_t POLY_PAT = 0x57;

constexpr int OFF_X = 0;
constexpr int OFF_PHIK = 0;
constexpr int OFF_VA = 32768;
constexpr int OFF_WOA = 0;
constexpr int OFF_PHIQ = 57344;
constexpr int OFF_KVR = 90112;
constexpr int OFF_QP = 98304;
constexpr int OFF_WOB = 57344;
constexpr int OFF_RING = 114688;
constexpr int OFF_WBD = 212992;
constexpr int OFF_SLC = 221184;
constexpr int OFF_QSQ = 228352;
constexpr int OFF_GATE = 229376;
constexpr int OFF_RED = 229888;
constexpr int OFF_BAR = 229952;
constexpr int SMEM_BYTES = 230400 + 1024;

constexpr int B_FULL = 0, B_EMPTY = RING, B_X = 2 * RING, B_WOA = B_X + 7, B_WOB = B_WOA + 1, B_KVR = B_WOA + 2,
              B_X0FREE = B_WOA + 3, B_X1FREE = B_WOA + 4, B_B1 = B_WOA + 5, B_SLOW = B_WOA + 6, B_BUILD = B_WOA + 7,
              B_SIG = B_WOA + 8;

constexpr int C_KV = 0, C_PART = 1, C_RED = 2, C_DONE = 3, C_OA = 4, C_OB = 20, C_N = 36;

__device__ __align__(1024) uint8_t g_kv_img[32 * 8192];
__device__ float g_ksq[512];
__device__ float g_vmx[512];
__device__ float g_gate[S_LEN];
__device__ __align__(16) float g_kvpart[16 * 16 * 64 * 32];
__device__ __align__(1024) uint8_t g_kvr_img[16 * 4096];
__device__ __align__(1024) uint8_t g_o_img[2 * 16 * 14 * 8192];
__device__ unsigned g_cnt[C_N * 32];

#define PROF_CLK(i) do { } while (0)
#define PROF_MARK(i) do { } while (0)
__device__ __forceinline__ uint32_t smem_u32(const void* p) { return (uint32_t)__cvta_generic_to_shared(p); }
__device__ __forceinline__ void mbar_init(uint32_t a, int cnt) {
  asm volatile("mbarrier.init.shared::cta.b64 [%0], %1;" ::"r"(a), "r"(cnt) : "memory");
}
__device__ __forceinline__ void mbar_expect_tx(uint32_t a, uint32_t bytes) {
  asm volatile("mbarrier.arrive.expect_tx.shared::cta.b64 _, [%0], %1;" ::"r"(a), "r"(bytes) : "memory");
}
__device__ __forceinline__ void mbar_arrive(uint32_t a, uint32_t cnt) {
  asm volatile("mbarrier.arrive.shared::cta.b64 _, [%0], %1;" ::"r"(a), "r"(cnt) : "memory");
}
__device__ __forceinline__ bool mbar_try(uint32_t a, uint32_t parity) {
  uint32_t ok;
  asm volatile("{\n.reg .pred p;\nmbarrier.try_wait.parity.shared::cta.b64 p, [%1], %2;\nselp.u32 %0, 1, 0, p;\n}"
               : "=r"(ok) : "r"(a), "r"(parity) : "memory");
  return ok != 0;
}
__device__ __forceinline__ void mbar_wait(uint32_t a, uint32_t parity) {
  if (mbar_try(a, parity)) return;
  uint32_t n = 0;
  while (!mbar_try(a, parity)) {
    if (++n > (1u << 24)) break;
  }
}
__device__ __forceinline__ void tma_2d(uint32_t dst, const CUtensorMap* tm, int c0, int c1, uint32_t bar) {
  asm volatile("cp.async.bulk.tensor.2d.shared::cluster.global.mbarrier::complete_tx::bytes [%0], [%1, {%3, %4}], [%2];"
               ::"r"(dst), "l"(tm), "r"(bar), "r"(c0), "r"(c1) : "memory");
}
__device__ __forceinline__ void bulk_g2s(uint32_t dst, const void* src, uint32_t bytes, uint32_t bar) {
  asm volatile("cp.async.bulk.shared::cluster.global.mbarrier::complete_tx::bytes [%0], [%1], %2, [%3];"
               ::"r"(dst), "l"(src), "r"(bytes), "r"(bar) : "memory");
}
__device__ __forceinline__ void fence_async_smem() { asm volatile("fence.proxy.async.shared::cta;" ::: "memory"); }
__device__ __forceinline__ void fence_async_all() { asm volatile("fence.proxy.async;" ::: "memory"); }
__device__ __forceinline__ void bar_sync(int id, int n) { asm volatile("bar.sync %0, %1;" ::"r"(id), "r"(n) : "memory"); }
__device__ __forceinline__ bool bar_or(int id, int n, bool v) {
  uint32_t r;
  asm volatile("{\n.reg .pred p, q;\nsetp.ne.u32 p, %3, 0;\nbar.red.or.pred q, %1, %2, p;\nselp.u32 %0, 1, 0, q;\n}"
               : "=r"(r) : "r"(id), "r"(n), "r"((uint32_t)v) : "memory");
  return r != 0;
}
__device__ __forceinline__ void cnt_arrive(int idx) {
  asm volatile("red.release.gpu.global.add.u32 [%0], 1;" ::"l"(&g_cnt[idx * 32]) : "memory");
}
__device__ __forceinline__ void cnt_wait(int idx, unsigned target) {
  unsigned v, n = 0;
  while (true) {
    asm volatile("ld.acquire.gpu.global.u32 %0, [%1];" : "=r"(v) : "l"(&g_cnt[idx * 32]) : "memory");
    if (v >= target) break;
    if (++n > (1u << 22)) break;
  }
}
__device__ __forceinline__ void wg_fence() { asm volatile("wgmma.fence.sync.aligned;" ::: "memory"); }
__device__ __forceinline__ void wg_commit() { asm volatile("wgmma.commit_group.sync.aligned;" ::: "memory"); }
template <int N> __device__ __forceinline__ void wg_wait() { asm volatile("wgmma.wait_group.sync.aligned %0;" ::"n"(N) : "memory"); }
template <int N> __device__ __forceinline__ void fence_regs(float (&d)[N]) {
#pragma unroll
  for (int i = 0; i < N; i++) asm volatile("" : "+f"(d[i])::"memory");
}
__device__ __forceinline__ uint64_t make_desc(uint32_t saddr, uint32_t lbo, uint32_t sbo, uint32_t swz) {
  return (uint64_t)((saddr & 0x3FFFF) >> 4) | ((uint64_t)(lbo >> 4) << 16) | ((uint64_t)(sbo >> 4) << 32) | ((uint64_t)swz << 62);
}
__device__ __forceinline__ float ex2f(float x) { float y; asm("ex2.approx.ftz.f32 %0, %1;" : "=f"(y) : "f"(x)); return y; }
__device__ __forceinline__ float rcpf(float x) { float y; asm("rcp.approx.ftz.f32 %0, %1;" : "=f"(y) : "f"(x)); return y; }
__device__ __forceinline__ uint32_t pack_bf16(float lo, float hi) {
  uint32_t r; asm("cvt.rn.bf16x2.f32 %0, %1, %2;" : "=r"(r) : "f"(hi), "f"(lo)); return r;
}
__device__ __forceinline__ uint32_t lop_and_or(uint32_t a, uint32_t m, uint32_t c) {
  uint32_t r; asm("lop3.b32 %0, %1, %2, %3, 0xEA;" : "=r"(r) : "r"(a), "r"(m), "r"(c)); return r;
}
__device__ __forceinline__ void sts32(uint32_t a, uint32_t v) { asm volatile("st.shared.b32 [%0], %1;" ::"r"(a), "r"(v) : "memory"); }
__device__ __forceinline__ void sts64(uint32_t a, uint32_t v0, uint32_t v1) { asm volatile("st.shared.v2.b32 [%0], {%1, %2};" ::"r"(a), "r"(v0), "r"(v1) : "memory"); }
__device__ __forceinline__ void sts128(uint32_t a, uint4 v) {
  asm volatile("st.shared.v4.b32 [%0], {%1, %2, %3, %4};" ::"r"(a), "r"(v.x), "r"(v.y), "r"(v.z), "r"(v.w) : "memory");
}
__device__ __forceinline__ float ldcg_f(const float* p) { float v; asm volatile("ld.global.cg.f32 %0, [%1];" : "=f"(v) : "l"(p) : "memory"); return v; }
__device__ __forceinline__ float4 ldcg_f4(const float* p) {
  float4 v; asm volatile("ld.global.cg.v4.f32 {%0, %1, %2, %3}, [%4];" : "=f"(v.x), "=f"(v.y), "=f"(v.z), "=f"(v.w) : "l"(p) : "memory"); return v;
}
__device__ __forceinline__ float quad_sum(float v) { v += __shfl_xor_sync(~0u, v, 1); v += __shfl_xor_sync(~0u, v, 2); return v; }
__device__ __forceinline__ float quad_max(float v) { v = fmaxf(v, __shfl_xor_sync(~0u, v, 1)); v = fmaxf(v, __shfl_xor_sync(~0u, v, 2)); return v; }
__device__ __forceinline__ float quad_min(float v) { v = fminf(v, __shfl_xor_sync(~0u, v, 1)); v = fminf(v, __shfl_xor_sync(~0u, v, 2)); return v; }

template <int SD> __device__ __forceinline__ void wgmma_ss_n56_ta0_tb1(float (&d)[28], uint64_t da, uint64_t db) {
  asm volatile("wgmma.mma_async.sync.aligned.m64n56k16.f32.bf16.bf16 {%0, %1, %2, %3, %4, %5, %6, %7, %8, %9, %10, %11, %12, %13, %14, %15, %16, %17, %18, %19, %20, %21, %22, %23, %24, %25, %26, %27}, %28, %29, %30, 1, 1, 0, 1;\n"
    : "+f"(d[0]), "+f"(d[1]), "+f"(d[2]), "+f"(d[3]), "+f"(d[4]), "+f"(d[5]), "+f"(d[6]), "+f"(d[7]), "+f"(d[8]), "+f"(d[9]), "+f"(d[10]), "+f"(d[11]), "+f"(d[12]), "+f"(d[13]), "+f"(d[14]), "+f"(d[15]), "+f"(d[16]), "+f"(d[17]), "+f"(d[18]), "+f"(d[19]), "+f"(d[20]), "+f"(d[21]), "+f"(d[22]), "+f"(d[23]), "+f"(d[24]), "+f"(d[25]), "+f"(d[26]), "+f"(d[27])
    : "l"(da), "l"(db), "n"(SD));
}
template <int SD> __device__ __forceinline__ void wgmma_ss_n8_ta0_tb1(float (&d)[4], uint64_t da, uint64_t db) {
  asm volatile("wgmma.mma_async.sync.aligned.m64n8k16.f32.bf16.bf16 {%0, %1, %2, %3}, %4, %5, %6, 1, 1, 0, 1;\n"
    : "+f"(d[0]), "+f"(d[1]), "+f"(d[2]), "+f"(d[3])
    : "l"(da), "l"(db), "n"(SD));
}
template <int SD> __device__ __forceinline__ void wgmma_rs_n64_tb1(float (&d)[32], uint32_t a0, uint32_t a1, uint32_t a2, uint32_t a3, uint64_t db) {
  asm volatile("wgmma.mma_async.sync.aligned.m64n64k16.f32.bf16.bf16 {%0, %1, %2, %3, %4, %5, %6, %7, %8, %9, %10, %11, %12, %13, %14, %15, %16, %17, %18, %19, %20, %21, %22, %23, %24, %25, %26, %27, %28, %29, %30, %31}, {%32, %33, %34, %35}, %36, %37, 1, 1, 1;\n"
    : "+f"(d[0]), "+f"(d[1]), "+f"(d[2]), "+f"(d[3]), "+f"(d[4]), "+f"(d[5]), "+f"(d[6]), "+f"(d[7]), "+f"(d[8]), "+f"(d[9]), "+f"(d[10]), "+f"(d[11]), "+f"(d[12]), "+f"(d[13]), "+f"(d[14]), "+f"(d[15]), "+f"(d[16]), "+f"(d[17]), "+f"(d[18]), "+f"(d[19]), "+f"(d[20]), "+f"(d[21]), "+f"(d[22]), "+f"(d[23]), "+f"(d[24]), "+f"(d[25]), "+f"(d[26]), "+f"(d[27]), "+f"(d[28]), "+f"(d[29]), "+f"(d[30]), "+f"(d[31])
    : "r"(a0), "r"(a1), "r"(a2), "r"(a3), "l"(db), "n"(SD));
}
template <int SD> __device__ __forceinline__ void wgmma_ss_n32_ta1_tb1(float (&d)[16], uint64_t da, uint64_t db) {
  asm volatile("wgmma.mma_async.sync.aligned.m64n32k16.f32.bf16.bf16 {%0, %1, %2, %3, %4, %5, %6, %7, %8, %9, %10, %11, %12, %13, %14, %15}, %16, %17, %18, 1, 1, 1, 1;\n"
    : "+f"(d[0]), "+f"(d[1]), "+f"(d[2]), "+f"(d[3]), "+f"(d[4]), "+f"(d[5]), "+f"(d[6]), "+f"(d[7]), "+f"(d[8]), "+f"(d[9]), "+f"(d[10]), "+f"(d[11]), "+f"(d[12]), "+f"(d[13]), "+f"(d[14]), "+f"(d[15])
    : "l"(da), "l"(db), "n"(SD));
}
template <int SD> __device__ __forceinline__ void wgmma_ss_n32_ta0_tb1(float (&d)[16], uint64_t da, uint64_t db) {
  asm volatile("wgmma.mma_async.sync.aligned.m64n32k16.f32.bf16.bf16 {%0, %1, %2, %3, %4, %5, %6, %7, %8, %9, %10, %11, %12, %13, %14, %15}, %16, %17, %18, 1, 1, 0, 1;\n"
    : "+f"(d[0]), "+f"(d[1]), "+f"(d[2]), "+f"(d[3]), "+f"(d[4]), "+f"(d[5]), "+f"(d[6]), "+f"(d[7]), "+f"(d[8]), "+f"(d[9]), "+f"(d[10]), "+f"(d[11]), "+f"(d[12]), "+f"(d[13]), "+f"(d[14]), "+f"(d[15])
    : "l"(da), "l"(db), "n"(SD));
}
template <int SD> __device__ __forceinline__ void wgmma_rs_n64_tb0(float (&d)[32], uint32_t a0, uint32_t a1, uint32_t a2, uint32_t a3, uint64_t db) {
  asm volatile("wgmma.mma_async.sync.aligned.m64n64k16.f32.bf16.bf16 {%0, %1, %2, %3, %4, %5, %6, %7, %8, %9, %10, %11, %12, %13, %14, %15, %16, %17, %18, %19, %20, %21, %22, %23, %24, %25, %26, %27, %28, %29, %30, %31}, {%32, %33, %34, %35}, %36, %37, 1, 1, 0;\n"
    : "+f"(d[0]), "+f"(d[1]), "+f"(d[2]), "+f"(d[3]), "+f"(d[4]), "+f"(d[5]), "+f"(d[6]), "+f"(d[7]), "+f"(d[8]), "+f"(d[9]), "+f"(d[10]), "+f"(d[11]), "+f"(d[12]), "+f"(d[13]), "+f"(d[14]), "+f"(d[15]), "+f"(d[16]), "+f"(d[17]), "+f"(d[18]), "+f"(d[19]), "+f"(d[20]), "+f"(d[21]), "+f"(d[22]), "+f"(d[23]), "+f"(d[24]), "+f"(d[25]), "+f"(d[26]), "+f"(d[27]), "+f"(d[28]), "+f"(d[29]), "+f"(d[30]), "+f"(d[31])
    : "r"(a0), "r"(a1), "r"(a2), "r"(a3), "l"(db), "n"(SD));
}
template <int SD> __device__ __forceinline__ void wgmma_rs_n32_tb1(float (&d)[16], uint32_t a0, uint32_t a1, uint32_t a2, uint32_t a3, uint64_t db) {
  asm volatile("wgmma.mma_async.sync.aligned.m64n32k16.f32.bf16.bf16 {%0, %1, %2, %3, %4, %5, %6, %7, %8, %9, %10, %11, %12, %13, %14, %15}, {%16, %17, %18, %19}, %20, %21, 1, 1, 1;\n"
    : "+f"(d[0]), "+f"(d[1]), "+f"(d[2]), "+f"(d[3]), "+f"(d[4]), "+f"(d[5]), "+f"(d[6]), "+f"(d[7]), "+f"(d[8]), "+f"(d[9]), "+f"(d[10]), "+f"(d[11]), "+f"(d[12]), "+f"(d[13]), "+f"(d[14]), "+f"(d[15])
    : "r"(a0), "r"(a1), "r"(a2), "r"(a3), "l"(db), "n"(SD));
}

__device__ __forceinline__ uint32_t sw64_off(int row, int d) { return row * 64 + ((((d >> 3) ^ (row >> 1)) & 3) << 4) + (d & 7) * 2; }

__device__ __forceinline__ uint32_t exp2_pair_fma(float t0, float t1, uint32_t c_half, uint32_t c_3) {
  uint32_t y0, y;
  asm("prmt.b32 %0, %1, %2, 0x6521;" : "=r"(y0) : "r"(__float_as_uint(t0)), "r"(__float_as_uint(t1)));
  uint32_t h = lop_and_or(y0, 0x007F007Fu, c_half);
  uint32_t e = lop_and_or(y0, 0xFF80FF80u, c_3);
  asm("fma.rn.bf16x2 %0, %1, %2, %3;" : "=r"(y) : "r"(y0), "r"(h), "r"(e));
  return y;
}

template <bool TO_SMEM>
__device__ __forceinline__ void feature_map(float (&p)[32], uint32_t (&ph)[32], int lq, uint32_t base, int row0) {
  const float L2E = 1.4426950408889634f;
  const bool tail_ok = lq < 2;
  float mx[4], mn[4];
#pragma unroll
  for (int g = 0; g < 4; g++) {
    const int o = 16 * (g >> 1) + 2 * (g & 1);
    if (!tail_ok) { p[o + 12] = p[o]; p[o + 13] = p[o]; }
    mx[g] = fmaxf(fmaxf(fmaxf(p[o], p[o + 1]), fmaxf(p[o + 4], p[o + 5])), fmaxf(fmaxf(p[o + 8], p[o + 9]), fmaxf(p[o + 12], p[o + 13])));
    mn[g] = fminf(fminf(fminf(p[o], p[o + 1]), fminf(p[o + 4], p[o + 5])), fminf(fminf(p[o + 8], p[o + 9]), fminf(p[o + 12], p[o + 13])));
  }
#pragma unroll
  for (int o = 1; o <= 2; o <<= 1)
#pragma unroll
    for (int g = 0; g < 4; g++) { mx[g] = fmaxf(mx[g], __shfl_xor_sync(~0u, mx[g], o)); mn[g] = fminf(mn[g], __shfl_xor_sync(~0u, mn[g], o)); }
  float b[32], sa[4], sb[4];
#pragma unroll
  for (int g = 0; g < 4; g++) {
    const int o = 16 * (g >> 1) + 2 * (g & 1);
    const float cx = -mx[g] * L2E, cn = mn[g] * L2E;
#pragma unroll
    for (int i = 0; i < 8; i++) {
      const int k = o + 4 * (i >> 1) + (i & 1);
      b[k] = ex2f(fmaf(p[k], -L2E, cn));
      p[k] = ex2f(fmaf(p[k], L2E, cx));
    }
    if (!tail_ok) { p[o + 12] = p[o + 13] = b[o + 12] = b[o + 13] = 0.f; }
    sa[g] = ((p[o] + p[o + 1]) + (p[o + 4] + p[o + 5])) + ((p[o + 8] + p[o + 9]) + (p[o + 12] + p[o + 13]));
    sb[g] = ((b[o] + b[o + 1]) + (b[o + 4] + b[o + 5])) + ((b[o + 8] + b[o + 9]) + (b[o + 12] + b[o + 13]));
  }
#pragma unroll
  for (int o = 1; o <= 2; o <<= 1)
#pragma unroll
    for (int g = 0; g < 4; g++) { sa[g] += __shfl_xor_sync(~0u, sa[g], o); sb[g] += __shfl_xor_sync(~0u, sb[g], o); }
#pragma unroll
  for (int g = 0; g < 4; g++) {
    const int e = g >> 1, rr = g & 1, o = 16 * e + 2 * rr;
    const float ra = rcpf(sa[g]), rb = rcpf(sb[g]);
    const int row = row0 + 8 * rr;
    const uint32_t rbase = base + e * 16384 + row * 128 + lq * 4;
#pragma unroll
    for (int jj = 0; jj < 4; jj++) {
      uint32_t pa = pack_bf16(p[o + 4 * jj] * ra, p[o + 4 * jj + 1] * ra), pb = pack_bf16(b[o + 4 * jj] * rb, b[o + 4 * jj + 1] * rb);
      if (TO_SMEM) {
        sts32(rbase + ((jj ^ (row & 7)) << 4), pa);
        sts32(rbase + (((4 + jj) ^ (row & 7)) << 4), pb);
      } else {
        ph[e * 16 + jj * 2 + rr] = pa;
        ph[e * 16 + (4 + jj) * 2 + rr] = pb;
      }
    }
  }
}

template <bool TO_SMEM>
__device__ __forceinline__ void phi_from_acc(const float (&acc)[28], uint32_t sb, uint32_t (&ph)[32], int lq, uint32_t base, int row0) {
  uint32_t a[16];
#pragma unroll
  for (int i = 0; i < 14; i++) a[i] = pack_bf16(acc[2 * i], acc[2 * i + 1]);
  a[14] = pack_bf16(acc[1], acc[0]);
  a[15] = pack_bf16(acc[3], acc[2]);
  float p[32];
  const uint64_t dWbd = make_desc(sb + OFF_WBD, 1024, 1024, 1);
  wg_fence();
  wgmma_rs_n64_tb1<0>(p, a[0], a[1], a[2], a[3], dWbd);
  wgmma_rs_n64_tb1<1>(p, a[4], a[5], a[6], a[7], dWbd + 128);
  wgmma_rs_n64_tb1<1>(p, a[8], a[9], a[10], a[11], dWbd + 256);
  wgmma_rs_n64_tb1<1>(p, a[12], a[13], a[14], a[15], dWbd + 384);
  wg_commit();
  wg_wait<0>();
  fence_regs(p);
  feature_map<TO_SMEM>(p, ph, lq, base, row0);
}

__device__ __forceinline__ void store_phi(uint32_t base, const uint32_t (&ph)[32], int row0, int lq) {
#pragma unroll
  for (int e = 0; e < 2; e++)
#pragma unroll
    for (int ch = 0; ch < 8; ch++)
#pragma unroll
      for (int rr = 0; rr < 2; rr++) {
        int row = row0 + 8 * rr;
        sts32(base + e * 16384 + row * 128 + ((ch ^ (row & 7)) << 4) + lq * 4, ph[e * 16 + ch * 2 + rr]);
      }
}

__device__ __forceinline__ void store_heads(uint32_t base, uint32_t head_stride, const uint32_t (&a)[14], int row0, int lq) {
#pragma unroll
  for (int j = 0; j < 7; j++) {
    int col = 8 * j + 2 * lq;
    int e = col >= DH;
    int d = col - DH * e;
#pragma unroll
    for (int rr = 0; rr < 2; rr++) sts32(base + e * head_stride + sw64_off(row0 + 8 * rr, d), a[2 * j + rr]);
  }
}

__device__ __forceinline__ void store_o(const float (&o)[16], float s0, float s1, float eps, int branch, int pt, int mh, int head,
                                        int rowl, int lane) {
  const int lq = lane & 3;
  float d0 = __shfl_sync(~0u, o[12], (lane & ~3) | 2), d1 = __shfl_sync(~0u, o[14], (lane & ~3) | 2);
  float r0 = __fdividef(s0, d0 + eps), r1 = __fdividef(s1, d1 + eps);
  uint8_t* img = g_o_img + (size_t)((branch * 16 + pt) * 14 + mh) * 8192;
#pragma unroll
  for (int j = 0; j < 4; j++) {
    int d = 8 * j + 2 * lq;
    if (d < DH) {
      int col = head * DH + d;
      int c = col >> 6, cc = col & 63;
      uint8_t* p = img + c * 16384 + rowl * 128 + (((cc >> 3) ^ (rowl & 7)) << 4) + (cc & 7) * 2;
      *(uint32_t*)p = pack_bf16(o[4 * j] * r0, o[4 * j + 1] * r0);
      *(uint32_t*)(p + 1024) = pack_bf16(o[4 * j + 2] * r1, o[4 * j + 3] * r1);
    }
  }
}

struct Params {
  const __nv_bfloat16* w_phi;
  const __nv_bfloat16* wk;
  const __nv_bfloat16* wv;
  const __nv_bfloat16* gate_w;
  __nv_bfloat16* out;
};

__global__ void __launch_bounds__(NTHREADS, 1)
fused_kernel(const __grid_constant__ CUtensorMap tm_x, const __grid_constant__ CUtensorMap tm_wqkv,
             const __grid_constant__ CUtensorMap tm_wq, const __grid_constant__ CUtensorMap tm_woa,
             const __grid_constant__ CUtensorMap tm_wob, const Params prm) {
  extern __shared__ uint8_t smem_raw[];
  const uint32_t sb = (smem_u32(smem_raw) + 1023u) & ~1023u;
  uint8_t* sgen = smem_raw + (sb - smem_u32(smem_raw));
  const int tid = threadIdx.x, lane = tid & 31;
  const int warp = __shfl_sync(~0u, tid >> 5, 0), wg = warp >> 2;
  const int pt = blockIdx.x >> 3, hp = blockIdx.x & 7;
  const uint32_t bars = sb + OFF_BAR;
  auto BAR = [&](int i) { return bars + 8u * i; };

  if (tid == 0) { PROF_MARK(0); PROF_CLK(30); }
  if (tid == 512) {
    for (int i = 0; i < RING; i++) { mbar_init(BAR(B_FULL + i), 1); mbar_init(BAR(B_EMPTY + i), 16); }
    for (int i = 0; i < 7; i++) mbar_init(BAR(B_X + i), 1);
    mbar_init(BAR(B_WOA), 1); mbar_init(BAR(B_WOB), 1); mbar_init(BAR(B_KVR), 1);
    mbar_init(BAR(B_X0FREE), 8); mbar_init(BAR(B_X1FREE), 16); mbar_init(BAR(B_B1), 2); mbar_init(BAR(B_SLOW), 1);
    mbar_init(BAR(B_BUILD), 3);
    mbar_init(BAR(B_SIG + 0), 8); mbar_init(BAR(B_SIG + 1), 8); mbar_init(BAR(B_SIG + 2), 16); mbar_init(BAR(B_SIG + 3), 16);
    asm volatile("fence.mbarrier_init.release.cluster;" ::: "memory");
    fence_async_smem();
    for (int c = 0; c < 6; c++) {
      mbar_expect_tx(BAR(B_X + c), 16384);
      tma_2d(sb + OFF_X + c * 16384, &tm_x, c * 64, pt * 128, BAR(B_X + c));
      mbar_expect_tx(BAR(B_FULL + 2 * c), 8192);
      tma_2d(sb + OFF_RING + (2 * c) * 8192, &tm_wq, hp * 56, c * 64, BAR(B_FULL + 2 * c));
      mbar_expect_tx(BAR(B_FULL + 2 * c + 1), 8192);
      tma_2d(sb + OFF_RING + (2 * c + 1) * 8192, &tm_wqkv, DM + hp * 56, c * 64, BAR(B_FULL + 2 * c + 1));
    }
    mbar_expect_tx(BAR(B_X + 6), 16384);
    tma_2d(sb + OFF_X + 6 * 16384, &tm_x, 6 * 64, pt * 128, BAR(B_X + 6));
  }
  __syncthreads();

  if (wg == 4) {
    if (warp == 16) {
      asm volatile("setmaxnreg.dec.sync.aligned.u32 32;");
      if (lane == 0) {
        int item = 12;
        auto acquire = [&](int it) -> uint32_t {
          int slot = it % RING;
          mbar_wait(BAR(B_EMPTY + slot), ((it / RING) - 1) & 1);
          mbar_expect_tx(BAR(B_FULL + slot), 8192);
          return slot;
        };
        for (; item < 28; item++) {
          uint32_t slot = acquire(item);
          int r = item / 14, c = (item % 14) >> 1, nh = item & 1;
          if (r == 0 && nh == 0) tma_2d(sb + OFF_RING + slot * 8192, &tm_wq, hp * 56, c * 64, BAR(B_FULL + slot));
          else {
            int part = (r == 0) ? 1 : (nh == 0 ? 0 : 2);
            tma_2d(sb + OFF_RING + slot * 8192, &tm_wqkv, part * DM + hp * 56, c * 64, BAR(B_FULL + slot));
          }
        }
        PROF_MARK(20);
        cnt_wait(C_KV, NCTA);
        PROF_MARK(21);
        fence_async_all();
        for (int j = 0; j < 32; j++, item++) {
          uint32_t slot = acquire(item);
          bulk_g2s(sb + OFF_RING + slot * 8192, g_kv_img + j * 8192, 8192, BAR(B_FULL + slot));
        }
        mbar_wait(BAR(B_SLOW), 0);
        if (*(volatile int*)(sgen + OFF_RED + 8)) {
          for (int j = 0; j < 32; j++, item++) {
            uint32_t slot = acquire(item);
            bulk_g2s(sb + OFF_RING + slot * 8192, g_kv_img + j * 8192, 8192, BAR(B_FULL + slot));
          }
        }
        for (int br = 0; br < 2; br++) {
          cnt_wait((br ? C_OB : C_OA) + pt, 8);
          fence_async_all();
          for (int j = 0; j < 14; j++, item++) {
            uint32_t slot = acquire(item);
            bulk_g2s(sb + OFF_RING + slot * 8192, g_o_img + (size_t)((br * 16 + pt) * 14 + j) * 8192, 8192, BAR(B_FULL + slot));
          }
        }
      }
    } else {
      {
        const int t = tid - 544;
        uint2 lo[5], hi[5], wp[5];
#pragma unroll
        for (int i = 0; i < 5; i++) {
          const int k = t + 96 * i;
          lo[i] = hi[i] = wp[i] = make_uint2(0, 0);
          if (k < DM) {
            const __nv_bfloat16* src = (hp < 4 ? prm.wk : prm.wv) + k * DH + (hp & 3) * 8;
            lo[i] = *(const uint2*)src;
            if ((hp & 3) != 3) hi[i] = *(const uint2*)(src + 4);
            else if (hp == 3) hi[i].x = ((const unsigned short*)prm.gate_w)[k];
          }
          if (k < 392) wp[i] = *(const uint2*)(prm.w_phi + 2 * hp * DH * DH + k * 4);
        }
        for (int i = t; i < 512; i += 96) sts128(sb + OFF_WBD + i * 16, make_uint4(0, 0, 0, 0));
        bar_sync(4, 96);
#pragma unroll
        for (int i = 0; i < 5; i++) {
          const int k = t + 96 * i;
          if (k < DM) sts128(sb + OFF_SLC + k * 16, make_uint4(lo[i].x, lo[i].y, hi[i].x, hi[i].y));
          if (k < 392) {
            const int row = k / 7, n = (row >= DH ? 32 : 0) + (k % 7) * 4;
            sts64(sb + OFF_WBD + row * 128 + (((n >> 3) ^ (row & 7)) << 4) + (n & 4) * 2, wp[i].x, wp[i].y);
          }
        }
        fence_async_smem();
        __syncwarp();
        if (lane == 0) mbar_arrive(BAR(B_BUILD), 1);
      }
      asm volatile("setmaxnreg.dec.sync.aligned.u32 32;");
      if (warp == 18) {
        if (lane == 0) {
          mbar_wait(BAR(B_SIG + 0), 0); cnt_arrive(C_KV);
          mbar_wait(BAR(B_SIG + 1), 0); cnt_arrive(C_PART);
          mbar_wait(BAR(B_SIG + 2), 0); cnt_arrive(C_OA + pt);
          mbar_wait(BAR(B_SIG + 3), 0); cnt_arrive(C_OB + pt);
        }
      } else if (warp == 19) {
        if (lane == 0) {
          cnt_wait(C_KV, NCTA);
          fence_async_all();
          mbar_expect_tx(BAR(B_B1), 512);
          bulk_g2s(sb + OFF_GATE, g_gate + pt * 128, 512, BAR(B_B1));
        }
        __syncwarp();
        float ksq = 0.f, vmx = 0.f;
#pragma unroll
        for (int sl = 0; sl < 4; sl++) {
          float4 a = ldcg_f4(g_ksq + sl * 128 + lane * 4), b = ldcg_f4(g_vmx + sl * 128 + lane * 4);
          float m = fmaxf(fmaxf(a.x, a.y), fmaxf(a.z, a.w));
#pragma unroll
          for (int o = 16; o > 0; o >>= 1) m = fmaxf(m, __shfl_xor_sync(~0u, m, o));
          ksq += m;
          vmx = fmaxf(vmx, fmaxf(fmaxf(b.x, b.y), fmaxf(b.z, b.w)));
        }
#pragma unroll
        for (int o = 16; o > 0; o >>= 1) vmx = fmaxf(vmx, __shfl_xor_sync(~0u, vmx, o));
        if (lane == 0) {
          float* red = (float*)(sgen + OFF_RED);
          red[0] = ksq; red[1] = vmx;
          mbar_arrive(BAR(B_B1), 1);
        }
      } else {
        if (lane == 0) {
          mbar_wait(BAR(B_X0FREE), 0);
          mbar_expect_tx(BAR(B_WOA), 57344);
          for (int c = 0; c < 7; c++) tma_2d(sb + OFF_WOA + c * 8192, &tm_woa, hp * 56, c * 64, BAR(B_WOA));
          PROF_MARK(22);
          cnt_wait(C_PART, NCTA);
          PROF_MARK(23);
        }
        __syncwarp();
        {
          const int head = blockIdx.x >> 3, f = (blockIdx.x & 7) * 8 + (lane >> 2), d0 = (lane & 3) * 8;
          const float* src = g_kvpart + ((size_t)head * 64 + f) * 32 + d0;
          float4 s0 = make_float4(0, 0, 0, 0), s1 = s0;
#pragma unroll 2
          for (int t = 0; t < 16; t++) {
            float4 a = ldcg_f4(src + (size_t)t * 16 * 64 * 32), b = ldcg_f4(src + (size_t)t * 16 * 64 * 32 + 4);
            s0.x += a.x; s0.y += a.y; s0.z += a.z; s0.w += a.w; s1.x += b.x; s1.y += b.y; s1.z += b.z; s1.w += b.w;
          }
          uint4 v = make_uint4(pack_bf16(s0.x, s0.y), pack_bf16(s0.z, s0.w), pack_bf16(s1.x, s1.y), pack_bf16(s1.z, s1.w));
          *(uint4*)(g_kvr_img + head * 4096 + sw64_off(f, d0)) = v;
        }
        __syncwarp();
        if (lane == 0) {
          cnt_arrive(C_RED);
          PROF_MARK(24);
          cnt_wait(C_RED, NCTA);
          PROF_MARK(25);
          fence_async_all();
          mbar_expect_tx(BAR(B_KVR), 8192);
          bulk_g2s(sb + OFF_KVR, g_kvr_img + hp * 8192, 8192, BAR(B_KVR));
          mbar_wait(BAR(B_X1FREE), 0);
          mbar_expect_tx(BAR(B_WOB), 57344);
          for (int c = 0; c < 7; c++) tma_2d(sb + OFF_WOB + c * 8192, &tm_wob, hp * 56, c * 64, BAR(B_WOB));
        }
      }
    }
  } else {
    const int mh = wg & 1, nh = wg >> 1, wq = warp & 3, lq = lane & 3;
    const int rowl = wq * 16 + (lane >> 2);
    const int row0 = mh * 64 + rowl;
    const uint64_t dX = make_desc(sb + OFF_X + mh * 8192, 16, 1024, 1);
    const uint64_t dRingN = make_desc(sb + OFF_RING, 1024, 1024, 1);
    const uint64_t dSlc = make_desc(sb + OFF_SLC, 128, 128, 0);
    float acc[28], accs[4];
    uint32_t keep[32];

    if (tid == 0) PROF_MARK(1);
#pragma unroll
    for (int c = 0; c < 7; c++) {
      const int slot = (c < 6) ? 2 * c + nh : nh;
      mbar_wait(BAR(B_X + c), 0);
      mbar_wait(BAR(B_FULL + slot), c < 6 ? 0 : 1);
      wg_fence();
#pragma unroll
      for (int ks = 0; ks < 4; ks++) {
        if (c == 0 && ks == 0) wgmma_ss_n56_ta0_tb1<0>(acc, dX, dRingN + slot * 512);
        else wgmma_ss_n56_ta0_tb1<1>(acc, dX + c * 1024 + ks * 2, dRingN + slot * 512 + ks * 128);
      }
      wg_commit();
      if (c > 0) {
        wg_wait<1>();
        if (lane == 0) mbar_arrive(BAR(B_EMPTY + 2 * (c - 1) + nh), 2);
      }
    }
    wg_wait<0>();
    fence_regs(acc);
    if (lane == 0) mbar_arrive(BAR(B_EMPTY + nh), 2);
    asm volatile("setmaxnreg.inc.sync.aligned.u32 112;");
    mbar_wait(BAR(B_BUILD), 0);

    if (tid == 0) PROF_MARK(2);
    if (tid == 256) PROF_MARK(3);
    if (nh == 0) {
      wg_fence();
      wgmma_ss_n8_ta0_tb1<0>(accs, dX, dSlc);
#pragma unroll
      for (int kk = 1; kk < 28; kk++) wgmma_ss_n8_ta0_tb1<1>(accs, dX + (kk >> 2) * 1024 + (kk & 3) * 2, dSlc + kk * 16);
      wg_commit();
      wg_wait<0>();
      fence_regs(accs);
      const int sl = hp & 3;
      float mxv = 0.f;
#pragma unroll
      for (int rr = 0; rr < 2; rr++) {
        const int pos = pt * 128 + row0 + 8 * rr, kr = pos & 63;
        float v0 = accs[2 * rr], v1 = accs[2 * rr + 1];
        const bool real = (sl < 3) || (lq < 2);
        uint32_t outv;
        if (hp < 4) {
          const bool poly = (POLY_PAT >> (kr >> 3)) & 1;
          float sq = quad_sum(real ? v0 * v0 + v1 * v1 : 0.f);
          mxv = fmaxf(mxv, sq);
          if (real) outv = poly ? pack_bf16(2.f * v0, 2.f * v1) : pack_bf16(v0, v1);
          else if (lq == 2) {
            g_gate[pos] = rcpf(1.f + ex2f(-1.4426950408889634f * v0));
            outv = poly ? 0x443F4000u : 0x00003F80u;
          } else outv = poly ? 0x3AB03F4Du : 0u;
        } else {
          mxv = fmaxf(mxv, real ? fmaxf(fabsf(v0), fabsf(v1)) : 0.f);
          if (!(fabsf(v0) <= 3.0e38f) || !(fabsf(v1) <= 3.0e38f)) mxv = __int_as_float(0x7f800000);
          outv = real ? pack_bf16(v0, v1) : (lq == 2 ? 0x00003F80u : 0u);
        }
        *(uint32_t*)(g_kv_img + (pos >> 6) * 8192 + (hp < 4 ? 0 : 4096) + sw64_off(kr, sl * 8 + 2 * lq)) = outv;
      }
      if (!(mxv <= 3.0e38f)) mxv = __int_as_float(0x7f800000);
#pragma unroll
      for (int o = 16; o > 0; o >>= 1) mxv = fmaxf(mxv, __shfl_xor_sync(~0u, mxv, o));
      if (lane == 0) (hp < 4 ? g_ksq : g_vmx)[sl * 128 + pt * 8 + mh * 4 + wq] = mxv;
      __syncwarp();
      if (lane == 0) mbar_arrive(BAR(B_SIG + 0), 1);
      const float QS = 0.18898223650461362f * 1.4426950408889634f;
      float sq[4] = {0.f, 0.f, 0.f, 0.f};
#pragma unroll
      for (int j = 0; j < 7; j++) {
#pragma unroll
        for (int rr = 0; rr < 2; rr++) {
          float v0 = acc[4 * j + 2 * rr] * QS, v1 = acc[4 * j + 2 * rr + 1] * QS;
          keep[2 * j + rr] = pack_bf16(v0, v1);
          float s2 = v0 * v0 + v1 * v1;
          if (j < 3) sq[rr] += s2;
          else if (j > 3) sq[2 + rr] += s2;
          else { sq[rr] += (lq < 2) ? s2 : 0.f; sq[2 + rr] += (lq < 2) ? 0.f : s2; }
        }
      }
#pragma unroll
      for (int i = 0; i < 4; i++) sq[i] = quad_sum(sq[i]);
      float* qsq = (float*)(sgen + OFF_QSQ);
      if (lq == 0) {
        qsq[(mh + 0) * 64 + rowl] = sq[0]; qsq[(mh + 0) * 64 + rowl + 8] = sq[1];
        qsq[(mh + 2) * 64 + rowl] = sq[2]; qsq[(mh + 2) * 64 + rowl + 8] = sq[3];
      }
    } else {
      phi_from_acc<false>(acc, sb, keep, lq, 0, 0);
    }

    if (tid == 0) PROF_MARK(4);
    if (tid == 256) PROF_MARK(5);
#pragma unroll
    for (int c = 0; c < 7; c++) {
      const int item = 14 + 2 * c + nh;
      const int slot = (c < 5) ? item - 12 : item - 24;
      mbar_wait(BAR(B_FULL + slot), c < 5 ? 1 : 0);
      wg_fence();
#pragma unroll
      for (int ks = 0; ks < 4; ks++) {
        if (c == 0 && ks == 0) wgmma_ss_n56_ta0_tb1<0>(acc, dX, dRingN + slot * 512);
        else wgmma_ss_n56_ta0_tb1<1>(acc, dX + c * 1024 + ks * 2, dRingN + slot * 512 + ks * 128);
      }
      wg_commit();
      if (c > 0) {
        wg_wait<1>();
        const int pslot = (c - 1 < 5) ? item - 2 - 12 : item - 2 - 24;
        if (lane == 0) mbar_arrive(BAR(B_EMPTY + pslot), 2);
      }
    }
    wg_wait<0>();
    fence_regs(acc);
    if (lane == 0) mbar_arrive(BAR(B_EMPTY + 2 + nh), 2);
    bar_sync(1, 512);
    if (tid == 0) PROF_MARK(6);

    if (nh == 0) {
      uint32_t q14[14];
#pragma unroll
      for (int i = 0; i < 14; i++) q14[i] = keep[i];
      store_heads(sb + OFF_QP + mh * 4096, 8192, q14, rowl, lq);
      phi_from_acc<true>(acc, sb, keep, lq, sb + OFF_PHIQ, row0);
      fence_async_smem();
    } else {
      store_phi(sb + OFF_PHIK, keep, row0, lq);
      uint32_t va[14];
#pragma unroll
      for (int j = 0; j < 7; j++) { va[2 * j] = pack_bf16(acc[4 * j], acc[4 * j + 1]); va[2 * j + 1] = pack_bf16(acc[4 * j + 2], acc[4 * j + 3]); }
      store_heads(sb + OFF_VA, 8192, va, row0, lq);
      sts64(sb + OFF_VA + (lq & 1) * 8192 + sw64_off(row0 + 8 * (lq >> 1), 28), 0x00003F80u, 0u);
      fence_async_smem();
      bar_sync(3, 256);
      float kv[16];
      const uint64_t dA = make_desc(sb + OFF_PHIK + mh * 16384, 1024, 1024, 1);
      const uint64_t dB = make_desc(sb + OFF_VA + mh * 8192, 512, 512, 2);
      wg_fence();
      wgmma_ss_n32_ta1_tb1<0>(kv, dA, dB);
#pragma unroll
      for (int ks = 1; ks < 8; ks++) wgmma_ss_n32_ta1_tb1<1>(kv, dA + ks * 128, dB + ks * 64);
      wg_commit();
      wg_wait<0>();
      fence_regs(kv);
      if (lane == 0) mbar_arrive(BAR(B_X0FREE), 1);
      float* dst = g_kvpart + ((size_t)(pt * 16 + 2 * hp + mh) * 64 + rowl) * 32 + 2 * lq;
#pragma unroll
      for (int j = 0; j < 4; j++) {
        *(float2*)(dst + 8 * j) = make_float2(kv[4 * j], kv[4 * j + 1]);
        *(float2*)(dst + 8 * 32 + 8 * j) = make_float2(kv[4 * j + 2], kv[4 * j + 3]);
      }
      __syncwarp();
      if (lane == 0) mbar_arrive(BAR(B_SIG + 1), 1);
    }

    if (tid == 0) PROF_MARK(7);
    if (tid == 256) PROF_MARK(8);
    mbar_wait(BAR(B_B1), 0);
    if (tid == 0) PROF_MARK(9);
    const float* red = (const float*)(sgen + OFF_RED);
    const float ksq = red[0], vmx = red[1];
    const float g0 = ((const float*)(sgen + OFF_GATE))[row0], g1 = ((const float*)(sgen + OFF_GATE))[row0 + 8];
    const float* qsq = (const float*)(sgen + OFF_QSQ);
    const float b0 = sqrtf(qsq[wg * 64 + rowl] * ksq) * 1.02f, b1 = sqrtf(qsq[wg * 64 + rowl + 8] * ksq) * 1.02f;
    const bool bad = !(b0 <= 92.f) || !(b1 <= 92.f) || !(vmx <= 1.0e12f);
    const bool slow = __any_sync(~0u, bar_or(1, 512, bad));
    if (tid == 0) { *(volatile int*)(sgen + OFF_RED + 8) = slow; mbar_arrive(BAR(B_SLOW), 1); }

    uint32_t q[8];
    {
      const uint32_t qa = sb + OFF_QP + wg * 4096;
      const int r = wq * 16 + (lane & 7) + ((lane >> 3) & 1) * 8;
#pragma unroll
      for (int ks = 0; ks < 2; ks++)
        asm volatile("ldmatrix.sync.aligned.m8n8.x4.shared.b16 {%0, %1, %2, %3}, [%4];"
                     : "=r"(q[4 * ks]), "=r"(q[4 * ks + 1]), "=r"(q[4 * ks + 2]), "=r"(q[4 * ks + 3])
                     : "r"(qa + sw64_off(r, ks * 16 + (lane >> 4) * 8)) : "memory");
      if (lq >= 2) {
        q[6] = slow ? 0u : (lq == 2 ? pack_bf16(64.f - b0, 1.f) : 0x3F803F80u);
        q[7] = slow ? 0u : (lq == 2 ? pack_bf16(64.f - b1, 1.f) : 0x3F803F80u);
      }
    }

    const uint64_t dK = make_desc(sb + OFF_RING, 16, 512, 2);
    const uint64_t dV = make_desc(sb + OFF_RING + 4096, 512, 512, 2);
    float o[16];
#pragma unroll
    for (int i = 0; i < 16; i++) o[i] = 0.f;
    int item = 28;

    auto a_final = [&]() {
      float num[16];
      mbar_wait(BAR(B_KVR), 0);
      const uint64_t dA = make_desc(sb + OFF_PHIQ + nh * 16384 + mh * 8192, 16, 1024, 1);
      const uint64_t dB = make_desc(sb + OFF_KVR + nh * 4096, 512, 512, 2);
      wg_fence();
      wgmma_ss_n32_ta0_tb1<0>(num, dA, dB);
#pragma unroll
      for (int ks = 1; ks < 4; ks++) wgmma_ss_n32_ta0_tb1<1>(num, dA + ks * 2, dB + ks * 64);
      wg_commit();
      wg_wait<0>();
      fence_regs(num);
      if (lane == 0) mbar_arrive(BAR(B_X1FREE), 1);
      store_o(num, g0, g1, 1e-6f, 0, pt, mh, 2 * hp + nh, rowl, lane);
      __syncwarp();
      if (lane == 0) mbar_arrive(BAR(B_SIG + 2), 1);
    };

    if (tid == 0) PROF_MARK(10);
    if (!slow) {
      uint32_t c_half = 0x3F003F00u, c_3 = 0x00030003u;
      int slot0 = 28 % RING;
      uint32_t par = (28 / RING) & 1;
#pragma unroll 1
      for (int it = 0; it < 8; it++) {
        if (it == 4) { if (tid == 0) PROF_MARK(11); a_final(); if (tid == 0) PROF_MARK(12); }
        float s[32];
        mbar_wait(BAR(B_FULL + slot0), par);
        wg_fence();
        wgmma_rs_n64_tb0<0>(s, q[0], q[1], q[2], q[3], dK + slot0 * 512);
        wgmma_rs_n64_tb0<1>(s, q[4], q[5], q[6], q[7], dK + slot0 * 512 + 2);
        wg_commit();
#pragma unroll
        for (int u = 0; u < 4; u++) {
          wg_wait<0>();
          fence_regs(s);
          if (lane == 0 && (u > 0 || it > 0)) mbar_arrive(BAR(B_EMPTY + (u > 0 ? slot0 + u - 1 : (slot0 + RING - 1) % RING)), 1);
          uint32_t p[16];
#pragma unroll
          for (int j = 0; j < 8; j++) {
            if ((POLY_PAT >> j) & 1) {
              p[2 * j] = exp2_pair_fma(s[4 * j], s[4 * j + 1], c_half, c_3);
              p[2 * j + 1] = exp2_pair_fma(s[4 * j + 2], s[4 * j + 3], c_half, c_3);
            } else {
              p[2 * j] = pack_bf16(ex2f(s[4 * j]), ex2f(s[4 * j + 1]));
              p[2 * j + 1] = pack_bf16(ex2f(s[4 * j + 2]), ex2f(s[4 * j + 3]));
            }
          }
          if (u < 3) mbar_wait(BAR(B_FULL + slot0 + u + 1), par);
          wg_fence();
#pragma unroll
          for (int ks = 0; ks < 4; ks++)
            wgmma_rs_n32_tb1<1>(o, p[4 * ks], p[4 * ks + 1], p[4 * ks + 2], p[4 * ks + 3], dV + (slot0 + u) * 512 + ks * 64);
          if (u < 3) {
            wgmma_rs_n64_tb0<0>(s, q[0], q[1], q[2], q[3], dK + (slot0 + u + 1) * 512);
            wgmma_rs_n64_tb0<1>(s, q[4], q[5], q[6], q[7], dK + (slot0 + u + 1) * 512 + 2);
          }
          wg_commit();
        }
        slot0 += 4;
        if (slot0 == RING) { slot0 = 0; par ^= 1; }
      }
      item = 60;
      wg_wait<0>();
      fence_regs(o);
      if (lane == 0) mbar_arrive(BAR(B_EMPTY + 59 % RING), 1);
    } else {
      float m0 = -3.0e38f, m1 = -3.0e38f;
#pragma unroll 1
      for (int j64 = 0; j64 < 32; j64++, item++) {
        const int slot = item % RING;
        float s[32];
        mbar_wait(BAR(B_FULL + slot), (item / RING) & 1);
        wg_fence();
        wgmma_rs_n64_tb0<0>(s, q[0], q[1], q[2], q[3], dK + slot * 512);
        wgmma_rs_n64_tb0<1>(s, q[4], q[5], q[6], q[7], dK + slot * 512 + 2);
        wg_commit();
        wg_wait<0>();
        fence_regs(s);
#pragma unroll
        for (int j = 0; j < 8; j++) {
          const float sc = ((POLY_PAT >> j) & 1) ? 0.5f : 1.f;
          m0 = fmaxf(m0, fmaxf(s[4 * j], s[4 * j + 1]) * sc);
          m1 = fmaxf(m1, fmaxf(s[4 * j + 2], s[4 * j + 3]) * sc);
        }
        if (lane == 0) mbar_arrive(BAR(B_EMPTY + slot), 1);
      }
      m0 = quad_max(m0); m1 = quad_max(m1);
      a_final();
      float o2[16];
#pragma unroll
      for (int i = 0; i < 16; i++) o2[i] = 0.f;
#pragma unroll 1
      for (int j64 = 0; j64 < 32; j64++, item++) {
        const int slot = item % RING;
        float s[32];
        mbar_wait(BAR(B_FULL + slot), (item / RING) & 1);
        wg_fence();
        wgmma_rs_n64_tb0<0>(s, q[0], q[1], q[2], q[3], dK + slot * 512);
        wgmma_rs_n64_tb0<1>(s, q[4], q[5], q[6], q[7], dK + slot * 512 + 2);
        wg_commit();
        wg_wait<0>();
        fence_regs(s);
        uint32_t p[16];
#pragma unroll
        for (int j = 0; j < 8; j++) {
          const float sc = ((POLY_PAT >> j) & 1) ? 0.5f : 1.f;
          p[2 * j] = pack_bf16(ex2f(fmaf(s[4 * j], sc, -m0)), ex2f(fmaf(s[4 * j + 1], sc, -m0)));
          p[2 * j + 1] = pack_bf16(ex2f(fmaf(s[4 * j + 2], sc, -m1)), ex2f(fmaf(s[4 * j + 3], sc, -m1)));
        }
        wg_fence();
#pragma unroll
        for (int ks = 0; ks < 4; ks++)
          wgmma_rs_n32_tb1<1>(o2, p[4 * ks], p[4 * ks + 1], p[4 * ks + 2], p[4 * ks + 3], dV + slot * 512 + ks * 64);
        wg_commit();
        wg_wait<0>();
        fence_regs(o2);
        if (lane == 0) mbar_arrive(BAR(B_EMPTY + slot), 1);
      }
#pragma unroll
      for (int i = 0; i < 16; i++) o[i] = o2[i];
    }

    if (tid == 0) PROF_MARK(13);
    store_o(o, 1.f - g0, 1.f - g1, 0.f, 1, pt, mh, 2 * hp + nh, rowl, lane);
    __syncwarp();
    if (lane == 0) mbar_arrive(BAR(B_SIG + 3), 1);
    if (tid == 0) PROF_MARK(14);

    if (nh == 0) {
      const uint64_t dRingK = make_desc(sb + OFF_RING, 16, 1024, 1);
      const uint64_t dWo = make_desc(sb + OFF_WOA, 1024, 1024, 1);
      int prev = -1;
#pragma unroll
      for (int bc = 0; bc < 14; bc++) {
        const int itm = item + 2 * bc + mh, slot = itm % RING;
        if (bc == 0) mbar_wait(BAR(B_WOA), 0);
        if (bc == 7) { if (tid == 0) PROF_MARK(15); mbar_wait(BAR(B_WOB), 0); }
        if (bc == 8) { if (tid == 0) PROF_MARK(16); }
        mbar_wait(BAR(B_FULL + slot), (itm / RING) & 1);
        wg_fence();
#pragma unroll
        for (int ks = 0; ks < 4; ks++) {
          if (bc == 0 && ks == 0) wgmma_ss_n56_ta0_tb1<0>(acc, dRingK + slot * 512, dWo);
          else wgmma_ss_n56_ta0_tb1<1>(acc, dRingK + slot * 512 + ks * 2, dWo + bc * 512 + ks * 128);
        }
        wg_commit();
        if (bc > 0) {
          wg_wait<1>();
          if (lane == 0) mbar_arrive(BAR(B_EMPTY + prev), 4);
        }
        prev = slot;
      }
      wg_wait<0>();
      fence_regs(acc);
      if (tid == 0) PROF_MARK(17);
      __nv_bfloat16* op = prm.out + (size_t)(pt * 128 + row0) * DM + hp * 56 + 2 * lq;
#pragma unroll
      for (int j = 0; j < 7; j++) {
        *(uint32_t*)(op + 8 * j) = pack_bf16(acc[4 * j], acc[4 * j + 1]);
        *(uint32_t*)(op + 8 * DM + 8 * j) = pack_bf16(acc[4 * j + 2], acc[4 * j + 3]);
      }
      if (tid == 0) { PROF_MARK(18); PROF_CLK(31); }
      if (tid == 0) {
        unsigned prevd = atomicAdd(&g_cnt[C_DONE * 32], 1u);
        if (prevd == NCTA - 1) {
          for (int i = 0; i < C_N; i++) g_cnt[i * 32] = 0;
        }
      }
    }
  }
}

typedef CUresult (*EncodeFn)(CUtensorMap*, CUtensorMapDataType, cuuint32_t, void*, const cuuint64_t*, const cuuint64_t*,
                             const cuuint32_t*, const cuuint32_t*, CUtensorMapInterleave, CUtensorMapSwizzle,
                             CUtensorMapL2promotion, CUtensorMapFloatOOBfill);

void make_map(EncodeFn enc, CUtensorMap* tm, const void* ptr, uint64_t cols, uint64_t rows, uint32_t box_rows) {
  cuuint64_t dims[2] = {cols, rows};
  cuuint64_t strides[1] = {cols * 2};
  cuuint32_t box[2] = {64, box_rows};
  cuuint32_t es[2] = {1, 1};
  enc(tm, CU_TENSOR_MAP_DATA_TYPE_BFLOAT16, 2, const_cast<void*>(ptr), dims, strides, box, es, CU_TENSOR_MAP_INTERLEAVE_NONE,
      CU_TENSOR_MAP_SWIZZLE_128B, CU_TENSOR_MAP_L2_PROMOTION_L2_128B, CU_TENSOR_MAP_FLOAT_OOB_FILL_NONE);
}

}

extern "C" void kernel_launch(void* const* d_in, const int* in_sizes, int n_in, void* d_out, int out_size) {
  (void)in_sizes; (void)n_in; (void)out_size;
  static EncodeFn enc = nullptr;
  if (!enc) {
    void* fn = nullptr;
    cudaDriverEntryPointQueryResult qr;
    cudaGetDriverEntryPoint("cuTensorMapEncodeTiled", &fn, cudaEnableDefault, &qr);
    enc = (EncodeFn)fn;
    cudaFuncSetAttribute(fused_kernel, cudaFuncAttributeMaxDynamicSharedMemorySize, SMEM_BYTES);
  }
  CUtensorMap tm_x, tm_wqkv, tm_wq, tm_woa, tm_wob;
  make_map(enc, &tm_x, d_in[0], DM, S_LEN, 128);
  make_map(enc, &tm_wqkv, d_in[1], 3 * DM, DM, 64);
  make_map(enc, &tm_wq, d_in[5], DM, DM, 64);
  make_map(enc, &tm_woa, d_in[3], DM, DM, 64);
  make_map(enc, &tm_wob, d_in[8], DM, DM, 64);
  Params prm;
  prm.w_phi = (const __nv_bfloat16*)d_in[2];
  prm.wk = (const __nv_bfloat16*)d_in[6];
  prm.wv = (const __nv_bfloat16*)d_in[7];
  prm.gate_w = (const __nv_bfloat16*)d_in[9];
  prm.out = (__nv_bfloat16*)d_out;
  fused_kernel<<<NCTA, NTHREADS, SMEM_BYTES>>>(tm_x, tm_wqkv, tm_wq, tm_woa, tm_wob, prm);
}
```

```cpp
#include <cuda_runtime.h>
#include <cuda_bf16.h>
#include <cuda.h>
#include <stdint.h>

namespace {

constexpr int S_LEN = 2048, DM = 448, DH = 28;
constexpr int NCTA = 128;
constexpr int NTHREADS = 640;
constexpr int RING = 12;
constexpr uint32_t POLY_PAT = 0x57;

constexpr int OFF_X = 0;
constexpr int OFF_PHIK = 0;
constexpr int OFF_VA = 32768;
constexpr int OFF_WOA = 0;
constexpr int OFF_PHIQ = 57344;
constexpr int OFF_KVR = 90112;
constexpr int OFF_QP = 98304;
constexpr int OFF_WOB = 57344;
constexpr int OFF_RING = 114688;
constexpr int OFF_WBD = 212992;
constexpr int OFF_SLC = 221184;
constexpr int OFF_QSQ = 228352;
constexpr int OFF_GATE = 229376;
constexpr int OFF_RED = 229888;
constexpr int OFF_BAR = 229952;
constexpr int SMEM_BYTES = 230400 + 1024;

constexpr int B_FULL = 0, B_EMPTY = RING, B_X = 2 * RING, B_WOA = B_X + 7, B_WOB = B_WOA + 1, B_KVR = B_WOA + 2,
              B_X0FREE = B_WOA + 3, B_X1FREE = B_WOA + 4, B_B1 = B_WOA + 5, B_SLOW = B_WOA + 6, B_BUILD = B_WOA + 7,
              B_SIG = B_WOA + 8;

constexpr int C_KV = 0, C_PART = 1, C_RED = 2, C_DONE = 3, C_OA = 4, C_OB = 20, C_N = 36;

__device__ __align__(1024) uint8_t g_kv_img[32 * 8192];
__device__ float g_ksq[512];
__device__ float g_vmx[512];
__device__ float g_gate[S_LEN];
__device__ __align__(16) float g_kvpart[16 * 16 * 64 * 32];
__device__ __align__(1024) uint8_t g_kvr_img[16 * 4096];
__device__ __align__(1024) uint8_t g_o_img[2 * 16 * 14 * 8192];
__device__ unsigned g_cnt[C_N * 32];

#define PROF2(i) do { } while (0)
#define PROF_CLK(i) do { } while (0)
#define PROF_MARK(i) do { } while (0)
__device__ __forceinline__ uint32_t smem_u32(const void* p) { return (uint32_t)__cvta_generic_to_shared(p); }
__device__ __forceinline__ void mbar_init(uint32_t a, int cnt) {
  asm volatile("mbarrier.init.shared::cta.b64 [%0], %1;" ::"r"(a), "r"(cnt) : "memory");
}
__device__ __forceinline__ void mbar_expect_tx(uint32_t a, uint32_t bytes) {
  asm volatile("mbarrier.arrive.expect_tx.shared::cta.b64 _, [%0], %1;" ::"r"(a), "r"(bytes) : "memory");
}
__device__ __forceinline__ void mbar_arrive(uint32_t a, uint32_t cnt) {
  asm volatile("mbarrier.arrive.shared::cta.b64 _, [%0], %1;" ::"r"(a), "r"(cnt) : "memory");
}
__device__ __forceinline__ void mbar_wait(uint32_t a, uint32_t parity) {
  asm volatile(
      "{\n.reg .pred p;\n.reg .u32 c;\nmov.u32 c, 0;\n"
      "W_%=:\nmbarrier.try_wait.parity.shared::cta.b64 p, [%0], %1;\n"
      "add.u32 c, c, 1;\nsetp.lt.and.u32 p, c, 0x1000000, !p;\n@p bra W_%=;\n}"
      ::"r"(a), "r"(parity) : "memory");
}
__device__ __forceinline__ void tma_2d(uint32_t dst, const CUtensorMap* tm, int c0, int c1, uint32_t bar) {
  asm volatile("cp.async.bulk.tensor.2d.shared::cluster.global.mbarrier::complete_tx::bytes [%0], [%1, {%3, %4}], [%2];"
               ::"r"(dst), "l"(tm), "r"(bar), "r"(c0), "r"(c1) : "memory");
}
__device__ __forceinline__ void bulk_g2s(uint32_t dst, const void* src, uint32_t bytes, uint32_t bar) {
  asm volatile("cp.async.bulk.shared::cluster.global.mbarrier::complete_tx::bytes [%0], [%1], %2, [%3];"
               ::"r"(dst), "l"(src), "r"(bytes), "r"(bar) : "memory");
}
__device__ __forceinline__ void cp_async8(uint32_t dst, const void* src) {
  asm volatile("cp.async.ca.shared.global [%0], [%1], 8;" ::"r"(dst), "l"(src) : "memory");
}
__device__ __forceinline__ void fence_async_smem() { asm volatile("fence.proxy.async.shared::cta;" ::: "memory"); }
__device__ __forceinline__ void fence_async_all() { asm volatile("fence.proxy.async;" ::: "memory"); }
__device__ __forceinline__ void bar_sync(int id, int n) { asm volatile("bar.sync %0, %1;" ::"r"(id), "r"(n) : "memory"); }
__device__ __forceinline__ bool bar_or(int id, int n, bool v) {
  uint32_t r;
  asm volatile("{\n.reg .pred p, q;\nsetp.ne.u32 p, %3, 0;\nbar.red.or.pred q, %1, %2, p;\nselp.u32 %0, 1, 0, q;\n}"
               : "=r"(r) : "r"(id), "r"(n), "r"((uint32_t)v) : "memory");
  return r != 0;
}
__device__ __forceinline__ void cnt_arrive(int idx) {
  asm volatile("red.release.gpu.global.add.u32 [%0], 1;" ::"l"(&g_cnt[idx * 32]) : "memory");
}
__device__ __forceinline__ void cnt_wait(int idx, unsigned target) {
  unsigned v, n = 0;
#pragma unroll 1
  do {
    asm volatile("ld.acquire.gpu.global.u32 %0, [%1];" : "=r"(v) : "l"(&g_cnt[idx * 32]) : "memory");
  } while (v < target && ++n < (1u << 22));
}
__device__ __forceinline__ void wg_fence() { asm volatile("wgmma.fence.sync.aligned;" ::: "memory"); }
__device__ __forceinline__ void wg_commit() { asm volatile("wgmma.commit_group.sync.aligned;" ::: "memory"); }
template <int N> __device__ __forceinline__ void wg_wait() { asm volatile("wgmma.wait_group.sync.aligned %0;" ::"n"(N) : "memory"); }
template <int N> __device__ __forceinline__ void fence_regs(float (&d)[N]) {
#pragma unroll
  for (int i = 0; i < N; i++) asm volatile("" : "+f"(d[i])::"memory");
}
__device__ __forceinline__ uint64_t make_desc(uint32_t saddr, uint32_t lbo, uint32_t sbo, uint32_t swz) {
  return (uint64_t)((saddr & 0x3FFFF) >> 4) | ((uint64_t)(lbo >> 4) << 16) | ((uint64_t)(sbo >> 4) << 32) | ((uint64_t)swz << 62);
}
__device__ __forceinline__ float ex2f(float x) { float y; asm("ex2.approx.ftz.f32 %0, %1;" : "=f"(y) : "f"(x)); return y; }
__device__ __forceinline__ float rcpf(float x) { float y; asm("rcp.approx.ftz.f32 %0, %1;" : "=f"(y) : "f"(x)); return y; }
__device__ __forceinline__ uint32_t pack_bf16(float lo, float hi) {
  uint32_t r; asm("cvt.rn.bf16x2.f32 %0, %1, %2;" : "=r"(r) : "f"(hi), "f"(lo)); return r;
}
__device__ __forceinline__ uint32_t lop_and_or(uint32_t a, uint32_t m, uint32_t c) {
  uint32_t r; asm("lop3.b32 %0, %1, %2, %3, 0xEA;" : "=r"(r) : "r"(a), "r"(m), "r"(c)); return r;
}
__device__ __forceinline__ void sts32(uint32_t a, uint32_t v) { asm volatile("st.shared.b32 [%0], %1;" ::"r"(a), "r"(v) : "memory"); }
__device__ __forceinline__ void sts64(uint32_t a, uint32_t v0, uint32_t v1) { asm volatile("st.shared.v2.b32 [%0], {%1, %2};" ::"r"(a), "r"(v0), "r"(v1) : "memory"); }
__device__ __forceinline__ void sts128(uint32_t a, uint4 v) {
  asm volatile("st.shared.v4.b32 [%0], {%1, %2, %3, %4};" ::"r"(a), "r"(v.x), "r"(v.y), "r"(v.z), "r"(v.w) : "memory");
}
__device__ __forceinline__ float4 ldcg_f4(const float* p) {
  float4 v; asm volatile("ld.global.cg.v4.f32 {%0, %1, %2, %3}, [%4];" : "=f"(v.x), "=f"(v.y), "=f"(v.z), "=f"(v.w) : "l"(p) : "memory"); return v;
}
__device__ __forceinline__ float quad_sum(float v) { v += __shfl_xor_sync(~0u, v, 1); v += __shfl_xor_sync(~0u, v, 2); return v; }
__device__ __forceinline__ float quad_max(float v) { v = fmaxf(v, __shfl_xor_sync(~0u, v, 1)); v = fmaxf(v, __shfl_xor_sync(~0u, v, 2)); return v; }

template <int SD> __device__ __forceinline__ void wgmma_ss_n56_ta0_tb1(float (&d)[28], uint64_t da, uint64_t db) {
  asm volatile("wgmma.mma_async.sync.aligned.m64n56k16.f32.bf16.bf16 {%0, %1, %2, %3, %4, %5, %6, %7, %8, %9, %10, %11, %12, %13, %14, %15, %16, %17, %18, %19, %20, %21, %22, %23, %24, %25, %26, %27}, %28, %29, %30, 1, 1, 0, 1;\n"
    : "+f"(d[0]), "+f"(d[1]), "+f"(d[2]), "+f"(d[3]), "+f"(d[4]), "+f"(d[5]), "+f"(d[6]), "+f"(d[7]), "+f"(d[8]), "+f"(d[9]), "+f"(d[10]), "+f"(d[11]), "+f"(d[12]), "+f"(d[13]), "+f"(d[14]), "+f"(d[15]), "+f"(d[16]), "+f"(d[17]), "+f"(d[18]), "+f"(d[19]), "+f"(d[20]), "+f"(d[21]), "+f"(d[22]), "+f"(d[23]), "+f"(d[24]), "+f"(d[25]), "+f"(d[26]), "+f"(d[27])
    : "l"(da), "l"(db), "n"(SD));
}
template <int SD> __device__ __forceinline__ void wgmma_ss_n8_ta0_tb1(float (&d)[4], uint64_t da, uint64_t db) {
  asm volatile("wgmma.mma_async.sync.aligned.m64n8k16.f32.bf16.bf16 {%0, %1, %2, %3}, %4, %5, %6, 1, 1, 0, 1;\n"
    : "+f"(d[0]), "+f"(d[1]), "+f"(d[2]), "+f"(d[3])
    : "l"(da), "l"(db), "n"(SD));
}
template <int SD> __device__ __forceinline__ void wgmma_rs_n64_tb1(float (&d)[32], uint32_t a0, uint32_t a1, uint32_t a2, uint32_t a3, uint64_t db) {
  asm volatile("wgmma.mma_async.sync.aligned.m64n64k16.f32.bf16.bf16 {%0, %1, %2, %3, %4, %5, %6, %7, %8, %9, %10, %11, %12, %13, %14, %15, %16, %17, %18, %19, %20, %21, %22, %23, %24, %25, %26, %27, %28, %29, %30, %31}, {%32, %33, %34, %35}, %36, %37, 1, 1, 1;\n"
    : "+f"(d[0]), "+f"(d[1]), "+f"(d[2]), "+f"(d[3]), "+f"(d[4]), "+f"(d[5]), "+f"(d[6]), "+f"(d[7]), "+f"(d[8]), "+f"(d[9]), "+f"(d[10]), "+f"(d[11]), "+f"(d[12]), "+f"(d[13]), "+f"(d[14]), "+f"(d[15]), "+f"(d[16]), "+f"(d[17]), "+f"(d[18]), "+f"(d[19]), "+f"(d[20]), "+f"(d[21]), "+f"(d[22]), "+f"(d[23]), "+f"(d[24]), "+f"(d[25]), "+f"(d[26]), "+f"(d[27]), "+f"(d[28]), "+f"(d[29]), "+f"(d[30]), "+f"(d[31])
    : "r"(a0), "r"(a1), "r"(a2), "r"(a3), "l"(db), "n"(SD));
}
template <int SD> __device__ __forceinline__ void wgmma_ss_n32_ta1_tb1(float (&d)[16], uint64_t da, uint64_t db) {
  asm volatile("wgmma.mma_async.sync.aligned.m64n32k16.f32.bf16.bf16 {%0, %1, %2, %3, %4, %5, %6, %7, %8, %9, %10, %11, %12, %13, %14, %15}, %16, %17, %18, 1, 1, 1, 1;\n"
    : "+f"(d[0]), "+f"(d[1]), "+f"(d[2]), "+f"(d[3]), "+f"(d[4]), "+f"(d[5]), "+f"(d[6]), "+f"(d[7]), "+f"(d[8]), "+f"(d[9]), "+f"(d[10]), "+f"(d[11]), "+f"(d[12]), "+f"(d[13]), "+f"(d[14]), "+f"(d[15])
    : "l"(da), "l"(db), "n"(SD));
}
template <int SD> __device__ __forceinline__ void wgmma_ss_n32_ta0_tb1(float (&d)[16], uint64_t da, uint64_t db) {
  asm volatile("wgmma.mma_async.sync.aligned.m64n32k16.f32.bf16.bf16 {%0, %1, %2, %3, %4, %5, %6, %7, %8, %9, %10, %11, %12, %13, %14, %15}, %16, %17, %18, 1, 1, 0, 1;\n"
    : "+f"(d[0]), "+f"(d[1]), "+f"(d[2]), "+f"(d[3]), "+f"(d[4]), "+f"(d[5]), "+f"(d[6]), "+f"(d[7]), "+f"(d[8]), "+f"(d[9]), "+f"(d[10]), "+f"(d[11]), "+f"(d[12]), "+f"(d[13]), "+f"(d[14]), "+f"(d[15])
    : "l"(da), "l"(db), "n"(SD));
}
template <int SD> __device__ __forceinline__ void wgmma_rs_n64_tb0(float (&d)[32], uint32_t a0, uint32_t a1, uint32_t a2, uint32_t a3, uint64_t db) {
  asm volatile("wgmma.mma_async.sync.aligned.m64n64k16.f32.bf16.bf16 {%0, %1, %2, %3, %4, %5, %6, %7, %8, %9, %10, %11, %12, %13, %14, %15, %16, %17, %18, %19, %20, %21, %22, %23, %24, %25, %26, %27, %28, %29, %30, %31}, {%32, %33, %34, %35}, %36, %37, 1, 1, 0;\n"
    : "+f"(d[0]), "+f"(d[1]), "+f"(d[2]), "+f"(d[3]), "+f"(d[4]), "+f"(d[5]), "+f"(d[6]), "+f"(d[7]), "+f"(d[8]), "+f"(d[9]), "+f"(d[10]), "+f"(d[11]), "+f"(d[12]), "+f"(d[13]), "+f"(d[14]), "+f"(d[15]), "+f"(d[16]), "+f"(d[17]), "+f"(d[18]), "+f"(d[19]), "+f"(d[20]), "+f"(d[21]), "+f"(d[22]), "+f"(d[23]), "+f"(d[24]), "+f"(d[25]), "+f"(d[26]), "+f"(d[27]), "+f"(d[28]), "+f"(d[29]), "+f"(d[30]), "+f"(d[31])
    : "r"(a0), "r"(a1), "r"(a2), "r"(a3), "l"(db), "n"(SD));
}
template <int SD> __device__ __forceinline__ void wgmma_rs_n32_tb1(float (&d)[16], uint32_t a0, uint32_t a1, uint32_t a2, uint32_t a3, uint64_t db) {
  asm volatile("wgmma.mma_async.sync.aligned.m64n32k16.f32.bf16.bf16 {%0, %1, %2, %3, %4, %5, %6, %7, %8, %9, %10, %11, %12, %13, %14, %15}, {%16, %17, %18, %19}, %20, %21, 1, 1, 1;\n"
    : "+f"(d[0]), "+f"(d[1]), "+f"(d[2]), "+f"(d[3]), "+f"(d[4]), "+f"(d[5]), "+f"(d[6]), "+f"(d[7]), "+f"(d[8]), "+f"(d[9]), "+f"(d[10]), "+f"(d[11]), "+f"(d[12]), "+f"(d[13]), "+f"(d[14]), "+f"(d[15])
    : "r"(a0), "r"(a1), "r"(a2), "r"(a3), "l"(db), "n"(SD));
}

__device__ __forceinline__ uint32_t sw64_off(int row, int d) { return row * 64 + ((((d >> 3) ^ (row >> 1)) & 3) << 4) + (d & 7) * 2; }

__device__ __forceinline__ uint32_t exp2_pair_fma(float t0, float t1, uint32_t c_half, uint32_t c_3) {
  uint32_t y0, y;
  asm("prmt.b32 %0, %1, %2, 0x6521;" : "=r"(y0) : "r"(__float_as_uint(t0)), "r"(__float_as_uint(t1)));
  uint32_t h = lop_and_or(y0, 0x007F007Fu, c_half);
  uint32_t e = lop_and_or(y0, 0xFF80FF80u, c_3);
  asm("fma.rn.bf16x2 %0, %1, %2, %3;" : "=r"(y) : "r"(y0), "r"(h), "r"(e));
  return y;
}

__device__ __forceinline__ void phi_from_acc(const float (&acc)[28], uint32_t sb, uint32_t (&ph)[32], int lq) {
  uint32_t a[16];
#pragma unroll
  for (int i = 0; i < 14; i++) a[i] = pack_bf16(acc[2 * i], acc[2 * i + 1]);
  a[14] = pack_bf16(acc[1], acc[0]);
  a[15] = pack_bf16(acc[3], acc[2]);
  float p[32];
  const uint64_t dWbd = make_desc(sb + OFF_WBD, 1024, 1024, 1);
  wg_fence();
  wgmma_rs_n64_tb1<0>(p, a[0], a[1], a[2], a[3], dWbd);
  wgmma_rs_n64_tb1<1>(p, a[4], a[5], a[6], a[7], dWbd + 128);
  wgmma_rs_n64_tb1<1>(p, a[8], a[9], a[10], a[11], dWbd + 256);
  wgmma_rs_n64_tb1<1>(p, a[12], a[13], a[14], a[15], dWbd + 384);
  wg_commit();
  wg_wait<0>();
  fence_regs(p);
  const float L2E = 1.4426950408889634f;
  const bool tail_ok = lq < 2;
  float v[16];
#pragma unroll
  for (int i = 0; i < 16; i++) v[i] = p[i];
#pragma unroll 1
  for (int e = 0; e < 2; e++) {
    float mx[2], mn[2], b[16], sa[2], sn[2];
#pragma unroll
    for (int r = 0; r < 2; r++) {
      const int o = 2 * r;
      if (!tail_ok) { v[o + 12] = v[o]; v[o + 13] = v[o]; }
      mx[r] = fmaxf(fmaxf(fmaxf(v[o], v[o + 1]), fmaxf(v[o + 4], v[o + 5])), fmaxf(fmaxf(v[o + 8], v[o + 9]), fmaxf(v[o + 12], v[o + 13])));
      mn[r] = fminf(fminf(fminf(v[o], v[o + 1]), fminf(v[o + 4], v[o + 5])), fminf(fminf(v[o + 8], v[o + 9]), fminf(v[o + 12], v[o + 13])));
    }
#pragma unroll
    for (int o = 1; o <= 2; o <<= 1)
#pragma unroll
      for (int r = 0; r < 2; r++) { mx[r] = fmaxf(mx[r], __shfl_xor_sync(~0u, mx[r], o)); mn[r] = fminf(mn[r], __shfl_xor_sync(~0u, mn[r], o)); }
#pragma unroll
    for (int r = 0; r < 2; r++) {
      const int o = 2 * r;
      const float cx = -mx[r] * L2E, cn = mn[r] * L2E;
#pragma unroll
      for (int i = 0; i < 8; i++) {
        const int k = o + 4 * (i >> 1) + (i & 1);
        b[k] = ex2f(fmaf(v[k], -L2E, cn));
        v[k] = ex2f(fmaf(v[k], L2E, cx));
      }
      if (!tail_ok) { v[o + 12] = v[o + 13] = b[o + 12] = b[o + 13] = 0.f; }
      sa[r] = ((v[o] + v[o + 1]) + (v[o + 4] + v[o + 5])) + ((v[o + 8] + v[o + 9]) + (v[o + 12] + v[o + 13]));
      sn[r] = ((b[o] + b[o + 1]) + (b[o + 4] + b[o + 5])) + ((b[o + 8] + b[o + 9]) + (b[o + 12] + b[o + 13]));
    }
#pragma unroll
    for (int o = 1; o <= 2; o <<= 1)
#pragma unroll
      for (int r = 0; r < 2; r++) { sa[r] += __shfl_xor_sync(~0u, sa[r], o); sn[r] += __shfl_xor_sync(~0u, sn[r], o); }
#pragma unroll
    for (int i = 0; i < 16; i++) ph[i] = ph[16 + i];
#pragma unroll
    for (int r = 0; r < 2; r++) {
      const float ra = rcpf(sa[r]), rb = rcpf(sn[r]);
#pragma unroll
      for (int jj = 0; jj < 4; jj++) {
        ph[16 + jj * 2 + r] = pack_bf16(v[2 * r + 4 * jj] * ra, v[2 * r + 4 * jj + 1] * ra);
        ph[16 + (4 + jj) * 2 + r] = pack_bf16(b[2 * r + 4 * jj] * rb, b[2 * r + 4 * jj + 1] * rb);
      }
    }
#pragma unroll
    for (int i = 0; i < 16; i++) v[i] = p[16 + i];
  }
}

__device__ __forceinline__ void store_phi(uint32_t base, const uint32_t (&ph)[32], int row0, int lq) {
  const uint32_t rb = base + row0 * 128 + lq * 4 + ((row0 & 7) << 4);
#pragma unroll
  for (int ch = 0; ch < 8; ch++) {
    const uint32_t a = rb ^ (ch << 4);
#pragma unroll
    for (int e = 0; e < 2; e++)
#pragma unroll
      for (int rr = 0; rr < 2; rr++) sts32(a + e * 16384 + rr * 1024, ph[e * 16 + ch * 2 + rr]);
  }
}

__device__ __forceinline__ void store_heads(uint32_t base, const uint32_t (&a)[14], int row0, int lq) {
  const uint32_t rb = base + row0 * 64 + (((row0 >> 1) & 3) << 4);
  const uint32_t b0 = rb + lq * 4;
  const uint32_t b1 = (rb + 8192 + ((lq * 4 + 8) & 15)) ^ ((lq >> 1) << 4);
#pragma unroll
  for (int j = 0; j < 7; j++) {
    uint32_t ad;
    if (j < 3) ad = b0 ^ (j << 4);
    else if (j == 3) ad = (lq < 2) ? (b0 ^ 48u) : (b1 ^ 16u);
    else ad = (lq < 2) ? (b1 ^ ((j - 4) << 4)) : ((b1 ^ 16u) ^ ((j - 3) << 4));
    sts32(ad, a[2 * j]);
    sts32(ad + 512, a[2 * j + 1]);
  }
}

struct Params {
  const __nv_bfloat16* w_phi;
  const __nv_bfloat16* wk;
  const __nv_bfloat16* wv;
  const __nv_bfloat16* gate_w;
  __nv_bfloat16* out;
};

__global__ void __launch_bounds__(NTHREADS, 1)
fused_kernel(const __grid_constant__ CUtensorMap tm_x, const __grid_constant__ CUtensorMap tm_wqkv,
             const __grid_constant__ CUtensorMap tm_wq, const __grid_constant__ CUtensorMap tm_woa,
             const __grid_constant__ CUtensorMap tm_wob, const Params prm) {
  extern __shared__ uint8_t smem_raw[];
  const uint32_t sb = (smem_u32(smem_raw) + 1023u) & ~1023u;
  uint8_t* sgen = smem_raw + (sb - smem_u32(smem_raw));
  const int tid = threadIdx.x, lane = tid & 31;
  const int warp = __shfl_sync(~0u, tid >> 5, 0), wg = warp >> 2;
  const int pt = blockIdx.x >> 3, hp = blockIdx.x & 7;
  const uint32_t bars = sb + OFF_BAR;
  auto BAR = [&](int i) { return bars + 8u * i; };

  if (tid == 0) { PROF_MARK(0); PROF_CLK(30); }
  if (warp == 16) {
#pragma unroll 1
    for (int i = lane; i < B_SIG + 4; i += 32) {
      int cnt = 1;
      if ((i >= B_EMPTY && i < B_X) || i == B_X1FREE || i >= B_SIG + 2) cnt = 16;
      if (i == B_X0FREE || i == B_SIG || i == B_SIG + 1) cnt = 8;
      if (i == B_B1) cnt = 2;
      if (i == B_BUILD) cnt = 3;
      mbar_init(BAR(i), cnt);
    }
    asm volatile("fence.mbarrier_init.release.cluster;" ::: "memory");
    fence_async_smem();
    __syncwarp();
    asm volatile("bar.arrive 0, %0;" ::"n"(NTHREADS) : "memory");
  } else {
    bar_sync(0, NTHREADS);
  }

  if (wg == 4) {
    asm volatile("setmaxnreg.dec.sync.aligned.u32 32;");
    if (warp == 16) {
      if (lane == 0) {
        int slot = 0;
        uint32_t par = 1;
        auto acquire = [&]() -> uint32_t {
          mbar_wait(BAR(B_EMPTY + slot), par);
          mbar_expect_tx(BAR(B_FULL + slot), 8192);
          uint32_t cur = slot;
          if (++slot == RING) { slot = 0; par ^= 1; }
          return cur;
        };
#pragma unroll 1
        for (int i = 0; i < 14; i++) {
          const int c = i < 7 ? i : i - 7;
          if (i < 7) {
            mbar_expect_tx(BAR(B_X + c), 16384);
            tma_2d(sb + OFF_X + c * 16384, &tm_x, c * 64, pt * 128, BAR(B_X + c));
          }
          uint32_t sl = acquire();
          tma_2d(sb + OFF_RING + sl * 8192, i < 7 ? &tm_wq : &tm_wqkv, hp * 56, c * 64, BAR(B_FULL + sl));
          sl = acquire();
          tma_2d(sb + OFF_RING + sl * 8192, &tm_wqkv, (i < 7 ? DM : 2 * DM) + hp * 56, c * 64, BAR(B_FULL + sl));
        }
        PROF_MARK(20);
#pragma unroll 1
        for (int ph = 0; ph < 4; ph++) {
          const uint8_t* src = g_kv_img;
          int n = 32;
          if (ph == 0) cnt_wait(C_KV, NCTA);
          else if (ph == 1) {
            mbar_wait(BAR(B_SLOW), 0);
            if (!*(volatile int*)(sgen + OFF_RED + 8)) continue;
          } else {
            cnt_wait((ph == 3 ? C_OB : C_OA) + pt, 8);
            src = g_o_img + (size_t)(((ph - 2) * 16 + pt) * 14) * 8192;
            n = 14;
          }
          PROF_MARK(21 + (ph ? 5 : 0));
          fence_async_all();
#pragma unroll 1
          for (int j = 0; j < n; j++) {
            uint32_t sl = acquire();
            bulk_g2s(sb + OFF_RING + sl * 8192, src + j * 8192, 8192, BAR(B_FULL + sl));
          }
        }
      }
    } else {
      {
        const int t = tid - 544;
#pragma unroll 1
        for (int i = t; i < 512; i += 96) sts128(sb + OFF_WBD + i * 16, make_uint4(0, 0, 0, 0));
        bar_sync(4, 96);
#pragma unroll 1
        for (int k = t; k < DM; k += 96) {
          const __nv_bfloat16* src = (hp < 4 ? prm.wk : prm.wv) + k * DH + (hp & 3) * 8;
          cp_async8(sb + OFF_SLC + k * 16, src);
          if ((hp & 3) != 3) cp_async8(sb + OFF_SLC + k * 16 + 8, src + 4);
          else sts64(sb + OFF_SLC + k * 16 + 8, hp == 3 ? (uint32_t)((const unsigned short*)prm.gate_w)[k] : 0u, 0u);
          if (k < 392) {
            const int row = k / 7, n = (row >= DH ? 32 : 0) + (k % 7) * 4;
            cp_async8(sb + OFF_WBD + row * 128 + (((n >> 3) ^ (row & 7)) << 4) + (n & 4) * 2, prm.w_phi + 2 * hp * DH * DH + k * 4);
          }
        }
        asm volatile("cp.async.wait_all;" ::: "memory");
        fence_async_smem();
        __syncwarp();
        if (lane == 0) mbar_arrive(BAR(B_BUILD), 1);
      }
      if (warp == 18) {
        if (lane == 0) {
          mbar_wait(BAR(B_SIG + 0), 0); cnt_arrive(C_KV);
          mbar_wait(BAR(B_SIG + 1), 0); cnt_arrive(C_PART);
          mbar_wait(BAR(B_SIG + 2), 0); cnt_arrive(C_OA + pt);
          mbar_wait(BAR(B_SIG + 3), 0); cnt_arrive(C_OB + pt);
        }
      } else if (warp == 19) {
        if (lane == 0) {
          cnt_wait(C_KV, NCTA);
          fence_async_all();
          mbar_expect_tx(BAR(B_B1), 512);
          bulk_g2s(sb + OFF_GATE, g_gate + pt * 128, 512, BAR(B_B1));
        }
        __syncwarp();
        float ksq = 0.f, vmx = 0.f;
#pragma unroll 1
        for (int sl = 0; sl < 4; sl++) {
          float4 a = ldcg_f4(g_ksq + sl * 128 + lane * 4), b = ldcg_f4(g_vmx + sl * 128 + lane * 4);
          float m = fmaxf(fmaxf(a.x, a.y), fmaxf(a.z, a.w));
#pragma unroll
          for (int o = 16; o > 0; o >>= 1) m = fmaxf(m, __shfl_xor_sync(~0u, m, o));
          ksq += m;
          vmx = fmaxf(vmx, fmaxf(fmaxf(b.x, b.y), fmaxf(b.z, b.w)));
        }
#pragma unroll
        for (int o = 16; o > 0; o >>= 1) vmx = fmaxf(vmx, __shfl_xor_sync(~0u, vmx, o));
        if (lane == 0) {
          float* red = (float*)(sgen + OFF_RED);
          red[0] = ksq; red[1] = vmx;
          mbar_arrive(BAR(B_B1), 1);
        }
      } else {
        if (lane == 0) {
          mbar_wait(BAR(B_X0FREE), 0);
          mbar_expect_tx(BAR(B_WOA), 57344);
#pragma unroll 1
          for (int c = 0; c < 7; c++) tma_2d(sb + OFF_WOA + c * 8192, &tm_woa, hp * 56, c * 64, BAR(B_WOA));
          PROF_MARK(22);
          cnt_wait(C_PART, NCTA);
          PROF_MARK(23);
        }
        __syncwarp();
        {
          const int head = blockIdx.x >> 3, f = (blockIdx.x & 7) * 8 + (lane >> 2), d0 = (lane & 3) * 8;
          const float* src = g_kvpart + ((size_t)head * 64 + f) * 32 + d0;
          float4 s0 = make_float4(0, 0, 0, 0), s1 = s0;
#pragma unroll 2
          for (int t = 0; t < 16; t++) {
            float4 a = ldcg_f4(src + (size_t)t * 16 * 64 * 32), b = ldcg_f4(src + (size_t)t * 16 * 64 * 32 + 4);
            s0.x += a.x; s0.y += a.y; s0.z += a.z; s0.w += a.w; s1.x += b.x; s1.y += b.y; s1.z += b.z; s1.w += b.w;
          }
          uint4 v = make_uint4(pack_bf16(s0.x, s0.y), pack_bf16(s0.z, s0.w), pack_bf16(s1.x, s1.y), pack_bf16(s1.z, s1.w));
          *(uint4*)(g_kvr_img + head * 4096 + sw64_off(f, d0)) = v;
        }
        __syncwarp();
        if (lane == 0) {
          cnt_arrive(C_RED);
          PROF_MARK(24);
          cnt_wait(C_RED, NCTA);
          PROF_MARK(25);
          fence_async_all();
          mbar_expect_tx(BAR(B_KVR), 8192);
          bulk_g2s(sb + OFF_KVR, g_kvr_img + hp * 8192, 8192, BAR(B_KVR));
          mbar_wait(BAR(B_X1FREE), 0);
          mbar_expect_tx(BAR(B_WOB), 57344);
#pragma unroll 1
          for (int c = 0; c < 7; c++) tma_2d(sb + OFF_WOB + c * 8192, &tm_wob, hp * 56, c * 64, BAR(B_WOB));
        }
      }
    }
  } else {
    asm volatile("setmaxnreg.inc.sync.aligned.u32 112;");
    const int mh = wg & 1, nh = wg >> 1, wq = warp & 3;
    float acc[28];
    uint32_t keep[32];
    int item = nh;
#pragma unroll
    for (int i = 0; i < 28; i++) acc[i] = 0.f;

#pragma unroll 1
    for (int stage = 0; stage < 4; stage++) {
      {
        int slot = item % RING, prev = 0;
        uint32_t par = (item / RING) & 1;
        const bool tail = stage >= 2;
        const uint64_t dS = make_desc(tail ? sb + OFF_WOA + (stage - 2) * 57344 : sb + OFF_X + mh * 8192, 1024, 1024, 1);
        const uint64_t dR = make_desc(sb + OFF_RING, 1024, 1024, 1);
#pragma unroll 1
        for (int c = 0; c < 7; c++) {
          mbar_wait(BAR(tail ? B_WOA + stage - 2 : B_X + c), 0);
          mbar_wait(BAR(B_FULL + slot), par);
          const uint64_t ds = dS + c * (tail ? 512 : 1024), dr = dR + slot * 512;
          const uint64_t dA = tail ? dr : ds, dB = tail ? ds : dr;
          wg_fence();
          wgmma_ss_n56_ta0_tb1<1>(acc, dA, dB);
          wgmma_ss_n56_ta0_tb1<1>(acc, dA + 2, dB + 128);
          wgmma_ss_n56_ta0_tb1<1>(acc, dA + 4, dB + 256);
          wgmma_ss_n56_ta0_tb1<1>(acc, dA + 6, dB + 384);
          wg_commit();
          wg_wait<1>();
          if (lane == 0 && c > 0) mbar_arrive(BAR(B_EMPTY + prev), tail ? 4 : 2);
          prev = slot;
          slot += 2;
          if (slot >= RING) { slot -= RING; par ^= 1; }
        }
        wg_wait<0>();
        fence_regs(acc);
        if (lane == 0) mbar_arrive(BAR(B_EMPTY + prev), tail ? 4 : 2);
        item += 14;
      }
      if (stage == 2) { if (tid == 0) PROF_MARK(15); continue; }
      if (stage == 3) break;
      int lane_;
      asm volatile("mov.u32 %0, %%laneid;" : "=r"(lane_));
      const int lq = lane_ & 3;
      const int rowl = wq * 16 + (lane_ >> 2);
      const int row0 = mh * 64 + rowl;
      if (stage == 0) {
        if (tid == 0) PROF_MARK(2);
        if (tid == 256) PROF_MARK(3);
        mbar_wait(BAR(B_BUILD), 0);
      } else {
        bar_sync(1, 512);
        if (tid == 0) PROF_MARK(6);
        if (nh == 1) sts64(sb + OFF_VA + (lq & 1) * 8192 + sw64_off(row0 + 8 * (lq >> 1), 28), 0x00003F80u, 0u);
        uint32_t h[14];
#pragma unroll
        for (int i = 0; i < 14; i++) h[i] = nh ? pack_bf16(acc[2 * i], acc[2 * i + 1]) : keep[i];
        store_heads(nh ? sb + OFF_VA : sb + OFF_QP + mh * 4096, h, nh ? row0 : rowl, lq);
      }
      if (stage != nh) {
        phi_from_acc(acc, sb, keep, lq);
      } else if (stage == 0) {
        {
          float accs[4] = {0.f, 0.f, 0.f, 0.f};
          const uint64_t dX = make_desc(sb + OFF_X + mh * 8192, 1024, 1024, 1);
          const uint64_t dSlc = make_desc(sb + OFF_SLC, 128, 128, 0);
#pragma unroll 1
          for (int c = 0; c < 7; c++) {
            wg_fence();
            wgmma_ss_n8_ta0_tb1<1>(accs, dX + c * 1024, dSlc + c * 64);
            wgmma_ss_n8_ta0_tb1<1>(accs, dX + c * 1024 + 2, dSlc + c * 64 + 16);
            wgmma_ss_n8_ta0_tb1<1>(accs, dX + c * 1024 + 4, dSlc + c * 64 + 32);
            wgmma_ss_n8_ta0_tb1<1>(accs, dX + c * 1024 + 6, dSlc + c * 64 + 48);
            wg_commit();
          }
          const float QS = 0.18898223650461362f * 1.4426950408889634f;
          float sq[4] = {0.f, 0.f, 0.f, 0.f};
#pragma unroll
          for (int j = 0; j < 7; j++) {
#pragma unroll
            for (int rr = 0; rr < 2; rr++) {
              float v0 = acc[4 * j + 2 * rr] * QS, v1 = acc[4 * j + 2 * rr + 1] * QS;
              keep[2 * j + rr] = pack_bf16(v0, v1);
              float s2 = v0 * v0 + v1 * v1;
              if (j < 3) sq[rr] += s2;
              else if (j > 3) sq[2 + rr] += s2;
              else { sq[rr] += (lq < 2) ? s2 : 0.f; sq[2 + rr] += (lq < 2) ? 0.f : s2; }
            }
          }
#pragma unroll
          for (int i = 0; i < 4; i++) sq[i] = quad_sum(sq[i]);
          ((float*)(sgen + OFF_QSQ))[(mh + (lq & 2)) * 64 + rowl + 8 * (lq & 1)] = lq == 0 ? sq[0] : lq == 1 ? sq[1] : lq == 2 ? sq[2] : sq[3];
          wg_wait<0>();
          fence_regs(accs);
          const int sl = hp & 3;
          const bool isk = hp < 4, real = (sl < 3) || (lq < 2);
          float mxv = 0.f;
#pragma unroll
          for (int rr = 0; rr < 2; rr++) {
            const int pos = pt * 128 + row0 + 8 * rr, kr = pos & 63;
            const float v0 = accs[2 * rr], v1 = accs[2 * rr + 1];
            const bool poly = isk && ((POLY_PAT >> (kr >> 3)) & 1);
            const float sc = poly ? 2.f : 1.f;
            const float s2 = quad_sum(real ? v0 * v0 + v1 * v1 : 0.f);
            mxv = fmaxf(mxv, s2 <= 3.0e38f ? s2 : __int_as_float(0x7f800000));
            const uint32_t padv = lq == 2 ? (poly ? 0x443F4000u : 0x00003F80u) : (poly ? 0x3AB03F4Du : 0u);
            const uint32_t outv = real ? pack_bf16(sc * v0, sc * v1) : padv;
            if (hp == 3 && lq == 2) g_gate[pos] = rcpf(1.f + ex2f(-1.4426950408889634f * v0));
            *(uint32_t*)(g_kv_img + (pos >> 6) * 8192 + (isk ? 0 : 4096) + sw64_off(kr, sl * 8 + 2 * lq)) = outv;
          }
#pragma unroll
          for (int o = 16; o >= 4; o >>= 1) mxv = fmaxf(mxv, __shfl_xor_sync(~0u, mxv, o));
          if (lane == 0) (isk ? g_ksq : g_vmx)[sl * 128 + pt * 8 + mh * 4 + wq] = mxv;
          __syncwarp();
          if (lane == 0) mbar_arrive(BAR(B_SIG + 0), 1);
        }
      }
      if (stage == 0) {
        if (tid == 0) PROF_MARK(4);
        if (tid == 256) PROF_MARK(5);
#pragma unroll
        for (int i = 0; i < 28; i++) acc[i] = 0.f;
        continue;
      }

      store_phi(nh ? sb + OFF_PHIK : sb + OFF_PHIQ, keep, row0, lq);
      fence_async_smem();
      if (nh == 1) {
        bar_sync(3, 256);
        float kv[16];
        const uint64_t dA = make_desc(sb + OFF_PHIK + mh * 16384, 1024, 1024, 1);
        const uint64_t dB = make_desc(sb + OFF_VA + mh * 8192, 512, 512, 2);
        wg_fence();
        wgmma_ss_n32_ta1_tb1<0>(kv, dA, dB);
#pragma unroll
        for (int ks = 1; ks < 8; ks++) wgmma_ss_n32_ta1_tb1<1>(kv, dA + ks * 128, dB + ks * 64);
        wg_commit();
        wg_wait<0>();
        fence_regs(kv);
        if (lane == 0) mbar_arrive(BAR(B_X0FREE), 1);
        float* dst = g_kvpart + ((size_t)(pt * 16 + 2 * hp + mh) * 64 + rowl) * 32 + 2 * lq;
#pragma unroll
        for (int j = 0; j < 4; j++) {
          *(float2*)(dst + 8 * j) = make_float2(kv[4 * j], kv[4 * j + 1]);
          *(float2*)(dst + 8 * 32 + 8 * j) = make_float2(kv[4 * j + 2], kv[4 * j + 3]);
        }
        __syncwarp();
        if (lane == 0) mbar_arrive(BAR(B_SIG + 1), 1);
      }
      if (tid == 0) PROF_MARK(7);
      if (tid == 256) PROF_MARK(8);

      mbar_wait(BAR(B_B1), 0);
      if (tid == 0) PROF_MARK(9);
      const float* red = (const float*)(sgen + OFF_RED);
      const float ksq = red[0], vsq = red[1];
      const float* qsq = (const float*)(sgen + OFF_QSQ);
      float b0, b1;
      asm("sqrt.approx.ftz.f32 %0, %1;" : "=f"(b0) : "f"(qsq[wg * 64 + rowl] * ksq));
      asm("sqrt.approx.ftz.f32 %0, %1;" : "=f"(b1) : "f"(qsq[wg * 64 + rowl + 8] * ksq));
      b0 *= 1.02f; b1 *= 1.02f;
      const bool bad = !(b0 <= 92.f) || !(b1 <= 92.f) || !(vsq <= 1.0e24f);
      const bool slow = __any_sync(~0u, bar_or(1, 512, bad));
      if (tid == 0) { *(volatile int*)(sgen + OFF_RED + 8) = slow; mbar_arrive(BAR(B_SLOW), 1); }

      uint32_t q[8];
      {
        const uint32_t qa = sb + OFF_QP + wg * 4096;
        const int r = wq * 16 + (lane_ & 7) + ((lane_ >> 3) & 1) * 8;
#pragma unroll
        for (int ks = 0; ks < 2; ks++)
          asm volatile("ldmatrix.sync.aligned.m8n8.x4.shared.b16 {%0, %1, %2, %3}, [%4];"
                       : "=r"(q[4 * ks]), "=r"(q[4 * ks + 1]), "=r"(q[4 * ks + 2]), "=r"(q[4 * ks + 3])
                       : "r"(qa + sw64_off(r, ks * 16 + (lane_ >> 4) * 8)) : "memory");
        if (lq >= 2) {
          q[6] = slow ? 0u : (lq == 2 ? pack_bf16(64.f - b0, 1.f) : 0x3F803F80u);
          q[7] = slow ? 0u : (lq == 2 ? pack_bf16(64.f - b1, 1.f) : 0x3F803F80u);
        }
      }

      const uint64_t dK = make_desc(sb + OFF_RING, 16, 512, 2);
      const uint64_t dV = make_desc(sb + OFF_RING + 4096, 512, 512, 2);
      int slot = 28 % RING, prev = 0;
      uint32_t par = (28 / RING) & 1;
      float m0 = -3.0e38f, m1 = -3.0e38f;
      if (__builtin_expect(slow, 0)) {
#pragma unroll 1
        for (int j64 = 0; j64 < 32; j64++) {
          float s[32];
          mbar_wait(BAR(B_FULL + slot), par);
          wg_fence();
          wgmma_rs_n64_tb0<0>(s, q[0], q[1], q[2], q[3], dK + slot * 512);
          wgmma_rs_n64_tb0<1>(s, q[4], q[5], q[6], q[7], dK + slot * 512 + 2);
          wg_commit();
          wg_wait<0>();
          fence_regs(s);
#pragma unroll
          for (int j = 0; j < 8; j++) {
            const float sc = ((POLY_PAT >> j) & 1) ? 0.5f : 1.f;
            m0 = fmaxf(m0, fmaxf(s[4 * j], s[4 * j + 1]) * sc);
            m1 = fmaxf(m1, fmaxf(s[4 * j + 2], s[4 * j + 3]) * sc);
          }
          if (lane == 0) mbar_arrive(BAR(B_EMPTY + slot), 1);
          if (++slot == RING) { slot = 0; par ^= 1; }
        }
        m0 = quad_max(m0); m1 = quad_max(m1);
      }
      float o[16];
#pragma unroll
      for (int i = 0; i < 16; i++) o[i] = 0.f;
      if (tid == 0) PROF_MARK(10);
#pragma unroll 1
      for (int half = 0; half < 2; half++) {
        if (!slow) {
          const uint32_t c_half = 0x3F003F00u, c_3 = 0x00030003u;
#pragma unroll 1
          for (int j64 = 0; j64 < 16; j64++) {
            float s[32];
            mbar_wait(BAR(B_FULL + slot), par);
            wg_fence();
            wgmma_rs_n64_tb0<0>(s, q[0], q[1], q[2], q[3], dK + slot * 512);
            wgmma_rs_n64_tb0<1>(s, q[4], q[5], q[6], q[7], dK + slot * 512 + 2);
            wg_commit();
            wg_wait<0>();
            fence_regs(s);
            if (lane == 0 && j64 > 0) mbar_arrive(BAR(B_EMPTY + prev), 1);
            uint32_t p[16];
#pragma unroll
            for (int j = 0; j < 8; j++) {
              if ((POLY_PAT >> j) & 1) {
                p[2 * j] = exp2_pair_fma(s[4 * j], s[4 * j + 1], c_half, c_3);
                p[2 * j + 1] = exp2_pair_fma(s[4 * j + 2], s[4 * j + 3], c_half, c_3);
              } else {
                p[2 * j] = pack_bf16(ex2f(s[4 * j]), ex2f(s[4 * j + 1]));
                p[2 * j + 1] = pack_bf16(ex2f(s[4 * j + 2]), ex2f(s[4 * j + 3]));
              }
            }
            wg_fence();
#pragma unroll
            for (int ks = 0; ks < 4; ks++)
              wgmma_rs_n32_tb1<1>(o, p[4 * ks], p[4 * ks + 1], p[4 * ks + 2], p[4 * ks + 3], dV + slot * 512 + ks * 64);
            wg_commit();
            prev = slot;
            if (++slot == RING) { slot = 0; par ^= 1; }
          }
          wg_wait<0>();
          fence_regs(o);
        } else {
#pragma unroll 1
          for (int j64 = 0; j64 < 16; j64++) {
            float s[32];
            mbar_wait(BAR(B_FULL + slot), par);
            wg_fence();
            wgmma_rs_n64_tb0<0>(s, q[0], q[1], q[2], q[3], dK + slot * 512);
            wgmma_rs_n64_tb0<1>(s, q[4], q[5], q[6], q[7], dK + slot * 512 + 2);
            wg_commit();
            wg_wait<0>();
            fence_regs(s);
            if (lane == 0 && j64 > 0) mbar_arrive(BAR(B_EMPTY + prev), 1);
            uint32_t p[16];
#pragma unroll
            for (int j = 0; j < 8; j++) {
              const float sc = ((POLY_PAT >> j) & 1) ? 0.5f : 1.f;
              p[2 * j] = pack_bf16(ex2f(fmaf(s[4 * j], sc, -m0)), ex2f(fmaf(s[4 * j + 1], sc, -m0)));
              p[2 * j + 1] = pack_bf16(ex2f(fmaf(s[4 * j + 2], sc, -m1)), ex2f(fmaf(s[4 * j + 3], sc, -m1)));
            }
            wg_fence();
#pragma unroll
            for (int ks = 0; ks < 4; ks++)
              wgmma_rs_n32_tb1<1>(o, p[4 * ks], p[4 * ks + 1], p[4 * ks + 2], p[4 * ks + 3], dV + slot * 512 + ks * 64);
            wg_commit();
            prev = slot;
            if (++slot == RING) { slot = 0; par ^= 1; }
          }
          wg_wait<0>();
          fence_regs(o);
        }
        if (lane == 0) mbar_arrive(BAR(B_EMPTY + prev), 1);
        float t[16];
        if (half == 0) {
          if (tid == 0) PROF_MARK(11);
          mbar_wait(BAR(B_KVR), 0);
          const uint64_t dA = make_desc(sb + OFF_PHIQ + nh * 16384 + mh * 8192, 16, 1024, 1);
          const uint64_t dB = make_desc(sb + OFF_KVR + nh * 4096, 512, 512, 2);
          wg_fence();
          wgmma_ss_n32_ta0_tb1<0>(t, dA, dB);
#pragma unroll
          for (int ks = 1; ks < 4; ks++) wgmma_ss_n32_ta0_tb1<1>(t, dA + ks * 2, dB + ks * 64);
          wg_commit();
          wg_wait<0>();
          fence_regs(t);
          if (lane == 0) mbar_arrive(BAR(B_X1FREE), 1);
        } else {
          if (tid == 0) PROF_MARK(13);
#pragma unroll
          for (int i = 0; i < 16; i++) t[i] = o[i];
        }
        {
          const float g0 = ((const float*)(sgen + OFF_GATE))[row0], g1 = ((const float*)(sgen + OFF_GATE))[row0 + 8];
          const float eps = half ? 0.f : 1e-6f;
          const float d0 = __shfl_sync(~0u, t[12], (lane_ & ~3) | 2), d1 = __shfl_sync(~0u, t[14], (lane_ & ~3) | 2);
          const float r0 = __fdividef(half ? 1.f - g0 : g0, d0 + eps), r1 = __fdividef(half ? 1.f - g1 : g1, d1 + eps);
          uint8_t* img = g_o_img + (size_t)((half * 16 + pt) * 14 + mh) * 8192 + rowl * 128;
          const int col0 = (2 * hp + nh) * DH + 2 * lq;
#pragma unroll
          for (int j = 0; j < 4; j++) {
            const int col = col0 + 8 * j;
            uint8_t* p = img + (col >> 6) * 16384 + ((((col >> 3) ^ rowl) & 7) << 4) + (col & 7) * 2;
            const uint32_t v0 = pack_bf16(t[4 * j] * r0, t[4 * j + 1] * r0), v1 = pack_bf16(t[4 * j + 2] * r1, t[4 * j + 3] * r1);
            if (j < 3 || lq < 2) { *(uint32_t*)p = v0; *(uint32_t*)(p + 1024) = v1; }
          }
          __syncwarp();
          if (lane == 0) mbar_arrive(BAR(B_SIG + 2 + half), 1);
        }
        if (tid == 0) PROF_MARK(12 + 2 * half);
      }
      if (nh == 1) return;
      item = (slow ? 92 : 60) + mh;
#pragma unroll
      for (int i = 0; i < 32; i++) keep[i] = 0u;
#pragma unroll
      for (int i = 0; i < 28; i++) acc[i] = 0.f;
    }
    if (tid == 0) PROF_MARK(17);
    __nv_bfloat16* op = prm.out + (size_t)(pt * 128 + mh * 64 + wq * 16 + (lane >> 2)) * DM + hp * 56 + 2 * (lane & 3);
#pragma unroll
    for (int j = 0; j < 7; j++) {
      *(uint32_t*)(op + 8 * j) = pack_bf16(acc[4 * j], acc[4 * j + 1]);
      *(uint32_t*)(op + 8 * DM + 8 * j) = pack_bf16(acc[4 * j + 2], acc[4 * j + 3]);
    }
    if (tid == 0) { PROF_MARK(18); PROF_CLK(31); }
    if (tid == 0) {
      unsigned prevd = atomicAdd(&g_cnt[C_DONE * 32], 1u);
      if (prevd == NCTA - 1) {
#pragma unroll 1
        for (int i = 0; i < C_N; i++) g_cnt[i * 32] = 0;
      }
    }
  }
}

typedef CUresult (*EncodeFn)(CUtensorMap*, CUtensorMapDataType, cuuint32_t, void*, const cuuint64_t*, const cuuint64_t*,
                             const cuuint32_t*, const cuuint32_t*, CUtensorMapInterleave, CUtensorMapSwizzle,
                             CUtensorMapL2promotion, CUtensorMapFloatOOBfill);

void make_map(EncodeFn enc, CUtensorMap* tm, const void* ptr, uint64_t cols, uint64_t rows, uint32_t box_rows) {
  cuuint64_t dims[2] = {cols, rows};
  cuuint64_t strides[1] = {cols * 2};
  cuuint32_t box[2] = {64, box_rows};
  cuuint32_t es[2] = {1, 1};
  enc(tm, CU_TENSOR_MAP_DATA_TYPE_BFLOAT16, 2, const_cast<void*>(ptr), dims, strides, box, es, CU_TENSOR_MAP_INTERLEAVE_NONE,
      CU_TENSOR_MAP_SWIZZLE_128B, CU_TENSOR_MAP_L2_PROMOTION_L2_128B, CU_TENSOR_MAP_FLOAT_OOB_FILL_NONE);
}

}

extern "C" void kernel_launch(void* const* d_in, const int* in_sizes, int n_in, void* d_out, int out_size) {
  (void)in_sizes; (void)n_in; (void)out_size;
  static EncodeFn enc = nullptr;
  if (!enc) {
    void* fn = nullptr;
    cudaDriverEntryPointQueryResult qr;
    cudaGetDriverEntryPoint("cuTensorMapEncodeTiled", &fn, cudaEnableDefault, &qr);
    enc = (EncodeFn)fn;
    cudaFuncSetAttribute(fused_kernel, cudaFuncAttributeMaxDynamicSharedMemorySize, SMEM_BYTES);
  }
  CUtensorMap tm_x, tm_wqkv, tm_wq, tm_woa, tm_wob;
  make_map(enc, &tm_x, d_in[0], DM, S_LEN, 128);
  make_map(enc, &tm_wqkv, d_in[1], 3 * DM, DM, 64);
  make_map(enc, &tm_wq, d_in[5], DM, DM, 64);
  make_map(enc, &tm_woa, d_in[3], DM, DM, 64);
  make_map(enc, &tm_wob, d_in[8], DM, DM, 64);
  Params prm;
  prm.w_phi = (const __nv_bfloat16*)d_in[2];
  prm.wk = (const __nv_bfloat16*)d_in[6];
  prm.wv = (const __nv_bfloat16*)d_in[7];
  prm.gate_w = (const __nv_bfloat16*)d_in[9];
  prm.out = (__nv_bfloat16*)d_out;
  fused_kernel<<<NCTA, NTHREADS, SMEM_BYTES>>>(tm_x, tm_wqkv, tm_wq, tm_woa, tm_wob, prm);
}
```

```cpp
#include <cuda_runtime.h>
#include <cuda_bf16.h>
#include <cuda.h>
#include <stdint.h>

namespace {

constexpr int S_LEN = 2048, DM = 448, DH = 28;
constexpr int NCTA = 128;
constexpr int NTHREADS = 640;
constexpr int RING = 12;
constexpr uint32_t POLY_PAT = 0x57;

constexpr int OFF_X = 0;
constexpr int OFF_PHIK = 0;
constexpr int OFF_VA = 32768;
constexpr int OFF_WOA = 0;
constexpr int OFF_PHIQ = 57344;
constexpr int OFF_KVR = 90112;
constexpr int OFF_QP = 98304;
constexpr int OFF_WOB = 57344;
constexpr int OFF_RING = 114688;
constexpr int OFF_WBD = 212992;
constexpr int OFF_SLC = 221184;
constexpr int OFF_QSQ = 228352;
constexpr int OFF_GATE = 229376;
constexpr int OFF_RED = 229888;
constexpr int OFF_BAR = 229952;
constexpr int SMEM_BYTES = 230400 + 1024;

constexpr int B_FULL = 0, B_EMPTY = RING, B_X = 2 * RING, B_WOA = B_X + 7, B_WOB = B_WOA + 1, B_KVR = B_WOA + 2,
              B_X0FREE = B_WOA + 3, B_X1FREE = B_WOA + 4, B_B1 = B_WOA + 5, B_SLOW = B_WOA + 6, B_BUILD = B_WOA + 7,
              B_SIG = B_WOA + 8;

constexpr int C_KV = 0, C_PART = 1, C_RED = 2, C_DONE = 3, C_OA = 4, C_OB = 20, C_N = 36;

__device__ __align__(1024) uint8_t g_kv_img[32 * 8192];
__device__ float g_ksq[512];
__device__ float g_vmx[512];
__device__ float g_gate[S_LEN];
__device__ __align__(16) float g_kvpart[16 * 16 * 64 * 32];
__device__ __align__(1024) uint8_t g_kvr_img[16 * 4096];
__device__ __align__(1024) uint8_t g_o_img[2 * 16 * 14 * 8192];
__device__ unsigned g_cnt[C_N * 32];

#define PROF2(i) do { } while (0)
#define PROF_CLK(i) do { } while (0)
#define PROF_MARK(i) do { } while (0)
__device__ __forceinline__ uint32_t smem_u32(const void* p) { return (uint32_t)__cvta_generic_to_shared(p); }
__device__ __forceinline__ void mbar_init(uint32_t a, int cnt) {
  asm volatile("mbarrier.init.shared::cta.b64 [%0], %1;" ::"r"(a), "r"(cnt) : "memory");
}
__device__ __forceinline__ void mbar_expect_tx(uint32_t a, uint32_t bytes) {
  asm volatile("mbarrier.arrive.expect_tx.shared::cta.b64 _, [%0], %1;" ::"r"(a), "r"(bytes) : "memory");
}
__device__ __forceinline__ void mbar_arrive(uint32_t a, uint32_t cnt) {
  asm volatile("mbarrier.arrive.shared::cta.b64 _, [%0], %1;" ::"r"(a), "r"(cnt) : "memory");
}
__device__ __forceinline__ void mbar_wait(uint32_t a, uint32_t parity) {
  asm volatile(
      "{\n.reg .pred p;\n.reg .u32 c;\nmov.u32 c, 0;\n"
      "W_%=:\nmbarrier.try_wait.parity.shared::cta.b64 p, [%0], %1;\n"
      "add.u32 c, c, 1;\nsetp.lt.and.u32 p, c, 0x1000000, !p;\n@p bra W_%=;\n}"
      ::"r"(a), "r"(parity) : "memory");
}
__device__ __forceinline__ void tma_2d(uint32_t dst, const CUtensorMap* tm, int c0, int c1, uint32_t bar) {
  asm volatile("cp.async.bulk.tensor.2d.shared::cluster.global.mbarrier::complete_tx::bytes [%0], [%1, {%3, %4}], [%2];"
               ::"r"(dst), "l"(tm), "r"(bar), "r"(c0), "r"(c1) : "memory");
}
__device__ __forceinline__ void bulk_g2s(uint32_t dst, const void* src, uint32_t bytes, uint32_t bar) {
  asm volatile("cp.async.bulk.shared::cluster.global.mbarrier::complete_tx::bytes [%0], [%1], %2, [%3];"
               ::"r"(dst), "l"(src), "r"(bytes), "r"(bar) : "memory");
}
__device__ __forceinline__ void cp_async8(uint32_t dst, const void* src) {
  asm volatile("cp.async.ca.shared.global [%0], [%1], 8;" ::"r"(dst), "l"(src) : "memory");
}
__device__ __forceinline__ void fence_async_smem() { asm volatile("fence.proxy.async.shared::cta;" ::: "memory"); }
__device__ __forceinline__ void fence_async_all() { asm volatile("fence.proxy.async;" ::: "memory"); }
__device__ __forceinline__ void bar_sync(int id, int n) { asm volatile("bar.sync %0, %1;" ::"r"(id), "r"(n) : "memory"); }
__device__ __forceinline__ bool bar_or(int id, int n, bool v) {
  uint32_t r;
  asm volatile("{\n.reg .pred p, q;\nsetp.ne.u32 p, %3, 0;\nbar.red.or.pred q, %1, %2, p;\nselp.u32 %0, 1, 0, q;\n}"
               : "=r"(r) : "r"(id), "r"(n), "r"((uint32_t)v) : "memory");
  return r != 0;
}
__device__ __forceinline__ void cnt_arrive(int idx) {
  asm volatile("red.release.gpu.global.add.u32 [%0], 1;" ::"l"(&g_cnt[idx * 32]) : "memory");
}
__device__ __forceinline__ void cnt_wait(int idx, unsigned target) {
  unsigned v, n = 0;
#pragma unroll 1
  do {
    asm volatile("ld.acquire.gpu.global.u32 %0, [%1];" : "=r"(v) : "l"(&g_cnt[idx * 32]) : "memory");
  } while (v < target && ++n < (1u << 22));
}
__device__ __forceinline__ void wg_fence() { asm volatile("wgmma.fence.sync.aligned;" ::: "memory"); }
__device__ __forceinline__ void wg_commit() { asm volatile("wgmma.commit_group.sync.aligned;" ::: "memory"); }
template <int N> __device__ __forceinline__ void wg_wait() { asm volatile("wgmma.wait_group.sync.aligned %0;" ::"n"(N) : "memory"); }
template <int N> __device__ __forceinline__ void fence_regs(float (&d)[N]) {
#pragma unroll
  for (int i = 0; i < N; i++) asm volatile("" : "+f"(d[i])::"memory");
}
__device__ __forceinline__ uint64_t make_desc(uint32_t saddr, uint32_t lbo, uint32_t sbo, uint32_t swz) {
  return (uint64_t)((saddr & 0x3FFFF) >> 4) | ((uint64_t)(lbo >> 4) << 16) | ((uint64_t)(sbo >> 4) << 32) | ((uint64_t)swz << 62);
}
__device__ __forceinline__ float ex2f(float x) { float y; asm("ex2.approx.ftz.f32 %0, %1;" : "=f"(y) : "f"(x)); return y; }
__device__ __forceinline__ float rcpf(float x) { float y; asm("rcp.approx.ftz.f32 %0, %1;" : "=f"(y) : "f"(x)); return y; }
__device__ __forceinline__ uint32_t pack_bf16(float lo, float hi) {
  uint32_t r; asm("cvt.rn.bf16x2.f32 %0, %1, %2;" : "=r"(r) : "f"(hi), "f"(lo)); return r;
}
__device__ __forceinline__ uint32_t lop_and_or(uint32_t a, uint32_t m, uint32_t c) {
  uint32_t r; asm("lop3.b32 %0, %1, %2, %3, 0xEA;" : "=r"(r) : "r"(a), "r"(m), "r"(c)); return r;
}
__device__ __forceinline__ void sts32(uint32_t a, uint32_t v) { asm volatile("st.shared.b32 [%0], %1;" ::"r"(a), "r"(v) : "memory"); }
__device__ __forceinline__ void sts64(uint32_t a, uint32_t v0, uint32_t v1) { asm volatile("st.shared.v2.b32 [%0], {%1, %2};" ::"r"(a), "r"(v0), "r"(v1) : "memory"); }
__device__ __forceinline__ void sts128(uint32_t a, uint4 v) {
  asm volatile("st.shared.v4.b32 [%0], {%1, %2, %3, %4};" ::"r"(a), "r"(v.x), "r"(v.y), "r"(v.z), "r"(v.w) : "memory");
}
__device__ __forceinline__ float4 ldcg_f4(const float* p) {
  float4 v; asm volatile("ld.global.cg.v4.f32 {%0, %1, %2, %3}, [%4];" : "=f"(v.x), "=f"(v.y), "=f"(v.z), "=f"(v.w) : "l"(p) : "memory"); return v;
}
__device__ __forceinline__ float quad_sum(float v) { v += __shfl_xor_sync(~0u, v, 1); v += __shfl_xor_sync(~0u, v, 2); return v; }
__device__ __forceinline__ float quad_max(float v) { v = fmaxf(v, __shfl_xor_sync(~0u, v, 1)); v = fmaxf(v, __shfl_xor_sync(~0u, v, 2)); return v; }

template <int SD> __device__ __forceinline__ void wgmma_ss_n56_ta0_tb1(float (&d)[28], uint64_t da, uint64_t db) {
  asm volatile("wgmma.mma_async.sync.aligned.m64n56k16.f32.bf16.bf16 {%0, %1, %2, %3, %4, %5, %6, %7, %8, %9, %10, %11, %12, %13, %14, %15, %16, %17, %18, %19, %20, %21, %22, %23, %24, %25, %26, %27}, %28, %29, %30, 1, 1, 0, 1;\n"
    : "+f"(d[0]), "+f"(d[1]), "+f"(d[2]), "+f"(d[3]), "+f"(d[4]), "+f"(d[5]), "+f"(d[6]), "+f"(d[7]), "+f"(d[8]), "+f"(d[9]), "+f"(d[10]), "+f"(d[11]), "+f"(d[12]), "+f"(d[13]), "+f"(d[14]), "+f"(d[15]), "+f"(d[16]), "+f"(d[17]), "+f"(d[18]), "+f"(d[19]), "+f"(d[20]), "+f"(d[21]), "+f"(d[22]), "+f"(d[23]), "+f"(d[24]), "+f"(d[25]), "+f"(d[26]), "+f"(d[27])
    : "l"(da), "l"(db), "n"(SD));
}
template <int SD> __device__ __forceinline__ void wgmma_ss_n8_ta0_tb1(float (&d)[4], uint64_t da, uint64_t db) {
  asm volatile("wgmma.mma_async.sync.aligned.m64n8k16.f32.bf16.bf16 {%0, %1, %2, %3}, %4, %5, %6, 1, 1, 0, 1;\n"
    : "+f"(d[0]), "+f"(d[1]), "+f"(d[2]), "+f"(d[3])
    : "l"(da), "l"(db), "n"(SD));
}
template <int SD> __device__ __forceinline__ void wgmma_rs_n64_tb1(float (&d)[32], uint32_t a0, uint32_t a1, uint32_t a2, uint32_t a3, uint64_t db) {
  asm volatile("wgmma.mma_async.sync.aligned.m64n64k16.f32.bf16.bf16 {%0, %1, %2, %3, %4, %5, %6, %7, %8, %9, %10, %11, %12, %13, %14, %15, %16, %17, %18, %19, %20, %21, %22, %23, %24, %25, %26, %27, %28, %29, %30, %31}, {%32, %33, %34, %35}, %36, %37, 1, 1, 1;\n"
    : "+f"(d[0]), "+f"(d[1]), "+f"(d[2]), "+f"(d[3]), "+f"(d[4]), "+f"(d[5]), "+f"(d[6]), "+f"(d[7]), "+f"(d[8]), "+f"(d[9]), "+f"(d[10]), "+f"(d[11]), "+f"(d[12]), "+f"(d[13]), "+f"(d[14]), "+f"(d[15]), "+f"(d[16]), "+f"(d[17]), "+f"(d[18]), "+f"(d[19]), "+f"(d[20]), "+f"(d[21]), "+f"(d[22]), "+f"(d[23]), "+f"(d[24]), "+f"(d[25]), "+f"(d[26]), "+f"(d[27]), "+f"(d[28]), "+f"(d[29]), "+f"(d[30]), "+f"(d[31])
    : "r"(a0), "r"(a1), "r"(a2), "r"(a3), "l"(db), "n"(SD));
}
template <int SD> __device__ __forceinline__ void wgmma_ss_n32_ta1_tb1(float (&d)[16], uint64_t da, uint64_t db) {
  asm volatile("wgmma.mma_async.sync.aligned.m64n32k16.f32.bf16.bf16 {%0, %1, %2, %3, %4, %5, %6, %7, %8, %9, %10, %11, %12, %13, %14, %15}, %16, %17, %18, 1, 1, 1, 1;\n"
    : "+f"(d[0]), "+f"(d[1]), "+f"(d[2]), "+f"(d[3]), "+f"(d[4]), "+f"(d[5]), "+f"(d[6]), "+f"(d[7]), "+f"(d[8]), "+f"(d[9]), "+f"(d[10]), "+f"(d[11]), "+f"(d[12]), "+f"(d[13]), "+f"(d[14]), "+f"(d[15])
    : "l"(da), "l"(db), "n"(SD));
}
template <int SD> __device__ __forceinline__ void wgmma_ss_n32_ta0_tb1(float (&d)[16], uint64_t da, uint64_t db) {
  asm volatile("wgmma.mma_async.sync.aligned.m64n32k16.f32.bf16.bf16 {%0, %1, %2, %3, %4, %5, %6, %7, %8, %9, %10, %11, %12, %13, %14, %15}, %16, %17, %18, 1, 1, 0, 1;\n"
    : "+f"(d[0]), "+f"(d[1]), "+f"(d[2]), "+f"(d[3]), "+f"(d[4]), "+f"(d[5]), "+f"(d[6]), "+f"(d[7]), "+f"(d[8]), "+f"(d[9]), "+f"(d[10]), "+f"(d[11]), "+f"(d[12]), "+f"(d[13]), "+f"(d[14]), "+f"(d[15])
    : "l"(da), "l"(db), "n"(SD));
}
template <int SD> __device__ __forceinline__ void wgmma_rs_n64_tb0(float (&d)[32], uint32_t a0, uint32_t a1, uint32_t a2, uint32_t a3, uint64_t db) {
  asm volatile("wgmma.mma_async.sync.aligned.m64n64k16.f32.bf16.bf16 {%0, %1, %2, %3, %4, %5, %6, %7, %8, %9, %10, %11, %12, %13, %14, %15, %16, %17, %18, %19, %20, %21, %22, %23, %24, %25, %26, %27, %28, %29, %30, %31}, {%32, %33, %34, %35}, %36, %37, 1, 1, 0;\n"
    : "+f"(d[0]), "+f"(d[1]), "+f"(d[2]), "+f"(d[3]), "+f"(d[4]), "+f"(d[5]), "+f"(d[6]), "+f"(d[7]), "+f"(d[8]), "+f"(d[9]), "+f"(d[10]), "+f"(d[11]), "+f"(d[12]), "+f"(d[13]), "+f"(d[14]), "+f"(d[15]), "+f"(d[16]), "+f"(d[17]), "+f"(d[18]), "+f"(d[19]), "+f"(d[20]), "+f"(d[21]), "+f"(d[22]), "+f"(d[23]), "+f"(d[24]), "+f"(d[25]), "+f"(d[26]), "+f"(d[27]), "+f"(d[28]), "+f"(d[29]), "+f"(d[30]), "+f"(d[31])
    : "r"(a0), "r"(a1), "r"(a2), "r"(a3), "l"(db), "n"(SD));
}
template <int SD> __device__ __forceinline__ void wgmma_rs_n32_tb1(float (&d)[16], uint32_t a0, uint32_t a1, uint32_t a2, uint32_t a3, uint64_t db) {
  asm volatile("wgmma.mma_async.sync.aligned.m64n32k16.f32.bf16.bf16 {%0, %1, %2, %3, %4, %5, %6, %7, %8, %9, %10, %11, %12, %13, %14, %15}, {%16, %17, %18, %19}, %20, %21, 1, 1, 1;\n"
    : "+f"(d[0]), "+f"(d[1]), "+f"(d[2]), "+f"(d[3]), "+f"(d[4]), "+f"(d[5]), "+f"(d[6]), "+f"(d[7]), "+f"(d[8]), "+f"(d[9]), "+f"(d[10]), "+f"(d[11]), "+f"(d[12]), "+f"(d[13]), "+f"(d[14]), "+f"(d[15])
    : "r"(a0), "r"(a1), "r"(a2), "r"(a3), "l"(db), "n"(SD));
}

__device__ __forceinline__ uint32_t sw64_off(int row, int d) { return row * 64 + ((((d >> 3) ^ (row >> 1)) & 3) << 4) + (d & 7) * 2; }

__device__ __forceinline__ uint32_t exp2_pair_fma(float t0, float t1, uint32_t c_half, uint32_t c_3) {
  uint32_t y0, y;
  asm("prmt.b32 %0, %1, %2, 0x6521;" : "=r"(y0) : "r"(__float_as_uint(t0)), "r"(__float_as_uint(t1)));
  uint32_t h = lop_and_or(y0, 0x007F007Fu, c_half);
  uint32_t e = lop_and_or(y0, 0xFF80FF80u, c_3);
  asm("fma.rn.bf16x2 %0, %1, %2, %3;" : "=r"(y) : "r"(y0), "r"(h), "r"(e));
  return y;
}

__device__ __forceinline__ void phi_from_acc(const float (&acc)[28], uint32_t sb, uint32_t (&ph)[32], int lq) {
  uint32_t a[16];
#pragma unroll
  for (int i = 0; i < 14; i++) a[i] = pack_bf16(acc[2 * i], acc[2 * i + 1]);
  a[14] = pack_bf16(acc[1], acc[0]);
  a[15] = pack_bf16(acc[3], acc[2]);
  float p[32];
  const uint64_t dWbd = make_desc(sb + OFF_WBD, 1024, 1024, 1);
  wg_fence();
  wgmma_rs_n64_tb1<0>(p, a[0], a[1], a[2], a[3], dWbd);
  wgmma_rs_n64_tb1<1>(p, a[4], a[5], a[6], a[7], dWbd + 128);
  wgmma_rs_n64_tb1<1>(p, a[8], a[9], a[10], a[11], dWbd + 256);
  wgmma_rs_n64_tb1<1>(p, a[12], a[13], a[14], a[15], dWbd + 384);
  wg_commit();
  wg_wait<0>();
  fence_regs(p);
  const float L2E = 1.4426950408889634f;
  const bool tail_ok = lq < 2;
  float v[16];
#pragma unroll
  for (int i = 0; i < 16; i++) v[i] = p[i];
#pragma unroll 1
  for (int e = 0; e < 2; e++) {
    float mx[2], mn[2], b[16], sa[2], sn[2];
#pragma unroll
    for (int r = 0; r < 2; r++) {
      const int o = 2 * r;
      if (!tail_ok) { v[o + 12] = v[o]; v[o + 13] = v[o]; }
      mx[r] = fmaxf(fmaxf(fmaxf(v[o], v[o + 1]), fmaxf(v[o + 4], v[o + 5])), fmaxf(fmaxf(v[o + 8], v[o + 9]), fmaxf(v[o + 12], v[o + 13])));
      mn[r] = fminf(fminf(fminf(v[o], v[o + 1]), fminf(v[o + 4], v[o + 5])), fminf(fminf(v[o + 8], v[o + 9]), fminf(v[o + 12], v[o + 13])));
    }
#pragma unroll
    for (int o = 1; o <= 2; o <<= 1)
#pragma unroll
      for (int r = 0; r < 2; r++) { mx[r] = fmaxf(mx[r], __shfl_xor_sync(~0u, mx[r], o)); mn[r] = fminf(mn[r], __shfl_xor_sync(~0u, mn[r], o)); }
#pragma unroll
    for (int r = 0; r < 2; r++) {
      const int o = 2 * r;
      const float cx = -mx[r] * L2E, cn = mn[r] * L2E;
#pragma unroll
      for (int i = 0; i < 8; i++) {
        const int k = o + 4 * (i >> 1) + (i & 1);
        b[k] = ex2f(fmaf(v[k], -L2E, cn));
        v[k] = ex2f(fmaf(v[k], L2E, cx));
      }
      if (!tail_ok) { v[o + 12] = v[o + 13] = b[o + 12] = b[o + 13] = 0.f; }
      sa[r] = ((v[o] + v[o + 1]) + (v[o + 4] + v[o + 5])) + ((v[o + 8] + v[o + 9]) + (v[o + 12] + v[o + 13]));
      sn[r] = ((b[o] + b[o + 1]) + (b[o + 4] + b[o + 5])) + ((b[o + 8] + b[o + 9]) + (b[o + 12] + b[o + 13]));
    }
#pragma unroll
    for (int o = 1; o <= 2; o <<= 1)
#pragma unroll
      for (int r = 0; r < 2; r++) { sa[r] += __shfl_xor_sync(~0u, sa[r], o); sn[r] += __shfl_xor_sync(~0u, sn[r], o); }
#pragma unroll
    for (int i = 0; i < 16; i++) ph[i] = ph[16 + i];
#pragma unroll
    for (int r = 0; r < 2; r++) {
      const float ra = rcpf(sa[r]), rb = rcpf(sn[r]);
#pragma unroll
      for (int jj = 0; jj < 4; jj++) {
        ph[16 + jj * 2 + r] = pack_bf16(v[2 * r + 4 * jj] * ra, v[2 * r + 4 * jj + 1] * ra);
        ph[16 + (4 + jj) * 2 + r] = pack_bf16(b[2 * r + 4 * jj] * rb, b[2 * r + 4 * jj + 1] * rb);
      }
    }
#pragma unroll
    for (int i = 0; i < 16; i++) v[i] = p[16 + i];
  }
}

__device__ __forceinline__ void store_phi(uint32_t base, const uint32_t (&ph)[32], int row0, int lq) {
  const uint32_t rb = base + row0 * 128 + lq * 4 + ((row0 & 7) << 4);
#pragma unroll
  for (int ch = 0; ch < 8; ch++) {
    const uint32_t a = rb ^ (ch << 4);
#pragma unroll
    for (int e = 0; e < 2; e++)
#pragma unroll
      for (int rr = 0; rr < 2; rr++) sts32(a + e * 16384 + rr * 1024, ph[e * 16 + ch * 2 + rr]);
  }
}

__device__ __forceinline__ void store_heads(uint32_t base, const uint32_t (&a)[14], int row0, int lq) {
  const uint32_t rb = base + row0 * 64 + (((row0 >> 1) & 3) << 4);
  const uint32_t b0 = rb + lq * 4;
  const uint32_t b1 = (rb + 8192 + ((lq * 4 + 8) & 15)) ^ ((lq >> 1) << 4);
#pragma unroll
  for (int j = 0; j < 7; j++) {
    uint32_t ad;
    if (j < 3) ad = b0 ^ (j << 4);
    else if (j == 3) ad = (lq < 2) ? (b0 ^ 48u) : (b1 ^ 16u);
    else ad = (lq < 2) ? (b1 ^ ((j - 4) << 4)) : ((b1 ^ 16u) ^ ((j - 3) << 4));
    sts32(ad, a[2 * j]);
    sts32(ad + 512, a[2 * j + 1]);
  }
}

struct Params {
  const __nv_bfloat16* w_phi;
  const __nv_bfloat16* wk;
  const __nv_bfloat16* wv;
  const __nv_bfloat16* gate_w;
  __nv_bfloat16* out;
};

__global__ void __launch_bounds__(NTHREADS, 1)
fused_kernel(const __grid_constant__ CUtensorMap tm_x, const __grid_constant__ CUtensorMap tm_wqkv,
             const __grid_constant__ CUtensorMap tm_wq, const __grid_constant__ CUtensorMap tm_woa,
             const __grid_constant__ CUtensorMap tm_wob, const Params prm) {
  extern __shared__ uint8_t smem_raw[];
  const uint32_t sb = (smem_u32(smem_raw) + 1023u) & ~1023u;
  uint8_t* sgen = smem_raw + (sb - smem_u32(smem_raw));
  const int tid = threadIdx.x, lane = tid & 31;
  const int warp = __shfl_sync(~0u, tid >> 5, 0), wg = warp >> 2;
  const int pt = blockIdx.x >> 3, hp = blockIdx.x & 7;
  const uint32_t bars = sb + OFF_BAR;
  auto BAR = [&](int i) { return bars + 8u * i; };

  if (tid == 0) { PROF_MARK(0); PROF_CLK(30); }
  if (warp == 16) {
#pragma unroll 1
    for (int i = lane; i < B_SIG + 4; i += 32) {
      int cnt = 1;
      if ((i >= B_EMPTY && i < B_X) || i == B_X1FREE || i >= B_SIG + 2) cnt = 16;
      if (i == B_X0FREE || i == B_SIG || i == B_SIG + 1) cnt = 8;
      if (i == B_B1) cnt = 2;
      if (i == B_BUILD) cnt = 3;
      mbar_init(BAR(i), cnt);
    }
    asm volatile("fence.mbarrier_init.release.cluster;" ::: "memory");
    fence_async_smem();
    __syncwarp();
    asm volatile("bar.arrive 0, %0;" ::"n"(NTHREADS) : "memory");
  } else {
    bar_sync(0, NTHREADS);
  }

  if (wg == 4) {
    asm volatile("setmaxnreg.dec.sync.aligned.u32 32;");
    if (warp == 16) {
      if (lane == 0) {
        int slot = 0;
        uint32_t par = 1;
        auto acquire = [&]() -> uint32_t {
          mbar_wait(BAR(B_EMPTY + slot), par);
          mbar_expect_tx(BAR(B_FULL + slot), 8192);
          uint32_t cur = slot;
          if (++slot == RING) { slot = 0; par ^= 1; }
          return cur;
        };
#pragma unroll 1
        for (int i = 0; i < 14; i++) {
          const int c = i < 7 ? i : i - 7;
          if (i < 7) {
            mbar_expect_tx(BAR(B_X + c), 16384);
            tma_2d(sb + OFF_X + c * 16384, &tm_x, c * 64, pt * 128, BAR(B_X + c));
          }
          uint32_t sl = acquire();
          tma_2d(sb + OFF_RING + sl * 8192, i < 7 ? &tm_wq : &tm_wqkv, hp * 56, c * 64, BAR(B_FULL + sl));
          sl = acquire();
          tma_2d(sb + OFF_RING + sl * 8192, &tm_wqkv, (i < 7 ? DM : 2 * DM) + hp * 56, c * 64, BAR(B_FULL + sl));
        }
        PROF_MARK(20);
#pragma unroll 1
        for (int ph = 0; ph < 4; ph++) {
          const uint8_t* src = g_kv_img;
          int n = 32;
          if (ph == 0) cnt_wait(C_KV, NCTA);
          else if (ph == 1) {
            mbar_wait(BAR(B_SLOW), 0);
            if (!*(volatile int*)(sgen + OFF_RED + 8)) continue;
          } else {
            cnt_wait((ph == 3 ? C_OB : C_OA) + pt, 8);
            src = g_o_img + (size_t)(((ph - 2) * 16 + pt) * 14) * 8192;
            n = 14;
          }
          PROF_MARK(21 + (ph ? 5 : 0));
          fence_async_all();
#pragma unroll 1
          for (int j = 0; j < n; j++) {
            uint32_t sl = acquire();
            bulk_g2s(sb + OFF_RING + sl * 8192, src + j * 8192, 8192, BAR(B_FULL + sl));
          }
        }
      }
    } else {
      {
        const int t = tid - 544;
#pragma unroll 1
        for (int i = t; i < 512; i += 96) sts128(sb + OFF_WBD + i * 16, make_uint4(0, 0, 0, 0));
        bar_sync(4, 96);
#pragma unroll 1
        for (int k = t; k < DM; k += 96) {
          const __nv_bfloat16* src = (hp < 4 ? prm.wk : prm.wv) + k * DH + (hp & 3) * 8;
          cp_async8(sb + OFF_SLC + k * 16, src);
          if ((hp & 3) != 3) cp_async8(sb + OFF_SLC + k * 16 + 8, src + 4);
          else sts64(sb + OFF_SLC + k * 16 + 8, hp == 3 ? (uint32_t)((const unsigned short*)prm.gate_w)[k] : 0u, 0u);
          if (k < 392) {
            const int row = k / 7, n = (row >= DH ? 32 : 0) + (k % 7) * 4;
            cp_async8(sb + OFF_WBD + row * 128 + (((n >> 3) ^ (row & 7)) << 4) + (n & 4) * 2, prm.w_phi + 2 * hp * DH * DH + k * 4);
          }
        }
        asm volatile("cp.async.wait_all;" ::: "memory");
        fence_async_smem();
        __syncwarp();
        if (lane == 0) mbar_arrive(BAR(B_BUILD), 1);
      }
      if (warp == 18) {
        if (lane == 0) {
          mbar_wait(BAR(B_SIG + 0), 0); cnt_arrive(C_KV);
          mbar_wait(BAR(B_SIG + 1), 0); cnt_arrive(C_PART);
          mbar_wait(BAR(B_SIG + 2), 0); cnt_arrive(C_OA + pt);
          mbar_wait(BAR(B_SIG + 3), 0); cnt_arrive(C_OB + pt);
        }
      } else if (warp == 19) {
        if (lane == 0) {
          cnt_wait(C_KV, NCTA);
          fence_async_all();
          mbar_expect_tx(BAR(B_B1), 512);
          bulk_g2s(sb + OFF_GATE, g_gate + pt * 128, 512, BAR(B_B1));
        }
        __syncwarp();
        float ksq = 0.f, vmx = 0.f;
#pragma unroll 1
        for (int sl = 0; sl < 4; sl++) {
          float4 a = ldcg_f4(g_ksq + sl * 128 + lane * 4), b = ldcg_f4(g_vmx + sl * 128 + lane * 4);
          float m = fmaxf(fmaxf(a.x, a.y), fmaxf(a.z, a.w));
#pragma unroll
          for (int o = 16; o > 0; o >>= 1) m = fmaxf(m, __shfl_xor_sync(~0u, m, o));
          ksq += m;
          vmx = fmaxf(vmx, fmaxf(fmaxf(b.x, b.y), fmaxf(b.z, b.w)));
        }
#pragma unroll
        for (int o = 16; o > 0; o >>= 1) vmx = fmaxf(vmx, __shfl_xor_sync(~0u, vmx, o));
        if (lane == 0) {
          float* red = (float*)(sgen + OFF_RED);
          red[0] = ksq; red[1] = vmx;
          mbar_arrive(BAR(B_B1), 1);
        }
      } else {
        if (lane == 0) {
          mbar_wait(BAR(B_X0FREE), 0);
          mbar_expect_tx(BAR(B_WOA), 57344);
#pragma unroll 1
          for (int c = 0; c < 7; c++) tma_2d(sb + OFF_WOA + c * 8192, &tm_woa, hp * 56, c * 64, BAR(B_WOA));
          PROF_MARK(22);
          cnt_wait(C_PART, NCTA);
          PROF_MARK(23);
        }
        __syncwarp();
        {
          const int head = blockIdx.x >> 3, f = (blockIdx.x & 7) * 8 + (lane >> 2), d0 = (lane & 3) * 8;
          const float* src = g_kvpart + ((size_t)head * 64 + f) * 32 + d0;
          float4 s0 = make_float4(0, 0, 0, 0), s1 = s0;
#pragma unroll 2
          for (int t = 0; t < 16; t++) {
            float4 a = ldcg_f4(src + (size_t)t * 16 * 64 * 32), b = ldcg_f4(src + (size_t)t * 16 * 64 * 32 + 4);
            s0.x += a.x; s0.y += a.y; s0.z += a.z; s0.w += a.w; s1.x += b.x; s1.y += b.y; s1.z += b.z; s1.w += b.w;
          }
          uint4 v = make_uint4(pack_bf16(s0.x, s0.y), pack_bf16(s0.z, s0.w), pack_bf16(s1.x, s1.y), pack_bf16(s1.z, s1.w));
          *(uint4*)(g_kvr_img + head * 4096 + sw64_off(f, d0)) = v;
        }
        __syncwarp();
        if (lane == 0) {
          cnt_arrive(C_RED);
          PROF_MARK(24);
          cnt_wait(C_RED, NCTA);
          PROF_MARK(25);
          fence_async_all();
          mbar_expect_tx(BAR(B_KVR), 8192);
          bulk_g2s(sb + OFF_KVR, g_kvr_img + hp * 8192, 8192, BAR(B_KVR));
          mbar_wait(BAR(B_X1FREE), 0);
          mbar_expect_tx(BAR(B_WOB), 57344);
#pragma unroll 1
          for (int c = 0; c < 7; c++) tma_2d(sb + OFF_WOB + c * 8192, &tm_wob, hp * 56, c * 64, BAR(B_WOB));
        }
      }
    }
  } else {
    asm volatile("setmaxnreg.inc.sync.aligned.u32 112;");
    const int mh = wg & 1, nh = wg >> 1, wq = warp & 3;
    float acc[28];
    uint32_t keep[32];
    int item = nh;
#pragma unroll
    for (int i = 0; i < 28; i++) acc[i] = 0.f;

#pragma unroll 1
    for (int stage = 0; stage < 4; stage++) {
      {
        int slot = item % RING, prev = 0;
        uint32_t par = (item / RING) & 1;
        const bool tail = stage >= 2;
        const uint64_t dS = make_desc(tail ? sb + OFF_WOA + (stage - 2) * 57344 : sb + OFF_X + mh * 8192, 1024, 1024, 1);
        const uint64_t dR = make_desc(sb + OFF_RING, 1024, 1024, 1);
#pragma unroll 1
        for (int c = 0; c < 7; c++) {
          mbar_wait(BAR(tail ? B_WOA + stage - 2 : B_X + c), 0);
          mbar_wait(BAR(B_FULL + slot), par);
          const uint64_t ds = dS + c * (tail ? 512 : 1024), dr = dR + slot * 512;
          const uint64_t dA = tail ? dr : ds, dB = tail ? ds : dr;
          wg_fence();
          wgmma_ss_n56_ta0_tb1<1>(acc, dA, dB);
          wgmma_ss_n56_ta0_tb1<1>(acc, dA + 2, dB + 128);
          wgmma_ss_n56_ta0_tb1<1>(acc, dA + 4, dB + 256);
          wgmma_ss_n56_ta0_tb1<1>(acc, dA + 6, dB + 384);
          wg_commit();
          wg_wait<1>();
          if (lane == 0 && c > 0) mbar_arrive(BAR(B_EMPTY + prev), tail ? 4 : 2);
          prev = slot;
          slot += 2;
          if (slot >= RING) { slot -= RING; par ^= 1; }
        }
        wg_wait<0>();
        fence_regs(acc);
        if (lane == 0) mbar_arrive(BAR(B_EMPTY + prev), tail ? 4 : 2);
        item += 14;
      }
      if (stage == 2) { if (tid == 0) PROF_MARK(15); continue; }
      if (stage == 3) break;
      int lane_;
      asm volatile("mov.u32 %0, %%laneid;" : "=r"(lane_));
      const int lq = lane_ & 3;
      const int rowl = wq * 16 + (lane_ >> 2);
      const int row0 = mh * 64 + rowl;
      if (stage == 0) {
        if (tid == 0) PROF_MARK(2);
        if (tid == 256) PROF_MARK(3);
        mbar_wait(BAR(B_BUILD), 0);
      } else {
        bar_sync(1, 512);
        if (tid == 0) PROF_MARK(6);
        if (nh == 1) sts64(sb + OFF_VA + (lq & 1) * 8192 + sw64_off(row0 + 8 * (lq >> 1), 28), 0x00003F80u, 0u);
        uint32_t h[14];
#pragma unroll
        for (int i = 0; i < 14; i++) h[i] = nh ? pack_bf16(acc[2 * i], acc[2 * i + 1]) : keep[i];
        store_heads(nh ? sb + OFF_VA : sb + OFF_QP + mh * 4096, h, nh ? row0 : rowl, lq);
      }
      if (stage != nh) {
        phi_from_acc(acc, sb, keep, lq);
      } else if (stage == 0) {
        {
          float accs[4] = {0.f, 0.f, 0.f, 0.f};
          const uint64_t dX = make_desc(sb + OFF_X + mh * 8192, 1024, 1024, 1);
          const uint64_t dSlc = make_desc(sb + OFF_SLC, 128, 128, 0);
#pragma unroll 1
          for (int c = 0; c < 7; c++) {
            wg_fence();
            wgmma_ss_n8_ta0_tb1<1>(accs, dX + c * 1024, dSlc + c * 64);
            wgmma_ss_n8_ta0_tb1<1>(accs, dX + c * 1024 + 2, dSlc + c * 64 + 16);
            wgmma_ss_n8_ta0_tb1<1>(accs, dX + c * 1024 + 4, dSlc + c * 64 + 32);
            wgmma_ss_n8_ta0_tb1<1>(accs, dX + c * 1024 + 6, dSlc + c * 64 + 48);
            wg_commit();
          }
          const float QS = 0.18898223650461362f * 1.4426950408889634f;
          float sq[4] = {0.f, 0.f, 0.f, 0.f};
#pragma unroll
          for (int j = 0; j < 7; j++) {
#pragma unroll
            for (int rr = 0; rr < 2; rr++) {
              float v0 = acc[4 * j + 2 * rr] * QS, v1 = acc[4 * j + 2 * rr + 1] * QS;
              keep[2 * j + rr] = pack_bf16(v0, v1);
              float s2 = v0 * v0 + v1 * v1;
              if (j < 3) sq[rr] += s2;
              else if (j > 3) sq[2 + rr] += s2;
              else { sq[rr] += (lq < 2) ? s2 : 0.f; sq[2 + rr] += (lq < 2) ? 0.f : s2; }
            }
          }
#pragma unroll
          for (int i = 0; i < 4; i++) sq[i] = quad_sum(sq[i]);
          ((float*)(sgen + OFF_QSQ))[(mh + (lq & 2)) * 64 + rowl + 8 * (lq & 1)] = lq == 0 ? sq[0] : lq == 1 ? sq[1] : lq == 2 ? sq[2] : sq[3];
          wg_wait<0>();
          fence_regs(accs);
          const int sl = hp & 3;
          const bool isk = hp < 4, real = (sl < 3) || (lq < 2);
          float mxv = 0.f;
#pragma unroll
          for (int rr = 0; rr < 2; rr++) {
            const int pos = pt * 128 + row0 + 8 * rr, kr = pos & 63;
            const float v0 = accs[2 * rr], v1 = accs[2 * rr + 1];
            const bool poly = isk && ((POLY_PAT >> (kr >> 3)) & 1);
            const float sc = poly ? 2.f : 1.f;
            const float s2 = quad_sum(real ? v0 * v0 + v1 * v1 : 0.f);
            mxv = fmaxf(mxv, s2 <= 3.0e38f ? s2 : __int_as_float(0x7f800000));
            const uint32_t padv = lq == 2 ? (poly ? 0x443F4000u : 0x00003F80u) : (poly ? 0x3AB03F4Du : 0u);
            const uint32_t outv = real ? pack_bf16(sc * v0, sc * v1) : padv;
            if (hp == 3 && lq == 2) g_gate[pos] = rcpf(1.f + ex2f(-1.4426950408889634f * v0));
            *(uint32_t*)(g_kv_img + (pos >> 6) * 8192 + (isk ? 0 : 4096) + sw64_off(kr, sl * 8 + 2 * lq)) = outv;
          }
#pragma unroll
          for (int o = 16; o >= 4; o >>= 1) mxv = fmaxf(mxv, __shfl_xor_sync(~0u, mxv, o));
          if (lane == 0) (isk ? g_ksq : g_vmx)[sl * 128 + pt * 8 + mh * 4 + wq] = mxv;
          __syncwarp();
          if (lane == 0) mbar_arrive(BAR(B_SIG + 0), 1);
        }
      }
      if (stage == 0) {
        if (tid == 0) PROF_MARK(4);
        if (tid == 256) PROF_MARK(5);
#pragma unroll
        for (int i = 0; i < 28; i++) acc[i] = 0.f;
        continue;
      }

      store_phi(nh ? sb + OFF_PHIK : sb + OFF_PHIQ, keep, row0, lq);
      fence_async_smem();
      if (nh == 1) {
        bar_sync(3, 256);
        float kv[16];
        const uint64_t dA = make_desc(sb + OFF_PHIK + mh * 16384, 1024, 1024, 1);
        const uint64_t dB = make_desc(sb + OFF_VA + mh * 8192, 512, 512, 2);
        wg_fence();
        wgmma_ss_n32_ta1_tb1<0>(kv, dA, dB);
#pragma unroll
        for (int ks = 1; ks < 8; ks++) wgmma_ss_n32_ta1_tb1<1>(kv, dA + ks * 128, dB + ks * 64);
        wg_commit();
        wg_wait<0>();
        fence_regs(kv);
        if (lane == 0) mbar_arrive(BAR(B_X0FREE), 1);
        float* dst = g_kvpart + ((size_t)(pt * 16 + 2 * hp + mh) * 64 + rowl) * 32 + 2 * lq;
#pragma unroll
        for (int j = 0; j < 4; j++) {
          *(float2*)(dst + 8 * j) = make_float2(kv[4 * j], kv[4 * j + 1]);
          *(float2*)(dst + 8 * 32 + 8 * j) = make_float2(kv[4 * j + 2], kv[4 * j + 3]);
        }
        __syncwarp();
        if (lane == 0) mbar_arrive(BAR(B_SIG + 1), 1);
      }
      if (tid == 0) PROF_MARK(7);
      if (tid == 256) PROF_MARK(8);

      mbar_wait(BAR(B_B1), 0);
      if (tid == 0) PROF_MARK(9);
      const float* red = (const float*)(sgen + OFF_RED);
      const float ksq = red[0], vsq = red[1];
      const float* qsq = (const float*)(sgen + OFF_QSQ);
      float b0, b1;
      asm("sqrt.approx.ftz.f32 %0, %1;" : "=f"(b0) : "f"(qsq[wg * 64 + rowl] * ksq));
      asm("sqrt.approx.ftz.f32 %0, %1;" : "=f"(b1) : "f"(qsq[wg * 64 + rowl + 8] * ksq));
      b0 *= 1.02f; b1 *= 1.02f;
      const bool bad = !(b0 <= 92.f) || !(b1 <= 92.f) || !(vsq <= 1.0e24f);
      const bool slow = __any_sync(~0u, bar_or(1, 512, bad));
      if (tid == 0) { *(volatile int*)(sgen + OFF_RED + 8) = slow; mbar_arrive(BAR(B_SLOW), 1); }

      uint32_t q[8];
      {
        const uint32_t qa = sb + OFF_QP + wg * 4096;
        const int r = wq * 16 + (lane_ & 7) + ((lane_ >> 3) & 1) * 8;
#pragma unroll
        for (int ks = 0; ks < 2; ks++)
          asm volatile("ldmatrix.sync.aligned.m8n8.x4.shared.b16 {%0, %1, %2, %3}, [%4];"
                       : "=r"(q[4 * ks]), "=r"(q[4 * ks + 1]), "=r"(q[4 * ks + 2]), "=r"(q[4 * ks + 3])
                       : "r"(qa + sw64_off(r, ks * 16 + (lane_ >> 4) * 8)) : "memory");
        if (lq >= 2) {
          q[6] = slow ? 0u : (lq == 2 ? pack_bf16(64.f - b0, 1.f) : 0x3F803F80u);
          q[7] = slow ? 0u : (lq == 2 ? pack_bf16(64.f - b1, 1.f) : 0x3F803F80u);
        }
      }

      const uint64_t dK = make_desc(sb + OFF_RING, 16, 512, 2);
      const uint64_t dV = make_desc(sb + OFF_RING + 4096, 512, 512, 2);
      int slot = 28 % RING, prev = 0;
      uint32_t par = (28 / RING) & 1;
      float m0 = -3.0e38f, m1 = -3.0e38f;
      if (__builtin_expect(slow, 0)) {
#pragma unroll 1
        for (int j64 = 0; j64 < 32; j64++) {
          float s[32];
          mbar_wait(BAR(B_FULL + slot), par);
          wg_fence();
          wgmma_rs_n64_tb0<0>(s, q[0], q[1], q[2], q[3], dK + slot * 512);
          wgmma_rs_n64_tb0<1>(s, q[4], q[5], q[6], q[7], dK + slot * 512 + 2);
          wg_commit();
          wg_wait<0>();
          fence_regs(s);
#pragma unroll
          for (int j = 0; j < 8; j++) {
            const float sc = ((POLY_PAT >> j) & 1) ? 0.5f : 1.f;
            m0 = fmaxf(m0, fmaxf(s[4 * j], s[4 * j + 1]) * sc);
            m1 = fmaxf(m1, fmaxf(s[4 * j + 2], s[4 * j + 3]) * sc);
          }
          if (lane == 0) mbar_arrive(BAR(B_EMPTY + slot), 1);
          if (++slot == RING) { slot = 0; par ^= 1; }
        }
        m0 = quad_max(m0); m1 = quad_max(m1);
      }
      float o[16];
#pragma unroll
      for (int i = 0; i < 16; i++) o[i] = 0.f;
      if (tid == 0) PROF_MARK(10);
#pragma unroll 1
      for (int half = 0; half < 2; half++) {
        const uint32_t c_half = 0x3F003F00u, c_3 = 0x00030003u;
#pragma unroll 1
        for (int j64 = 0; j64 < 16; j64++) {
          float s[32];
          mbar_wait(BAR(B_FULL + slot), par);
          wg_fence();
          wgmma_rs_n64_tb0<0>(s, q[0], q[1], q[2], q[3], dK + slot * 512);
          wgmma_rs_n64_tb0<1>(s, q[4], q[5], q[6], q[7], dK + slot * 512 + 2);
          wg_commit();
          wg_wait<0>();
          fence_regs(s);
          if (lane == 0 && j64 > 0) mbar_arrive(BAR(B_EMPTY + prev), 1);
          uint32_t p[16];
          if (__builtin_expect(!slow, 1)) {
#pragma unroll
            for (int j = 0; j < 8; j++) {
              if ((POLY_PAT >> j) & 1) {
                p[2 * j] = exp2_pair_fma(s[4 * j], s[4 * j + 1], c_half, c_3);
                p[2 * j + 1] = exp2_pair_fma(s[4 * j + 2], s[4 * j + 3], c_half, c_3);
              } else {
                p[2 * j] = pack_bf16(ex2f(s[4 * j]), ex2f(s[4 * j + 1]));
                p[2 * j + 1] = pack_bf16(ex2f(s[4 * j + 2]), ex2f(s[4 * j + 3]));
              }
            }
          } else {
#pragma unroll
            for (int j = 0; j < 8; j++) {
              const float sc = ((POLY_PAT >> j) & 1) ? 0.5f : 1.f;
              p[2 * j] = pack_bf16(ex2f(fmaf(s[4 * j], sc, -m0)), ex2f(fmaf(s[4 * j + 1], sc, -m0)));
              p[2 * j + 1] = pack_bf16(ex2f(fmaf(s[4 * j + 2], sc, -m1)), ex2f(fmaf(s[4 * j + 3], sc, -m1)));
            }
          }
          wg_fence();
#pragma unroll
          for (int ks = 0; ks < 4; ks++)
            wgmma_rs_n32_tb1<1>(o, p[4 * ks], p[4 * ks + 1], p[4 * ks + 2], p[4 * ks + 3], dV + slot * 512 + ks * 64);
          wg_commit();
          prev = slot;
          if (++slot == RING) { slot = 0; par ^= 1; }
        }
        wg_wait<0>();
        fence_regs(o);
        if (lane == 0) mbar_arrive(BAR(B_EMPTY + prev), 1);
        float t[16];
        if (half == 0) {
          if (tid == 0) PROF_MARK(11);
          mbar_wait(BAR(B_KVR), 0);
          const uint64_t dA = make_desc(sb + OFF_PHIQ + nh * 16384 + mh * 8192, 16, 1024, 1);
          const uint64_t dB = make_desc(sb + OFF_KVR + nh * 4096, 512, 512, 2);
          wg_fence();
          wgmma_ss_n32_ta0_tb1<0>(t, dA, dB);
#pragma unroll
          for (int ks = 1; ks < 4; ks++) wgmma_ss_n32_ta0_tb1<1>(t, dA + ks * 2, dB + ks * 64);
          wg_commit();
          wg_wait<0>();
          fence_regs(t);
          if (lane == 0) mbar_arrive(BAR(B_X1FREE), 1);
        } else {
          if (tid == 0) PROF_MARK(13);
#pragma unroll
          for (int i = 0; i < 16; i++) t[i] = o[i];
        }
        {
          const float g0 = ((const float*)(sgen + OFF_GATE))[row0], g1 = ((const float*)(sgen + OFF_GATE))[row0 + 8];
          const float eps = half ? 0.f : 1e-6f;
          const float d0 = __shfl_sync(~0u, t[12], (lane_ & ~3) | 2), d1 = __shfl_sync(~0u, t[14], (lane_ & ~3) | 2);
          const float r0 = __fdividef(half ? 1.f - g0 : g0, d0 + eps), r1 = __fdividef(half ? 1.f - g1 : g1, d1 + eps);
          uint8_t* img = g_o_img + (size_t)((half * 16 + pt) * 14 + mh) * 8192 + rowl * 128;
          const int col0 = (2 * hp + nh) * DH + 2 * lq;
#pragma unroll
          for (int j = 0; j < 4; j++) {
            const int col = col0 + 8 * j;
            uint8_t* p = img + (col >> 6) * 16384 + ((((col >> 3) ^ rowl) & 7) << 4) + (col & 7) * 2;
            const uint32_t v0 = pack_bf16(t[4 * j] * r0, t[4 * j + 1] * r0), v1 = pack_bf16(t[4 * j + 2] * r1, t[4 * j + 3] * r1);
            if (j < 3 || lq < 2) { *(uint32_t*)p = v0; *(uint32_t*)(p + 1024) = v1; }
          }
          __syncwarp();
          if (lane == 0) mbar_arrive(BAR(B_SIG + 2 + half), 1);
        }
        if (tid == 0) PROF_MARK(12 + 2 * half);
      }
      if (nh == 1) return;
      item = (slow ? 92 : 60) + mh;
#pragma unroll
      for (int i = 0; i < 32; i++) keep[i] = 0u;
#pragma unroll
      for (int i = 0; i < 28; i++) acc[i] = 0.f;
    }
    if (tid == 0) PROF_MARK(17);
    __nv_bfloat16* op = prm.out + (size_t)(pt * 128 + mh * 64 + wq * 16 + (lane >> 2)) * DM + hp * 56 + 2 * (lane & 3);
#pragma unroll
    for (int j = 0; j < 7; j++) {
      *(uint32_t*)(op + 8 * j) = pack_bf16(acc[4 * j], acc[4 * j + 1]);
      *(uint32_t*)(op + 8 * DM + 8 * j) = pack_bf16(acc[4 * j + 2], acc[4 * j + 3]);
    }
    if (tid == 0) { PROF_MARK(18); PROF_CLK(31); }
    if (tid == 0) {
      unsigned prevd = atomicAdd(&g_cnt[C_DONE * 32], 1u);
      if (prevd == NCTA - 1) {
#pragma unroll 1
        for (int i = 0; i < C_N; i++) g_cnt[i * 32] = 0;
      }
    }
  }
}

typedef CUresult (*EncodeFn)(CUtensorMap*, CUtensorMapDataType, cuuint32_t, void*, const cuuint64_t*, const cuuint64_t*,
                             const cuuint32_t*, const cuuint32_t*, CUtensorMapInterleave, CUtensorMapSwizzle,
                             CUtensorMapL2promotion, CUtensorMapFloatOOBfill);

void make_map(EncodeFn enc, CUtensorMap* tm, const void* ptr, uint64_t cols, uint64_t rows, uint32_t box_rows) {
  cuuint64_t dims[2] = {cols, rows};
  cuuint64_t strides[1] = {cols * 2};
  cuuint32_t box[2] = {64, box_rows};
  cuuint32_t es[2] = {1, 1};
  enc(tm, CU_TENSOR_MAP_DATA_TYPE_BFLOAT16, 2, const_cast<void*>(ptr), dims, strides, box, es, CU_TENSOR_MAP_INTERLEAVE_NONE,
      CU_TENSOR_MAP_SWIZZLE_128B, CU_TENSOR_MAP_L2_PROMOTION_L2_128B, CU_TENSOR_MAP_FLOAT_OOB_FILL_NONE);
}

}

extern "C" void kernel_launch(void* const* d_in, const int* in_sizes, int n_in, void* d_out, int out_size) {
  (void)in_sizes; (void)n_in; (void)out_size;
  static EncodeFn enc = nullptr;
  if (!enc) {
    void* fn = nullptr;
    cudaDriverEntryPointQueryResult qr;
    cudaGetDriverEntryPoint("cuTensorMapEncodeTiled", &fn, cudaEnableDefault, &qr);
    enc = (EncodeFn)fn;
    cudaFuncSetAttribute(fused_kernel, cudaFuncAttributeMaxDynamicSharedMemorySize, SMEM_BYTES);
  }
  CUtensorMap tm_x, tm_wqkv, tm_wq, tm_woa, tm_wob;
  make_map(enc, &tm_x, d_in[0], DM, S_LEN, 128);
  make_map(enc, &tm_wqkv, d_in[1], 3 * DM, DM, 64);
  make_map(enc, &tm_wq, d_in[5], DM, DM, 64);
  make_map(enc, &tm_woa, d_in[3], DM, DM, 64);
  make_map(enc, &tm_wob, d_in[8], DM, DM, 64);
  Params prm;
  prm.w_phi = (const __nv_bfloat16*)d_in[2];
  prm.wk = (const __nv_bfloat16*)d_in[6];
  prm.wv = (const __nv_bfloat16*)d_in[7];
  prm.gate_w = (const __nv_bfloat16*)d_in[9];
  prm.out = (__nv_bfloat16*)d_out;
  fused_kernel<<<NCTA, NTHREADS, SMEM_BYTES>>>(tm_x, tm_wqkv, tm_wq, tm_woa, tm_wob, prm);
}
```

```cpp
#include <cuda_runtime.h>
#include <cuda_bf16.h>
#include <cuda.h>
#include <stdint.h>

namespace {

constexpr int S_LEN = 2048, DM = 448, DH = 28;
constexpr int NCTA = 128;
constexpr int NTHREADS = 640;
constexpr uint32_t POLY_PAT = 0x57;

#define KB_AT (wg >> 1)
#define QB_AT (5 + (wg >> 1))

constexpr int OFF_X = 0;
constexpr int OFF_KA = 0;
constexpr int OFF_VA = 16384;
constexpr int OFF_QP = 32768;
constexpr int OFF_QA = 57344;
constexpr int OFF_KVR = 73728;
constexpr int OFF_PHI = 81920;
constexpr int OFF_WO = 0;
constexpr int OFF_RING = 114688;
constexpr int OFF_WPH = 212992;
constexpr int OFF_SLC = 217088;
constexpr int OFF_QSQ = 224256;
constexpr int OFF_GATE = 225280;
constexpr int OFF_RED = 225792;
constexpr int OFF_BAR = 225856;
constexpr int SMEM_BYTES = 226368 + 1024;

constexpr int B_FULL = 0, B_X = 12, B_EMPTY = 19, B_WO = 31  , B_KVR = 33, B_X0FREE = 34, B_X1FREE = 35, B_B1 = 36,
              B_SLOW = 37, B_BUILD = 38, B_STG = 39, B_SIG = 40  , B_N = 44;

constexpr int C_KV = 0, C_PART = 1, C_RED = 2, C_DONE = 3, C_OA = 4, C_OB = 20, C_N = 36;

__device__ __align__(1024) uint8_t g_kv_img[32 * 8192];
__device__ __align__(16) float g_ksq[512];
__device__ __align__(16) float g_vsq[512];
__device__ __align__(16) float g_gate[S_LEN];
__device__ __align__(1024) float g_kvpart[128 * 32 * 256];
__device__ __align__(1024) uint8_t g_kvr_img[16 * 4096];
__device__ __align__(1024) uint8_t g_o_img[2 * 16 * 14 * 8192];
__device__ unsigned g_cnt[C_N * 32];

#define PROF2(i) do { } while (0)
#define PROF_CLK(i) do { } while (0)
#define PROF_MARK(i) do { } while (0)
__device__ __forceinline__ uint32_t smem_u32(const void* p) { return (uint32_t)__cvta_generic_to_shared(p); }
__device__ __forceinline__ void mbar_init(uint32_t a, int cnt) {
  asm volatile("mbarrier.init.shared::cta.b64 [%0], %1;" ::"r"(a), "r"(cnt) : "memory");
}
__device__ __forceinline__ void mbar_expect_tx(uint32_t a, uint32_t bytes) {
  asm volatile("mbarrier.arrive.expect_tx.shared::cta.b64 _, [%0], %1;" ::"r"(a), "r"(bytes) : "memory");
}
__device__ __forceinline__ void mbar_arrive(uint32_t a, uint32_t cnt) {
  asm volatile("mbarrier.arrive.shared::cta.b64 _, [%0], %1;" ::"r"(a), "r"(cnt) : "memory");
}
__device__ __forceinline__ void mbar_wait(uint32_t a, uint32_t parity) {
  asm volatile(
      "{\n.reg .pred p;\n.reg .u32 c;\nmov.u32 c, 0;\n"
      "W_%=:\nmbarrier.try_wait.parity.shared::cta.b64 p, [%0], %1;\n"
      "add.u32 c, c, 1;\nsetp.lt.and.u32 p, c, 0x1000000, !p;\n@p bra W_%=;\n}"
      ::"r"(a), "r"(parity) : "memory");
}
__device__ __forceinline__ uint32_t mbar_test(uint32_t a, uint32_t parity) {
  uint32_t ok;
  asm volatile("{\n.reg .pred p;\nmbarrier.test_wait.parity.shared::cta.b64 p, [%1], %2;\nselp.u32 %0, 1, 0, p;\n}"
               : "=r"(ok) : "r"(a), "r"(parity) : "memory");
  return ok;
}
__device__ __forceinline__ bool elect_one() {
  uint32_t r;
  asm volatile("{\n.reg .pred p;\nelect.sync _|p, 0xffffffff;\nselp.u32 %0, 1, 0, p;\n}" : "=r"(r));
  return r != 0;
}
__device__ __forceinline__ void tma_2d(uint32_t dst, const CUtensorMap* tm, int c0, int c1, uint32_t bar) {
  asm volatile("cp.async.bulk.tensor.2d.shared::cluster.global.mbarrier::complete_tx::bytes [%0], [%1, {%3, %4}], [%2];"
               ::"r"(dst), "l"(tm), "r"(bar), "r"(c0), "r"(c1) : "memory");
}
__device__ __forceinline__ void bulk_g2s(uint32_t dst, const void* src, uint32_t bytes, uint32_t bar) {
  asm volatile("cp.async.bulk.shared::cluster.global.mbarrier::complete_tx::bytes [%0], [%1], %2, [%3];"
               ::"r"(dst), "l"(src), "r"(bytes), "r"(bar) : "memory");
}
__device__ __forceinline__ void cp_async8(uint32_t dst, const void* src) {
  asm volatile("cp.async.ca.shared.global [%0], [%1], 8;" ::"r"(dst), "l"(src) : "memory");
}
__device__ __forceinline__ void fence_async_smem() { asm volatile("fence.proxy.async.shared::cta;" ::: "memory"); }
__device__ __forceinline__ void fence_async_all() { asm volatile("fence.proxy.async;" ::: "memory"); }
__device__ __forceinline__ void bar_sync(int id, int n) { asm volatile("bar.sync %0, %1;" ::"r"(id), "r"(n) : "memory"); }
__device__ __forceinline__ void cnt_arrive(int idx) {
  asm volatile("red.release.gpu.global.add.u32 [%0], 1;" ::"l"(&g_cnt[idx * 32]) : "memory");
}
__device__ __forceinline__ void cnt_wait(int idx, unsigned target) {
  unsigned v, n = 0;
#pragma unroll 1
  while (true) {
    asm volatile("ld.relaxed.gpu.global.u32 %0, [%1];" : "=r"(v) : "l"(&g_cnt[idx * 32]) : "memory");
    if (v >= target || ++n >= (1u << 22)) break;
    __nanosleep(64);
  }
  asm volatile("fence.acq_rel.gpu;" ::: "memory");
}
__device__ __forceinline__ void wg_fence() { asm volatile("wgmma.fence.sync.aligned;" ::: "memory"); }
__device__ __forceinline__ void wg_commit() { asm volatile("wgmma.commit_group.sync.aligned;" ::: "memory"); }
template <int N> __device__ __forceinline__ void wg_wait() { asm volatile("wgmma.wait_group.sync.aligned %0;" ::"n"(N) : "memory"); }
template <int N> __device__ __forceinline__ void fence_regs(float (&d)[N]) {
#pragma unroll
  for (int i = 0; i < N; i++) asm volatile("" : "+f"(d[i])::"memory");
}
__device__ __forceinline__ uint64_t make_desc(uint32_t saddr, uint32_t lbo, uint32_t sbo, uint32_t swz) {
  return (uint64_t)((saddr & 0x3FFFF) >> 4) | ((uint64_t)(lbo >> 4) << 16) | ((uint64_t)(sbo >> 4) << 32) | ((uint64_t)swz << 62);
}
__device__ __forceinline__ float ex2f(float x) { float y; asm("ex2.approx.ftz.f32 %0, %1;" : "=f"(y) : "f"(x)); return y; }
__device__ __forceinline__ float rcpf(float x) { float y; asm("rcp.approx.ftz.f32 %0, %1;" : "=f"(y) : "f"(x)); return y; }
__device__ __forceinline__ uint32_t pack_bf16(float lo, float hi) {
  uint32_t r; asm("cvt.rn.bf16x2.f32 %0, %1, %2;" : "=r"(r) : "f"(hi), "f"(lo)); return r;
}
__device__ __forceinline__ uint32_t lop_and_or(uint32_t a, uint32_t m, uint32_t c) {
  uint32_t r; asm("lop3.b32 %0, %1, %2, %3, 0xEA;" : "=r"(r) : "r"(a), "r"(m), "r"(c)); return r;
}
__device__ __forceinline__ void sts32(uint32_t a, uint32_t v) { asm volatile("st.shared.b32 [%0], %1;" ::"r"(a), "r"(v) : "memory"); }
__device__ __forceinline__ void sts64(uint32_t a, uint32_t v0, uint32_t v1) { asm volatile("st.shared.v2.b32 [%0], {%1, %2};" ::"r"(a), "r"(v0), "r"(v1) : "memory"); }
__device__ __forceinline__ void sts128(uint32_t a, uint4 v) {
  asm volatile("st.shared.v4.b32 [%0], {%1, %2, %3, %4};" ::"r"(a), "r"(v.x), "r"(v.y), "r"(v.z), "r"(v.w) : "memory");
}
__device__ __forceinline__ float4 ldcg_f4(const float* p) {
  float4 v; asm volatile("ld.global.cg.v4.f32 {%0, %1, %2, %3}, [%4];" : "=f"(v.x), "=f"(v.y), "=f"(v.z), "=f"(v.w) : "l"(p) : "memory"); return v;
}
__device__ __forceinline__ float quad_sum(float v) { v += __shfl_xor_sync(~0u, v, 1); v += __shfl_xor_sync(~0u, v, 2); return v; }
__device__ __forceinline__ float quad_max(float v) { v = fmaxf(v, __shfl_xor_sync(~0u, v, 1)); v = fmaxf(v, __shfl_xor_sync(~0u, v, 2)); return v; }

template <int SD> __device__ __forceinline__ void wgmma_ss_n56_ta0_tb1(float (&d)[28], uint64_t da, uint64_t db) {
  asm volatile("wgmma.mma_async.sync.aligned.m64n56k16.f32.bf16.bf16 {%0, %1, %2, %3, %4, %5, %6, %7, %8, %9, %10, %11, %12, %13, %14, %15, %16, %17, %18, %19, %20, %21, %22, %23, %24, %25, %26, %27}, %28, %29, %30, 1, 1, 0, 1;\n"
    : "+f"(d[0]), "+f"(d[1]), "+f"(d[2]), "+f"(d[3]), "+f"(d[4]), "+f"(d[5]), "+f"(d[6]), "+f"(d[7]), "+f"(d[8]), "+f"(d[9]), "+f"(d[10]), "+f"(d[11]), "+f"(d[12]), "+f"(d[13]), "+f"(d[14]), "+f"(d[15]), "+f"(d[16]), "+f"(d[17]), "+f"(d[18]), "+f"(d[19]), "+f"(d[20]), "+f"(d[21]), "+f"(d[22]), "+f"(d[23]), "+f"(d[24]), "+f"(d[25]), "+f"(d[26]), "+f"(d[27])
    : "l"(da), "l"(db), "n"(SD));
}
template <int SD> __device__ __forceinline__ void wgmma_ss_n8_ta0_tb1(float (&d)[4], uint64_t da, uint64_t db) {
  asm volatile("wgmma.mma_async.sync.aligned.m64n8k16.f32.bf16.bf16 {%0, %1, %2, %3}, %4, %5, %6, 1, 1, 0, 1;\n"
    : "+f"(d[0]), "+f"(d[1]), "+f"(d[2]), "+f"(d[3])
    : "l"(da), "l"(db), "n"(SD));
}
template <int SD> __device__ __forceinline__ void wgmma_ss_n32_ta1_tb1(float (&d)[16], uint64_t da, uint64_t db) {
  asm volatile("wgmma.mma_async.sync.aligned.m64n32k16.f32.bf16.bf16 {%0, %1, %2, %3, %4, %5, %6, %7, %8, %9, %10, %11, %12, %13, %14, %15}, %16, %17, %18, 1, 1, 1, 1;\n"
    : "+f"(d[0]), "+f"(d[1]), "+f"(d[2]), "+f"(d[3]), "+f"(d[4]), "+f"(d[5]), "+f"(d[6]), "+f"(d[7]), "+f"(d[8]), "+f"(d[9]), "+f"(d[10]), "+f"(d[11]), "+f"(d[12]), "+f"(d[13]), "+f"(d[14]), "+f"(d[15])
    : "l"(da), "l"(db), "n"(SD));
}
template <int SD> __device__ __forceinline__ void wgmma_ss_n32_ta0_tb1(float (&d)[16], uint64_t da, uint64_t db) {
  asm volatile("wgmma.mma_async.sync.aligned.m64n32k16.f32.bf16.bf16 {%0, %1, %2, %3, %4, %5, %6, %7, %8, %9, %10, %11, %12, %13, %14, %15}, %16, %17, %18, 1, 1, 0, 1;\n"
    : "+f"(d[0]), "+f"(d[1]), "+f"(d[2]), "+f"(d[3]), "+f"(d[4]), "+f"(d[5]), "+f"(d[6]), "+f"(d[7]), "+f"(d[8]), "+f"(d[9]), "+f"(d[10]), "+f"(d[11]), "+f"(d[12]), "+f"(d[13]), "+f"(d[14]), "+f"(d[15])
    : "l"(da), "l"(db), "n"(SD));
}
template <int SD> __device__ __forceinline__ void wgmma_rs_n64_tb0(float (&d)[32], uint32_t a0, uint32_t a1, uint32_t a2, uint32_t a3, uint64_t db) {
  asm volatile("wgmma.mma_async.sync.aligned.m64n64k16.f32.bf16.bf16 {%0, %1, %2, %3, %4, %5, %6, %7, %8, %9, %10, %11, %12, %13, %14, %15, %16, %17, %18, %19, %20, %21, %22, %23, %24, %25, %26, %27, %28, %29, %30, %31}, {%32, %33, %34, %35}, %36, %37, 1, 1, 0;\n"
    : "+f"(d[0]), "+f"(d[1]), "+f"(d[2]), "+f"(d[3]), "+f"(d[4]), "+f"(d[5]), "+f"(d[6]), "+f"(d[7]), "+f"(d[8]), "+f"(d[9]), "+f"(d[10]), "+f"(d[11]), "+f"(d[12]), "+f"(d[13]), "+f"(d[14]), "+f"(d[15]), "+f"(d[16]), "+f"(d[17]), "+f"(d[18]), "+f"(d[19]), "+f"(d[20]), "+f"(d[21]), "+f"(d[22]), "+f"(d[23]), "+f"(d[24]), "+f"(d[25]), "+f"(d[26]), "+f"(d[27]), "+f"(d[28]), "+f"(d[29]), "+f"(d[30]), "+f"(d[31])
    : "r"(a0), "r"(a1), "r"(a2), "r"(a3), "l"(db), "n"(SD));
}
template <int SD> __device__ __forceinline__ void wgmma_rs_n32_tb1(float (&d)[16], uint32_t a0, uint32_t a1, uint32_t a2, uint32_t a3, uint64_t db) {
  asm volatile("wgmma.mma_async.sync.aligned.m64n32k16.f32.bf16.bf16 {%0, %1, %2, %3, %4, %5, %6, %7, %8, %9, %10, %11, %12, %13, %14, %15}, {%16, %17, %18, %19}, %20, %21, 1, 1, 1;\n"
    : "+f"(d[0]), "+f"(d[1]), "+f"(d[2]), "+f"(d[3]), "+f"(d[4]), "+f"(d[5]), "+f"(d[6]), "+f"(d[7]), "+f"(d[8]), "+f"(d[9]), "+f"(d[10]), "+f"(d[11]), "+f"(d[12]), "+f"(d[13]), "+f"(d[14]), "+f"(d[15])
    : "r"(a0), "r"(a1), "r"(a2), "r"(a3), "l"(db), "n"(SD));
}

__device__ __forceinline__ uint32_t sw64_off(int row, int d) { return row * 64 + ((((d >> 3) ^ (row >> 1)) & 3) << 4) + (d & 7) * 2; }

__device__ __forceinline__ uint32_t exp2_pair_fma(float t0, float t1, uint32_t c_half, uint32_t c_3) {
  uint32_t y0, y;
  asm("prmt.b32 %0, %1, %2, 0x6521;" : "=r"(y0) : "r"(__float_as_uint(t0)), "r"(__float_as_uint(t1)));
  uint32_t h = lop_and_or(y0, 0x007F007Fu, c_half);
  uint32_t e = lop_and_or(y0, 0xFF80FF80u, c_3);
  asm("fma.rn.bf16x2 %0, %1, %2, %3;" : "=r"(y) : "r"(y0), "r"(h), "r"(e));
  return y;
}

__device__ __forceinline__ void feature_map(float (&v)[16], uint32_t (&ph)[16], int lq) {
  const float L2E = 1.4426950408889634f;
  const bool tail_ok = lq < 2;
  float mx[2], mn[2], b[16], sa[2], sn[2];
#pragma unroll
  for (int r = 0; r < 2; r++) {
    const int o = 2 * r;
    if (!tail_ok) { v[o + 12] = v[o]; v[o + 13] = v[o]; }
    mx[r] = fmaxf(fmaxf(fmaxf(v[o], v[o + 1]), fmaxf(v[o + 4], v[o + 5])), fmaxf(fmaxf(v[o + 8], v[o + 9]), fmaxf(v[o + 12], v[o + 13])));
    mn[r] = fminf(fminf(fminf(v[o], v[o + 1]), fminf(v[o + 4], v[o + 5])), fminf(fminf(v[o + 8], v[o + 9]), fminf(v[o + 12], v[o + 13])));
  }
#pragma unroll
  for (int o = 1; o <= 2; o <<= 1)
#pragma unroll
    for (int r = 0; r < 2; r++) { mx[r] = fmaxf(mx[r], __shfl_xor_sync(~0u, mx[r], o)); mn[r] = fminf(mn[r], __shfl_xor_sync(~0u, mn[r], o)); }
#pragma unroll
  for (int r = 0; r < 2; r++) {
    const int o = 2 * r;
    const float cx = -mx[r] * L2E, cn = mn[r] * L2E;
#pragma unroll
    for (int i = 0; i < 8; i++) {
      const int k = o + 4 * (i >> 1) + (i & 1);
      b[k] = ex2f(fmaf(v[k], -L2E, cn));
      v[k] = ex2f(fmaf(v[k], L2E, cx));
    }
    if (!tail_ok) { v[o + 12] = v[o + 13] = b[o + 12] = b[o + 13] = 0.f; }
    sa[r] = ((v[o] + v[o + 1]) + (v[o + 4] + v[o + 5])) + ((v[o + 8] + v[o + 9]) + (v[o + 12] + v[o + 13]));
    sn[r] = ((b[o] + b[o + 1]) + (b[o + 4] + b[o + 5])) + ((b[o + 8] + b[o + 9]) + (b[o + 12] + b[o + 13]));
  }
#pragma unroll
  for (int o = 1; o <= 2; o <<= 1)
#pragma unroll
    for (int r = 0; r < 2; r++) { sa[r] += __shfl_xor_sync(~0u, sa[r], o); sn[r] += __shfl_xor_sync(~0u, sn[r], o); }
#pragma unroll
  for (int r = 0; r < 2; r++) {
    const float ra = rcpf(sa[r]), rb = rcpf(sn[r]);
#pragma unroll
    for (int jj = 0; jj < 4; jj++) {
      ph[jj * 2 + r] = pack_bf16(v[2 * r + 4 * jj] * ra, v[2 * r + 4 * jj + 1] * ra);
      ph[(4 + jj) * 2 + r] = pack_bf16(b[2 * r + 4 * jj] * rb, b[2 * r + 4 * jj + 1] * rb);
    }
  }
}

__device__ __forceinline__ void store_heads(uint32_t base, const uint32_t (&a)[14], uint32_t pad, int row0, int lq) {
  const uint32_t rb = base + row0 * 64 + (((row0 >> 1) & 3) << 4);
  const uint32_t b0 = rb + lq * 4;
  const uint32_t b1 = (rb + 8192 + ((lq * 4 + 8) & 15)) ^ ((lq >> 1) << 4);
#pragma unroll
  for (int j = 0; j < 7; j++) {
    uint32_t ad;
    if (j < 3) ad = b0 ^ (j << 4);
    else if (j == 3) ad = (lq < 2) ? (b0 ^ 48u) : (b1 ^ 16u);
    else ad = (lq < 2) ? (b1 ^ ((j - 4) << 4)) : ((b1 ^ 16u) ^ ((j - 3) << 4));
    sts32(ad, a[2 * j]);
    sts32(ad + 512, a[2 * j + 1]);
  }
  sts64((rb ^ 48u) + 8 + (lq & 1) * 8192 + (lq >> 1) * 512, pad, 0u);
}

struct Params {
  const __nv_bfloat16* w_phi;
  const __nv_bfloat16* wk;
  const __nv_bfloat16* wv;
  const __nv_bfloat16* gate_w;
  __nv_bfloat16* out;
};

__global__ void __launch_bounds__(NTHREADS, 1)
fused_kernel(const __grid_constant__ CUtensorMap tm_x, const __grid_constant__ CUtensorMap tm_wqkv,
             const __grid_constant__ CUtensorMap tm_wq, const __grid_constant__ CUtensorMap tm_woa,
             const __grid_constant__ CUtensorMap tm_wob, const Params prm) {
  extern __shared__ uint8_t smem_raw[];
  uint32_t sb = (smem_u32(smem_raw) + 1023u) & ~1023u;
  uint8_t* sgen = smem_raw + (sb - smem_u32(smem_raw));
  asm volatile("mov.u32 %0, %0;" : "+r"(sb));
  const int tid = threadIdx.x, lane = tid & 31;
  const int warp = __shfl_sync(~0u, tid >> 5, 0), wg = warp >> 2;
  const int pt = blockIdx.x >> 3, hp = blockIdx.x & 7;
  const uint32_t bars = sb + OFF_BAR;
  auto BAR = [&](int i) { return bars + 8u * i; };

  if (tid == 0) { PROF_MARK(0); PROF_CLK(30); PROF2(15); }
  if (elect_one()) {
    if (warp < B_EMPTY) {
      mbar_init(BAR(warp), 1);
      fence_async_smem();
      const bool isx = warp >= B_X;
      const int c = isx ? warp - B_X : warp >> 1;
      mbar_expect_tx(BAR(warp), isx ? 16384 : 8192);
      tma_2d(isx ? sb + OFF_X + c * 16384 : sb + OFF_RING + warp * 8192, isx ? &tm_x : ((warp & 1) ? &tm_wqkv : &tm_wq),
             isx ? c * 64 : hp * 56 + ((warp & 1) ? DM : 0), isx ? pt * 128 : c * 64, BAR(warp));
    }
#pragma unroll 1
    for (int i = B_EMPTY + (warp + 1) % 20; i < B_N; i += 20) {
      int cnt = 16;
      if ((i >= B_WO && i <= B_KVR) || i == B_SLOW || i == B_STG) cnt = 1;
      if (i == B_B1) cnt = 2;
      if (i == B_BUILD) cnt = 3;
      if (i == B_SIG) cnt = 8;
      mbar_init(BAR(i), cnt);
    }
    fence_async_smem();
  }
  __syncthreads();

  if (wg == 4) {
    asm volatile("setmaxnreg.dec.sync.aligned.u32 32;");
    if (warp == 16) {
      if (elect_one()) {
#pragma unroll 1
        for (int i = 6; i < 14; i++) {
          const int c = i < 7 ? i : i - 7, ps = i % 6;
#pragma unroll 1
          for (int h = 0; h < 2; h++) {
            const int sl = 2 * ps + h;
            mbar_wait(BAR(B_EMPTY + sl), (i / 6 - 1) & 1);
            mbar_expect_tx(BAR(B_FULL + sl), 8192);
            tma_2d(sb + OFF_RING + sl * 8192, (i < 7 && !h) ? &tm_wq : &tm_wqkv, hp * 56 + (h ? (i < 7 ? DM : 2 * DM) : 0), c * 64,
                   BAR(B_FULL + sl));
          }
        }
        PROF_MARK(20);
        cnt_wait(C_KV, NCTA);
        PROF_MARK(21);
        fence_async_all();
        int slot = 4, ng = 8;
        uint32_t par = 1;
#pragma unroll 1
        for (int n = 0; n < ng; n++) {
          mbar_wait(BAR(B_EMPTY + slot), par);
          if (n < 3) { mbar_wait(BAR(B_EMPTY + slot + 1), par); mbar_wait(BAR(B_EMPTY + slot + 2), par); mbar_wait(BAR(B_EMPTY + slot + 3), par); }
          mbar_expect_tx(BAR(B_FULL + slot), 32768);
          bulk_g2s(sb + OFF_RING + slot * 8192, g_kv_img + (n & 7) * 32768, 32768, BAR(B_FULL + slot));
          slot += 4;
          if (slot == 12) { slot = 0; par ^= 1; }
          if (n == 7) {
            mbar_wait(BAR(B_SLOW), 0);
            if (*(volatile int*)(sgen + OFF_RED + 8)) ng = 16;
          }
        }
#pragma unroll 1
        for (int i = 0; i < 14; i++) {
          const int ps = i % 6, g4 = (ps >> 1) * 4, bi = g4 + 1 + (ps & 1);
          if (i == 0 || i == 7) {
            cnt_wait((i ? C_OB : C_OA) + pt, 8);
            PROF_MARK(26);
            fence_async_all();
          }
          if (i < 6) mbar_wait(BAR(B_EMPTY + g4), g4 >= slot ? par : par ^ 1);
          else mbar_wait(BAR(B_EMPTY + bi), (ps < 2) ^ ((i / 6 - 1) & 1));
          mbar_expect_tx(BAR(B_FULL + bi), 16384);
          bulk_g2s(sb + OFF_RING + ps * 16384, g_o_img + (size_t)(pt * 14 + (i < 7 ? 2 * i : 2 * i + 210)) * 8192, 16384, BAR(B_FULL + bi));
        }
      }
    } else {
      {
        const int t = tid - 544;
#pragma unroll 1
        for (int i = t; i < 256; i += 96) sts128(sb + OFF_WPH + i * 16, make_uint4(0, 0, 0, 0));
        bar_sync(2, 96);
#pragma unroll 1
        for (int k = t; k < DM; k += 96) {
          const __nv_bfloat16* src = (hp < 4 ? prm.wk : prm.wv) + k * DH + (hp & 3) * 8;
          cp_async8(sb + OFF_SLC + k * 16, src);
          if ((hp & 3) != 3) cp_async8(sb + OFF_SLC + k * 16 + 8, src + 4);
          else sts64(sb + OFF_SLC + k * 16 + 8, hp == 3 ? (uint32_t)((const unsigned short*)prm.gate_w)[k] : 0u, 0u);
          if (k < 392) {
            const int row = k / 7, e = row >= DH;
            cp_async8(sb + OFF_WPH + e * 2048 + sw64_off(row - DH * e, (k % 7) * 4), prm.w_phi + 2 * hp * DH * DH + k * 4);
          }
        }
        asm volatile("cp.async.wait_all;" ::: "memory");
        fence_async_smem();
        __syncwarp();
        if (lane == 0) mbar_arrive(BAR(B_BUILD), 1);
      }
      if (warp == 18) {
        if (lane == 0) {
#pragma unroll 1
          for (int i = 0; i < 4; i++) {
            mbar_wait(BAR(B_SIG + i), 0);
            cnt_arrive(i == 0 ? C_KV : i == 1 ? C_PART : (i == 2 ? C_OA : C_OB) + pt);
          }
        }
      } else if (warp == 19) {
        if (elect_one()) {
          mbar_wait(BAR(B_SIG + 0), 0);
          cnt_wait(C_KV, NCTA);
          fence_async_all();
          mbar_expect_tx(BAR(B_B1), 512);
          bulk_g2s(sb + OFF_GATE, g_gate + pt * 128, 512, BAR(B_B1));
        }
        __syncwarp();
        float ksq = 0.f, vsq = 0.f;
#pragma unroll
        for (int sl = 0; sl < 4; sl++) {
          float4 a = ldcg_f4(g_ksq + sl * 128 + lane * 4), b = ldcg_f4(g_vsq + sl * 128 + lane * 4);
          float m = fmaxf(fmaxf(a.x, a.y), fmaxf(a.z, a.w));
          m = __uint_as_float(__reduce_max_sync(~0u, __float_as_uint(m)));
          ksq += m;
          vsq = fmaxf(vsq, fmaxf(fmaxf(b.x, b.y), fmaxf(b.z, b.w)));
        }
        vsq = __uint_as_float(__reduce_max_sync(~0u, __float_as_uint(vsq)));
        if (lane == 0) {
          float* red = (float*)(sgen + OFF_RED);
          red[0] = ksq; red[1] = vsq;
          mbar_arrive(BAR(B_B1), 1);
        }
      } else {
        if (elect_one()) {
          mbar_wait(BAR(B_X0FREE), 0);
          mbar_expect_tx(BAR(B_WO), 57344);
#pragma unroll 1
          for (int c = 0; c < 7; c++) tma_2d(sb + OFF_WO + c * 8192, &tm_woa, hp * 56, c * 64, BAR(B_WO));
          PROF_MARK(22);
          cnt_wait(C_PART, NCTA);
          PROF_MARK(23);
          fence_async_all();
          mbar_expect_tx(BAR(B_STG), 32768);
          bulk_g2s(sb + OFF_PHI, g_kvpart + (size_t)blockIdx.x * 8192, 32768, BAR(B_STG));
        }
        __syncwarp();
        mbar_wait(BAR(B_STG), 0);
        {
          const float4* src = (const float4*)(sgen + OFF_PHI) + lane * 2;
          float4 s0 = make_float4(0, 0, 0, 0), s1 = s0;
#pragma unroll 2
          for (int t = 0; t < 32; t++) {
            float4 a = src[t * 64], b = src[t * 64 + 1];
            s0.x += a.x; s0.y += a.y; s0.z += a.z; s0.w += a.w; s1.x += b.x; s1.y += b.y; s1.z += b.z; s1.w += b.w;
          }
          uint4 v = make_uint4(pack_bf16(s0.x, s0.y), pack_bf16(s0.z, s0.w), pack_bf16(s1.x, s1.y), pack_bf16(s1.z, s1.w));
          *(uint4*)(g_kvr_img + (blockIdx.x >> 3) * 4096 + sw64_off((blockIdx.x & 7) * 8 + (lane >> 2), (lane & 3) * 8)) = v;
        }
        __syncwarp();
        if (elect_one()) {
          cnt_arrive(C_RED);
          PROF_MARK(24);
          cnt_wait(C_RED, NCTA);
          PROF_MARK(25);
          fence_async_all();
          mbar_expect_tx(BAR(B_KVR), 8192);
          bulk_g2s(sb + OFF_KVR, g_kvr_img + hp * 8192, 8192, BAR(B_KVR));
          mbar_wait(BAR(B_X1FREE), 0);
          mbar_expect_tx(BAR(B_WO + 1), 57344);
#pragma unroll 1
          for (int c = 0; c < 7; c++) tma_2d(sb + OFF_WO + 57344 + c * 8192, &tm_wob, hp * 56, c * 64, BAR(B_WO + 1));
        }
      }
    }
  } else {
    asm volatile("setmaxnreg.inc.sync.aligned.u32 112;");
    const int mh = wg & 1, nh = wg >> 1, wq = warp & 3;
    float acc[28];
    uint32_t keep[14];
#pragma unroll
    for (int i = 0; i < 28; i++) acc[i] = 0.f;

#pragma unroll 1
    for (int stage = 0; stage < 4; stage++) {
      {
        const bool tail = stage >= 2;
        int ps = stage & 1, prev = 0;
        uint32_t w = stage & 1;
        const uint64_t dS = make_desc(tail ? sb + OFF_WO + (stage - 2) * 57344 : sb + OFF_X + mh * 8192, 1024, 1024, 1);
        const uint64_t dR = make_desc(sb + OFF_RING + (tail ? mh : nh) * 8192, 1024, 1024, 1);
#pragma unroll 1
        for (int c = 0; c < 7; c++) {
          const int bi = tail ? (ps >> 1) * 4 + 1 + (ps & 1) : 2 * ps + nh;
          mbar_wait(BAR(tail ? B_WO + stage - 2 : B_X + c), 0);
          mbar_wait(BAR(B_FULL + bi), w ^ (tail && ps < 2));
          const uint64_t ds = dS + c * (tail ? 512 : 1024), dr = dR + ps * 1024;
          const uint64_t dA = tail ? dr : ds, dB = tail ? ds : dr;
          wg_fence();
          wgmma_ss_n56_ta0_tb1<1>(acc, dA, dB);
          wgmma_ss_n56_ta0_tb1<1>(acc, dA + 2, dB + 128);
          wgmma_ss_n56_ta0_tb1<1>(acc, dA + 4, dB + 256);
          wgmma_ss_n56_ta0_tb1<1>(acc, dA + 6, dB + 384);
          wg_commit();
          wg_wait<1>();
          if (lane == 0 && c > 0) mbar_arrive(BAR(B_EMPTY + prev), 2);
          prev = bi;
          if (++ps == 6) { ps = 0; w ^= 1; }
        }
        wg_wait<0>();
        fence_regs(acc);
        if (lane == 0) mbar_arrive(BAR(B_EMPTY + prev), 2);
      }
      if (stage == 2) { if (tid == 0) PROF_MARK(15); continue; }
      if (stage == 3) break;
      int lane_;
      asm volatile("mov.u32 %0, %%laneid;" : "=r"(lane_));
      const int lq = lane_ & 3;
      const int rowl = wq * 16 + (lane_ >> 2);
      const int row0 = mh * 64 + rowl;

      if (stage == 0) {
        if (tid == 0) PROF_MARK(2);
        if (tid == 256) PROF_MARK(3);
        float accs[4] = {0.f, 0.f, 0.f, 0.f};
        if (nh == 0) {
          mbar_wait(BAR(B_BUILD), 0);
          const uint64_t dX = make_desc(sb + OFF_X + mh * 8192, 1024, 1024, 1);
          const uint64_t dSlc = make_desc(sb + OFF_SLC, 128, 128, 0);
#pragma unroll 1
          for (int c = 0; c < 7; c++) {
            wg_fence();
            wgmma_ss_n8_ta0_tb1<1>(accs, dX + c * 1024, dSlc + c * 64);
            wgmma_ss_n8_ta0_tb1<1>(accs, dX + c * 1024 + 2, dSlc + c * 64 + 16);
            wgmma_ss_n8_ta0_tb1<1>(accs, dX + c * 1024 + 4, dSlc + c * 64 + 32);
            wgmma_ss_n8_ta0_tb1<1>(accs, dX + c * 1024 + 6, dSlc + c * 64 + 48);
            wg_commit();
          }
        }
        const float qs = nh ? 1.f : 0.18898223650461362f * 1.4426950408889634f;
#pragma unroll
        for (int i = 0; i < 28; i++) acc[i] *= qs;
#pragma unroll
        for (int i = 0; i < 14; i++) keep[i] = pack_bf16(acc[2 * i], acc[2 * i + 1]);
        if (nh == 0) {
          float sq[4] = {0.f, 0.f, 0.f, 0.f};
#pragma unroll
          for (int j = 0; j < 7; j++) {
#pragma unroll
            for (int rr = 0; rr < 2; rr++) {
              const float s2 = acc[4 * j + 2 * rr] * acc[4 * j + 2 * rr] + acc[4 * j + 2 * rr + 1] * acc[4 * j + 2 * rr + 1];
              if (j < 3) sq[rr] += s2;
              else if (j > 3) sq[2 + rr] += s2;
              else { sq[rr] += (lq < 2) ? s2 : 0.f; sq[2 + rr] += (lq < 2) ? 0.f : s2; }
            }
          }
#pragma unroll
          for (int i = 0; i < 4; i++) sq[i] = quad_sum(sq[i]);
          const float mine = lq == 0 ? sq[0] : lq == 1 ? sq[1] : lq == 2 ? sq[2] : sq[3];
          ((float*)(sgen + OFF_QSQ))[(mh + (lq & 2)) * 64 + rowl + 8 * (lq & 1)] = mine <= 3.0e38f ? mine : __int_as_float(0x7f800000);
        }
        wg_wait<0>();
        fence_regs(accs);
        if (nh == 0) {
          const int sl = hp & 3;
          const bool isk = hp < 4, real = (sl < 3) || (lq < 2);
          float mxv = 0.f;
#pragma unroll
          for (int rr = 0; rr < 2; rr++) {
            const int pos = pt * 128 + row0 + 8 * rr, kr = pos & 63;
            const float v0 = accs[2 * rr], v1 = accs[2 * rr + 1];
            const bool poly = isk && ((POLY_PAT >> (kr >> 3)) & 1);
            const float sc = poly ? 2.f : 1.f;
            const float s2 = quad_sum(real ? v0 * v0 + v1 * v1 : 0.f);
            mxv = fmaxf(mxv, s2 <= 3.0e38f ? s2 : __int_as_float(0x7f800000));
            const uint32_t padv = lq == 2 ? (poly ? 0x443F4000u : 0x00003F80u) : (poly ? 0x3AB03F4Du : 0u);
            const uint32_t outv = real ? pack_bf16(sc * v0, sc * v1) : padv;
            if (hp == 3 && lq == 2) g_gate[pos] = rcpf(1.f + ex2f(-1.4426950408889634f * v0));
            *(uint32_t*)(g_kv_img + (pos >> 6) * 8192 + (isk ? 0 : 4096) + sw64_off(kr, sl * 8 + 2 * lq)) = outv;
          }
          mxv = __uint_as_float(__reduce_max_sync(~0u, __float_as_uint(mxv)));
          if (lane == 0) (isk ? g_ksq : g_vsq)[sl * 128 + pt * 8 + mh * 4 + wq] = mxv;
          __syncwarp();
          if (lane == 0) mbar_arrive(BAR(B_SIG + 0), 1);
        }
        if (tid == 0) PROF_MARK(4);
        if (tid == 256) PROF_MARK(5);
#pragma unroll
        for (int i = 0; i < 28; i++) acc[i] = 0.f;
        continue;
      }

      bar_sync(1, 512);
      if (tid == 0) PROF_MARK(6);
#pragma unroll 1
      for (int r = 0; r < 2; r++) {
        store_heads(sb + (r ? (nh ? OFF_VA : OFF_QA) : (nh ? OFF_KA : OFF_QP)), keep, (r & nh) ? 0x00003F80u : 0u, row0, lq);
#pragma unroll
        for (int i = 0; i < 14; i++) keep[i] = pack_bf16(acc[2 * i], acc[2 * i + 1]);
      }
      fence_async_smem();
      if (tid == 0) PROF_MARK(7);

      mbar_wait(BAR(B_B1), 0);
      if (tid == 0) PROF_MARK(9);
      const float* red = (const float*)(sgen + OFF_RED);
      const float ksq = red[0] * (1.02f * 1.02f), vsq = red[1];
      const float* qsq = (const float*)(sgen + OFF_QSQ);
      float b0, b1;
      asm("sqrt.approx.ftz.f32 %0, %1;" : "=f"(b0) : "f"(qsq[wg * 64 + rowl] * ksq));
      asm("sqrt.approx.ftz.f32 %0, %1;" : "=f"(b1) : "f"(qsq[wg * 64 + rowl + 8] * ksq));
      const float4 qa4 = ((const float4*)qsq)[lane_], qb4 = ((const float4*)qsq)[32 + lane_];
      const float qmax = fmaxf(fmaxf(fmaxf(qa4.x, qa4.y), fmaxf(qa4.z, qa4.w)), fmaxf(fmaxf(qb4.x, qb4.y), fmaxf(qb4.z, qb4.w)));
      const bool slow = __any_sync(~0u, !(qmax * ksq <= 92.f * 92.f) || !(vsq <= 1.0e24f));
      if (tid == 0) { *(volatile int*)(sgen + OFF_RED + 8) = slow; mbar_arrive(BAR(B_SLOW), 1); }
      bar_sync(1, 512);

      uint32_t q[8];
      {
        const uint32_t qa = sb + OFF_QP + nh * 8192;
        const int r = mh * 64 + wq * 16 + (lane_ & 7) + ((lane_ >> 3) & 1) * 8;
#pragma unroll
        for (int ks = 0; ks < 2; ks++)
          asm volatile("ldmatrix.sync.aligned.m8n8.x4.shared.b16 {%0, %1, %2, %3}, [%4];"
                       : "=r"(q[4 * ks]), "=r"(q[4 * ks + 1]), "=r"(q[4 * ks + 2]), "=r"(q[4 * ks + 3])
                       : "r"(qa + sw64_off(r, ks * 16 + (lane_ >> 4) * 8)) : "memory");
        if (lq >= 2 && !slow) {
          q[6] = lq == 2 ? pack_bf16(64.f - b0, 1.f) : 0x3F803F80u;
          q[7] = lq == 2 ? pack_bf16(64.f - b1, 1.f) : 0x3F803F80u;
        }
      }

      const uint64_t dK = make_desc(sb + OFF_RING, 512, 512, 2);
      const uint64_t dhi = dK & 0xffffffff00000000ull;
      const uint32_t dlo0 = (uint32_t)dK;
      int slot = 4, prev = 0;
      uint32_t par = 0;
      float m0 = -3.0e38f, m1 = -3.0e38f;
      if (__builtin_expect(slow, 0)) {
#pragma unroll 1
        for (int j64 = 0; j64 < 32; j64++) {
          float s[32];
          if ((j64 & 3) == 0) mbar_wait(BAR(B_FULL + slot), par);
          const uint32_t lo = dlo0 + (slot + (j64 & 3)) * 512;
          wg_fence();
          wgmma_rs_n64_tb0<0>(s, q[0], q[1], q[2], q[3], dhi | lo);
          wgmma_rs_n64_tb0<1>(s, q[4], q[5], q[6], q[7], dhi | (lo + 2));
          wg_commit();
          wg_wait<0>();
          fence_regs(s);
#pragma unroll
          for (int j = 0; j < 8; j++) {
            const float sc = ((POLY_PAT >> j) & 1) ? 0.5f : 1.f;
            m0 = fmaxf(m0, fmaxf(s[4 * j], s[4 * j + 1]) * sc);
            m1 = fmaxf(m1, fmaxf(s[4 * j + 2], s[4 * j + 3]) * sc);
          }
          if ((j64 & 3) == 3) {
            if (lane == 0) mbar_arrive(BAR(B_EMPTY + slot), 1);
            slot += 4;
            if (slot == 12) { slot = 0; par ^= 1; }
          }
        }
        m0 = quad_max(m0); m1 = quad_max(m1);
      }
      float o[16];
#pragma unroll
      for (int i = 0; i < 16; i++) o[i] = 0.f;
      if (tid == 0) PROF_MARK(10);
      const int kb = KB_AT, qb = QB_AT;
      uint32_t ok = 0;
#pragma unroll 1
      for (int it = 0; it <= 8; it++) {
        if (it == kb || it == qb || it == 8) {
          float t[16];
          if (it < 8) {
            if (tid == 0) PROF_MARK(it == kb ? 27 : 11);
            const uint64_t dA = make_desc(sb + (it == kb ? OFF_KA : OFF_QA) + nh * 8192 + mh * 4096, 512, 512, 2);
            const uint64_t dB = make_desc(sb + OFF_WPH + nh * 2048, 512, 512, 2);
            float pa[16];
            wg_fence();
            wgmma_ss_n32_ta0_tb1<0>(pa, dA, dB);
            wgmma_ss_n32_ta0_tb1<1>(pa, dA + 2, dB + 64);
            wg_commit();
            wg_wait<0>();
            fence_regs(pa);
            uint32_t ph[16];
            feature_map(pa, ph, lq);
            if (it == kb) {
              const uint32_t rb = sb + OFF_PHI + wg * 8192 + rowl * 128 + lq * 4 + ((rowl & 7) << 4);
#pragma unroll
              for (int ch = 0; ch < 8; ch++) { sts32(rb ^ (ch << 4), ph[2 * ch]); sts32((rb ^ (ch << 4)) + 1024, ph[2 * ch + 1]); }
              fence_async_smem();
              bar_sync(4 + wg, 128);
              const uint64_t dP = make_desc(sb + OFF_PHI + wg * 8192, 1024, 1024, 1);
              const uint64_t dV = make_desc(sb + OFF_VA + nh * 8192 + mh * 4096, 512, 512, 2);
              float kv[16];
              wg_fence();
              wgmma_ss_n32_ta1_tb1<0>(kv, dP, dV);
#pragma unroll
              for (int ks = 1; ks < 4; ks++) wgmma_ss_n32_ta1_tb1<1>(kv, dP + ks * 128, dV + ks * 64);
              wg_commit();
              wg_wait<0>();
              fence_regs(kv);
              float* dst = g_kvpart + ((size_t)((2 * hp + nh) * 8 + wq * 2) * 32 + pt * 2 + mh) * 256 + (lane_ >> 2) * 32 + 2 * lq;
#pragma unroll
              for (int j = 0; j < 4; j++) {
                *(float2*)(dst + 8 * j) = make_float2(kv[4 * j], kv[4 * j + 1]);
                *(float2*)(dst + 32 * 256 + 8 * j) = make_float2(kv[4 * j + 2], kv[4 * j + 3]);
              }
              __syncwarp();
              if (lane == 0) { mbar_arrive(BAR(B_X0FREE), 1); mbar_arrive(BAR(B_SIG + 1), 1); }
              if (tid == 0) PROF_MARK(28);
            } else {
              mbar_wait(BAR(B_KVR), 0);
              const uint64_t dR = make_desc(sb + OFF_KVR + nh * 4096, 512, 512, 2);
              wg_fence();
              wgmma_rs_n32_tb1<0>(t, ph[0], ph[1], ph[2], ph[3], dR);
#pragma unroll
              for (int ks = 1; ks < 4; ks++) wgmma_rs_n32_tb1<1>(t, ph[4 * ks], ph[4 * ks + 1], ph[4 * ks + 2], ph[4 * ks + 3], dR + ks * 64);
              wg_commit();
              wg_wait<0>();
              fence_regs(t);
              if (lane == 0) mbar_arrive(BAR(B_X1FREE), 1);
            }
          } else {
            wg_wait<0>();
            fence_regs(o);
            if (lane == 0) mbar_arrive(BAR(B_EMPTY + prev), 1);
            if (tid == 0) PROF_MARK(13);
#pragma unroll
            for (int i = 0; i < 16; i++) t[i] = o[i];
          }
          if (it != kb) {
            const int br = it == 8;
            const float g0 = ((const float*)(sgen + OFF_GATE))[row0], g1 = ((const float*)(sgen + OFF_GATE))[row0 + 8];
            const float eps = br ? 0.f : 1e-6f;
            const float d0 = __shfl_sync(~0u, t[12], (lane_ & ~3) | 2), d1 = __shfl_sync(~0u, t[14], (lane_ & ~3) | 2);
            const float r0 = __fdividef(br ? 1.f - g0 : g0, d0 + eps), r1 = __fdividef(br ? 1.f - g1 : g1, d1 + eps);
            uint8_t* img = g_o_img + (size_t)((br * 16 + pt) * 14 + mh) * 8192 + rowl * 128;
            const int col0 = (2 * hp + nh) * DH + 2 * lq;
#pragma unroll
            for (int j = 0; j < 4; j++) {
              const int col = col0 + 8 * j;
              uint8_t* p = img + (col >> 6) * 16384 + ((((col >> 3) ^ rowl) & 7) << 4) + (col & 7) * 2;
              const uint32_t v0 = pack_bf16(t[4 * j] * r0, t[4 * j + 1] * r0), v1 = pack_bf16(t[4 * j + 2] * r1, t[4 * j + 3] * r1);
              if (j < 3 || lq < 2) { *(uint32_t*)p = v0; *(uint32_t*)(p + 1024) = v1; }
            }
            __syncwarp();
            if (lane == 0) mbar_arrive(BAR(B_SIG + 2 + br), 1);
            if (tid == 0) PROF_MARK(12 + 2 * br);
            if (br) break;
          }
        }
        float s[32];
        const uint32_t lo = dlo0 + slot * 512;
        if (!ok) mbar_wait(BAR(B_FULL + slot), par);
        wg_fence();
        wgmma_rs_n64_tb0<0>(s, q[0], q[1], q[2], q[3], dhi | lo);
        wgmma_rs_n64_tb0<1>(s, q[4], q[5], q[6], q[7], dhi | (lo + 2));
        wg_commit();
        int nslot = slot + 4;
        uint32_t npar = par;
        if (nslot == 12) { nslot = 0; npar ^= 1; }
#pragma unroll
        for (int u = 0; u < 4; u++) {
          wg_wait<0>();
          fence_regs(s);
          if (u == 0 && lane == 0 && it > 0) mbar_arrive(BAR(B_EMPTY + prev), 1);
          if (u == 2) ok = mbar_test(BAR(B_FULL + nslot), npar);
          uint32_t p[16];
          if (__builtin_expect(!slow, 1)) {
#pragma unroll
            for (int j = 0; j < 8; j++) {
              if ((POLY_PAT >> j) & 1) {
                p[2 * j] = exp2_pair_fma(s[4 * j], s[4 * j + 1], 0x3F003F00u, 0x00030003u);
                p[2 * j + 1] = exp2_pair_fma(s[4 * j + 2], s[4 * j + 3], 0x3F003F00u, 0x00030003u);
              } else {
                p[2 * j] = pack_bf16(ex2f(s[4 * j]), ex2f(s[4 * j + 1]));
                p[2 * j + 1] = pack_bf16(ex2f(s[4 * j + 2]), ex2f(s[4 * j + 3]));
              }
            }
          } else {
#pragma unroll
            for (int j = 0; j < 8; j++) {
              const float sc = ((POLY_PAT >> j) & 1) ? 0.5f : 1.f;
              p[2 * j] = pack_bf16(ex2f(fmaf(s[4 * j], sc, -m0)), ex2f(fmaf(s[4 * j + 1], sc, -m0)));
              p[2 * j + 1] = pack_bf16(ex2f(fmaf(s[4 * j + 2], sc, -m1)), ex2f(fmaf(s[4 * j + 3], sc, -m1)));
            }
          }
          wg_fence();
#pragma unroll
          for (int ks = 0; ks < 4; ks++)
            wgmma_rs_n32_tb1<1>(o, p[4 * ks], p[4 * ks + 1], p[4 * ks + 2], p[4 * ks + 3], dhi | (lo + u * 512 + 256 + ks * 64));
          if (u < 3) {
            wgmma_rs_n64_tb0<0>(s, q[0], q[1], q[2], q[3], dhi | (lo + (u + 1) * 512));
            wgmma_rs_n64_tb0<1>(s, q[4], q[5], q[6], q[7], dhi | (lo + (u + 1) * 512 + 2));
          }
          wg_commit();
        }
        prev = slot; slot = nslot; par = npar;
      }
      wg_wait<0>();
      if (nh == 1) return;
#pragma unroll
      for (int i = 0; i < 14; i++) keep[i] = 0u;
#pragma unroll
      for (int i = 0; i < 28; i++) acc[i] = 0.f;
    }
    if (tid == 0) PROF_MARK(17);
    __nv_bfloat16* op = prm.out + (size_t)(pt * 128 + mh * 64 + wq * 16 + (lane >> 2)) * DM + hp * 56 + 2 * (lane & 3);
#pragma unroll
    for (int j = 0; j < 7; j++) {
      *(uint32_t*)(op + 8 * j) = pack_bf16(acc[4 * j], acc[4 * j + 1]);
      *(uint32_t*)(op + 8 * DM + 8 * j) = pack_bf16(acc[4 * j + 2], acc[4 * j + 3]);
    }
    if (tid == 0) { PROF_MARK(18); PROF_CLK(31); }
    if (tid == 0) {
      unsigned prevd = atomicAdd(&g_cnt[C_DONE * 32], 1u);
      if (prevd == NCTA - 1) {
#pragma unroll 1
        for (int i = 0; i < C_N; i++) g_cnt[i * 32] = 0;
      }
    }
  }
}

typedef CUresult (*EncodeFn)(CUtensorMap*, CUtensorMapDataType, cuuint32_t, void*, const cuuint64_t*, const cuuint64_t*,
                             const cuuint32_t*, const cuuint32_t*, CUtensorMapInterleave, CUtensorMapSwizzle,
                             CUtensorMapL2promotion, CUtensorMapFloatOOBfill);

void make_map(EncodeFn enc, CUtensorMap* tm, const void* ptr, uint64_t cols, uint64_t rows, uint32_t box_rows) {
  cuuint64_t dims[2] = {cols, rows};
  cuuint64_t strides[1] = {cols * 2};
  cuuint32_t box[2] = {64, box_rows};
  cuuint32_t es[2] = {1, 1};
  enc(tm, CU_TENSOR_MAP_DATA_TYPE_BFLOAT16, 2, const_cast<void*>(ptr), dims, strides, box, es, CU_TENSOR_MAP_INTERLEAVE_NONE,
      CU_TENSOR_MAP_SWIZZLE_128B, CU_TENSOR_MAP_L2_PROMOTION_L2_128B, CU_TENSOR_MAP_FLOAT_OOB_FILL_NONE);
}

}

extern "C" void kernel_launch(void* const* d_in, const int* in_sizes, int n_in, void* d_out, int out_size) {
  (void)in_sizes; (void)n_in; (void)out_size;
  static EncodeFn enc = nullptr;
  if (!enc) {
    void* fn = nullptr;
    cudaDriverEntryPointQueryResult qr;
    cudaGetDriverEntryPoint("cuTensorMapEncodeTiled", &fn, cudaEnableDefault, &qr);
    enc = (EncodeFn)fn;
    cudaFuncSetAttribute(fused_kernel, cudaFuncAttributeMaxDynamicSharedMemorySize, SMEM_BYTES);
  }
  CUtensorMap tm_x, tm_wqkv, tm_wq, tm_woa, tm_wob;
  make_map(enc, &tm_x, d_in[0], DM, S_LEN, 128);
  make_map(enc, &tm_wqkv, d_in[1], 3 * DM, DM, 64);
  make_map(enc, &tm_wq, d_in[5], DM, DM, 64);
  make_map(enc, &tm_woa, d_in[3], DM, DM, 64);
  make_map(enc, &tm_wob, d_in[8], DM, DM, 64);
  Params prm;
  prm.w_phi = (const __nv_bfloat16*)d_in[2];
  prm.wk = (const __nv_bfloat16*)d_in[6];
  prm.wv = (const __nv_bfloat16*)d_in[7];
  prm.gate_w = (const __nv_bfloat16*)d_in[9];
  prm.out = (__nv_bfloat16*)d_out;
  fused_kernel<<<NCTA, NTHREADS, SMEM_BYTES>>>(tm_x, tm_wqkv, tm_wq, tm_woa, tm_wob, prm);
}
```

```cpp
#include <cuda_runtime.h>
#include <cuda_bf16.h>
#include <cuda.h>
#include <stdint.h>

namespace {

constexpr int S_LEN = 2048, DM = 448, DH = 28;
constexpr int NCTA = 128;
constexpr int NTHREADS = 640;
constexpr uint32_t POLY_PAT = 0x57;

#define KB_AT (wg >> 1)
#define QB_AT (5 + (wg >> 1))

constexpr int OFF_X = 0;
constexpr int OFF_KA = 0;
constexpr int OFF_VA = 16384;
constexpr int OFF_QP = 32768;
constexpr int OFF_QA = 57344;
constexpr int OFF_KVR = 73728;
constexpr int OFF_PHI = 81920;
constexpr int OFF_WO = 0;
constexpr int OFF_RING = 114688;
constexpr int OFF_WPH = 212992;
constexpr int OFF_SLC = 217088;
constexpr int OFF_QSQ = 224256;
constexpr int OFF_GATE = 225280;
constexpr int OFF_RED = 225792;
constexpr int OFF_BAR = 225856;
constexpr int SMEM_BYTES = 226368 + 1024;

constexpr int B_FULL = 0, B_X = 12, B_EMPTY = 19, B_WO = 31  , B_KVR = 33, B_X0FREE = 34, B_X1FREE = 35, B_B1 = 36,
              B_SLOW = 37, B_BUILD = 38, B_STG = 39, B_SIG = 40  , B_N = 44;

constexpr int C_KV = 0, C_PART = 1, C_RED = 2, C_DONE = 3, C_OA = 4, C_OB = 20, C_N = 36;

__device__ __align__(1024) uint8_t g_kv_img[32 * 8192];
__device__ __align__(16) float g_ksq[512];
__device__ __align__(16) float g_vsq[512];
__device__ __align__(16) float g_gate[S_LEN];
__device__ __align__(1024) float g_kvpart[128 * 32 * 256];
__device__ __align__(1024) uint8_t g_kvr_img[16 * 4096];
__device__ __align__(1024) uint8_t g_o_img[2 * 16 * 14 * 8192];
__device__ unsigned g_cnt[C_N * 32];

#define PROF2(i) do { } while (0)
#define PROF_CLK(i) do { } while (0)
#define PROF_MARK(i) do { } while (0)
__device__ __forceinline__ uint32_t smem_u32(const void* p) { return (uint32_t)__cvta_generic_to_shared(p); }
__device__ __forceinline__ void mbar_init(uint32_t a, int cnt) {
  asm volatile("mbarrier.init.shared::cta.b64 [%0], %1;" ::"r"(a), "r"(cnt) : "memory");
}
__device__ __forceinline__ void mbar_expect_tx(uint32_t a, uint32_t bytes) {
  asm volatile("mbarrier.arrive.expect_tx.shared::cta.b64 _, [%0], %1;" ::"r"(a), "r"(bytes) : "memory");
}
__device__ __forceinline__ void mbar_arrive(uint32_t a, uint32_t cnt) {
  asm volatile("mbarrier.arrive.shared::cta.b64 _, [%0], %1;" ::"r"(a), "r"(cnt) : "memory");
}
__device__ __forceinline__ void mbar_wait(uint32_t a, uint32_t parity) {
  asm volatile(
      "{\n.reg .pred p;\n.reg .u32 c;\nmov.u32 c, 0;\n"
      "W_%=:\nmbarrier.try_wait.parity.shared::cta.b64 p, [%0], %1;\n"
      "add.u32 c, c, 1;\nsetp.lt.and.u32 p, c, 0x1000000, !p;\n@p bra W_%=;\n}"
      ::"r"(a), "r"(parity) : "memory");
}
__device__ __forceinline__ uint32_t mbar_test(uint32_t a, uint32_t parity) {
  uint32_t ok;
  asm volatile("{\n.reg .pred p;\nmbarrier.test_wait.parity.shared::cta.b64 p, [%1], %2;\nselp.u32 %0, 1, 0, p;\n}"
               : "=r"(ok) : "r"(a), "r"(parity) : "memory");
  return ok;
}
__device__ __forceinline__ bool elect_one() {
  uint32_t r;
  asm volatile("{\n.reg .pred p;\nelect.sync _|p, 0xffffffff;\nselp.u32 %0, 1, 0, p;\n}" : "=r"(r));
  return r != 0;
}
__device__ __forceinline__ void tma_2d(uint32_t dst, const CUtensorMap* tm, int c0, int c1, uint32_t bar) {
  asm volatile("cp.async.bulk.tensor.2d.shared::cluster.global.mbarrier::complete_tx::bytes [%0], [%1, {%3, %4}], [%2];"
               ::"r"(dst), "l"(tm), "r"(bar), "r"(c0), "r"(c1) : "memory");
}
__device__ __forceinline__ void bulk_g2s(uint32_t dst, const void* src, uint32_t bytes, uint32_t bar) {
  asm volatile("cp.async.bulk.shared::cluster.global.mbarrier::complete_tx::bytes [%0], [%1], %2, [%3];"
               ::"r"(dst), "l"(src), "r"(bytes), "r"(bar) : "memory");
}
__device__ __forceinline__ void cp_async8(uint32_t dst, const void* src) {
  asm volatile("cp.async.ca.shared.global [%0], [%1], 8;" ::"r"(dst), "l"(src) : "memory");
}
__device__ __forceinline__ void fence_async_smem() { asm volatile("fence.proxy.async.shared::cta;" ::: "memory"); }
__device__ __forceinline__ void fence_async_all() { asm volatile("fence.proxy.async;" ::: "memory"); }
__device__ __forceinline__ void bar_sync(int id, int n) { asm volatile("bar.sync %0, %1;" ::"r"(id), "r"(n) : "memory"); }
__device__ __forceinline__ void cnt_arrive(int idx) {
  asm volatile("red.release.gpu.global.add.u32 [%0], 1;" ::"l"(&g_cnt[idx * 32]) : "memory");
}
__device__ __forceinline__ void cnt_wait(int idx, unsigned target) {
  unsigned v, n = 0;
#pragma unroll 1
  while (true) {
    asm volatile("ld.relaxed.gpu.global.u32 %0, [%1];" : "=r"(v) : "l"(&g_cnt[idx * 32]) : "memory");
    if (v >= target || ++n >= (1u << 22)) break;
    __nanosleep(64);
  }
  asm volatile("fence.acq_rel.gpu;" ::: "memory");
}
__device__ __forceinline__ void wg_fence() { asm volatile("wgmma.fence.sync.aligned;" ::: "memory"); }
__device__ __forceinline__ void wg_commit() { asm volatile("wgmma.commit_group.sync.aligned;" ::: "memory"); }
template <int N> __device__ __forceinline__ void wg_wait() { asm volatile("wgmma.wait_group.sync.aligned %0;" ::"n"(N) : "memory"); }
template <int N> __device__ __forceinline__ void fence_regs(float (&d)[N]) {
#pragma unroll
  for (int i = 0; i < N; i++) asm volatile("" : "+f"(d[i])::"memory");
}
__device__ __forceinline__ uint64_t make_desc(uint32_t saddr, uint32_t lbo, uint32_t sbo, uint32_t swz) {
  return (uint64_t)((saddr & 0x3FFFF) >> 4) | ((uint64_t)(lbo >> 4) << 16) | ((uint64_t)(sbo >> 4) << 32) | ((uint64_t)swz << 62);
}
__device__ __forceinline__ float ex2f(float x) { float y; asm("ex2.approx.ftz.f32 %0, %1;" : "=f"(y) : "f"(x)); return y; }
__device__ __forceinline__ float rcpf(float x) { float y; asm("rcp.approx.ftz.f32 %0, %1;" : "=f"(y) : "f"(x)); return y; }
__device__ __forceinline__ uint32_t pack_bf16(float lo, float hi) {
  uint32_t r; asm("cvt.rn.bf16x2.f32 %0, %1, %2;" : "=r"(r) : "f"(hi), "f"(lo)); return r;
}
__device__ __forceinline__ uint32_t lop_and_or(uint32_t a, uint32_t m, uint32_t c) {
  uint32_t r; asm("lop3.b32 %0, %1, %2, %3, 0xEA;" : "=r"(r) : "r"(a), "r"(m), "r"(c)); return r;
}
__device__ __forceinline__ void sts32(uint32_t a, uint32_t v) { asm volatile("st.shared.b32 [%0], %1;" ::"r"(a), "r"(v) : "memory"); }
__device__ __forceinline__ void sts64(uint32_t a, uint32_t v0, uint32_t v1) { asm volatile("st.shared.v2.b32 [%0], {%1, %2};" ::"r"(a), "r"(v0), "r"(v1) : "memory"); }
__device__ __forceinline__ void sts128(uint32_t a, uint4 v) {
  asm volatile("st.shared.v4.b32 [%0], {%1, %2, %3, %4};" ::"r"(a), "r"(v.x), "r"(v.y), "r"(v.z), "r"(v.w) : "memory");
}
__device__ __forceinline__ float4 ldcg_f4(const float* p) {
  float4 v; asm volatile("ld.global.cg.v4.f32 {%0, %1, %2, %3}, [%4];" : "=f"(v.x), "=f"(v.y), "=f"(v.z), "=f"(v.w) : "l"(p) : "memory"); return v;
}
__device__ __forceinline__ float quad_sum(float v) { v += __shfl_xor_sync(~0u, v, 1); v += __shfl_xor_sync(~0u, v, 2); return v; }
__device__ __forceinline__ float quad_max(float v) { v = fmaxf(v, __shfl_xor_sync(~0u, v, 1)); v = fmaxf(v, __shfl_xor_sync(~0u, v, 2)); return v; }

template <int SD> __device__ __forceinline__ void wgmma_ss_n56_ta0_tb1(float (&d)[28], uint64_t da, uint64_t db) {
  asm volatile("wgmma.mma_async.sync.aligned.m64n56k16.f32.bf16.bf16 {%0, %1, %2, %3, %4, %5, %6, %7, %8, %9, %10, %11, %12, %13, %14, %15, %16, %17, %18, %19, %20, %21, %22, %23, %24, %25, %26, %27}, %28, %29, %30, 1, 1, 0, 1;\n"
    : "+f"(d[0]), "+f"(d[1]), "+f"(d[2]), "+f"(d[3]), "+f"(d[4]), "+f"(d[5]), "+f"(d[6]), "+f"(d[7]), "+f"(d[8]), "+f"(d[9]), "+f"(d[10]), "+f"(d[11]), "+f"(d[12]), "+f"(d[13]), "+f"(d[14]), "+f"(d[15]), "+f"(d[16]), "+f"(d[17]), "+f"(d[18]), "+f"(d[19]), "+f"(d[20]), "+f"(d[21]), "+f"(d[22]), "+f"(d[23]), "+f"(d[24]), "+f"(d[25]), "+f"(d[26]), "+f"(d[27])
    : "l"(da), "l"(db), "n"(SD));
}
template <int SD> __device__ __forceinline__ void wgmma_ss_n8_ta0_tb1(float (&d)[4], uint64_t da, uint64_t db) {
  asm volatile("wgmma.mma_async.sync.aligned.m64n8k16.f32.bf16.bf16 {%0, %1, %2, %3}, %4, %5, %6, 1, 1, 0, 1;\n"
    : "+f"(d[0]), "+f"(d[1]), "+f"(d[2]), "+f"(d[3])
    : "l"(da), "l"(db), "n"(SD));
}
template <int SD> __device__ __forceinline__ void wgmma_ss_n32_ta1_tb1(float (&d)[16], uint64_t da, uint64_t db) {
  asm volatile("wgmma.mma_async.sync.aligned.m64n32k16.f32.bf16.bf16 {%0, %1, %2, %3, %4, %5, %6, %7, %8, %9, %10, %11, %12, %13, %14, %15}, %16, %17, %18, 1, 1, 1, 1;\n"
    : "+f"(d[0]), "+f"(d[1]), "+f"(d[2]), "+f"(d[3]), "+f"(d[4]), "+f"(d[5]), "+f"(d[6]), "+f"(d[7]), "+f"(d[8]), "+f"(d[9]), "+f"(d[10]), "+f"(d[11]), "+f"(d[12]), "+f"(d[13]), "+f"(d[14]), "+f"(d[15])
    : "l"(da), "l"(db), "n"(SD));
}
template <int SD> __device__ __forceinline__ void wgmma_ss_n32_ta0_tb1(float (&d)[16], uint64_t da, uint64_t db) {
  asm volatile("wgmma.mma_async.sync.aligned.m64n32k16.f32.bf16.bf16 {%0, %1, %2, %3, %4, %5, %6, %7, %8, %9, %10, %11, %12, %13, %14, %15}, %16, %17, %18, 1, 1, 0, 1;\n"
    : "+f"(d[0]), "+f"(d[1]), "+f"(d[2]), "+f"(d[3]), "+f"(d[4]), "+f"(d[5]), "+f"(d[6]), "+f"(d[7]), "+f"(d[8]), "+f"(d[9]), "+f"(d[10]), "+f"(d[11]), "+f"(d[12]), "+f"(d[13]), "+f"(d[14]), "+f"(d[15])
    : "l"(da), "l"(db), "n"(SD));
}
template <int SD> __device__ __forceinline__ void wgmma_rs_n64_tb0(float (&d)[32], uint32_t a0, uint32_t a1, uint32_t a2, uint32_t a3, uint64_t db) {
  asm volatile("wgmma.mma_async.sync.aligned.m64n64k16.f32.bf16.bf16 {%0, %1, %2, %3, %4, %5, %6, %7, %8, %9, %10, %11, %12, %13, %14, %15, %16, %17, %18, %19, %20, %21, %22, %23, %24, %25, %26, %27, %28, %29, %30, %31}, {%32, %33, %34, %35}, %36, %37, 1, 1, 0;\n"
    : "+f"(d[0]), "+f"(d[1]), "+f"(d[2]), "+f"(d[3]), "+f"(d[4]), "+f"(d[5]), "+f"(d[6]), "+f"(d[7]), "+f"(d[8]), "+f"(d[9]), "+f"(d[10]), "+f"(d[11]), "+f"(d[12]), "+f"(d[13]), "+f"(d[14]), "+f"(d[15]), "+f"(d[16]), "+f"(d[17]), "+f"(d[18]), "+f"(d[19]), "+f"(d[20]), "+f"(d[21]), "+f"(d[22]), "+f"(d[23]), "+f"(d[24]), "+f"(d[25]), "+f"(d[26]), "+f"(d[27]), "+f"(d[28]), "+f"(d[29]), "+f"(d[30]), "+f"(d[31])
    : "r"(a0), "r"(a1), "r"(a2), "r"(a3), "l"(db), "n"(SD));
}
template <int SD> __device__ __forceinline__ void wgmma_rs_n32_tb1(float (&d)[16], uint32_t a0, uint32_t a1, uint32_t a2, uint32_t a3, uint64_t db) {
  asm volatile("wgmma.mma_async.sync.aligned.m64n32k16.f32.bf16.bf16 {%0, %1, %2, %3, %4, %5, %6, %7, %8, %9, %10, %11, %12, %13, %14, %15}, {%16, %17, %18, %19}, %20, %21, 1, 1, 1;\n"
    : "+f"(d[0]), "+f"(d[1]), "+f"(d[2]), "+f"(d[3]), "+f"(d[4]), "+f"(d[5]), "+f"(d[6]), "+f"(d[7]), "+f"(d[8]), "+f"(d[9]), "+f"(d[10]), "+f"(d[11]), "+f"(d[12]), "+f"(d[13]), "+f"(d[14]), "+f"(d[15])
    : "r"(a0), "r"(a1), "r"(a2), "r"(a3), "l"(db), "n"(SD));
}

__device__ __forceinline__ uint32_t sw64_off(int row, int d) { return row * 64 + ((((d >> 3) ^ (row >> 1)) & 3) << 4) + (d & 7) * 2; }

__device__ __forceinline__ uint32_t exp2_pair_fma(float t0, float t1, uint32_t c_half, uint32_t c_3) {
  uint32_t y0, y;
  asm("prmt.b32 %0, %1, %2, 0x6521;" : "=r"(y0) : "r"(__float_as_uint(t0)), "r"(__float_as_uint(t1)));
  uint32_t h = lop_and_or(y0, 0x007F007Fu, c_half);
  uint32_t e = lop_and_or(y0, 0xFF80FF80u, c_3);
  asm("fma.rn.bf16x2 %0, %1, %2, %3;" : "=r"(y) : "r"(y0), "r"(h), "r"(e));
  return y;
}

__device__ __forceinline__ void feature_map(float (&v)[16], uint32_t (&ph)[16], int lq) {
  const float L2E = 1.4426950408889634f;
  const bool tail_ok = lq < 2;
  float mx[2], mn[2], b[16], sa[2], sn[2];
#pragma unroll
  for (int r = 0; r < 2; r++) {
    const int o = 2 * r;
    if (!tail_ok) { v[o + 12] = v[o]; v[o + 13] = v[o]; }
    mx[r] = fmaxf(fmaxf(fmaxf(v[o], v[o + 1]), fmaxf(v[o + 4], v[o + 5])), fmaxf(fmaxf(v[o + 8], v[o + 9]), fmaxf(v[o + 12], v[o + 13])));
    mn[r] = fminf(fminf(fminf(v[o], v[o + 1]), fminf(v[o + 4], v[o + 5])), fminf(fminf(v[o + 8], v[o + 9]), fminf(v[o + 12], v[o + 13])));
  }
#pragma unroll
  for (int o = 1; o <= 2; o <<= 1)
#pragma unroll
    for (int r = 0; r < 2; r++) { mx[r] = fmaxf(mx[r], __shfl_xor_sync(~0u, mx[r], o)); mn[r] = fminf(mn[r], __shfl_xor_sync(~0u, mn[r], o)); }
#pragma unroll
  for (int r = 0; r < 2; r++) {
    const int o = 2 * r;
    const float cx = -mx[r] * L2E, cn = mn[r] * L2E;
#pragma unroll
    for (int i = 0; i < 8; i++) {
      const int k = o + 4 * (i >> 1) + (i & 1);
      b[k] = ex2f(fmaf(v[k], -L2E, cn));
      v[k] = ex2f(fmaf(v[k], L2E, cx));
    }
    if (!tail_ok) { v[o + 12] = v[o + 13] = b[o + 12] = b[o + 13] = 0.f; }
    sa[r] = ((v[o] + v[o + 1]) + (v[o + 4] + v[o + 5])) + ((v[o + 8] + v[o + 9]) + (v[o + 12] + v[o + 13]));
    sn[r] = ((b[o] + b[o + 1]) + (b[o + 4] + b[o + 5])) + ((b[o + 8] + b[o + 9]) + (b[o + 12] + b[o + 13]));
  }
#pragma unroll
  for (int o = 1; o <= 2; o <<= 1)
#pragma unroll
    for (int r = 0; r < 2; r++) { sa[r] += __shfl_xor_sync(~0u, sa[r], o); sn[r] += __shfl_xor_sync(~0u, sn[r], o); }
#pragma unroll
  for (int r = 0; r < 2; r++) {
    const float ra = rcpf(sa[r]), rb = rcpf(sn[r]);
#pragma unroll
    for (int jj = 0; jj < 4; jj++) {
      ph[jj * 2 + r] = pack_bf16(v[2 * r + 4 * jj] * ra, v[2 * r + 4 * jj + 1] * ra);
      ph[(4 + jj) * 2 + r] = pack_bf16(b[2 * r + 4 * jj] * rb, b[2 * r + 4 * jj + 1] * rb);
    }
  }
}

__device__ __forceinline__ void store_heads(uint32_t base, const uint32_t (&a)[14], uint32_t pad, int row0, int lq) {
  const uint32_t rb = base + row0 * 64 + (((row0 >> 1) & 3) << 4);
  const uint32_t b0 = rb + lq * 4;
  const uint32_t b1 = (rb + 8192 + ((lq * 4 + 8) & 15)) ^ ((lq >> 1) << 4);
#pragma unroll
  for (int j = 0; j < 7; j++) {
    uint32_t ad;
    if (j < 3) ad = b0 ^ (j << 4);
    else if (j == 3) ad = (lq < 2) ? (b0 ^ 48u) : (b1 ^ 16u);
    else ad = (lq < 2) ? (b1 ^ ((j - 4) << 4)) : ((b1 ^ 16u) ^ ((j - 3) << 4));
    sts32(ad, a[2 * j]);
    sts32(ad + 512, a[2 * j + 1]);
  }
  sts64((rb ^ 48u) + 8 + (lq & 1) * 8192 + (lq >> 1) * 512, pad, 0u);
}

struct Params {
  const __nv_bfloat16* w_phi;
  const __nv_bfloat16* wk;
  const __nv_bfloat16* wv;
  const __nv_bfloat16* gate_w;
  __nv_bfloat16* out;
};

__global__ void __launch_bounds__(NTHREADS, 1)
fused_kernel(const __grid_constant__ CUtensorMap tm_x, const __grid_constant__ CUtensorMap tm_wqkv,
             const __grid_constant__ CUtensorMap tm_wq, const __grid_constant__ CUtensorMap tm_woa,
             const __grid_constant__ CUtensorMap tm_wob, const Params prm) {
  extern __shared__ uint8_t smem_raw[];
  uint32_t sb = (smem_u32(smem_raw) + 1023u) & ~1023u;
  uint8_t* sgen = smem_raw + (sb - smem_u32(smem_raw));
  asm volatile("mov.u32 %0, %0;" : "+r"(sb));
  const int tid = threadIdx.x, lane = tid & 31;
  const int warp = __shfl_sync(~0u, tid >> 5, 0), wg = warp >> 2;
  const int pt = blockIdx.x >> 3, hp = blockIdx.x & 7;
  const uint32_t bars = sb + OFF_BAR;
  auto BAR = [&](int i) { return bars + 8u * i; };

  if (tid == 0) { PROF_MARK(0); PROF_CLK(30); PROF2(15); }
  if (elect_one()) {
    if (warp < B_EMPTY) {
      mbar_init(BAR(warp), 1);
      fence_async_smem();
      const bool isx = warp >= B_X;
      const int c = isx ? warp - B_X : warp >> 1;
      mbar_expect_tx(BAR(warp), isx ? 16384 : 8192);
      tma_2d(isx ? sb + OFF_X + c * 16384 : sb + OFF_RING + warp * 8192, isx ? &tm_x : ((warp & 1) ? &tm_wqkv : &tm_wq),
             isx ? c * 64 : hp * 56 + ((warp & 1) ? DM : 0), isx ? pt * 128 : c * 64, BAR(warp));
    }
#pragma unroll 1
    for (int i = B_EMPTY + (warp + 1) % 20; i < B_N; i += 20) {
      int cnt = 16;
      if ((i >= B_WO && i <= B_KVR) || i == B_SLOW || i == B_STG) cnt = 1;
      if (i == B_B1) cnt = 2;
      if (i == B_BUILD) cnt = 3;
      if (i == B_SIG) cnt = 8;
      mbar_init(BAR(i), cnt);
    }
    fence_async_smem();
  }
  __syncthreads();

  if (wg == 4) {
    asm volatile("setmaxnreg.dec.sync.aligned.u32 32;");
    if (warp == 16) {
      if (elect_one()) {
#pragma unroll 1
        for (int i = 6; i < 14; i++) {
          const int c = i < 7 ? i : i - 7, ps = i % 6;
#pragma unroll 1
          for (int h = 0; h < 2; h++) {
            const int sl = 2 * ps + h;
            mbar_wait(BAR(B_EMPTY + sl), (i / 6 - 1) & 1);
            mbar_expect_tx(BAR(B_FULL + sl), 8192);
            tma_2d(sb + OFF_RING + sl * 8192, (i < 7 && !h) ? &tm_wq : &tm_wqkv, hp * 56 + (h ? (i < 7 ? DM : 2 * DM) : 0), c * 64,
                   BAR(B_FULL + sl));
          }
        }
        PROF_MARK(20);
        cnt_wait(C_KV, NCTA);
        PROF_MARK(21);
        fence_async_all();
        int slot = 4, ng = 8;
        uint32_t par = 1;
#pragma unroll 1
        for (int n = 0; n < ng; n++) {
          mbar_wait(BAR(B_EMPTY + slot), par);
          if (n < 3) { mbar_wait(BAR(B_EMPTY + slot + 1), par); mbar_wait(BAR(B_EMPTY + slot + 2), par); mbar_wait(BAR(B_EMPTY + slot + 3), par); }
          mbar_expect_tx(BAR(B_FULL + slot), 32768);
          bulk_g2s(sb + OFF_RING + slot * 8192, g_kv_img + (n & 7) * 32768, 32768, BAR(B_FULL + slot));
          slot += 4;
          if (slot == 12) { slot = 0; par ^= 1; }
          if (n == 7) {
            mbar_wait(BAR(B_SLOW), 0);
            if (*(volatile int*)(sgen + OFF_RED + 8)) ng = 16;
          }
        }
#pragma unroll 1
        for (int i = 0; i < 14; i++) {
          const int ps = i % 6, g4 = (ps >> 1) * 4, bi = g4 + 1 + (ps & 1);
          if (i == 0 || i == 7) {
            cnt_wait((i ? C_OB : C_OA) + pt, 8);
            PROF_MARK(26);
            fence_async_all();
          }
          if (i < 6) mbar_wait(BAR(B_EMPTY + g4), g4 >= slot ? par : par ^ 1);
          else mbar_wait(BAR(B_EMPTY + bi), (ps < 2) ^ ((i / 6 - 1) & 1));
          mbar_expect_tx(BAR(B_FULL + bi), 16384);
          bulk_g2s(sb + OFF_RING + ps * 16384, g_o_img + (size_t)(pt * 14 + (i < 7 ? 2 * i : 2 * i + 210)) * 8192, 16384, BAR(B_FULL + bi));
        }
      }
    } else {
      {
        const int t = tid - 544;
#pragma unroll 1
        for (int i = t; i < 256; i += 96) sts128(sb + OFF_WPH + i * 16, make_uint4(0, 0, 0, 0));
        bar_sync(2, 96);
#pragma unroll 1
        for (int k = t; k < DM; k += 96) {
          const __nv_bfloat16* src = (hp < 4 ? prm.wk : prm.wv) + k * DH + (hp & 3) * 8;
          cp_async8(sb + OFF_SLC + k * 16, src);
          if ((hp & 3) != 3) cp_async8(sb + OFF_SLC + k * 16 + 8, src + 4);
          else sts64(sb + OFF_SLC + k * 16 + 8, hp == 3 ? (uint32_t)((const unsigned short*)prm.gate_w)[k] : 0u, 0u);
          if (k < 392) {
            const int row = k / 7, e = row >= DH;
            cp_async8(sb + OFF_WPH + e * 2048 + sw64_off(row - DH * e, (k % 7) * 4), prm.w_phi + 2 * hp * DH * DH + k * 4);
          }
        }
        asm volatile("cp.async.wait_all;" ::: "memory");
        fence_async_smem();
        __syncwarp();
        if (lane == 0) mbar_arrive(BAR(B_BUILD), 1);
      }
      if (warp == 18) {
        if (lane == 0) {
#pragma unroll 1
          for (int i = 0; i < 4; i++) {
            mbar_wait(BAR(B_SIG + i), 0);
            cnt_arrive(i == 0 ? C_KV : i == 1 ? C_PART : (i == 2 ? C_OA : C_OB) + pt);
          }
        }
      } else if (warp == 19) {
        if (elect_one()) {
          mbar_wait(BAR(B_SIG + 0), 0);
          cnt_wait(C_KV, NCTA);
          fence_async_all();
          mbar_expect_tx(BAR(B_B1), 512);
          bulk_g2s(sb + OFF_GATE, g_gate + pt * 128, 512, BAR(B_B1));
        }
        __syncwarp();
        float ksq = 0.f, vsq = 0.f;
#pragma unroll
        for (int sl = 0; sl < 4; sl++) {
          float4 a = ldcg_f4(g_ksq + sl * 128 + lane * 4), b = ldcg_f4(g_vsq + sl * 128 + lane * 4);
          float m = fmaxf(fmaxf(a.x, a.y), fmaxf(a.z, a.w));
          m = __uint_as_float(__reduce_max_sync(~0u, __float_as_uint(m)));
          ksq += m;
          vsq = fmaxf(vsq, fmaxf(fmaxf(b.x, b.y), fmaxf(b.z, b.w)));
        }
        vsq = __uint_as_float(__reduce_max_sync(~0u, __float_as_uint(vsq)));
        if (lane == 0) {
          float* red = (float*)(sgen + OFF_RED);
          red[0] = ksq; red[1] = vsq;
          mbar_arrive(BAR(B_B1), 1);
        }
      } else {
        if (elect_one()) {
          mbar_wait(BAR(B_X0FREE), 0);
          mbar_expect_tx(BAR(B_WO), 57344);
#pragma unroll 1
          for (int c = 0; c < 7; c++) tma_2d(sb + OFF_WO + c * 8192, &tm_woa, hp * 56, c * 64, BAR(B_WO));
          PROF_MARK(22);
          cnt_wait(C_PART, NCTA);
          PROF_MARK(23);
          fence_async_all();
          mbar_expect_tx(BAR(B_STG), 32768);
          bulk_g2s(sb + OFF_PHI, g_kvpart + (size_t)blockIdx.x * 8192, 32768, BAR(B_STG));
        }
        __syncwarp();
        mbar_wait(BAR(B_STG), 0);
        {
          const float4* src = (const float4*)(sgen + OFF_PHI) + lane * 2;
          float4 s0 = make_float4(0, 0, 0, 0), s1 = s0;
#pragma unroll 2
          for (int t = 0; t < 32; t++) {
            float4 a = src[t * 64], b = src[t * 64 + 1];
            s0.x += a.x; s0.y += a.y; s0.z += a.z; s0.w += a.w; s1.x += b.x; s1.y += b.y; s1.z += b.z; s1.w += b.w;
          }
          uint4 v = make_uint4(pack_bf16(s0.x, s0.y), pack_bf16(s0.z, s0.w), pack_bf16(s1.x, s1.y), pack_bf16(s1.z, s1.w));
          *(uint4*)(g_kvr_img + (blockIdx.x >> 3) * 4096 + sw64_off((blockIdx.x & 7) * 8 + (lane >> 2), (lane & 3) * 8)) = v;
        }
        __syncwarp();
        if (elect_one()) {
          cnt_arrive(C_RED);
          PROF_MARK(24);
          cnt_wait(C_RED, NCTA);
          PROF_MARK(25);
          fence_async_all();
          mbar_expect_tx(BAR(B_KVR), 8192);
          bulk_g2s(sb + OFF_KVR, g_kvr_img + hp * 8192, 8192, BAR(B_KVR));
          mbar_wait(BAR(B_X1FREE), 0);
          mbar_expect_tx(BAR(B_WO + 1), 57344);
#pragma unroll 1
          for (int c = 0; c < 7; c++) tma_2d(sb + OFF_WO + 57344 + c * 8192, &tm_wob, hp * 56, c * 64, BAR(B_WO + 1));
        }
      }
    }
  } else {
    asm volatile("setmaxnreg.inc.sync.aligned.u32 112;");
    const int mh = wg & 1, nh = wg >> 1, wq = warp & 3;
    float acc[28];
    uint32_t keep[14];
#pragma unroll
    for (int i = 0; i < 28; i++) acc[i] = 0.f;

#pragma unroll 1
    for (int stage = 0; stage < 4; stage++) {
      {
        const bool tail = stage >= 2;
        int ps = stage & 1, prev = 0;
        uint32_t w = stage & 1;
        const uint64_t dS = make_desc(tail ? sb + OFF_WO + (stage - 2) * 57344 : sb + OFF_X + mh * 8192, 1024, 1024, 1);
        const uint64_t dR = make_desc(sb + OFF_RING + (tail ? mh : nh) * 8192, 1024, 1024, 1);
#pragma unroll 1
        for (int c = 0; c < 7; c++) {
          const int bi = tail ? (ps >> 1) * 4 + 1 + (ps & 1) : 2 * ps + nh;
          mbar_wait(BAR(tail ? B_WO + stage - 2 : B_X + c), 0);
          mbar_wait(BAR(B_FULL + bi), w ^ (tail && ps < 2));
          const uint64_t ds = dS + c * (tail ? 512 : 1024), dr = dR + ps * 1024;
          const uint64_t dA = tail ? dr : ds, dB = tail ? ds : dr;
          wg_fence();
          wgmma_ss_n56_ta0_tb1<1>(acc, dA, dB);
          wgmma_ss_n56_ta0_tb1<1>(acc, dA + 2, dB + 128);
          wgmma_ss_n56_ta0_tb1<1>(acc, dA + 4, dB + 256);
          wgmma_ss_n56_ta0_tb1<1>(acc, dA + 6, dB + 384);
          wg_commit();
          wg_wait<1>();
          if (lane == 0 && c > 0) mbar_arrive(BAR(B_EMPTY + prev), 2);
          prev = bi;
          if (++ps == 6) { ps = 0; w ^= 1; }
        }
        wg_wait<0>();
        fence_regs(acc);
        if (lane == 0) mbar_arrive(BAR(B_EMPTY + prev), 2);
      }
      if (stage == 2) { if (tid == 0) PROF_MARK(15); continue; }
      if (stage == 3) break;
      int lane_;
      asm volatile("mov.u32 %0, %%laneid;" : "=r"(lane_));
      const int lq = lane_ & 3;
      const int rowl = wq * 16 + (lane_ >> 2);
      const int row0 = mh * 64 + rowl;

      if (stage == 0) {
        if (tid == 0) PROF_MARK(2);
        if (tid == 256) PROF_MARK(3);
        float accs[4] = {0.f, 0.f, 0.f, 0.f};
        if (nh == 0) {
          mbar_wait(BAR(B_BUILD), 0);
          const uint64_t dX = make_desc(sb + OFF_X + mh * 8192, 1024, 1024, 1);
          const uint64_t dSlc = make_desc(sb + OFF_SLC, 128, 128, 0);
#pragma unroll 1
          for (int c = 0; c < 7; c++) {
            wg_fence();
            wgmma_ss_n8_ta0_tb1<1>(accs, dX + c * 1024, dSlc + c * 64);
            wgmma_ss_n8_ta0_tb1<1>(accs, dX + c * 1024 + 2, dSlc + c * 64 + 16);
            wgmma_ss_n8_ta0_tb1<1>(accs, dX + c * 1024 + 4, dSlc + c * 64 + 32);
            wgmma_ss_n8_ta0_tb1<1>(accs, dX + c * 1024 + 6, dSlc + c * 64 + 48);
            wg_commit();
          }
        }
        const float qs = nh ? 1.f : 0.18898223650461362f * 1.4426950408889634f;
#pragma unroll
        for (int i = 0; i < 28; i++) acc[i] *= qs;
#pragma unroll
        for (int i = 0; i < 14; i++) keep[i] = pack_bf16(acc[2 * i], acc[2 * i + 1]);
        if (nh == 0) {
          float sq[4] = {0.f, 0.f, 0.f, 0.f};
#pragma unroll
          for (int j = 0; j < 7; j++) {
#pragma unroll
            for (int rr = 0; rr < 2; rr++) {
              const float s2 = acc[4 * j + 2 * rr] * acc[4 * j + 2 * rr] + acc[4 * j + 2 * rr + 1] * acc[4 * j + 2 * rr + 1];
              if (j < 3) sq[rr] += s2;
              else if (j > 3) sq[2 + rr] += s2;
              else { sq[rr] += (lq < 2) ? s2 : 0.f; sq[2 + rr] += (lq < 2) ? 0.f : s2; }
            }
          }
#pragma unroll
          for (int i = 0; i < 4; i++) sq[i] = quad_sum(sq[i]);
          const float mine = lq == 0 ? sq[0] : lq == 1 ? sq[1] : lq == 2 ? sq[2] : sq[3];
          ((float*)(sgen + OFF_QSQ))[(mh + (lq & 2)) * 64 + rowl + 8 * (lq & 1)] = mine <= 3.0e38f ? mine : __int_as_float(0x7f800000);
        }
        wg_wait<0>();
        fence_regs(accs);
        if (nh == 0) {
          const int sl = hp & 3;
          const bool isk = hp < 4, real = (sl < 3) || (lq < 2);
          float mxv = 0.f;
#pragma unroll
          for (int rr = 0; rr < 2; rr++) {
            const int pos = pt * 128 + row0 + 8 * rr, kr = pos & 63;
            const float v0 = accs[2 * rr], v1 = accs[2 * rr + 1];
            const bool poly = isk && ((POLY_PAT >> (kr >> 3)) & 1);
            const float sc = poly ? 2.f : 1.f;
            const float s2 = quad_sum(real ? v0 * v0 + v1 * v1 : 0.f);
            mxv = fmaxf(mxv, s2 <= 3.0e38f ? s2 : __int_as_float(0x7f800000));
            const uint32_t padv = lq == 2 ? (poly ? 0x443F4000u : 0x00003F80u) : (poly ? 0x3AB03F4Du : 0u);
            const uint32_t outv = real ? pack_bf16(sc * v0, sc * v1) : padv;
            if (hp == 3 && lq == 2) g_gate[pos] = rcpf(1.f + ex2f(-1.4426950408889634f * v0));
            *(uint32_t*)(g_kv_img + (pos >> 6) * 8192 + (isk ? 0 : 4096) + sw64_off(kr, sl * 8 + 2 * lq)) = outv;
          }
          mxv = __uint_as_float(__reduce_max_sync(~0u, __float_as_uint(mxv)));
          if (lane == 0) (isk ? g_ksq : g_vsq)[sl * 128 + pt * 8 + mh * 4 + wq] = mxv;
          __syncwarp();
          if (lane == 0) mbar_arrive(BAR(B_SIG + 0), 1);
        }
        if (tid == 0) PROF_MARK(4);
        if (tid == 256) PROF_MARK(5);
#pragma unroll
        for (int i = 0; i < 28; i++) acc[i] = 0.f;
        continue;
      }

      bar_sync(1, 512);
      if (tid == 0) PROF_MARK(6);
#pragma unroll 1
      for (int r = 0; r < 2; r++) {
        store_heads(sb + (r ? (nh ? OFF_VA : OFF_QA) : (nh ? OFF_KA : OFF_QP)), keep, (r & nh) ? 0x00003F80u : 0u, row0, lq);
#pragma unroll
        for (int i = 0; i < 14; i++) keep[i] = pack_bf16(acc[2 * i], acc[2 * i + 1]);
      }
      fence_async_smem();
      if (tid == 0) PROF_MARK(7);

      mbar_wait(BAR(B_B1), 0);
      if (tid == 0) PROF_MARK(9);
      const float* red = (const float*)(sgen + OFF_RED);
      const float ksq = red[0] * (1.02f * 1.02f), vsq = red[1];
      const float* qsq = (const float*)(sgen + OFF_QSQ);
      float b0, b1;
      asm("sqrt.approx.ftz.f32 %0, %1;" : "=f"(b0) : "f"(qsq[wg * 64 + rowl] * ksq));
      asm("sqrt.approx.ftz.f32 %0, %1;" : "=f"(b1) : "f"(qsq[wg * 64 + rowl + 8] * ksq));
      const float4 qa4 = ((const float4*)qsq)[lane_], qb4 = ((const float4*)qsq)[32 + lane_];
      const float qmax = fmaxf(fmaxf(fmaxf(qa4.x, qa4.y), fmaxf(qa4.z, qa4.w)), fmaxf(fmaxf(qb4.x, qb4.y), fmaxf(qb4.z, qb4.w)));
      const bool slow = __any_sync(~0u, !(qmax * ksq <= 92.f * 92.f) || !(vsq <= 1.0e24f));
      if (tid == 0) { *(volatile int*)(sgen + OFF_RED + 8) = slow; mbar_arrive(BAR(B_SLOW), 1); }
      bar_sync(1, 512);

      uint32_t q[8];
      {
        const uint32_t qa = sb + OFF_QP + nh * 8192;
        const int r = mh * 64 + wq * 16 + (lane_ & 7) + ((lane_ >> 3) & 1) * 8;
#pragma unroll
        for (int ks = 0; ks < 2; ks++)
          asm volatile("ldmatrix.sync.aligned.m8n8.x4.shared.b16 {%0, %1, %2, %3}, [%4];"
                       : "=r"(q[4 * ks]), "=r"(q[4 * ks + 1]), "=r"(q[4 * ks + 2]), "=r"(q[4 * ks + 3])
                       : "r"(qa + sw64_off(r, ks * 16 + (lane_ >> 4) * 8)) : "memory");
        if (lq >= 2 && !slow) {
          q[6] = lq == 2 ? pack_bf16(64.f - b0, 1.f) : 0x3F803F80u;
          q[7] = lq == 2 ? pack_bf16(64.f - b1, 1.f) : 0x3F803F80u;
        }
      }

      const uint64_t dK = make_desc(sb + OFF_RING, 512, 512, 2);
      const uint64_t dhi = dK & 0xffffffff00000000ull;
      const uint32_t dlo0 = (uint32_t)dK;
      int slot = 4, prev = 0;
      uint32_t par = 0;
      float m0 = -3.0e38f, m1 = -3.0e38f;
      if (__builtin_expect(slow, 0)) {
#pragma unroll 1
        for (int j64 = 0; j64 < 32; j64++) {
          float s[32];
          if ((j64 & 3) == 0) mbar_wait(BAR(B_FULL + slot), par);
          const uint32_t lo = dlo0 + (slot + (j64 & 3)) * 512;
          wg_fence();
          wgmma_rs_n64_tb0<0>(s, q[0], q[1], q[2], q[3], dhi | lo);
          wgmma_rs_n64_tb0<1>(s, q[4], q[5], q[6], q[7], dhi | (lo + 2));
          wg_commit();
          wg_wait<0>();
          fence_regs(s);
#pragma unroll
          for (int j = 0; j < 8; j++) {
            const float sc = ((POLY_PAT >> j) & 1) ? 0.5f : 1.f;
            m0 = fmaxf(m0, fmaxf(s[4 * j], s[4 * j + 1]) * sc);
            m1 = fmaxf(m1, fmaxf(s[4 * j + 2], s[4 * j + 3]) * sc);
          }
          if ((j64 & 3) == 3) {
            if (lane == 0) mbar_arrive(BAR(B_EMPTY + slot), 1);
            slot += 4;
            if (slot == 12) { slot = 0; par ^= 1; }
          }
        }
        m0 = quad_max(m0); m1 = quad_max(m1);
      }
      float o[16];
#pragma unroll
      for (int i = 0; i < 16; i++) o[i] = 0.f;
      if (tid == 0) PROF_MARK(10);
      const int kb = KB_AT, qb = QB_AT;
      uint32_t ok = 0;
#pragma unroll 1
      for (int it = 0; it <= 8; it++) {
        uint32_t p[16];
        if (it == kb || it == qb || it == 8) {
          float t[16];
          wg_wait<0>();
          fence_regs(o);
          if (it < 8) {
            if (tid == 0) PROF_MARK(it == kb ? 27 : 11);
            const uint64_t dA = make_desc(sb + (it == kb ? OFF_KA : OFF_QA) + nh * 8192 + mh * 4096, 512, 512, 2);
            const uint64_t dB = make_desc(sb + OFF_WPH + nh * 2048, 512, 512, 2);
            float pa[16];
            wg_fence();
            wgmma_ss_n32_ta0_tb1<0>(pa, dA, dB);
            wgmma_ss_n32_ta0_tb1<1>(pa, dA + 2, dB + 64);
            wg_commit();
            wg_wait<0>();
            fence_regs(pa);
            uint32_t ph[16];
            feature_map(pa, ph, lq);
            if (it != kb) mbar_wait(BAR(B_KVR), 0);
            const uint32_t rb = sb + OFF_PHI + wg * 8192 + rowl * 128 + lq * 4 + ((rowl & 7) << 4);
#pragma unroll
            for (int ch = 0; ch < 8; ch++) { sts32(rb ^ (ch << 4), ph[2 * ch]); sts32((rb ^ (ch << 4)) + 1024, ph[2 * ch + 1]); }
            fence_async_smem();
            bar_sync(4 + wg, 128);
            const uint64_t dP = make_desc(sb + OFF_PHI + wg * 8192, 1024, 1024, 1);
            if (it == kb) {
              const uint64_t dV = make_desc(sb + OFF_VA + nh * 8192 + mh * 4096, 512, 512, 2);
              float kv[16];
              wg_fence();
              wgmma_ss_n32_ta1_tb1<0>(kv, dP, dV);
#pragma unroll
              for (int ks = 1; ks < 4; ks++) wgmma_ss_n32_ta1_tb1<1>(kv, dP + ks * 128, dV + ks * 64);
              wg_commit();
              wg_wait<0>();
              fence_regs(kv);
              float* dst = g_kvpart + ((size_t)((2 * hp + nh) * 8 + wq * 2) * 32 + pt * 2 + mh) * 256 + (lane_ >> 2) * 32 + 2 * lq;
#pragma unroll
              for (int j = 0; j < 4; j++) {
                *(float2*)(dst + 8 * j) = make_float2(kv[4 * j], kv[4 * j + 1]);
                *(float2*)(dst + 32 * 256 + 8 * j) = make_float2(kv[4 * j + 2], kv[4 * j + 3]);
              }
              __syncwarp();
              if (lane == 0) { mbar_arrive(BAR(B_X0FREE), 1); mbar_arrive(BAR(B_SIG + 1), 1); }
              if (tid == 0) PROF_MARK(28);
            } else {
              const uint64_t dR = make_desc(sb + OFF_KVR + nh * 4096, 512, 512, 2);
              wg_fence();
              wgmma_ss_n32_ta0_tb1<0>(t, dP, dR);
#pragma unroll
              for (int ks = 1; ks < 4; ks++) wgmma_ss_n32_ta0_tb1<1>(t, dP + ks * 2, dR + ks * 64);
              wg_commit();
              wg_wait<0>();
              fence_regs(t);
              if (lane == 0) mbar_arrive(BAR(B_X1FREE), 1);
            }
          } else {
            if (lane == 0) mbar_arrive(BAR(B_EMPTY + prev), 1);
            if (tid == 0) PROF_MARK(13);
#pragma unroll
            for (int i = 0; i < 16; i++) t[i] = o[i];
          }
          if (it != kb) {
            const int br = it == 8;
            const float g0 = ((const float*)(sgen + OFF_GATE))[row0], g1 = ((const float*)(sgen + OFF_GATE))[row0 + 8];
            const float eps = br ? 0.f : 1e-6f;
            const float d0 = __shfl_sync(~0u, t[12], (lane_ & ~3) | 2), d1 = __shfl_sync(~0u, t[14], (lane_ & ~3) | 2);
            const float r0 = __fdividef(br ? 1.f - g0 : g0, d0 + eps), r1 = __fdividef(br ? 1.f - g1 : g1, d1 + eps);
            uint8_t* img = g_o_img + (size_t)((br * 16 + pt) * 14 + mh) * 8192 + rowl * 128;
            const int col0 = (2 * hp + nh) * DH + 2 * lq;
#pragma unroll
            for (int j = 0; j < 4; j++) {
              const int col = col0 + 8 * j;
              uint8_t* gp = img + (col >> 6) * 16384 + ((((col >> 3) ^ rowl) & 7) << 4) + (col & 7) * 2;
              const uint32_t v0 = pack_bf16(t[4 * j] * r0, t[4 * j + 1] * r0), v1 = pack_bf16(t[4 * j + 2] * r1, t[4 * j + 3] * r1);
              if (j < 3 || lq < 2) { *(uint32_t*)gp = v0; *(uint32_t*)(gp + 1024) = v1; }
            }
            __syncwarp();
            if (lane == 0) mbar_arrive(BAR(B_SIG + 2 + br), 1);
            if (tid == 0) PROF_MARK(12 + 2 * br);
            if (br) break;
          }
        }
        float s[32];
        const uint32_t lo = dlo0 + slot * 512;
        if (!ok) mbar_wait(BAR(B_FULL + slot), par);
        wg_fence();
        wgmma_rs_n64_tb0<0>(s, q[0], q[1], q[2], q[3], dhi | lo);
        wgmma_rs_n64_tb0<1>(s, q[4], q[5], q[6], q[7], dhi | (lo + 2));
        wg_commit();
        int nslot = slot + 4;
        uint32_t npar = par;
        if (nslot == 12) { nslot = 0; npar ^= 1; }
#pragma unroll
        for (int u = 0; u < 4; u++) {
          wg_wait<0>();
          fence_regs(s);
          if (u == 0 && lane == 0 && it > 0) mbar_arrive(BAR(B_EMPTY + prev), 1);
          if (u == 2) ok = mbar_test(BAR(B_FULL + nslot), npar);
          if (__builtin_expect(!slow, 1)) {
#pragma unroll
            for (int j = 0; j < 8; j++) {
              if ((POLY_PAT >> j) & 1) {
                p[2 * j] = exp2_pair_fma(s[4 * j], s[4 * j + 1], 0x3F003F00u, 0x00030003u);
                p[2 * j + 1] = exp2_pair_fma(s[4 * j + 2], s[4 * j + 3], 0x3F003F00u, 0x00030003u);
              } else {
                p[2 * j] = pack_bf16(ex2f(s[4 * j]), ex2f(s[4 * j + 1]));
                p[2 * j + 1] = pack_bf16(ex2f(s[4 * j + 2]), ex2f(s[4 * j + 3]));
              }
            }
          } else {
#pragma unroll
            for (int j = 0; j < 8; j++) {
              const float sc = ((POLY_PAT >> j) & 1) ? 0.5f : 1.f;
              p[2 * j] = pack_bf16(ex2f(fmaf(s[4 * j], sc, -m0)), ex2f(fmaf(s[4 * j + 1], sc, -m0)));
              p[2 * j + 1] = pack_bf16(ex2f(fmaf(s[4 * j + 2], sc, -m1)), ex2f(fmaf(s[4 * j + 3], sc, -m1)));
            }
          }
          wg_fence();
#pragma unroll
          for (int ks = 0; ks < 4; ks++)
            wgmma_rs_n32_tb1<1>(o, p[4 * ks], p[4 * ks + 1], p[4 * ks + 2], p[4 * ks + 3], dhi | (lo + u * 512 + 256 + ks * 64));
          if (u < 3) {
            wgmma_rs_n64_tb0<0>(s, q[0], q[1], q[2], q[3], dhi | (lo + (u + 1) * 512));
            wgmma_rs_n64_tb0<1>(s, q[4], q[5], q[6], q[7], dhi | (lo + (u + 1) * 512 + 2));
          }
          wg_commit();
        }
        prev = slot; slot = nslot; par = npar;
      }
      wg_wait<0>();
      if (nh == 1) return;
#pragma unroll
      for (int i = 0; i < 14; i++) keep[i] = 0u;
#pragma unroll
      for (int i = 0; i < 28; i++) acc[i] = 0.f;
    }
    if (tid == 0) PROF_MARK(17);
    __nv_bfloat16* op = prm.out + (size_t)(pt * 128 + mh * 64 + wq * 16 + (lane >> 2)) * DM + hp * 56 + 2 * (lane & 3);
#pragma unroll
    for (int j = 0; j < 7; j++) {
      *(uint32_t*)(op + 8 * j) = pack_bf16(acc[4 * j], acc[4 * j + 1]);
      *(uint32_t*)(op + 8 * DM + 8 * j) = pack_bf16(acc[4 * j + 2], acc[4 * j + 3]);
    }
    if (tid == 0) { PROF_MARK(18); PROF_CLK(31); }
    if (tid == 0) {
      unsigned prevd = atomicAdd(&g_cnt[C_DONE * 32], 1u);
      if (prevd == NCTA - 1) {
#pragma unroll 1
        for (int i = 0; i < C_N; i++) g_cnt[i * 32] = 0;
      }
    }
  }
}

typedef CUresult (*EncodeFn)(CUtensorMap*, CUtensorMapDataType, cuuint32_t, void*, const cuuint64_t*, const cuuint64_t*,
                             const cuuint32_t*, const cuuint32_t*, CUtensorMapInterleave, CUtensorMapSwizzle,
                             CUtensorMapL2promotion, CUtensorMapFloatOOBfill);

void make_map(EncodeFn enc, CUtensorMap* tm, const void* ptr, uint64_t cols, uint64_t rows, uint32_t box_rows) {
  cuuint64_t dims[2] = {cols, rows};
  cuuint64_t strides[1] = {cols * 2};
  cuuint32_t box[2] = {64, box_rows};
  cuuint32_t es[2] = {1, 1};
  enc(tm, CU_TENSOR_MAP_DATA_TYPE_BFLOAT16, 2, const_cast<void*>(ptr), dims, strides, box, es, CU_TENSOR_MAP_INTERLEAVE_NONE,
      CU_TENSOR_MAP_SWIZZLE_128B, CU_TENSOR_MAP_L2_PROMOTION_L2_128B, CU_TENSOR_MAP_FLOAT_OOB_FILL_NONE);
}

}

extern "C" void kernel_launch(void* const* d_in, const int* in_sizes, int n_in, void* d_out, int out_size) {
  (void)in_sizes; (void)n_in; (void)out_size;
  static EncodeFn enc = nullptr;
  if (!enc) {
    void* fn = nullptr;
    cudaDriverEntryPointQueryResult qr;
    cudaGetDriverEntryPoint("cuTensorMapEncodeTiled", &fn, cudaEnableDefault, &qr);
    enc = (EncodeFn)fn;
    cudaFuncSetAttribute(fused_kernel, cudaFuncAttributeMaxDynamicSharedMemorySize, SMEM_BYTES);
  }
  CUtensorMap tm_x, tm_wqkv, tm_wq, tm_woa, tm_wob;
  make_map(enc, &tm_x, d_in[0], DM, S_LEN, 128);
  make_map(enc, &tm_wqkv, d_in[1], 3 * DM, DM, 64);
  make_map(enc, &tm_wq, d_in[5], DM, DM, 64);
  make_map(enc, &tm_woa, d_in[3], DM, DM, 64);
  make_map(enc, &tm_wob, d_in[8], DM, DM, 64);
  Params prm;
  prm.w_phi = (const __nv_bfloat16*)d_in[2];
  prm.wk = (const __nv_bfloat16*)d_in[6];
  prm.wv = (const __nv_bfloat16*)d_in[7];
  prm.gate_w = (const __nv_bfloat16*)d_in[9];
  prm.out = (__nv_bfloat16*)d_out;
  fused_kernel<<<NCTA, NTHREADS, SMEM_BYTES>>>(tm_x, tm_wqkv, tm_wq, tm_woa, tm_wob, prm);
}
```

```cpp
#include <cuda_runtime.h>
#include <cuda_bf16.h>
#include <cuda.h>
#include <stdint.h>

namespace {

constexpr int S_LEN = 2048, DM = 448, DH = 28;
constexpr int NCTA = 128;
constexpr int NTHREADS = 640;
constexpr uint32_t POLY_PAT = 0x57;

#define KB_AT (wg >> 1)
#define QB_AT (5 + (wg >> 1))

constexpr int OFF_X = 0;
constexpr int OFF_KA = 0;
constexpr int OFF_VA = 16384;
constexpr int OFF_QP = 32768;
constexpr int OFF_QA = 57344;
constexpr int OFF_KVR = 73728;
constexpr int OFF_PHI = 81920;
constexpr int OFF_WO = 0;
constexpr int OFF_RING = 114688;
constexpr int OFF_WPH = 212992;
constexpr int OFF_SLC = 217088;
constexpr int OFF_QSQ = 224256;
constexpr int OFF_GATE = 225280;
constexpr int OFF_RED = 225792;
constexpr int OFF_BAR = 225856;
constexpr int SMEM_BYTES = 226368 + 1024;

constexpr int B_FULL = 0, B_X = 12, B_EMPTY = 19, B_WO = 31  , B_KVR = 33, B_X0FREE = 34, B_X1FREE = 35, B_B1 = 36,
              B_SLOW = 37, B_BUILD = 38, B_STG = 39, B_SIG = 40  , B_N = 44;

constexpr int C_KV = 0, C_PART = 1, C_RED = 2, C_DONE = 3, C_OA = 4, C_OB = 20, C_N = 36;

__device__ __align__(1024) uint8_t g_kv_img[32 * 8192];
__device__ __align__(16) float g_ksq[512];
__device__ __align__(16) float g_vsq[512];
__device__ __align__(16) float g_gate[S_LEN];
__device__ __align__(1024) float g_kvpart[128 * 32 * 256];
__device__ __align__(1024) uint8_t g_kvr_img[16 * 4096];
__device__ __align__(1024) uint8_t g_o_img[2 * 16 * 14 * 8192];
__device__ unsigned g_cnt[C_N * 32];

#define PROF2(i) do { } while (0)
#define PROF_CLK(i) do { } while (0)
#define PROF_MARK(i) do { } while (0)
__device__ __forceinline__ uint32_t smem_u32(const void* p) { return (uint32_t)__cvta_generic_to_shared(p); }
__device__ __forceinline__ void mbar_init(uint32_t a, int cnt) {
  asm volatile("mbarrier.init.shared::cta.b64 [%0], %1;" ::"r"(a), "r"(cnt) : "memory");
}
__device__ __forceinline__ void mbar_expect_tx(uint32_t a, uint32_t bytes) {
  asm volatile("mbarrier.arrive.expect_tx.shared::cta.b64 _, [%0], %1;" ::"r"(a), "r"(bytes) : "memory");
}
__device__ __forceinline__ void mbar_arrive(uint32_t a, uint32_t cnt) {
  asm volatile("mbarrier.arrive.shared::cta.b64 _, [%0], %1;" ::"r"(a), "r"(cnt) : "memory");
}
__device__ __forceinline__ void mbar_wait(uint32_t a, uint32_t parity) {
  asm volatile(
      "{\n.reg .pred p;\n.reg .u32 c;\nmov.u32 c, 0;\n"
      "W_%=:\nmbarrier.try_wait.parity.shared::cta.b64 p, [%0], %1;\n"
      "add.u32 c, c, 1;\nsetp.lt.and.u32 p, c, 0x1000000, !p;\n@p bra W_%=;\n}"
      ::"r"(a), "r"(parity) : "memory");
}
__device__ __forceinline__ uint32_t mbar_test(uint32_t a, uint32_t parity) {
  uint32_t ok;
  asm volatile("{\n.reg .pred p;\nmbarrier.test_wait.parity.shared::cta.b64 p, [%1], %2;\nselp.u32 %0, 1, 0, p;\n}"
               : "=r"(ok) : "r"(a), "r"(parity) : "memory");
  return ok;
}
__device__ __forceinline__ bool elect_one() {
  uint32_t r;
  asm volatile("{\n.reg .pred p;\nelect.sync _|p, 0xffffffff;\nselp.u32 %0, 1, 0, p;\n}" : "=r"(r));
  return r != 0;
}
__device__ __forceinline__ void tma_2d(uint32_t dst, const CUtensorMap* tm, int c0, int c1, uint32_t bar) {
  asm volatile("cp.async.bulk.tensor.2d.shared::cluster.global.mbarrier::complete_tx::bytes [%0], [%1, {%3, %4}], [%2];"
               ::"r"(dst), "l"(tm), "r"(bar), "r"(c0), "r"(c1) : "memory");
}
__device__ __forceinline__ void bulk_g2s(uint32_t dst, const void* src, uint32_t bytes, uint32_t bar) {
  asm volatile("cp.async.bulk.shared::cluster.global.mbarrier::complete_tx::bytes [%0], [%1], %2, [%3];"
               ::"r"(dst), "l"(src), "r"(bytes), "r"(bar) : "memory");
}
__device__ __forceinline__ void cp_async8(uint32_t dst, const void* src) {
  asm volatile("cp.async.ca.shared.global [%0], [%1], 8;" ::"r"(dst), "l"(src) : "memory");
}
__device__ __forceinline__ void fence_async_smem() { asm volatile("fence.proxy.async.shared::cta;" ::: "memory"); }
__device__ __forceinline__ void fence_async_all() { asm volatile("fence.proxy.async;" ::: "memory"); }
__device__ __forceinline__ void bar_sync(int id, int n) { asm volatile("bar.sync %0, %1;" ::"r"(id), "r"(n) : "memory"); }
__device__ __forceinline__ void cnt_arrive(int idx) {
  asm volatile("red.release.gpu.global.add.u32 [%0], 1;" ::"l"(&g_cnt[idx * 32]) : "memory");
}
__device__ __forceinline__ void cnt_wait(int idx, unsigned target) {
  unsigned v, n = 0;
#pragma unroll 1
  while (true) {
    asm volatile("ld.relaxed.gpu.global.u32 %0, [%1];" : "=r"(v) : "l"(&g_cnt[idx * 32]) : "memory");
    if (v >= target || ++n >= (1u << 22)) break;
    __nanosleep(64);
  }
  asm volatile("fence.acq_rel.gpu;" ::: "memory");
}
__device__ __forceinline__ void wg_fence() { asm volatile("wgmma.fence.sync.aligned;" ::: "memory"); }
__device__ __forceinline__ void wg_commit() { asm volatile("wgmma.commit_group.sync.aligned;" ::: "memory"); }
template <int N> __device__ __forceinline__ void wg_wait() { asm volatile("wgmma.wait_group.sync.aligned %0;" ::"n"(N) : "memory"); }
template <int N> __device__ __forceinline__ void fence_regs(float (&d)[N]) {
#pragma unroll
  for (int i = 0; i < N; i++) asm volatile("" : "+f"(d[i])::"memory");
}
__device__ __forceinline__ uint64_t make_desc(uint32_t saddr, uint32_t lbo, uint32_t sbo, uint32_t swz) {
  return (uint64_t)((saddr & 0x3FFFF) >> 4) | ((uint64_t)(lbo >> 4) << 16) | ((uint64_t)(sbo >> 4) << 32) | ((uint64_t)swz << 62);
}
__device__ __forceinline__ float ex2f(float x) { float y; asm("ex2.approx.ftz.f32 %0, %1;" : "=f"(y) : "f"(x)); return y; }
__device__ __forceinline__ float rcpf(float x) { float y; asm("rcp.approx.ftz.f32 %0, %1;" : "=f"(y) : "f"(x)); return y; }
__device__ __forceinline__ uint32_t pack_bf16(float lo, float hi) {
  uint32_t r; asm("cvt.rn.bf16x2.f32 %0, %1, %2;" : "=r"(r) : "f"(hi), "f"(lo)); return r;
}
__device__ __forceinline__ uint32_t lop_and_or(uint32_t a, uint32_t m, uint32_t c) {
  uint32_t r; asm("lop3.b32 %0, %1, %2, %3, 0xEA;" : "=r"(r) : "r"(a), "r"(m), "r"(c)); return r;
}
__device__ __forceinline__ void sts32(uint32_t a, uint32_t v) { asm volatile("st.shared.b32 [%0], %1;" ::"r"(a), "r"(v) : "memory"); }
__device__ __forceinline__ void sts64(uint32_t a, uint32_t v0, uint32_t v1) { asm volatile("st.shared.v2.b32 [%0], {%1, %2};" ::"r"(a), "r"(v0), "r"(v1) : "memory"); }
__device__ __forceinline__ void sts128(uint32_t a, uint4 v) {
  asm volatile("st.shared.v4.b32 [%0], {%1, %2, %3, %4};" ::"r"(a), "r"(v.x), "r"(v.y), "r"(v.z), "r"(v.w) : "memory");
}
__device__ __forceinline__ float4 ldcg_f4(const float* p) {
  float4 v; asm volatile("ld.global.cg.v4.f32 {%0, %1, %2, %3}, [%4];" : "=f"(v.x), "=f"(v.y), "=f"(v.z), "=f"(v.w) : "l"(p) : "memory"); return v;
}
__device__ __forceinline__ float quad_sum(float v) { v += __shfl_xor_sync(~0u, v, 1); v += __shfl_xor_sync(~0u, v, 2); return v; }
__device__ __forceinline__ float quad_max(float v) { v = fmaxf(v, __shfl_xor_sync(~0u, v, 1)); v = fmaxf(v, __shfl_xor_sync(~0u, v, 2)); return v; }

template <int SD> __device__ __forceinline__ void wgmma_ss_n56_ta0_tb1(float (&d)[28], uint64_t da, uint64_t db) {
  if (SD) asm volatile("wgmma.mma_async.sync.aligned.m64n56k16.f32.bf16.bf16 {%0, %1, %2, %3, %4, %5, %6, %7, %8, %9, %10, %11, %12, %13, %14, %15, %16, %17, %18, %19, %20, %21, %22, %23, %24, %25, %26, %27}, %28, %29, 1, 1, 1, 0, 1;\n"
    : "+f"(d[0]), "+f"(d[1]), "+f"(d[2]), "+f"(d[3]), "+f"(d[4]), "+f"(d[5]), "+f"(d[6]), "+f"(d[7]), "+f"(d[8]), "+f"(d[9]), "+f"(d[10]), "+f"(d[11]), "+f"(d[12]), "+f"(d[13]), "+f"(d[14]), "+f"(d[15]), "+f"(d[16]), "+f"(d[17]), "+f"(d[18]), "+f"(d[19]), "+f"(d[20]), "+f"(d[21]), "+f"(d[22]), "+f"(d[23]), "+f"(d[24]), "+f"(d[25]), "+f"(d[26]), "+f"(d[27])
    : "l"(da), "l"(db));
  else asm volatile("wgmma.mma_async.sync.aligned.m64n56k16.f32.bf16.bf16 {%0, %1, %2, %3, %4, %5, %6, %7, %8, %9, %10, %11, %12, %13, %14, %15, %16, %17, %18, %19, %20, %21, %22, %23, %24, %25, %26, %27}, %28, %29, 0, 1, 1, 0, 1;\n"
    : "=f"(d[0]), "=f"(d[1]), "=f"(d[2]), "=f"(d[3]), "=f"(d[4]), "=f"(d[5]), "=f"(d[6]), "=f"(d[7]), "=f"(d[8]), "=f"(d[9]), "=f"(d[10]), "=f"(d[11]), "=f"(d[12]), "=f"(d[13]), "=f"(d[14]), "=f"(d[15]), "=f"(d[16]), "=f"(d[17]), "=f"(d[18]), "=f"(d[19]), "=f"(d[20]), "=f"(d[21]), "=f"(d[22]), "=f"(d[23]), "=f"(d[24]), "=f"(d[25]), "=f"(d[26]), "=f"(d[27])
    : "l"(da), "l"(db));
}
template <int SD> __device__ __forceinline__ void wgmma_ss_n8_ta0_tb1(float (&d)[4], uint64_t da, uint64_t db) {
  if (SD) asm volatile("wgmma.mma_async.sync.aligned.m64n8k16.f32.bf16.bf16 {%0, %1, %2, %3}, %4, %5, 1, 1, 1, 0, 1;\n"
    : "+f"(d[0]), "+f"(d[1]), "+f"(d[2]), "+f"(d[3])
    : "l"(da), "l"(db));
  else asm volatile("wgmma.mma_async.sync.aligned.m64n8k16.f32.bf16.bf16 {%0, %1, %2, %3}, %4, %5, 0, 1, 1, 0, 1;\n"
    : "=f"(d[0]), "=f"(d[1]), "=f"(d[2]), "=f"(d[3])
    : "l"(da), "l"(db));
}
template <int SD> __device__ __forceinline__ void wgmma_ss_n32_ta1_tb1(float (&d)[16], uint64_t da, uint64_t db) {
  if (SD) asm volatile("wgmma.mma_async.sync.aligned.m64n32k16.f32.bf16.bf16 {%0, %1, %2, %3, %4, %5, %6, %7, %8, %9, %10, %11, %12, %13, %14, %15}, %16, %17, 1, 1, 1, 1, 1;\n"
    : "+f"(d[0]), "+f"(d[1]), "+f"(d[2]), "+f"(d[3]), "+f"(d[4]), "+f"(d[5]), "+f"(d[6]), "+f"(d[7]), "+f"(d[8]), "+f"(d[9]), "+f"(d[10]), "+f"(d[11]), "+f"(d[12]), "+f"(d[13]), "+f"(d[14]), "+f"(d[15])
    : "l"(da), "l"(db));
  else asm volatile("wgmma.mma_async.sync.aligned.m64n32k16.f32.bf16.bf16 {%0, %1, %2, %3, %4, %5, %6, %7, %8, %9, %10, %11, %12, %13, %14, %15}, %16, %17, 0, 1, 1, 1, 1;\n"
    : "=f"(d[0]), "=f"(d[1]), "=f"(d[2]), "=f"(d[3]), "=f"(d[4]), "=f"(d[5]), "=f"(d[6]), "=f"(d[7]), "=f"(d[8]), "=f"(d[9]), "=f"(d[10]), "=f"(d[11]), "=f"(d[12]), "=f"(d[13]), "=f"(d[14]), "=f"(d[15])
    : "l"(da), "l"(db));
}
template <int SD> __device__ __forceinline__ void wgmma_ss_n32_ta0_tb1(float (&d)[16], uint64_t da, uint64_t db) {
  if (SD) asm volatile("wgmma.mma_async.sync.aligned.m64n32k16.f32.bf16.bf16 {%0, %1, %2, %3, %4, %5, %6, %7, %8, %9, %10, %11, %12, %13, %14, %15}, %16, %17, 1, 1, 1, 0, 1;\n"
    : "+f"(d[0]), "+f"(d[1]), "+f"(d[2]), "+f"(d[3]), "+f"(d[4]), "+f"(d[5]), "+f"(d[6]), "+f"(d[7]), "+f"(d[8]), "+f"(d[9]), "+f"(d[10]), "+f"(d[11]), "+f"(d[12]), "+f"(d[13]), "+f"(d[14]), "+f"(d[15])
    : "l"(da), "l"(db));
  else asm volatile("wgmma.mma_async.sync.aligned.m64n32k16.f32.bf16.bf16 {%0, %1, %2, %3, %4, %5, %6, %7, %8, %9, %10, %11, %12, %13, %14, %15}, %16, %17, 0, 1, 1, 0, 1;\n"
    : "=f"(d[0]), "=f"(d[1]), "=f"(d[2]), "=f"(d[3]), "=f"(d[4]), "=f"(d[5]), "=f"(d[6]), "=f"(d[7]), "=f"(d[8]), "=f"(d[9]), "=f"(d[10]), "=f"(d[11]), "=f"(d[12]), "=f"(d[13]), "=f"(d[14]), "=f"(d[15])
    : "l"(da), "l"(db));
}
template <int SD> __device__ __forceinline__ void wgmma_rs_n64_tb0(float (&d)[32], uint32_t a0, uint32_t a1, uint32_t a2, uint32_t a3, uint64_t db) {
  if (SD) asm volatile("wgmma.mma_async.sync.aligned.m64n64k16.f32.bf16.bf16 {%0, %1, %2, %3, %4, %5, %6, %7, %8, %9, %10, %11, %12, %13, %14, %15, %16, %17, %18, %19, %20, %21, %22, %23, %24, %25, %26, %27, %28, %29, %30, %31}, {%32, %33, %34, %35}, %36, 1, 1, 1, 0;\n"
    : "+f"(d[0]), "+f"(d[1]), "+f"(d[2]), "+f"(d[3]), "+f"(d[4]), "+f"(d[5]), "+f"(d[6]), "+f"(d[7]), "+f"(d[8]), "+f"(d[9]), "+f"(d[10]), "+f"(d[11]), "+f"(d[12]), "+f"(d[13]), "+f"(d[14]), "+f"(d[15]), "+f"(d[16]), "+f"(d[17]), "+f"(d[18]), "+f"(d[19]), "+f"(d[20]), "+f"(d[21]), "+f"(d[22]), "+f"(d[23]), "+f"(d[24]), "+f"(d[25]), "+f"(d[26]), "+f"(d[27]), "+f"(d[28]), "+f"(d[29]), "+f"(d[30]), "+f"(d[31])
    : "r"(a0), "r"(a1), "r"(a2), "r"(a3), "l"(db));
  else asm volatile("wgmma.mma_async.sync.aligned.m64n64k16.f32.bf16.bf16 {%0, %1, %2, %3, %4, %5, %6, %7, %8, %9, %10, %11, %12, %13, %14, %15, %16, %17, %18, %19, %20, %21, %22, %23, %24, %25, %26, %27, %28, %29, %30, %31}, {%32, %33, %34, %35}, %36, 0, 1, 1, 0;\n"
    : "=f"(d[0]), "=f"(d[1]), "=f"(d[2]), "=f"(d[3]), "=f"(d[4]), "=f"(d[5]), "=f"(d[6]), "=f"(d[7]), "=f"(d[8]), "=f"(d[9]), "=f"(d[10]), "=f"(d[11]), "=f"(d[12]), "=f"(d[13]), "=f"(d[14]), "=f"(d[15]), "=f"(d[16]), "=f"(d[17]), "=f"(d[18]), "=f"(d[19]), "=f"(d[20]), "=f"(d[21]), "=f"(d[22]), "=f"(d[23]), "=f"(d[24]), "=f"(d[25]), "=f"(d[26]), "=f"(d[27]), "=f"(d[28]), "=f"(d[29]), "=f"(d[30]), "=f"(d[31])
    : "r"(a0), "r"(a1), "r"(a2), "r"(a3), "l"(db));
}
template <int SD> __device__ __forceinline__ void wgmma_rs_n32_tb1(float (&d)[16], uint32_t a0, uint32_t a1, uint32_t a2, uint32_t a3, uint64_t db) {
  if (SD) asm volatile("wgmma.mma_async.sync.aligned.m64n32k16.f32.bf16.bf16 {%0, %1, %2, %3, %4, %5, %6, %7, %8, %9, %10, %11, %12, %13, %14, %15}, {%16, %17, %18, %19}, %20, 1, 1, 1, 1;\n"
    : "+f"(d[0]), "+f"(d[1]), "+f"(d[2]), "+f"(d[3]), "+f"(d[4]), "+f"(d[5]), "+f"(d[6]), "+f"(d[7]), "+f"(d[8]), "+f"(d[9]), "+f"(d[10]), "+f"(d[11]), "+f"(d[12]), "+f"(d[13]), "+f"(d[14]), "+f"(d[15])
    : "r"(a0), "r"(a1), "r"(a2), "r"(a3), "l"(db));
  else asm volatile("wgmma.mma_async.sync.aligned.m64n32k16.f32.bf16.bf16 {%0, %1, %2, %3, %4, %5, %6, %7, %8, %9, %10, %11, %12, %13, %14, %15}, {%16, %17, %18, %19}, %20, 0, 1, 1, 1;\n"
    : "=f"(d[0]), "=f"(d[1]), "=f"(d[2]), "=f"(d[3]), "=f"(d[4]), "=f"(d[5]), "=f"(d[6]), "=f"(d[7]), "=f"(d[8]), "=f"(d[9]), "=f"(d[10]), "=f"(d[11]), "=f"(d[12]), "=f"(d[13]), "=f"(d[14]), "=f"(d[15])
    : "r"(a0), "r"(a1), "r"(a2), "r"(a3), "l"(db));
}

__device__ __forceinline__ uint32_t sw64_off(int row, int d) { return row * 64 + ((((d >> 3) ^ (row >> 1)) & 3) << 4) + (d & 7) * 2; }

__device__ __forceinline__ uint32_t exp2_pair_fma(float t0, float t1, uint32_t c_half, uint32_t c_3) {
  uint32_t y0, y;
  asm("prmt.b32 %0, %1, %2, 0x6521;" : "=r"(y0) : "r"(__float_as_uint(t0)), "r"(__float_as_uint(t1)));
  uint32_t h = lop_and_or(y0, 0x007F007Fu, c_half);
  uint32_t e = lop_and_or(y0, 0xFF80FF80u, c_3);
  asm("fma.rn.bf16x2 %0, %1, %2, %3;" : "=r"(y) : "r"(y0), "r"(h), "r"(e));
  return y;
}

__device__ __forceinline__ void feature_map(float (&v)[16], uint32_t (&ph)[16], int lq) {
  const float L2E = 1.4426950408889634f;
  const bool tail_ok = lq < 2;
  float mx[2], mn[2], b[16], sa[2], sn[2];
#pragma unroll
  for (int r = 0; r < 2; r++) {
    const int o = 2 * r;
    if (!tail_ok) { v[o + 12] = v[o]; v[o + 13] = v[o]; }
    mx[r] = fmaxf(fmaxf(fmaxf(v[o], v[o + 1]), fmaxf(v[o + 4], v[o + 5])), fmaxf(fmaxf(v[o + 8], v[o + 9]), fmaxf(v[o + 12], v[o + 13])));
    mn[r] = fminf(fminf(fminf(v[o], v[o + 1]), fminf(v[o + 4], v[o + 5])), fminf(fminf(v[o + 8], v[o + 9]), fminf(v[o + 12], v[o + 13])));
  }
#pragma unroll
  for (int o = 1; o <= 2; o <<= 1)
#pragma unroll
    for (int r = 0; r < 2; r++) { mx[r] = fmaxf(mx[r], __shfl_xor_sync(~0u, mx[r], o)); mn[r] = fminf(mn[r], __shfl_xor_sync(~0u, mn[r], o)); }
#pragma unroll
  for (int r = 0; r < 2; r++) {
    const int o = 2 * r;
    const float cx = -mx[r] * L2E, cn = mn[r] * L2E;
#pragma unroll
    for (int i = 0; i < 8; i++) {
      const int k = o + 4 * (i >> 1) + (i & 1);
      b[k] = ex2f(fmaf(v[k], -L2E, cn));
      v[k] = ex2f(fmaf(v[k], L2E, cx));
    }
    if (!tail_ok) { v[o + 12] = v[o + 13] = b[o + 12] = b[o + 13] = 0.f; }
    sa[r] = ((v[o] + v[o + 1]) + (v[o + 4] + v[o + 5])) + ((v[o + 8] + v[o + 9]) + (v[o + 12] + v[o + 13]));
    sn[r] = ((b[o] + b[o + 1]) + (b[o + 4] + b[o + 5])) + ((b[o + 8] + b[o + 9]) + (b[o + 12] + b[o + 13]));
  }
#pragma unroll
  for (int o = 1; o <= 2; o <<= 1)
#pragma unroll
    for (int r = 0; r < 2; r++) { sa[r] += __shfl_xor_sync(~0u, sa[r], o); sn[r] += __shfl_xor_sync(~0u, sn[r], o); }
#pragma unroll
  for (int r = 0; r < 2; r++) {
    const float ra = rcpf(sa[r]), rb = rcpf(sn[r]);
#pragma unroll
    for (int jj = 0; jj < 4; jj++) {
      ph[jj * 2 + r] = pack_bf16(v[2 * r + 4 * jj] * ra, v[2 * r + 4 * jj + 1] * ra);
      ph[(4 + jj) * 2 + r] = pack_bf16(b[2 * r + 4 * jj] * rb, b[2 * r + 4 * jj + 1] * rb);
    }
  }
}

__device__ __forceinline__ void store_heads(uint32_t base, const uint32_t (&a)[14], uint32_t pad, int row0, int lq) {
  const uint32_t rb = base + row0 * 64 + (((row0 >> 1) & 3) << 4);
  const uint32_t b0 = rb + lq * 4;
  const uint32_t b1 = (rb + 8192 + ((lq * 4 + 8) & 15)) ^ ((lq >> 1) << 4);
#pragma unroll
  for (int j = 0; j < 7; j++) {
    uint32_t ad;
    if (j < 3) ad = b0 ^ (j << 4);
    else if (j == 3) ad = (lq < 2) ? (b0 ^ 48u) : (b1 ^ 16u);
    else ad = (lq < 2) ? (b1 ^ ((j - 4) << 4)) : ((b1 ^ 16u) ^ ((j - 3) << 4));
    sts32(ad, a[2 * j]);
    sts32(ad + 512, a[2 * j + 1]);
  }
  sts64((rb ^ 48u) + 8 + (lq & 1) * 8192 + (lq >> 1) * 512, pad, 0u);
}

struct Params {
  const __nv_bfloat16* w_phi;
  const __nv_bfloat16* wk;
  const __nv_bfloat16* wv;
  const __nv_bfloat16* gate_w;
  __nv_bfloat16* out;
};

__global__ void __launch_bounds__(NTHREADS, 1)
fused_kernel(const __grid_constant__ CUtensorMap tm_x, const __grid_constant__ CUtensorMap tm_wqkv,
             const __grid_constant__ CUtensorMap tm_wq, const __grid_constant__ CUtensorMap tm_woa,
             const __grid_constant__ CUtensorMap tm_wob, const Params prm) {
  extern __shared__ uint8_t smem_raw[];
  uint32_t sb = (smem_u32(smem_raw) + 1023u) & ~1023u;
  uint8_t* sgen = smem_raw + (sb - smem_u32(smem_raw));
  asm volatile("mov.u32 %0, %0;" : "+r"(sb));
  const int tid = threadIdx.x, lane = tid & 31;
  const int warp = __shfl_sync(~0u, tid >> 5, 0), wg = warp >> 2;
  const int pt = blockIdx.x >> 3, hp = blockIdx.x & 7;
  const uint32_t bars = sb + OFF_BAR;
  auto BAR = [&](int i) { return bars + 8u * i; };

  if (tid == 0) { PROF_MARK(0); PROF_CLK(30); PROF2(15); }
  if (elect_one()) {
    if (warp < B_EMPTY) {
      mbar_init(BAR(warp), 1);
      fence_async_smem();
      const bool isx = warp >= B_X;
      const int c = isx ? warp - B_X : warp >> 1;
      mbar_expect_tx(BAR(warp), isx ? 16384 : 8192);
      tma_2d(isx ? sb + OFF_X + c * 16384 : sb + OFF_RING + warp * 8192, isx ? &tm_x : ((warp & 1) ? &tm_wqkv : &tm_wq),
             isx ? c * 64 : hp * 56 + ((warp & 1) ? DM : 0), isx ? pt * 128 : c * 64, BAR(warp));
    }
#pragma unroll 1
    for (int i = B_EMPTY + (warp + 1) % 20; i < B_N; i += 20) {
      int cnt = 16;
      if ((i >= B_WO && i <= B_KVR) || i == B_SLOW || i == B_STG) cnt = 1;
      if (i == B_B1) cnt = 2;
      if (i == B_BUILD) cnt = 3;
      if (i == B_SIG) cnt = 8;
      mbar_init(BAR(i), cnt);
    }
    fence_async_smem();
  }
  __syncthreads();

  if (wg == 4) {
    asm volatile("setmaxnreg.dec.sync.aligned.u32 32;");
    if (warp == 16) {
      if (elect_one()) {
#pragma unroll 1
        for (int i = 6; i < 14; i++) {
          const int c = i < 7 ? i : i - 7, ps = i % 6;
#pragma unroll 1
          for (int h = 0; h < 2; h++) {
            const int sl = 2 * ps + h;
            mbar_wait(BAR(B_EMPTY + sl), (i / 6 - 1) & 1);
            mbar_expect_tx(BAR(B_FULL + sl), 8192);
            tma_2d(sb + OFF_RING + sl * 8192, (i < 7 && !h) ? &tm_wq : &tm_wqkv, hp * 56 + (h ? (i < 7 ? DM : 2 * DM) : 0), c * 64,
                   BAR(B_FULL + sl));
          }
        }
        PROF_MARK(20);
        cnt_wait(C_KV, NCTA);
        PROF_MARK(21);
        fence_async_all();
        int slot = 4, ng = 8;
        uint32_t par = 1;
#pragma unroll 1
        for (int n = 0; n < ng; n++) {
          mbar_wait(BAR(B_EMPTY + slot), par);
          if (n < 3) { mbar_wait(BAR(B_EMPTY + slot + 1), par); mbar_wait(BAR(B_EMPTY + slot + 2), par); mbar_wait(BAR(B_EMPTY + slot + 3), par); }
          mbar_expect_tx(BAR(B_FULL + slot), 32768);
          bulk_g2s(sb + OFF_RING + slot * 8192, g_kv_img + (n & 7) * 32768, 32768, BAR(B_FULL + slot));
          slot += 4;
          if (slot == 12) { slot = 0; par ^= 1; }
          if (n == 7) {
            mbar_wait(BAR(B_SLOW), 0);
            if (*(volatile int*)(sgen + OFF_RED + 8)) ng = 16;
          }
        }
#pragma unroll 1
        for (int i = 0; i < 14; i++) {
          const int ps = i % 6, g4 = (ps >> 1) * 4, bi = g4 + 1 + (ps & 1);
          if (i == 0 || i == 7) {
            cnt_wait((i ? C_OB : C_OA) + pt, 8);
            PROF_MARK(26);
            fence_async_all();
          }
          if (i < 6) mbar_wait(BAR(B_EMPTY + g4), g4 >= slot ? par : par ^ 1);
          else mbar_wait(BAR(B_EMPTY + bi), (ps < 2) ^ ((i / 6 - 1) & 1));
          mbar_expect_tx(BAR(B_FULL + bi), 16384);
          bulk_g2s(sb + OFF_RING + ps * 16384, g_o_img + (size_t)(pt * 14 + (i < 7 ? 2 * i : 2 * i + 210)) * 8192, 16384, BAR(B_FULL + bi));
        }
      }
    } else {
      {
        const int t = tid - 544;
#pragma unroll 1
        for (int i = t; i < 256; i += 96) sts128(sb + OFF_WPH + i * 16, make_uint4(0, 0, 0, 0));
        bar_sync(2, 96);
#pragma unroll 1
        for (int k = t; k < DM; k += 96) {
          const __nv_bfloat16* src = (hp < 4 ? prm.wk : prm.wv) + k * DH + (hp & 3) * 8;
          cp_async8(sb + OFF_SLC + k * 16, src);
          if ((hp & 3) != 3) cp_async8(sb + OFF_SLC + k * 16 + 8, src + 4);
          else sts64(sb + OFF_SLC + k * 16 + 8, hp == 3 ? (uint32_t)((const unsigned short*)prm.gate_w)[k] : 0u, 0u);
          if (k < 392) {
            const int row = k / 7, e = row >= DH;
            cp_async8(sb + OFF_WPH + e * 2048 + sw64_off(row - DH * e, (k % 7) * 4), prm.w_phi + 2 * hp * DH * DH + k * 4);
          }
        }
        asm volatile("cp.async.wait_all;" ::: "memory");
        fence_async_smem();
        __syncwarp();
        if (lane == 0) mbar_arrive(BAR(B_BUILD), 1);
      }
      if (warp == 18) {
        if (lane == 0) {
#pragma unroll 1
          for (int i = 0; i < 4; i++) {
            mbar_wait(BAR(B_SIG + i), 0);
            cnt_arrive(i == 0 ? C_KV : i == 1 ? C_PART : (i == 2 ? C_OA : C_OB) + pt);
          }
        }
      } else if (warp == 19) {
        if (elect_one()) {
          mbar_wait(BAR(B_SIG + 0), 0);
          cnt_wait(C_KV, NCTA);
          fence_async_all();
          mbar_expect_tx(BAR(B_B1), 512);
          bulk_g2s(sb + OFF_GATE, g_gate + pt * 128, 512, BAR(B_B1));
        }
        __syncwarp();
        float ksq = 0.f, vsq = 0.f;
#pragma unroll
        for (int sl = 0; sl < 4; sl++) {
          float4 a = ldcg_f4(g_ksq + sl * 128 + lane * 4), b = ldcg_f4(g_vsq + sl * 128 + lane * 4);
          float m = fmaxf(fmaxf(a.x, a.y), fmaxf(a.z, a.w));
          m = __uint_as_float(__reduce_max_sync(~0u, __float_as_uint(m)));
          ksq += m;
          vsq = fmaxf(vsq, fmaxf(fmaxf(b.x, b.y), fmaxf(b.z, b.w)));
        }
        vsq = __uint_as_float(__reduce_max_sync(~0u, __float_as_uint(vsq)));
        if (lane == 0) {
          float* red = (float*)(sgen + OFF_RED);
          red[0] = ksq; red[1] = vsq;
          mbar_arrive(BAR(B_B1), 1);
        }
      } else {
        if (elect_one()) {
          mbar_wait(BAR(B_X0FREE), 0);
          mbar_expect_tx(BAR(B_WO), 57344);
#pragma unroll 1
          for (int c = 0; c < 7; c++) tma_2d(sb + OFF_WO + c * 8192, &tm_woa, hp * 56, c * 64, BAR(B_WO));
          PROF_MARK(22);
          cnt_wait(C_PART, NCTA);
          PROF_MARK(23);
          fence_async_all();
          mbar_expect_tx(BAR(B_STG), 32768);
          bulk_g2s(sb + OFF_PHI, g_kvpart + (size_t)blockIdx.x * 8192, 32768, BAR(B_STG));
        }
        __syncwarp();
        mbar_wait(BAR(B_STG), 0);
        {
          const float4* src = (const float4*)(sgen + OFF_PHI) + lane * 2;
          float4 s0 = make_float4(0, 0, 0, 0), s1 = s0;
#pragma unroll 2
          for (int t = 0; t < 32; t++) {
            float4 a = src[t * 64], b = src[t * 64 + 1];
            s0.x += a.x; s0.y += a.y; s0.z += a.z; s0.w += a.w; s1.x += b.x; s1.y += b.y; s1.z += b.z; s1.w += b.w;
          }
          uint4 v = make_uint4(pack_bf16(s0.x, s0.y), pack_bf16(s0.z, s0.w), pack_bf16(s1.x, s1.y), pack_bf16(s1.z, s1.w));
          *(uint4*)(g_kvr_img + (blockIdx.x >> 3) * 4096 + sw64_off((blockIdx.x & 7) * 8 + (lane >> 2), (lane & 3) * 8)) = v;
        }
        __syncwarp();
        if (elect_one()) {
          cnt_arrive(C_RED);
          PROF_MARK(24);
          cnt_wait(C_RED, NCTA);
          PROF_MARK(25);
          fence_async_all();
          mbar_expect_tx(BAR(B_KVR), 8192);
          bulk_g2s(sb + OFF_KVR, g_kvr_img + hp * 8192, 8192, BAR(B_KVR));
          mbar_wait(BAR(B_X1FREE), 0);
          mbar_expect_tx(BAR(B_WO + 1), 57344);
#pragma unroll 1
          for (int c = 0; c < 7; c++) tma_2d(sb + OFF_WO + 57344 + c * 8192, &tm_wob, hp * 56, c * 64, BAR(B_WO + 1));
        }
      }
    }
  } else {
    asm volatile("setmaxnreg.inc.sync.aligned.u32 112;");
    const int mh = wg & 1, nh = wg >> 1, wq = warp & 3;
    float acc[28];
    uint32_t keep[14];
#pragma unroll
    for (int i = 0; i < 28; i++) acc[i] = 0.f;

#pragma unroll 1
    for (int stage = 0; stage < 4; stage++) {
      {
        const bool tail = stage >= 2;
        int ps = stage & 1, prev = 0;
        uint32_t w = stage & 1;
        const uint64_t dS = make_desc(tail ? sb + OFF_WO + (stage - 2) * 57344 : sb + OFF_X + mh * 8192, 1024, 1024, 1);
        const uint64_t dR = make_desc(sb + OFF_RING + (tail ? mh : nh) * 8192, 1024, 1024, 1);
#pragma unroll 1
        for (int c = 0; c < 7; c++) {
          const int bi = tail ? (ps >> 1) * 4 + 1 + (ps & 1) : 2 * ps + nh;
          mbar_wait(BAR(tail ? B_WO + stage - 2 : B_X + c), 0);
          mbar_wait(BAR(B_FULL + bi), w ^ (tail && ps < 2));
          const uint64_t ds = dS + c * (tail ? 512 : 1024), dr = dR + ps * 1024;
          const uint64_t dA = tail ? dr : ds, dB = tail ? ds : dr;
          wg_fence();
          wgmma_ss_n56_ta0_tb1<1>(acc, dA, dB);
          wgmma_ss_n56_ta0_tb1<1>(acc, dA + 2, dB + 128);
          wgmma_ss_n56_ta0_tb1<1>(acc, dA + 4, dB + 256);
          wgmma_ss_n56_ta0_tb1<1>(acc, dA + 6, dB + 384);
          wg_commit();
          wg_wait<1>();
          if (lane == 0 && c > 0) mbar_arrive(BAR(B_EMPTY + prev), 2);
          prev = bi;
          if (++ps == 6) { ps = 0; w ^= 1; }
        }
        wg_wait<0>();
        fence_regs(acc);
        if (lane == 0) mbar_arrive(BAR(B_EMPTY + prev), 2);
      }
      if (stage == 2) { if (tid == 0) PROF_MARK(15); continue; }
      if (stage == 3) break;
      int lane_;
      asm volatile("mov.u32 %0, %%laneid;" : "=r"(lane_));
      const int lq = lane_ & 3;
      const int rowl = wq * 16 + (lane_ >> 2);
      const int row0 = mh * 64 + rowl;

      if (stage == 0) {
        if (tid == 0) PROF_MARK(2);
        if (tid == 256) PROF_MARK(3);
        float accs[4] = {0.f, 0.f, 0.f, 0.f};
        if (nh == 0) {
          mbar_wait(BAR(B_BUILD), 0);
          const uint64_t dX = make_desc(sb + OFF_X + mh * 8192, 1024, 1024, 1);
          const uint64_t dSlc = make_desc(sb + OFF_SLC, 128, 128, 0);
#pragma unroll 1
          for (int c = 0; c < 7; c++) {
            wg_fence();
            wgmma_ss_n8_ta0_tb1<1>(accs, dX + c * 1024, dSlc + c * 64);
            wgmma_ss_n8_ta0_tb1<1>(accs, dX + c * 1024 + 2, dSlc + c * 64 + 16);
            wgmma_ss_n8_ta0_tb1<1>(accs, dX + c * 1024 + 4, dSlc + c * 64 + 32);
            wgmma_ss_n8_ta0_tb1<1>(accs, dX + c * 1024 + 6, dSlc + c * 64 + 48);
            wg_commit();
          }
        }
        const float qs = nh ? 1.f : 0.18898223650461362f * 1.4426950408889634f;
#pragma unroll
        for (int i = 0; i < 28; i++) acc[i] *= qs;
#pragma unroll
        for (int i = 0; i < 14; i++) keep[i] = pack_bf16(acc[2 * i], acc[2 * i + 1]);
        if (nh == 0) {
          float sq[4] = {0.f, 0.f, 0.f, 0.f};
#pragma unroll
          for (int j = 0; j < 7; j++) {
#pragma unroll
            for (int rr = 0; rr < 2; rr++) {
              const float s2 = acc[4 * j + 2 * rr] * acc[4 * j + 2 * rr] + acc[4 * j + 2 * rr + 1] * acc[4 * j + 2 * rr + 1];
              if (j < 3) sq[rr] += s2;
              else if (j > 3) sq[2 + rr] += s2;
              else { sq[rr] += (lq < 2) ? s2 : 0.f; sq[2 + rr] += (lq < 2) ? 0.f : s2; }
            }
          }
#pragma unroll
          for (int i = 0; i < 4; i++) sq[i] = quad_sum(sq[i]);
          const float mine = lq == 0 ? sq[0] : lq == 1 ? sq[1] : lq == 2 ? sq[2] : sq[3];
          ((float*)(sgen + OFF_QSQ))[(mh + (lq & 2)) * 64 + rowl + 8 * (lq & 1)] = mine <= 3.0e38f ? mine : __int_as_float(0x7f800000);
        }
        wg_wait<0>();
        fence_regs(accs);
        if (nh == 0) {
          const int sl = hp & 3;
          const bool isk = hp < 4, real = (sl < 3) || (lq < 2);
          float mxv = 0.f;
#pragma unroll
          for (int rr = 0; rr < 2; rr++) {
            const int pos = pt * 128 + row0 + 8 * rr, kr = pos & 63;
            const float v0 = accs[2 * rr], v1 = accs[2 * rr + 1];
            const bool poly = isk && ((POLY_PAT >> (kr >> 3)) & 1);
            const float sc = poly ? 2.f : 1.f;
            const float s2 = quad_sum(real ? v0 * v0 + v1 * v1 : 0.f);
            mxv = fmaxf(mxv, s2 <= 3.0e38f ? s2 : __int_as_float(0x7f800000));
            const uint32_t padv = lq == 2 ? (poly ? 0x443F4000u : 0x00003F80u) : (poly ? 0x3AB03F4Du : 0u);
            const uint32_t outv = real ? pack_bf16(sc * v0, sc * v1) : padv;
            if (hp == 3 && lq == 2) g_gate[pos] = rcpf(1.f + ex2f(-1.4426950408889634f * v0));
            *(uint32_t*)(g_kv_img + (pos >> 6) * 8192 + (isk ? 0 : 4096) + sw64_off(kr, sl * 8 + 2 * lq)) = outv;
          }
          mxv = __uint_as_float(__reduce_max_sync(~0u, __float_as_uint(mxv)));
          if (lane == 0) (isk ? g_ksq : g_vsq)[sl * 128 + pt * 8 + mh * 4 + wq] = mxv;
          __syncwarp();
          if (lane == 0) mbar_arrive(BAR(B_SIG + 0), 1);
        }
        if (tid == 0) PROF_MARK(4);
        if (tid == 256) PROF_MARK(5);
#pragma unroll
        for (int i = 0; i < 28; i++) acc[i] = 0.f;
        continue;
      }

      bar_sync(1, 512);
      if (tid == 0) PROF_MARK(6);
#pragma unroll 1
      for (int r = 0; r < 2; r++) {
        store_heads(sb + (r ? (nh ? OFF_VA : OFF_QA) : (nh ? OFF_KA : OFF_QP)), keep, (r & nh) ? 0x00003F80u : 0u, row0, lq);
#pragma unroll
        for (int i = 0; i < 14; i++) keep[i] = pack_bf16(acc[2 * i], acc[2 * i + 1]);
      }
      fence_async_smem();
      if (tid == 0) PROF_MARK(7);

      mbar_wait(BAR(B_B1), 0);
      if (tid == 0) PROF_MARK(9);
      const float* red = (const float*)(sgen + OFF_RED);
      const float ksq = red[0] * (1.02f * 1.02f), vsq = red[1];
      const float* qsq = (const float*)(sgen + OFF_QSQ);
      float b0, b1;
      asm("sqrt.approx.ftz.f32 %0, %1;" : "=f"(b0) : "f"(qsq[wg * 64 + rowl] * ksq));
      asm("sqrt.approx.ftz.f32 %0, %1;" : "=f"(b1) : "f"(qsq[wg * 64 + rowl + 8] * ksq));
      const float4 qa4 = ((const float4*)qsq)[lane_], qb4 = ((const float4*)qsq)[32 + lane_];
      const float qmax = fmaxf(fmaxf(fmaxf(qa4.x, qa4.y), fmaxf(qa4.z, qa4.w)), fmaxf(fmaxf(qb4.x, qb4.y), fmaxf(qb4.z, qb4.w)));
      const bool slow = __any_sync(~0u, !(qmax * ksq <= 92.f * 92.f) || !(vsq <= 1.0e24f));
      if (tid == 0) { *(volatile int*)(sgen + OFF_RED + 8) = slow; mbar_arrive(BAR(B_SLOW), 1); }
      bar_sync(1, 512);

      uint32_t q[8];
      {
        const uint32_t qa = sb + OFF_QP + nh * 8192;
        const int r = mh * 64 + wq * 16 + (lane_ & 7) + ((lane_ >> 3) & 1) * 8;
#pragma unroll
        for (int ks = 0; ks < 2; ks++)
          asm volatile("ldmatrix.sync.aligned.m8n8.x4.shared.b16 {%0, %1, %2, %3}, [%4];"
                       : "=r"(q[4 * ks]), "=r"(q[4 * ks + 1]), "=r"(q[4 * ks + 2]), "=r"(q[4 * ks + 3])
                       : "r"(qa + sw64_off(r, ks * 16 + (lane_ >> 4) * 8)) : "memory");
        if (lq >= 2 && !slow) {
          q[6] = lq == 2 ? pack_bf16(64.f - b0, 1.f) : 0x3F803F80u;
          q[7] = lq == 2 ? pack_bf16(64.f - b1, 1.f) : 0x3F803F80u;
        }
      }

      const uint64_t dK = make_desc(sb + OFF_RING, 512, 512, 2);
      const uint64_t dhi = dK & 0xffffffff00000000ull;
      const uint32_t dlo0 = (uint32_t)dK;
      int slot = 4, prev = 0;
      uint32_t par = 0;
      float m0 = -3.0e38f, m1 = -3.0e38f;
      if (__builtin_expect(slow, 0)) {
#pragma unroll 1
        for (int j64 = 0; j64 < 32; j64++) {
          float s[32];
          if ((j64 & 3) == 0) mbar_wait(BAR(B_FULL + slot), par);
          const uint32_t lo = dlo0 + (slot + (j64 & 3)) * 512;
          wg_fence();
          wgmma_rs_n64_tb0<0>(s, q[0], q[1], q[2], q[3], dhi | lo);
          wgmma_rs_n64_tb0<1>(s, q[4], q[5], q[6], q[7], dhi | (lo + 2));
          wg_commit();
          wg_wait<0>();
          fence_regs(s);
#pragma unroll
          for (int j = 0; j < 8; j++) {
            const float sc = ((POLY_PAT >> j) & 1) ? 0.5f : 1.f;
            m0 = fmaxf(m0, fmaxf(s[4 * j], s[4 * j + 1]) * sc);
            m1 = fmaxf(m1, fmaxf(s[4 * j + 2], s[4 * j + 3]) * sc);
          }
          if ((j64 & 3) == 3) {
            if (lane == 0) mbar_arrive(BAR(B_EMPTY + slot), 1);
            slot += 4;
            if (slot == 12) { slot = 0; par ^= 1; }
          }
        }
        m0 = quad_max(m0); m1 = quad_max(m1);
      }
      float o[16];
#pragma unroll
      for (int i = 0; i < 16; i++) o[i] = 0.f;
      if (tid == 0) PROF_MARK(10);
      const int kb = KB_AT, qb = QB_AT;
      uint32_t ok = 0;
#pragma unroll 1
      for (int it = 0; it <= 8; it++) {
        uint32_t p[16];
        if (it == kb || it == qb || it == 8) {
          float t[16];
          wg_wait<0>();
          fence_regs(o);
          if (it < 8) {
            if (tid == 0) PROF_MARK(it == kb ? 27 : 11);
            const uint64_t dA = make_desc(sb + (it == kb ? OFF_KA : OFF_QA) + nh * 8192 + mh * 4096, 512, 512, 2);
            const uint64_t dB = make_desc(sb + OFF_WPH + nh * 2048, 512, 512, 2);
            float pa[16];
            wg_fence();
            wgmma_ss_n32_ta0_tb1<0>(pa, dA, dB);
            wgmma_ss_n32_ta0_tb1<1>(pa, dA + 2, dB + 64);
            wg_commit();
            wg_wait<0>();
            fence_regs(pa);
            uint32_t ph[16];
            feature_map(pa, ph, lq);
            if (it != kb) mbar_wait(BAR(B_KVR), 0);
            const uint32_t rb = sb + OFF_PHI + wg * 8192 + rowl * 128 + lq * 4 + ((rowl & 7) << 4);
#pragma unroll
            for (int ch = 0; ch < 8; ch++) { sts32(rb ^ (ch << 4), ph[2 * ch]); sts32((rb ^ (ch << 4)) + 1024, ph[2 * ch + 1]); }
            fence_async_smem();
            bar_sync(4 + wg, 128);
            const uint64_t dP = make_desc(sb + OFF_PHI + wg * 8192, 1024, 1024, 1);
            if (it == kb) {
              const uint64_t dV = make_desc(sb + OFF_VA + nh * 8192 + mh * 4096, 512, 512, 2);
              float kv[16];
              wg_fence();
              wgmma_ss_n32_ta1_tb1<0>(kv, dP, dV);
#pragma unroll
              for (int ks = 1; ks < 4; ks++) wgmma_ss_n32_ta1_tb1<1>(kv, dP + ks * 128, dV + ks * 64);
              wg_commit();
              wg_wait<0>();
              fence_regs(kv);
              float* dst = g_kvpart + ((size_t)((2 * hp + nh) * 8 + wq * 2) * 32 + pt * 2 + mh) * 256 + (lane_ >> 2) * 32 + 2 * lq;
#pragma unroll
              for (int j = 0; j < 4; j++) {
                *(float2*)(dst + 8 * j) = make_float2(kv[4 * j], kv[4 * j + 1]);
                *(float2*)(dst + 32 * 256 + 8 * j) = make_float2(kv[4 * j + 2], kv[4 * j + 3]);
              }
              __syncwarp();
              if (lane == 0) { mbar_arrive(BAR(B_X0FREE), 1); mbar_arrive(BAR(B_SIG + 1), 1); }
              if (tid == 0) PROF_MARK(28);
              goto key_group;
            } else {
              const uint64_t dR = make_desc(sb + OFF_KVR + nh * 4096, 512, 512, 2);
              wg_fence();
              wgmma_ss_n32_ta0_tb1<0>(t, dP, dR);
#pragma unroll
              for (int ks = 1; ks < 4; ks++) wgmma_ss_n32_ta0_tb1<1>(t, dP + ks * 2, dR + ks * 64);
              wg_commit();
              wg_wait<0>();
              fence_regs(t);
              if (lane == 0) mbar_arrive(BAR(B_X1FREE), 1);
            }
          } else {
            if (lane == 0) mbar_arrive(BAR(B_EMPTY + prev), 1);
            if (tid == 0) PROF_MARK(13);
#pragma unroll
            for (int i = 0; i < 16; i++) t[i] = o[i];
          }
          {
            const int br = it == 8;
            const float g0 = ((const float*)(sgen + OFF_GATE))[row0], g1 = ((const float*)(sgen + OFF_GATE))[row0 + 8];
            const float eps = br ? 0.f : 1e-6f;
            const float d0 = __shfl_sync(~0u, t[12], (lane_ & ~3) | 2), d1 = __shfl_sync(~0u, t[14], (lane_ & ~3) | 2);
            const float r0 = __fdividef(br ? 1.f - g0 : g0, d0 + eps), r1 = __fdividef(br ? 1.f - g1 : g1, d1 + eps);
            uint8_t* img = g_o_img + (size_t)((br * 16 + pt) * 14 + mh) * 8192 + rowl * 128;
            const int col0 = (2 * hp + nh) * DH + 2 * lq;
#pragma unroll
            for (int j = 0; j < 4; j++) {
              const int col = col0 + 8 * j;
              uint8_t* gp = img + (col >> 6) * 16384 + ((((col >> 3) ^ rowl) & 7) << 4) + (col & 7) * 2;
              const uint32_t v0 = pack_bf16(t[4 * j] * r0, t[4 * j + 1] * r0), v1 = pack_bf16(t[4 * j + 2] * r1, t[4 * j + 3] * r1);
              if (j < 3 || lq < 2) { *(uint32_t*)gp = v0; *(uint32_t*)(gp + 1024) = v1; }
            }
            __syncwarp();
            if (lane == 0) mbar_arrive(BAR(B_SIG + 2 + br), 1);
            if (tid == 0) PROF_MARK(12 + 2 * br);
            if (br) break;
          }
        }
      key_group:
        float s[32];
        const uint32_t lo = dlo0 + slot * 512;
        if (!ok) mbar_wait(BAR(B_FULL + slot), par);
        wg_fence();
        wgmma_rs_n64_tb0<0>(s, q[0], q[1], q[2], q[3], dhi | lo);
        wgmma_rs_n64_tb0<1>(s, q[4], q[5], q[6], q[7], dhi | (lo + 2));
        wg_commit();
        int nslot = slot + 4;
        uint32_t npar = par;
        if (nslot == 12) { nslot = 0; npar ^= 1; }
#pragma unroll
        for (int u = 0; u < 4; u++) {
          wg_wait<0>();
          fence_regs(s);
          if (u == 0 && lane == 0 && it > 0) mbar_arrive(BAR(B_EMPTY + prev), 1);
          if (u == 2) ok = mbar_test(BAR(B_FULL + nslot), npar);
          if (__builtin_expect(!slow, 1)) {
#pragma unroll
            for (int j = 0; j < 8; j++) {
              if ((POLY_PAT >> j) & 1) {
                p[2 * j] = exp2_pair_fma(s[4 * j], s[4 * j + 1], 0x3F003F00u, 0x00030003u);
                p[2 * j + 1] = exp2_pair_fma(s[4 * j + 2], s[4 * j + 3], 0x3F003F00u, 0x00030003u);
              } else {
                p[2 * j] = pack_bf16(ex2f(s[4 * j]), ex2f(s[4 * j + 1]));
                p[2 * j + 1] = pack_bf16(ex2f(s[4 * j + 2]), ex2f(s[4 * j + 3]));
              }
            }
          } else {
#pragma unroll
            for (int j = 0; j < 8; j++) {
              const float sc = ((POLY_PAT >> j) & 1) ? 0.5f : 1.f;
              p[2 * j] = pack_bf16(ex2f(fmaf(s[4 * j], sc, -m0)), ex2f(fmaf(s[4 * j + 1], sc, -m0)));
              p[2 * j + 1] = pack_bf16(ex2f(fmaf(s[4 * j + 2], sc, -m1)), ex2f(fmaf(s[4 * j + 3], sc, -m1)));
            }
          }
          wg_fence();
#pragma unroll
          for (int ks = 0; ks < 4; ks++)
            wgmma_rs_n32_tb1<1>(o, p[4 * ks], p[4 * ks + 1], p[4 * ks + 2], p[4 * ks + 3], dhi | (lo + u * 512 + 256 + ks * 64));
          if (u < 3) {
            wgmma_rs_n64_tb0<0>(s, q[0], q[1], q[2], q[3], dhi | (lo + (u + 1) * 512));
            wgmma_rs_n64_tb0<1>(s, q[4], q[5], q[6], q[7], dhi | (lo + (u + 1) * 512 + 2));
          }
          wg_commit();
        }
        prev = slot; slot = nslot; par = npar;
      }
      wg_wait<0>();
      if (nh == 1) return;
#pragma unroll
      for (int i = 0; i < 14; i++) keep[i] = 0u;
#pragma unroll
      for (int i = 0; i < 28; i++) acc[i] = 0.f;
    }
    if (tid == 0) PROF_MARK(17);
    __nv_bfloat16* op = prm.out + (size_t)(pt * 128 + mh * 64 + wq * 16 + (lane >> 2)) * DM + hp * 56 + 2 * (lane & 3);
#pragma unroll
    for (int j = 0; j < 7; j++) {
      *(uint32_t*)(op + 8 * j) = pack_bf16(acc[4 * j], acc[4 * j + 1]);
      *(uint32_t*)(op + 8 * DM + 8 * j) = pack_bf16(acc[4 * j + 2], acc[4 * j + 3]);
    }
    if (tid == 0) { PROF_MARK(18); PROF_CLK(31); }
    if (tid == 0) {
      unsigned prevd = atomicAdd(&g_cnt[C_DONE * 32], 1u);
      if (prevd == NCTA - 1) {
#pragma unroll 1
        for (int i = 0; i < C_N; i++) g_cnt[i * 32] = 0;
      }
    }
  }
}

typedef CUresult (*EncodeFn)(CUtensorMap*, CUtensorMapDataType, cuuint32_t, void*, const cuuint64_t*, const cuuint64_t*,
                             const cuuint32_t*, const cuuint32_t*, CUtensorMapInterleave, CUtensorMapSwizzle,
                             CUtensorMapL2promotion, CUtensorMapFloatOOBfill);

void make_map(EncodeFn enc, CUtensorMap* tm, const void* ptr, uint64_t cols, uint64_t rows, uint32_t box_rows) {
  cuuint64_t dims[2] = {cols, rows};
  cuuint64_t strides[1] = {cols * 2};
  cuuint32_t box[2] = {64, box_rows};
  cuuint32_t es[2] = {1, 1};
  enc(tm, CU_TENSOR_MAP_DATA_TYPE_BFLOAT16, 2, const_cast<void*>(ptr), dims, strides, box, es, CU_TENSOR_MAP_INTERLEAVE_NONE,
      CU_TENSOR_MAP_SWIZZLE_128B, CU_TENSOR_MAP_L2_PROMOTION_L2_128B, CU_TENSOR_MAP_FLOAT_OOB_FILL_NONE);
}

}

extern "C" void kernel_launch(void* const* d_in, const int* in_sizes, int n_in, void* d_out, int out_size) {
  (void)in_sizes; (void)n_in; (void)out_size;
  static EncodeFn enc = nullptr;
  if (!enc) {
    void* fn = nullptr;
    cudaDriverEntryPointQueryResult qr;
    cudaGetDriverEntryPoint("cuTensorMapEncodeTiled", &fn, cudaEnableDefault, &qr);
    enc = (EncodeFn)fn;
    cudaFuncSetAttribute(fused_kernel, cudaFuncAttributeMaxDynamicSharedMemorySize, SMEM_BYTES);
  }
  CUtensorMap tm_x, tm_wqkv, tm_wq, tm_woa, tm_wob;
  make_map(enc, &tm_x, d_in[0], DM, S_LEN, 128);
  make_map(enc, &tm_wqkv, d_in[1], 3 * DM, DM, 64);
  make_map(enc, &tm_wq, d_in[5], DM, DM, 64);
  make_map(enc, &tm_woa, d_in[3], DM, DM, 64);
  make_map(enc, &tm_wob, d_in[8], DM, DM, 64);
  Params prm;
  prm.w_phi = (const __nv_bfloat16*)d_in[2];
  prm.wk = (const __nv_bfloat16*)d_in[6];
  prm.wv = (const __nv_bfloat16*)d_in[7];
  prm.gate_w = (const __nv_bfloat16*)d_in[9];
  prm.out = (__nv_bfloat16*)d_out;
  fused_kernel<<<NCTA, NTHREADS, SMEM_BYTES>>>(tm_x, tm_wqkv, tm_wq, tm_woa, tm_wob, prm);
}
```

```cpp
#include <cuda_runtime.h>
#include <cuda_bf16.h>
#include <cuda.h>
#include <stdint.h>

namespace {

constexpr int S_LEN = 2048, DM = 448, DH = 28;
constexpr int NCTA = 128;
constexpr int NTHREADS = 640;
constexpr uint32_t POLY_PAT = 0x57;

#define KB_AT (wg >> 1)
#define QB_AT (6 + (wg >> 1))

constexpr int OFF_X = 0;
constexpr int OFF_KA = 0;
constexpr int OFF_VA = 16384;
constexpr int OFF_QP = 32768;
constexpr int OFF_QA = 57344;
constexpr int OFF_KVR = 73728;
constexpr int OFF_PHI = 81920;
constexpr int OFF_WO = 0;
constexpr int OFF_RING = 114688;
constexpr int OFF_WPH = 212992;
constexpr int OFF_SLC = 217088;
constexpr int OFF_QSQ = 224256;
constexpr int OFF_GATE = 225280;
constexpr int OFF_RED = 225792;
constexpr int OFF_BAR = 225856;
constexpr int SMEM_BYTES = 226368 + 1024;

constexpr int B_FULL = 0, B_X = 12, B_EMPTY = 19, B_WO = 31  , B_KVR = 33, B_X0FREE = 34, B_X1FREE = 35, B_B1 = 36,
              B_SLOW = 37, B_BUILD = 38, B_STG = 39, B_SIG = 40  , B_N = 44;

constexpr int C_KV = 0, C_PART = 1, C_RED = 2, C_DONE = 3, C_OA = 4, C_OB = 20, C_N = 36;

__device__ __align__(1024) uint8_t g_kv_img[32 * 8192];
__device__ __align__(16) float g_ksq[512];
__device__ __align__(16) float g_vsq[512];
__device__ __align__(16) float g_gate[S_LEN];
__device__ __align__(1024) float g_kvpart[128 * 32 * 256];
__device__ __align__(1024) uint8_t g_kvr_img[16 * 4096];
__device__ __align__(1024) uint8_t g_o_img[2 * 16 * 14 * 8192];
__device__ unsigned g_cnt[C_N * 32];

#define PROF2(i) do { } while (0)
#define PROF_CLK(i) do { } while (0)
#define PROF_MARK(i) do { } while (0)
__device__ __forceinline__ uint32_t smem_u32(const void* p) { return (uint32_t)__cvta_generic_to_shared(p); }
__device__ __forceinline__ void mbar_init(uint32_t a, int cnt) {
  asm volatile("mbarrier.init.shared::cta.b64 [%0], %1;" ::"r"(a), "r"(cnt) : "memory");
}
__device__ __forceinline__ void mbar_expect_tx(uint32_t a, uint32_t bytes) {
  asm volatile("mbarrier.arrive.expect_tx.shared::cta.b64 _, [%0], %1;" ::"r"(a), "r"(bytes) : "memory");
}
__device__ __forceinline__ void mbar_arrive(uint32_t a, uint32_t cnt) {
  asm volatile("mbarrier.arrive.shared::cta.b64 _, [%0], %1;" ::"r"(a), "r"(cnt) : "memory");
}
__device__ __forceinline__ void mbar_wait(uint32_t a, uint32_t parity) {
  asm volatile(
      "{\n.reg .pred p;\n.reg .u32 c;\nmov.u32 c, 0;\n"
      "W_%=:\nmbarrier.try_wait.parity.shared::cta.b64 p, [%0], %1;\n"
      "add.u32 c, c, 1;\nsetp.lt.and.u32 p, c, 0x1000000, !p;\n@p bra W_%=;\n}"
      ::"r"(a), "r"(parity) : "memory");
}
__device__ __forceinline__ uint32_t mbar_test(uint32_t a, uint32_t parity) {
  uint32_t ok;
  asm volatile("{\n.reg .pred p;\nmbarrier.test_wait.parity.shared::cta.b64 p, [%1], %2;\nselp.u32 %0, 1, 0, p;\n}"
               : "=r"(ok) : "r"(a), "r"(parity) : "memory");
  return ok;
}
__device__ __forceinline__ bool elect_one() {
  uint32_t r;
  asm volatile("{\n.reg .pred p;\nelect.sync _|p, 0xffffffff;\nselp.u32 %0, 1, 0, p;\n}" : "=r"(r));
  return r != 0;
}
__device__ __forceinline__ void tma_2d(uint32_t dst, const CUtensorMap* tm, int c0, int c1, uint32_t bar) {
  asm volatile("cp.async.bulk.tensor.2d.shared::cluster.global.mbarrier::complete_tx::bytes [%0], [%1, {%3, %4}], [%2];"
               ::"r"(dst), "l"(tm), "r"(bar), "r"(c0), "r"(c1) : "memory");
}
__device__ __forceinline__ void bulk_g2s(uint32_t dst, const void* src, uint32_t bytes, uint32_t bar) {
  asm volatile("cp.async.bulk.shared::cluster.global.mbarrier::complete_tx::bytes [%0], [%1], %2, [%3];"
               ::"r"(dst), "l"(src), "r"(bytes), "r"(bar) : "memory");
}
__device__ __forceinline__ void cp_async8(uint32_t dst, const void* src) {
  asm volatile("cp.async.ca.shared.global [%0], [%1], 8;" ::"r"(dst), "l"(src) : "memory");
}
__device__ __forceinline__ void fence_async_smem() { asm volatile("fence.proxy.async.shared::cta;" ::: "memory"); }
__device__ __forceinline__ void fence_async_all() { asm volatile("fence.proxy.async;" ::: "memory"); }
__device__ __forceinline__ void bar_sync(int id, int n) { asm volatile("bar.sync %0, %1;" ::"r"(id), "r"(n) : "memory"); }
__device__ __forceinline__ void cnt_arrive(int idx) {
  asm volatile("red.release.gpu.global.add.u32 [%0], 1;" ::"l"(&g_cnt[idx * 32]) : "memory");
}
__device__ __forceinline__ void cnt_wait(int idx, unsigned target) {
  unsigned v, n = 0;
#pragma unroll 1
  while (true) {
    asm volatile("ld.acquire.gpu.global.u32 %0, [%1];" : "=r"(v) : "l"(&g_cnt[idx * 32]) : "memory");
    if (v >= target || ++n >= (1u << 22)) break;
    __nanosleep(32);
  }
}
__device__ __forceinline__ void wg_fence() { asm volatile("wgmma.fence.sync.aligned;" ::: "memory"); }
__device__ __forceinline__ void wg_commit() { asm volatile("wgmma.commit_group.sync.aligned;" ::: "memory"); }
template <int N> __device__ __forceinline__ void wg_wait() { asm volatile("wgmma.wait_group.sync.aligned %0;" ::"n"(N) : "memory"); }
template <int N> __device__ __forceinline__ void fence_regs(float (&d)[N]) {
#pragma unroll
  for (int i = 0; i < N; i++) asm volatile("" : "+f"(d[i])::"memory");
}
__device__ __forceinline__ uint64_t make_desc(uint32_t saddr, uint32_t lbo, uint32_t sbo, uint32_t swz) {
  return (uint64_t)((saddr & 0x3FFFF) >> 4) | ((uint64_t)(lbo >> 4) << 16) | ((uint64_t)(sbo >> 4) << 32) | ((uint64_t)swz << 62);
}
__device__ __forceinline__ float ex2f(float x) { float y; asm("ex2.approx.ftz.f32 %0, %1;" : "=f"(y) : "f"(x)); return y; }
__device__ __forceinline__ float rcpf(float x) { float y; asm("rcp.approx.ftz.f32 %0, %1;" : "=f"(y) : "f"(x)); return y; }
__device__ __forceinline__ uint32_t pack_bf16(float lo, float hi) {
  uint32_t r; asm("cvt.rn.bf16x2.f32 %0, %1, %2;" : "=r"(r) : "f"(hi), "f"(lo)); return r;
}
__device__ __forceinline__ uint32_t lop_and_or(uint32_t a, uint32_t m, uint32_t c) {
  uint32_t r; asm("lop3.b32 %0, %1, %2, %3, 0xEA;" : "=r"(r) : "r"(a), "r"(m), "r"(c)); return r;
}
__device__ __forceinline__ void sts32(uint32_t a, uint32_t v) { asm volatile("st.shared.b32 [%0], %1;" ::"r"(a), "r"(v) : "memory"); }
__device__ __forceinline__ void sts64(uint32_t a, uint32_t v0, uint32_t v1) { asm volatile("st.shared.v2.b32 [%0], {%1, %2};" ::"r"(a), "r"(v0), "r"(v1) : "memory"); }
__device__ __forceinline__ void sts128(uint32_t a, uint4 v) {
  asm volatile("st.shared.v4.b32 [%0], {%1, %2, %3, %4};" ::"r"(a), "r"(v.x), "r"(v.y), "r"(v.z), "r"(v.w) : "memory");
}
__device__ __forceinline__ float4 ldcg_f4(const float* p) {
  float4 v; asm volatile("ld.global.cg.v4.f32 {%0, %1, %2, %3}, [%4];" : "=f"(v.x), "=f"(v.y), "=f"(v.z), "=f"(v.w) : "l"(p) : "memory"); return v;
}
__device__ __forceinline__ float quad_sum(float v) { v += __shfl_xor_sync(~0u, v, 1); v += __shfl_xor_sync(~0u, v, 2); return v; }
__device__ __forceinline__ float quad_max(float v) { v = fmaxf(v, __shfl_xor_sync(~0u, v, 1)); v = fmaxf(v, __shfl_xor_sync(~0u, v, 2)); return v; }

template <int SD> __device__ __forceinline__ void wgmma_ss_n56_ta0_tb1(float (&d)[28], uint64_t da, uint64_t db) {
  if (SD) asm volatile("wgmma.mma_async.sync.aligned.m64n56k16.f32.bf16.bf16 {%0, %1, %2, %3, %4, %5, %6, %7, %8, %9, %10, %11, %12, %13, %14, %15, %16, %17, %18, %19, %20, %21, %22, %23, %24, %25, %26, %27}, %28, %29, 1, 1, 1, 0, 1;\n"
    : "+f"(d[0]), "+f"(d[1]), "+f"(d[2]), "+f"(d[3]), "+f"(d[4]), "+f"(d[5]), "+f"(d[6]), "+f"(d[7]), "+f"(d[8]), "+f"(d[9]), "+f"(d[10]), "+f"(d[11]), "+f"(d[12]), "+f"(d[13]), "+f"(d[14]), "+f"(d[15]), "+f"(d[16]), "+f"(d[17]), "+f"(d[18]), "+f"(d[19]), "+f"(d[20]), "+f"(d[21]), "+f"(d[22]), "+f"(d[23]), "+f"(d[24]), "+f"(d[25]), "+f"(d[26]), "+f"(d[27])
    : "l"(da), "l"(db));
  else asm volatile("wgmma.mma_async.sync.aligned.m64n56k16.f32.bf16.bf16 {%0, %1, %2, %3, %4, %5, %6, %7, %8, %9, %10, %11, %12, %13, %14, %15, %16, %17, %18, %19, %20, %21, %22, %23, %24, %25, %26, %27}, %28, %29, 0, 1, 1, 0, 1;\n"
    : "=f"(d[0]), "=f"(d[1]), "=f"(d[2]), "=f"(d[3]), "=f"(d[4]), "=f"(d[5]), "=f"(d[6]), "=f"(d[7]), "=f"(d[8]), "=f"(d[9]), "=f"(d[10]), "=f"(d[11]), "=f"(d[12]), "=f"(d[13]), "=f"(d[14]), "=f"(d[15]), "=f"(d[16]), "=f"(d[17]), "=f"(d[18]), "=f"(d[19]), "=f"(d[20]), "=f"(d[21]), "=f"(d[22]), "=f"(d[23]), "=f"(d[24]), "=f"(d[25]), "=f"(d[26]), "=f"(d[27])
    : "l"(da), "l"(db));
}
template <int SD> __device__ __forceinline__ void wgmma_ss_n8_ta0_tb1(float (&d)[4], uint64_t da, uint64_t db) {
  if (SD) asm volatile("wgmma.mma_async.sync.aligned.m64n8k16.f32.bf16.bf16 {%0, %1, %2, %3}, %4, %5, 1, 1, 1, 0, 1;\n"
    : "+f"(d[0]), "+f"(d[1]), "+f"(d[2]), "+f"(d[3])
    : "l"(da), "l"(db));
  else asm volatile("wgmma.mma_async.sync.aligned.m64n8k16.f32.bf16.bf16 {%0, %1, %2, %3}, %4, %5, 0, 1, 1, 0, 1;\n"
    : "=f"(d[0]), "=f"(d[1]), "=f"(d[2]), "=f"(d[3])
    : "l"(da), "l"(db));
}
template <int SD> __device__ __forceinline__ void wgmma_ss_n32_ta1_tb1(float (&d)[16], uint64_t da, uint64_t db) {
  if (SD) asm volatile("wgmma.mma_async.sync.aligned.m64n32k16.f32.bf16.bf16 {%0, %1, %2, %3, %4, %5, %6, %7, %8, %9, %10, %11, %12, %13, %14, %15}, %16, %17, 1, 1, 1, 1, 1;\n"
    : "+f"(d[0]), "+f"(d[1]), "+f"(d[2]), "+f"(d[3]), "+f"(d[4]), "+f"(d[5]), "+f"(d[6]), "+f"(d[7]), "+f"(d[8]), "+f"(d[9]), "+f"(d[10]), "+f"(d[11]), "+f"(d[12]), "+f"(d[13]), "+f"(d[14]), "+f"(d[15])
    : "l"(da), "l"(db));
  else asm volatile("wgmma.mma_async.sync.aligned.m64n32k16.f32.bf16.bf16 {%0, %1, %2, %3, %4, %5, %6, %7, %8, %9, %10, %11, %12, %13, %14, %15}, %16, %17, 0, 1, 1, 1, 1;\n"
    : "=f"(d[0]), "=f"(d[1]), "=f"(d[2]), "=f"(d[3]), "=f"(d[4]), "=f"(d[5]), "=f"(d[6]), "=f"(d[7]), "=f"(d[8]), "=f"(d[9]), "=f"(d[10]), "=f"(d[11]), "=f"(d[12]), "=f"(d[13]), "=f"(d[14]), "=f"(d[15])
    : "l"(da), "l"(db));
}
template <int SD> __device__ __forceinline__ void wgmma_ss_n32_ta0_tb1(float (&d)[16], uint64_t da, uint64_t db) {
  if (SD) asm volatile("wgmma.mma_async.sync.aligned.m64n32k16.f32.bf16.bf16 {%0, %1, %2, %3, %4, %5, %6, %7, %8, %9, %10, %11, %12, %13, %14, %15}, %16, %17, 1, 1, 1, 0, 1;\n"
    : "+f"(d[0]), "+f"(d[1]), "+f"(d[2]), "+f"(d[3]), "+f"(d[4]), "+f"(d[5]), "+f"(d[6]), "+f"(d[7]), "+f"(d[8]), "+f"(d[9]), "+f"(d[10]), "+f"(d[11]), "+f"(d[12]), "+f"(d[13]), "+f"(d[14]), "+f"(d[15])
    : "l"(da), "l"(db));
  else asm volatile("wgmma.mma_async.sync.aligned.m64n32k16.f32.bf16.bf16 {%0, %1, %2, %3, %4, %5, %6, %7, %8, %9, %10, %11, %12, %13, %14, %15}, %16, %17, 0, 1, 1, 0, 1;\n"
    : "=f"(d[0]), "=f"(d[1]), "=f"(d[2]), "=f"(d[3]), "=f"(d[4]), "=f"(d[5]), "=f"(d[6]), "=f"(d[7]), "=f"(d[8]), "=f"(d[9]), "=f"(d[10]), "=f"(d[11]), "=f"(d[12]), "=f"(d[13]), "=f"(d[14]), "=f"(d[15])
    : "l"(da), "l"(db));
}
template <int SD> __device__ __forceinline__ void wgmma_rs_n64_tb0(float (&d)[32], uint32_t a0, uint32_t a1, uint32_t a2, uint32_t a3, uint64_t db) {
  if (SD) asm volatile("wgmma.mma_async.sync.aligned.m64n64k16.f32.bf16.bf16 {%0, %1, %2, %3, %4, %5, %6, %7, %8, %9, %10, %11, %12, %13, %14, %15, %16, %17, %18, %19, %20, %21, %22, %23, %24, %25, %26, %27, %28, %29, %30, %31}, {%32, %33, %34, %35}, %36, 1, 1, 1, 0;\n"
    : "+f"(d[0]), "+f"(d[1]), "+f"(d[2]), "+f"(d[3]), "+f"(d[4]), "+f"(d[5]), "+f"(d[6]), "+f"(d[7]), "+f"(d[8]), "+f"(d[9]), "+f"(d[10]), "+f"(d[11]), "+f"(d[12]), "+f"(d[13]), "+f"(d[14]), "+f"(d[15]), "+f"(d[16]), "+f"(d[17]), "+f"(d[18]), "+f"(d[19]), "+f"(d[20]), "+f"(d[21]), "+f"(d[22]), "+f"(d[23]), "+f"(d[24]), "+f"(d[25]), "+f"(d[26]), "+f"(d[27]), "+f"(d[28]), "+f"(d[29]), "+f"(d[30]), "+f"(d[31])
    : "r"(a0), "r"(a1), "r"(a2), "r"(a3), "l"(db));
  else asm volatile("wgmma.mma_async.sync.aligned.m64n64k16.f32.bf16.bf16 {%0, %1, %2, %3, %4, %5, %6, %7, %8, %9, %10, %11, %12, %13, %14, %15, %16, %17, %18, %19, %20, %21, %22, %23, %24, %25, %26, %27, %28, %29, %30, %31}, {%32, %33, %34, %35}, %36, 0, 1, 1, 0;\n"
    : "=f"(d[0]), "=f"(d[1]), "=f"(d[2]), "=f"(d[3]), "=f"(d[4]), "=f"(d[5]), "=f"(d[6]), "=f"(d[7]), "=f"(d[8]), "=f"(d[9]), "=f"(d[10]), "=f"(d[11]), "=f"(d[12]), "=f"(d[13]), "=f"(d[14]), "=f"(d[15]), "=f"(d[16]), "=f"(d[17]), "=f"(d[18]), "=f"(d[19]), "=f"(d[20]), "=f"(d[21]), "=f"(d[22]), "=f"(d[23]), "=f"(d[24]), "=f"(d[25]), "=f"(d[26]), "=f"(d[27]), "=f"(d[28]), "=f"(d[29]), "=f"(d[30]), "=f"(d[31])
    : "r"(a0), "r"(a1), "r"(a2), "r"(a3), "l"(db));
}
template <int SD> __device__ __forceinline__ void wgmma_rs_n32_tb1(float (&d)[16], uint32_t a0, uint32_t a1, uint32_t a2, uint32_t a3, uint64_t db) {
  if (SD) asm volatile("wgmma.mma_async.sync.aligned.m64n32k16.f32.bf16.bf16 {%0, %1, %2, %3, %4, %5, %6, %7, %8, %9, %10, %11, %12, %13, %14, %15}, {%16, %17, %18, %19}, %20, 1, 1, 1, 1;\n"
    : "+f"(d[0]), "+f"(d[1]), "+f"(d[2]), "+f"(d[3]), "+f"(d[4]), "+f"(d[5]), "+f"(d[6]), "+f"(d[7]), "+f"(d[8]), "+f"(d[9]), "+f"(d[10]), "+f"(d[11]), "+f"(d[12]), "+f"(d[13]), "+f"(d[14]), "+f"(d[15])
    : "r"(a0), "r"(a1), "r"(a2), "r"(a3), "l"(db));
  else asm volatile("wgmma.mma_async.sync.aligned.m64n32k16.f32.bf16.bf16 {%0, %1, %2, %3, %4, %5, %6, %7, %8, %9, %10, %11, %12, %13, %14, %15}, {%16, %17, %18, %19}, %20, 0, 1, 1, 1;\n"
    : "=f"(d[0]), "=f"(d[1]), "=f"(d[2]), "=f"(d[3]), "=f"(d[4]), "=f"(d[5]), "=f"(d[6]), "=f"(d[7]), "=f"(d[8]), "=f"(d[9]), "=f"(d[10]), "=f"(d[11]), "=f"(d[12]), "=f"(d[13]), "=f"(d[14]), "=f"(d[15])
    : "r"(a0), "r"(a1), "r"(a2), "r"(a3), "l"(db));
}

__device__ __forceinline__ uint32_t sw64_off(int row, int d) { return row * 64 + ((((d >> 3) ^ (row >> 1)) & 3) << 4) + (d & 7) * 2; }

__device__ __forceinline__ uint32_t exp2_pair_fma(float t0, float t1, uint32_t c_half, uint32_t c_3) {
  uint32_t y0, y;
  asm("prmt.b32 %0, %1, %2, 0x6521;" : "=r"(y0) : "r"(__float_as_uint(t0)), "r"(__float_as_uint(t1)));
  uint32_t h = lop_and_or(y0, 0x007F007Fu, c_half);
  uint32_t e = lop_and_or(y0, 0xFF80FF80u, c_3);
  asm("fma.rn.bf16x2 %0, %1, %2, %3;" : "=r"(y) : "r"(y0), "r"(h), "r"(e));
  return y;
}

__device__ __forceinline__ void feature_map(float (&v)[16], uint32_t (&ph)[16], int lq) {
  const float L2E = 1.4426950408889634f;
  const bool tail_ok = lq < 2;
  float mx[2], mn[2], b[16], sa[2], sn[2];
#pragma unroll
  for (int r = 0; r < 2; r++) {
    const int o = 2 * r;
    if (!tail_ok) { v[o + 12] = v[o]; v[o + 13] = v[o]; }
    mx[r] = fmaxf(fmaxf(fmaxf(v[o], v[o + 1]), fmaxf(v[o + 4], v[o + 5])), fmaxf(fmaxf(v[o + 8], v[o + 9]), fmaxf(v[o + 12], v[o + 13])));
    mn[r] = fminf(fminf(fminf(v[o], v[o + 1]), fminf(v[o + 4], v[o + 5])), fminf(fminf(v[o + 8], v[o + 9]), fminf(v[o + 12], v[o + 13])));
  }
#pragma unroll
  for (int o = 1; o <= 2; o <<= 1)
#pragma unroll
    for (int r = 0; r < 2; r++) { mx[r] = fmaxf(mx[r], __shfl_xor_sync(~0u, mx[r], o)); mn[r] = fminf(mn[r], __shfl_xor_sync(~0u, mn[r], o)); }
#pragma unroll
  for (int r = 0; r < 2; r++) {
    const int o = 2 * r;
    const float cx = -mx[r] * L2E, cn = mn[r] * L2E;
#pragma unroll
    for (int i = 0; i < 8; i++) {
      const int k = o + 4 * (i >> 1) + (i & 1);
      b[k] = ex2f(fmaf(v[k], -L2E, cn));
      v[k] = ex2f(fmaf(v[k], L2E, cx));
    }
    if (!tail_ok) { v[o + 12] = v[o + 13] = b[o + 12] = b[o + 13] = 0.f; }
    sa[r] = ((v[o] + v[o + 1]) + (v[o + 4] + v[o + 5])) + ((v[o + 8] + v[o + 9]) + (v[o + 12] + v[o + 13]));
    sn[r] = ((b[o] + b[o + 1]) + (b[o + 4] + b[o + 5])) + ((b[o + 8] + b[o + 9]) + (b[o + 12] + b[o + 13]));
  }
#pragma unroll
  for (int o = 1; o <= 2; o <<= 1)
#pragma unroll
    for (int r = 0; r < 2; r++) { sa[r] += __shfl_xor_sync(~0u, sa[r], o); sn[r] += __shfl_xor_sync(~0u, sn[r], o); }
#pragma unroll
  for (int r = 0; r < 2; r++) {
    const float ra = rcpf(sa[r]), rb = rcpf(sn[r]);
#pragma unroll
    for (int jj = 0; jj < 4; jj++) {
      ph[jj * 2 + r] = pack_bf16(v[2 * r + 4 * jj] * ra, v[2 * r + 4 * jj + 1] * ra);
      ph[(4 + jj) * 2 + r] = pack_bf16(b[2 * r + 4 * jj] * rb, b[2 * r + 4 * jj + 1] * rb);
    }
  }
}

__device__ __forceinline__ void store_heads(uint32_t base, const uint32_t (&a)[14], uint32_t pad, int row0, int lq) {
  const uint32_t rb = base + row0 * 64 + (((row0 >> 1) & 3) << 4);
  const uint32_t b0 = rb + lq * 4;
  const uint32_t b1 = (rb + 8192 + ((lq * 4 + 8) & 15)) ^ ((lq >> 1) << 4);
#pragma unroll
  for (int j = 0; j < 7; j++) {
    uint32_t ad;
    if (j < 3) ad = b0 ^ (j << 4);
    else if (j == 3) ad = (lq < 2) ? (b0 ^ 48u) : (b1 ^ 16u);
    else ad = (lq < 2) ? (b1 ^ ((j - 4) << 4)) : ((b1 ^ 16u) ^ ((j - 3) << 4));
    sts32(ad, a[2 * j]);
    sts32(ad + 512, a[2 * j + 1]);
  }
  sts64((rb ^ 48u) + 8 + (lq & 1) * 8192 + (lq >> 1) * 512, pad, 0u);
}

struct Params {
  const __nv_bfloat16* w_phi;
  const __nv_bfloat16* wk;
  const __nv_bfloat16* wv;
  const __nv_bfloat16* gate_w;
  __nv_bfloat16* out;
};

__global__ void __launch_bounds__(NTHREADS, 1)
fused_kernel(const __grid_constant__ CUtensorMap tm_x, const __grid_constant__ CUtensorMap tm_wqkv,
             const __grid_constant__ CUtensorMap tm_wq, const __grid_constant__ CUtensorMap tm_woa,
             const __grid_constant__ CUtensorMap tm_wob, const Params prm) {
  extern __shared__ uint8_t smem_raw[];
  uint32_t sb = (smem_u32(smem_raw) + 1023u) & ~1023u;
  uint8_t* sgen = smem_raw + (sb - smem_u32(smem_raw));
  asm volatile("mov.u32 %0, %0;" : "+r"(sb));
  const int tid = threadIdx.x, lane = tid & 31;
  const int warp = __shfl_sync(~0u, tid >> 5, 0), wg = warp >> 2;
  const int pt = blockIdx.x >> 3, hp = blockIdx.x & 7;
  const uint32_t bars = sb + OFF_BAR;
  auto BAR = [&](int i) { return bars + 8u * i; };

  if (tid == 0) { PROF_MARK(0); PROF_CLK(30); PROF2(15); }
  if (elect_one()) {
    if (warp == 16) {
      mbar_init(BAR(B_X), 1); mbar_init(BAR(B_FULL), 1); mbar_init(BAR(B_FULL + 1), 1);
      fence_async_smem();
      mbar_expect_tx(BAR(B_X), 16384);
      tma_2d(sb + OFF_X, &tm_x, 0, pt * 128, BAR(B_X));
      mbar_expect_tx(BAR(B_FULL), 8192);
      tma_2d(sb + OFF_RING, &tm_wq, hp * 56, 0, BAR(B_FULL));
      mbar_expect_tx(BAR(B_FULL + 1), 8192);
      tma_2d(sb + OFF_RING + 8192, &tm_wqkv, DM + hp * 56, 0, BAR(B_FULL + 1));
    } else {
#pragma unroll 1
      for (int i = 2 + warp - (warp > 16); i < B_N; i += 19) {
        int cnt = (i >= B_EMPTY && i < B_WO) || i > B_SIG || i == B_X0FREE || i == B_X1FREE ? 16 : 1;
        if (i == B_BUILD) cnt = 3;
        if (i == B_SIG) cnt = 8;
        if (i != B_X) mbar_init(BAR(i), cnt);
      }
      fence_async_smem();
    }
  }
  __syncthreads();
  if (tid == 0) PROF2(14);

  if (wg == 4) {
    asm volatile("setmaxnreg.dec.sync.aligned.u32 32;");
    if (warp == 16) {
      if (elect_one()) {
#pragma unroll 1
        for (int i = 1; i < 14; i++) {
          const int c = i < 7 ? i : i - 7, ps = i % 6;
          if (i < 7) {
            mbar_expect_tx(BAR(B_X + c), 16384);
            tma_2d(sb + OFF_X + c * 16384, &tm_x, c * 64, pt * 128, BAR(B_X + c));
          }
#pragma unroll 1
          for (int h = 0; h < 2; h++) {
            const int sl = 2 * ps + h;
            if (i >= 6) mbar_wait(BAR(B_EMPTY + sl), (i / 6 - 1) & 1);
            mbar_expect_tx(BAR(B_FULL + sl), 8192);
            tma_2d(sb + OFF_RING + sl * 8192, (i < 7 && !h) ? &tm_wq : &tm_wqkv, hp * 56 + (h ? (i < 7 ? DM : 2 * DM) : 0), c * 64,
                   BAR(B_FULL + sl));
          }
        }
        PROF_MARK(20);
        cnt_wait(C_KV, NCTA);
        PROF_MARK(21);
        fence_async_all();
        int slot = 4, ng = 8;
        uint32_t par = 1;
#pragma unroll 1
        for (int n = 0; n < ng; n++) {
          mbar_wait(BAR(B_EMPTY + slot), par);
          if (n < 3) { mbar_wait(BAR(B_EMPTY + slot + 1), par); mbar_wait(BAR(B_EMPTY + slot + 2), par); mbar_wait(BAR(B_EMPTY + slot + 3), par); }
          mbar_expect_tx(BAR(B_FULL + slot), 32768);
          bulk_g2s(sb + OFF_RING + slot * 8192, g_kv_img + (n & 7) * 32768, 32768, BAR(B_FULL + slot));
          slot += 4;
          if (slot == 12) { slot = 0; par ^= 1; }
          if (n == 7) {
            mbar_wait(BAR(B_SLOW), 0);
            if (*(volatile int*)(sgen + OFF_RED + 8)) ng = 16;
          }
        }
#pragma unroll 1
        for (int i = 0; i < 14; i++) {
          const int ps = i % 6, g4 = (ps >> 1) * 4, bi = g4 + 1 + (ps & 1);
          if (i == 0 || i == 7) {
            cnt_wait((i ? C_OB : C_OA) + pt, 8);
            PROF_MARK(26);
            fence_async_all();
          }
          if (i < 6) mbar_wait(BAR(B_EMPTY + g4), g4 >= slot ? par : par ^ 1);
          else mbar_wait(BAR(B_EMPTY + bi), (ps < 2) ^ ((i / 6 - 1) & 1));
          mbar_expect_tx(BAR(B_FULL + bi), 16384);
          bulk_g2s(sb + OFF_RING + ps * 16384, g_o_img + (size_t)(pt * 14 + (i < 7 ? 2 * i : 2 * i + 210)) * 8192, 16384, BAR(B_FULL + bi));
        }
      }
    } else {
      {
        const int t = tid - 544;
#pragma unroll 1
        for (int i = t; i < 256; i += 96) sts128(sb + OFF_WPH + i * 16, make_uint4(0, 0, 0, 0));
        bar_sync(2, 96);
#pragma unroll 1
        for (int k = t; k < DM; k += 96) {
          const __nv_bfloat16* src = (hp < 4 ? prm.wk : prm.wv) + k * DH + (hp & 3) * 8;
          cp_async8(sb + OFF_SLC + k * 16, src);
          if ((hp & 3) != 3) cp_async8(sb + OFF_SLC + k * 16 + 8, src + 4);
          else sts64(sb + OFF_SLC + k * 16 + 8, hp == 3 ? (uint32_t)((const unsigned short*)prm.gate_w)[k] : 0u, 0u);
          if (k < 392) {
            const int row = k / 7, e = row >= DH;
            cp_async8(sb + OFF_WPH + e * 2048 + sw64_off(row - DH * e, (k % 7) * 4), prm.w_phi + 2 * hp * DH * DH + k * 4);
          }
        }
        asm volatile("cp.async.wait_all;" ::: "memory");
        fence_async_smem();
        __syncwarp();
        if (lane == 0) mbar_arrive(BAR(B_BUILD), 1);
      }
      if (warp == 18) {
        if (lane == 0) {
#pragma unroll 1
          for (int i = 0; i < 4; i++) {
            mbar_wait(BAR(B_SIG + i), 0);
            cnt_arrive(i == 0 ? C_KV : i == 1 ? C_PART : (i == 2 ? C_OA : C_OB) + pt);
          }
        }
      } else if (warp == 19) {
        if (lane == 0) {
          mbar_wait(BAR(B_SIG + 0), 0);
          cnt_wait(C_KV, NCTA);
        }
        __syncwarp();
        float ksq = 0.f, vsq = 0.f;
#pragma unroll
        for (int sl = 0; sl < 4; sl++) {
          float4 a = ldcg_f4(g_ksq + sl * 128 + lane * 4), b = ldcg_f4(g_vsq + sl * 128 + lane * 4);
          float m = fmaxf(fmaxf(a.x, a.y), fmaxf(a.z, a.w));
          m = __uint_as_float(__reduce_max_sync(~0u, __float_as_uint(m)));
          ksq += m;
          vsq = fmaxf(vsq, fmaxf(fmaxf(b.x, b.y), fmaxf(b.z, b.w)));
        }
        vsq = __uint_as_float(__reduce_max_sync(~0u, __float_as_uint(vsq)));
        if (lane == 0) {
          float* red = (float*)(sgen + OFF_RED);
          red[0] = ksq; red[1] = vsq;
          mbar_arrive(BAR(B_B1), 1);
        }
      } else {
        if (elect_one()) {
          mbar_wait(BAR(B_X0FREE), 0);
          mbar_expect_tx(BAR(B_WO), 57344);
#pragma unroll 1
          for (int c = 0; c < 7; c++) tma_2d(sb + OFF_WO + c * 8192, &tm_woa, hp * 56, c * 64, BAR(B_WO));
          PROF_MARK(22);
          cnt_wait(C_PART, NCTA);
          PROF_MARK(23);
          fence_async_all();
          mbar_expect_tx(BAR(B_STG), 32768);
          bulk_g2s(sb + OFF_PHI, g_kvpart + (size_t)blockIdx.x * 8192, 32768, BAR(B_STG));
        }
        __syncwarp();
        mbar_wait(BAR(B_STG), 0);
        {
          const float4* src = (const float4*)(sgen + OFF_PHI) + lane * 2;
          float4 s0 = make_float4(0, 0, 0, 0), s1 = s0;
#pragma unroll 2
          for (int t = 0; t < 32; t++) {
            float4 a = src[t * 64], b = src[t * 64 + 1];
            s0.x += a.x; s0.y += a.y; s0.z += a.z; s0.w += a.w; s1.x += b.x; s1.y += b.y; s1.z += b.z; s1.w += b.w;
          }
          uint4 v = make_uint4(pack_bf16(s0.x, s0.y), pack_bf16(s0.z, s0.w), pack_bf16(s1.x, s1.y), pack_bf16(s1.z, s1.w));
          *(uint4*)(g_kvr_img + (blockIdx.x >> 3) * 4096 + sw64_off((blockIdx.x & 7) * 8 + (lane >> 2), (lane & 3) * 8)) = v;
        }
        __syncwarp();
        if (elect_one()) {
          cnt_arrive(C_RED);
          PROF_MARK(24);
          cnt_wait(C_RED, NCTA);
          PROF_MARK(25);
          fence_async_all();
          mbar_expect_tx(BAR(B_KVR), 8192 + 512);
          bulk_g2s(sb + OFF_KVR, g_kvr_img + hp * 8192, 8192, BAR(B_KVR));
          bulk_g2s(sb + OFF_GATE, g_gate + pt * 128, 512, BAR(B_KVR));
          mbar_wait(BAR(B_X1FREE), 0);
          mbar_expect_tx(BAR(B_WO + 1), 57344);
#pragma unroll 1
          for (int c = 0; c < 7; c++) tma_2d(sb + OFF_WO + 57344 + c * 8192, &tm_wob, hp * 56, c * 64, BAR(B_WO + 1));
        }
      }
    }
  } else {
    asm volatile("setmaxnreg.inc.sync.aligned.u32 112;");
    const int mh = wg & 1, nh = wg >> 1, wq = warp & 3;
    float acc[28];
    uint32_t keep[14];
#pragma unroll
    for (int i = 0; i < 28; i++) acc[i] = 0.f;

#pragma unroll 1
    for (int stage = 0; stage < 4; stage++) {
      {
        const bool tail = stage >= 2;
        int ps = stage & 1, prev = 0;
        uint32_t w = stage & 1;
        const uint64_t dS = make_desc(tail ? sb + OFF_WO + (stage - 2) * 57344 : sb + OFF_X + mh * 8192, 1024, 1024, 1);
        const uint64_t dR = make_desc(sb + OFF_RING + (tail ? mh : nh) * 8192, 1024, 1024, 1);
#pragma unroll 1
        for (int c = 0; c < 7; c++) {
          const int bi = tail ? (ps >> 1) * 4 + 1 + (ps & 1) : 2 * ps + nh;
          mbar_wait(BAR(tail ? B_WO + stage - 2 : B_X + c), 0);
          if (tid == 0) PROF2(stage * 16 + c * 2);
          mbar_wait(BAR(B_FULL + bi), w ^ (tail && ps < 2));
          if (tid == 0) PROF2(stage * 16 + c * 2 + 1);
          const uint64_t ds = dS + c * (tail ? 512 : 1024), dr = dR + ps * 1024;
          const uint64_t dA = tail ? dr : ds, dB = tail ? ds : dr;
          wg_fence();
          wgmma_ss_n56_ta0_tb1<1>(acc, dA, dB);
          wgmma_ss_n56_ta0_tb1<1>(acc, dA + 2, dB + 128);
          wgmma_ss_n56_ta0_tb1<1>(acc, dA + 4, dB + 256);
          wgmma_ss_n56_ta0_tb1<1>(acc, dA + 6, dB + 384);
          wg_commit();
          if (stage != 3) {
            wg_wait<1>();
            if (lane == 0 && c > 0) mbar_arrive(BAR(B_EMPTY + prev), 2);
          } else if (c == 1) {
            wg_wait<1>();
            if (lane == 0) mbar_arrive(BAR(B_EMPTY + prev), 2);
          }
          prev = bi;
          if (++ps == 6) { ps = 0; w ^= 1; }
        }
        wg_wait<0>();
        fence_regs(acc);
        if (lane == 0) mbar_arrive(BAR(B_EMPTY + prev), 2);
      }
      if (stage == 2) { if (tid == 0) PROF_MARK(15); continue; }
      if (stage == 3) break;
      int lane_;
      asm volatile("mov.u32 %0, %%laneid;" : "=r"(lane_));
      const int lq = lane_ & 3;
      const int rowl = wq * 16 + (lane_ >> 2);
      const int row0 = mh * 64 + rowl;

      if (stage == 0) {
        if (tid == 0) PROF_MARK(2);
        if (tid == 256) PROF_MARK(3);
        float accs[4] = {0.f, 0.f, 0.f, 0.f};
        if (nh == 1) {
          mbar_wait(BAR(B_BUILD), 0);
          const uint64_t dX = make_desc(sb + OFF_X + mh * 8192, 1024, 1024, 1);
          const uint64_t dSlc = make_desc(sb + OFF_SLC, 128, 128, 0);
#pragma unroll 1
          for (int c = 0; c < 7; c++) {
            wg_fence();
            wgmma_ss_n8_ta0_tb1<1>(accs, dX + c * 1024, dSlc + c * 64);
            wgmma_ss_n8_ta0_tb1<1>(accs, dX + c * 1024 + 2, dSlc + c * 64 + 16);
            wgmma_ss_n8_ta0_tb1<1>(accs, dX + c * 1024 + 4, dSlc + c * 64 + 32);
            wgmma_ss_n8_ta0_tb1<1>(accs, dX + c * 1024 + 6, dSlc + c * 64 + 48);
            wg_commit();
          }
        }
        const float qs = nh ? 1.f : 0.18898223650461362f * 1.4426950408889634f;
#pragma unroll
        for (int i = 0; i < 28; i++) acc[i] *= qs;
#pragma unroll
        for (int i = 0; i < 14; i++) keep[i] = pack_bf16(acc[2 * i], acc[2 * i + 1]);
        if (nh == 0) {
          float sq[4] = {0.f, 0.f, 0.f, 0.f};
#pragma unroll
          for (int j = 0; j < 7; j++) {
#pragma unroll
            for (int rr = 0; rr < 2; rr++) {
              const float s2 = acc[4 * j + 2 * rr] * acc[4 * j + 2 * rr] + acc[4 * j + 2 * rr + 1] * acc[4 * j + 2 * rr + 1];
              if (j < 3) sq[rr] += s2;
              else if (j > 3) sq[2 + rr] += s2;
              else { sq[rr] += (lq < 2) ? s2 : 0.f; sq[2 + rr] += (lq < 2) ? 0.f : s2; }
            }
          }
#pragma unroll
          for (int i = 0; i < 4; i++) sq[i] = quad_sum(sq[i]);
          const float mine = lq == 0 ? sq[0] : lq == 1 ? sq[1] : lq == 2 ? sq[2] : sq[3];
          ((float*)(sgen + OFF_QSQ))[(mh + (lq & 2)) * 64 + rowl + 8 * (lq & 1)] = mine <= 3.0e38f ? mine : __int_as_float(0x7f800000);
        }
        wg_wait<0>();
        fence_regs(accs);
        if (nh == 1) {
          const int sl = hp & 3;
          const bool isk = hp < 4, real = (sl < 3) || (lq < 2);
          float mxv = 0.f;
#pragma unroll
          for (int rr = 0; rr < 2; rr++) {
            const int pos = pt * 128 + row0 + 8 * rr, kr = pos & 63;
            const float v0 = accs[2 * rr], v1 = accs[2 * rr + 1];
            const bool poly = isk && ((POLY_PAT >> (kr >> 3)) & 1);
            const float sc = poly ? 2.f : 1.f;
            const float s2 = quad_sum(real ? v0 * v0 + v1 * v1 : 0.f);
            mxv = fmaxf(mxv, s2 <= 3.0e38f ? s2 : __int_as_float(0x7f800000));
            const uint32_t padv = lq == 2 ? (poly ? 0x443F4000u : 0x00003F80u) : (poly ? 0x3AB03F4Du : 0u);
            const uint32_t outv = real ? pack_bf16(sc * v0, sc * v1) : padv;
            if (hp == 3 && lq == 2) g_gate[pos] = rcpf(1.f + ex2f(-1.4426950408889634f * v0));
            *(uint32_t*)(g_kv_img + (pos >> 6) * 8192 + (isk ? 0 : 4096) + sw64_off(kr, sl * 8 + 2 * lq)) = outv;
          }
          mxv = __uint_as_float(__reduce_max_sync(~0u, __float_as_uint(mxv)));
          if (lane == 0) (isk ? g_ksq : g_vsq)[sl * 128 + pt * 8 + mh * 4 + wq] = mxv;
          __syncwarp();
          if (lane == 0) mbar_arrive(BAR(B_SIG + 0), 1);
        }
        if (tid == 0) PROF_MARK(4);
        if (tid == 256) PROF_MARK(5);
#pragma unroll
        for (int i = 0; i < 28; i++) acc[i] = 0.f;
        continue;
      }

      bar_sync(1, 512);
      if (tid == 0) PROF_MARK(6);
#pragma unroll 1
      for (int r = 0; r < 2; r++) {
        store_heads(sb + (r ? (nh ? OFF_VA : OFF_QA) : (nh ? OFF_KA : OFF_QP)), keep, (r & nh) ? 0x00003F80u : 0u, row0, lq);
#pragma unroll
        for (int i = 0; i < 14; i++) keep[i] = pack_bf16(acc[2 * i], acc[2 * i + 1]);
      }
      fence_async_smem();
      if (tid == 0) PROF_MARK(7);

      mbar_wait(BAR(B_B1), 0);
      if (tid == 0) PROF_MARK(9);
      const float* red = (const float*)(sgen + OFF_RED);
      const float ksq = red[0] * (1.02f * 1.02f), vsq = red[1];
      const float* qsq = (const float*)(sgen + OFF_QSQ);
      float b0, b1;
      asm("sqrt.approx.ftz.f32 %0, %1;" : "=f"(b0) : "f"(qsq[wg * 64 + rowl] * ksq));
      asm("sqrt.approx.ftz.f32 %0, %1;" : "=f"(b1) : "f"(qsq[wg * 64 + rowl + 8] * ksq));
      const float4 qa4 = ((const float4*)qsq)[lane_], qb4 = ((const float4*)qsq)[32 + lane_];
      const float qmax = fmaxf(fmaxf(fmaxf(qa4.x, qa4.y), fmaxf(qa4.z, qa4.w)), fmaxf(fmaxf(qb4.x, qb4.y), fmaxf(qb4.z, qb4.w)));
      const bool slow = __any_sync(~0u, !(qmax * ksq <= 92.f * 92.f) || !(vsq <= 1.0e24f));
      if (tid == 0) { *(volatile int*)(sgen + OFF_RED + 8) = slow; mbar_arrive(BAR(B_SLOW), 1); }
      bar_sync(1, 512);

      uint32_t q[8];
      {
        const uint32_t qa = sb + OFF_QP + nh * 8192;
        const int r = mh * 64 + wq * 16 + (lane_ & 7) + ((lane_ >> 3) & 1) * 8;
#pragma unroll
        for (int ks = 0; ks < 2; ks++)
          asm volatile("ldmatrix.sync.aligned.m8n8.x4.shared.b16 {%0, %1, %2, %3}, [%4];"
                       : "=r"(q[4 * ks]), "=r"(q[4 * ks + 1]), "=r"(q[4 * ks + 2]), "=r"(q[4 * ks + 3])
                       : "r"(qa + sw64_off(r, ks * 16 + (lane_ >> 4) * 8)) : "memory");
        if (lq >= 2 && !slow) {
          q[6] = lq == 2 ? pack_bf16(64.f - b0, 1.f) : 0x3F803F80u;
          q[7] = lq == 2 ? pack_bf16(64.f - b1, 1.f) : 0x3F803F80u;
        }
      }

      const uint64_t dK = make_desc(sb + OFF_RING, 512, 512, 2);
      const uint64_t dhi = dK & 0xffffffff00000000ull;
      const uint32_t dlo0 = (uint32_t)dK;
      int slot = 4, prev = 0;
      uint32_t par = 0;
      float m0 = -3.0e38f, m1 = -3.0e38f;
      if (__builtin_expect(slow, 0)) {
#pragma unroll 1
        for (int j64 = 0; j64 < 32; j64++) {
          float s[32];
          if ((j64 & 3) == 0) mbar_wait(BAR(B_FULL + slot), par);
          const uint32_t lo = dlo0 + (slot + (j64 & 3)) * 512;
          wg_fence();
          wgmma_rs_n64_tb0<0>(s, q[0], q[1], q[2], q[3], dhi | lo);
          wgmma_rs_n64_tb0<1>(s, q[4], q[5], q[6], q[7], dhi | (lo + 2));
          wg_commit();
          wg_wait<0>();
          fence_regs(s);
#pragma unroll
          for (int j = 0; j < 8; j++) {
            const float sc = ((POLY_PAT >> j) & 1) ? 0.5f : 1.f;
            m0 = fmaxf(m0, fmaxf(s[4 * j], s[4 * j + 1]) * sc);
            m1 = fmaxf(m1, fmaxf(s[4 * j + 2], s[4 * j + 3]) * sc);
          }
          if ((j64 & 3) == 3) {
            if (lane == 0) mbar_arrive(BAR(B_EMPTY + slot), 1);
            slot += 4;
            if (slot == 12) { slot = 0; par ^= 1; }
          }
        }
        m0 = quad_max(m0); m1 = quad_max(m1);
      }
      float o[16];
#pragma unroll
      for (int i = 0; i < 16; i++) o[i] = 0.f;
      if (tid == 0) PROF_MARK(10);
      const int kb = KB_AT, qb = QB_AT;
      uint32_t ok = 0;
#pragma unroll 1
      for (int it = 0; it <= 8; it++) {
        uint32_t p[16];
        if (it == kb || it == qb || it == 8) {
          float t[16];
          wg_wait<0>();
          fence_regs(o);
          if (it < 8) {
            if (tid == 0) PROF_MARK(it == kb ? 27 : 11);
            const uint64_t dA = make_desc(sb + (it == kb ? OFF_KA : OFF_QA) + nh * 8192 + mh * 4096, 512, 512, 2);
            const uint64_t dB = make_desc(sb + OFF_WPH + nh * 2048, 512, 512, 2);
            float pa[16];
            wg_fence();
            wgmma_ss_n32_ta0_tb1<0>(pa, dA, dB);
            wgmma_ss_n32_ta0_tb1<1>(pa, dA + 2, dB + 64);
            wg_commit();
            wg_wait<0>();
            fence_regs(pa);
            uint32_t ph[16];
            feature_map(pa, ph, lq);
            if (it != kb) mbar_wait(BAR(B_KVR), 0);
            const uint32_t rb = sb + OFF_PHI + wg * 8192 + rowl * 128 + lq * 4 + ((rowl & 7) << 4);
#pragma unroll
            for (int ch = 0; ch < 8; ch++) { sts32(rb ^ (ch << 4), ph[2 * ch]); sts32((rb ^ (ch << 4)) + 1024, ph[2 * ch + 1]); }
            fence_async_smem();
            bar_sync(4 + wg, 128);
            const uint64_t dP = make_desc(sb + OFF_PHI + wg * 8192, 1024, 1024, 1);
            if (it == kb) {
              const uint64_t dV = make_desc(sb + OFF_VA + nh * 8192 + mh * 4096, 512, 512, 2);
              float kv[16];
              wg_fence();
              wgmma_ss_n32_ta1_tb1<0>(kv, dP, dV);
#pragma unroll
              for (int ks = 1; ks < 4; ks++) wgmma_ss_n32_ta1_tb1<1>(kv, dP + ks * 128, dV + ks * 64);
              wg_commit();
              wg_wait<0>();
              fence_regs(kv);
              float* dst = g_kvpart + ((size_t)((2 * hp + nh) * 8 + wq * 2) * 32 + pt * 2 + mh) * 256 + (lane_ >> 2) * 32 + 2 * lq;
#pragma unroll
              for (int j = 0; j < 4; j++) {
                *(float2*)(dst + 8 * j) = make_float2(kv[4 * j], kv[4 * j + 1]);
                *(float2*)(dst + 32 * 256 + 8 * j) = make_float2(kv[4 * j + 2], kv[4 * j + 3]);
              }
              __syncwarp();
              if (lane == 0) { mbar_arrive(BAR(B_X0FREE), 1); mbar_arrive(BAR(B_SIG + 1), 1); }
              if (tid == 0) PROF_MARK(28);
              goto key_group;
            } else {
              const uint64_t dR = make_desc(sb + OFF_KVR + nh * 4096, 512, 512, 2);
              wg_fence();
              wgmma_ss_n32_ta0_tb1<0>(t, dP, dR);
#pragma unroll
              for (int ks = 1; ks < 4; ks++) wgmma_ss_n32_ta0_tb1<1>(t, dP + ks * 2, dR + ks * 64);
              wg_commit();
              wg_wait<0>();
              fence_regs(t);
              if (lane == 0) mbar_arrive(BAR(B_X1FREE), 1);
            }
          } else {
            if (lane == 0) mbar_arrive(BAR(B_EMPTY + prev), 1);
            if (tid == 0) PROF_MARK(13);
#pragma unroll
            for (int i = 0; i < 16; i++) t[i] = o[i];
          }
          {
            const int br = it == 8;
            const float g0 = ((const float*)(sgen + OFF_GATE))[row0], g1 = ((const float*)(sgen + OFF_GATE))[row0 + 8];
            const float eps = br ? 0.f : 1e-6f;
            const float d0 = __shfl_sync(~0u, t[12], (lane_ & ~3) | 2), d1 = __shfl_sync(~0u, t[14], (lane_ & ~3) | 2);
            const float r0 = __fdividef(br ? 1.f - g0 : g0, d0 + eps), r1 = __fdividef(br ? 1.f - g1 : g1, d1 + eps);
            uint8_t* img = g_o_img + (size_t)((br * 16 + pt) * 14 + mh) * 8192 + rowl * 128;
            const int col0 = (2 * hp + nh) * DH + 2 * lq;
#pragma unroll
            for (int j = 0; j < 4; j++) {
              const int col = col0 + 8 * j;
              uint8_t* gp = img + (col >> 6) * 16384 + ((((col >> 3) ^ rowl) & 7) << 4) + (col & 7) * 2;
              const uint32_t v0 = pack_bf16(t[4 * j] * r0, t[4 * j + 1] * r0), v1 = pack_bf16(t[4 * j + 2] * r1, t[4 * j + 3] * r1);
              if (j < 3 || lq < 2) { *(uint32_t*)gp = v0; *(uint32_t*)(gp + 1024) = v1; }
            }
            __syncwarp();
            if (lane == 0) mbar_arrive(BAR(B_SIG + 2 + br), 1);
            if (tid == 0) PROF_MARK(12 + 2 * br);
            if (br) break;
          }
        }
      key_group:
        float s[32];
        const uint32_t lo = dlo0 + slot * 512;
        if (!ok) mbar_wait(BAR(B_FULL + slot), par);
        wg_fence();
        wgmma_rs_n64_tb0<0>(s, q[0], q[1], q[2], q[3], dhi | lo);
        wgmma_rs_n64_tb0<1>(s, q[4], q[5], q[6], q[7], dhi | (lo + 2));
        wg_commit();
        int nslot = slot + 4;
        uint32_t npar = par;
        if (nslot == 12) { nslot = 0; npar ^= 1; }
#pragma unroll
        for (int u = 0; u < 4; u++) {
          wg_wait<0>();
          fence_regs(s);
          if (u == 0 && lane == 0 && it > 0) mbar_arrive(BAR(B_EMPTY + prev), 1);
          if (u == 2) ok = mbar_test(BAR(B_FULL + nslot), npar);
          if (__builtin_expect(!slow, 1)) {
#pragma unroll
            for (int j = 0; j < 8; j++) {
              if ((POLY_PAT >> j) & 1) {
                p[2 * j] = exp2_pair_fma(s[4 * j], s[4 * j + 1], 0x3F003F00u, 0x00030003u);
                p[2 * j + 1] = exp2_pair_fma(s[4 * j + 2], s[4 * j + 3], 0x3F003F00u, 0x00030003u);
              } else {
                p[2 * j] = pack_bf16(ex2f(s[4 * j]), ex2f(s[4 * j + 1]));
                p[2 * j + 1] = pack_bf16(ex2f(s[4 * j + 2]), ex2f(s[4 * j + 3]));
              }
            }
          } else {
#pragma unroll
            for (int j = 0; j < 8; j++) {
              const float sc = ((POLY_PAT >> j) & 1) ? 0.5f : 1.f;
              p[2 * j] = pack_bf16(ex2f(fmaf(s[4 * j], sc, -m0)), ex2f(fmaf(s[4 * j + 1], sc, -m0)));
              p[2 * j + 1] = pack_bf16(ex2f(fmaf(s[4 * j + 2], sc, -m1)), ex2f(fmaf(s[4 * j + 3], sc, -m1)));
            }
          }
          wg_fence();
#pragma unroll
          for (int ks = 0; ks < 4; ks++)
            wgmma_rs_n32_tb1<1>(o, p[4 * ks], p[4 * ks + 1], p[4 * ks + 2], p[4 * ks + 3], dhi | (lo + u * 512 + 256 + ks * 64));
          if (u < 3) {
            wgmma_rs_n64_tb0<0>(s, q[0], q[1], q[2], q[3], dhi | (lo + (u + 1) * 512));
            wgmma_rs_n64_tb0<1>(s, q[4], q[5], q[6], q[7], dhi | (lo + (u + 1) * 512 + 2));
          }
          wg_commit();
        }
        prev = slot; slot = nslot; par = npar;
      }
      wg_wait<0>();
      if (nh == 1) return;
#pragma unroll
      for (int i = 0; i < 14; i++) keep[i] = 0u;
#pragma unroll
      for (int i = 0; i < 28; i++) acc[i] = 0.f;
    }
    if (tid == 0) PROF_MARK(17);
    __nv_bfloat16* op = prm.out + (size_t)(pt * 128 + mh * 64 + wq * 16 + (lane >> 2)) * DM + hp * 56 + 2 * (lane & 3);
#pragma unroll
    for (int j = 0; j < 7; j++) {
      *(uint32_t*)(op + 8 * j) = pack_bf16(acc[4 * j], acc[4 * j + 1]);
      *(uint32_t*)(op + 8 * DM + 8 * j) = pack_bf16(acc[4 * j + 2], acc[4 * j + 3]);
    }
    if (tid == 0) { PROF_MARK(18); PROF_CLK(31); }
    if (tid == 0) {
      unsigned prevd = atomicAdd(&g_cnt[C_DONE * 32], 1u);
      if (prevd == NCTA - 1) {
#pragma unroll 1
        for (int i = 0; i < C_N; i++) g_cnt[i * 32] = 0;
      }
    }
  }
}

typedef CUresult (*EncodeFn)(CUtensorMap*, CUtensorMapDataType, cuuint32_t, void*, const cuuint64_t*, const cuuint64_t*,
                             const cuuint32_t*, const cuuint32_t*, CUtensorMapInterleave, CUtensorMapSwizzle,
                             CUtensorMapL2promotion, CUtensorMapFloatOOBfill);

void make_map(EncodeFn enc, CUtensorMap* tm, const void* ptr, uint64_t cols, uint64_t rows, uint32_t box_rows) {
  cuuint64_t dims[2] = {cols, rows};
  cuuint64_t strides[1] = {cols * 2};
  cuuint32_t box[2] = {64, box_rows};
  cuuint32_t es[2] = {1, 1};
  enc(tm, CU_TENSOR_MAP_DATA_TYPE_BFLOAT16, 2, const_cast<void*>(ptr), dims, strides, box, es, CU_TENSOR_MAP_INTERLEAVE_NONE,
      CU_TENSOR_MAP_SWIZZLE_128B, CU_TENSOR_MAP_L2_PROMOTION_L2_128B, CU_TENSOR_MAP_FLOAT_OOB_FILL_NONE);
}

}

extern "C" void kernel_launch(void* const* d_in, const int* in_sizes, int n_in, void* d_out, int out_size) {
  (void)in_sizes; (void)n_in; (void)out_size;
  static EncodeFn enc = nullptr;
  if (!enc) {
    void* fn = nullptr;
    cudaDriverEntryPointQueryResult qr;
    cudaGetDriverEntryPoint("cuTensorMapEncodeTiled", &fn, cudaEnableDefault, &qr);
    enc = (EncodeFn)fn;
    cudaFuncSetAttribute(fused_kernel, cudaFuncAttributeMaxDynamicSharedMemorySize, SMEM_BYTES);
  }
  CUtensorMap tm_x, tm_wqkv, tm_wq, tm_woa, tm_wob;
  make_map(enc, &tm_x, d_in[0], DM, S_LEN, 128);
  make_map(enc, &tm_wqkv, d_in[1], 3 * DM, DM, 64);
  make_map(enc, &tm_wq, d_in[5], DM, DM, 64);
  make_map(enc, &tm_woa, d_in[3], DM, DM, 64);
  make_map(enc, &tm_wob, d_in[8], DM, DM, 64);
  Params prm;
  prm.w_phi = (const __nv_bfloat16*)d_in[2];
  prm.wk = (const __nv_bfloat16*)d_in[6];
  prm.wv = (const __nv_bfloat16*)d_in[7];
  prm.gate_w = (const __nv_bfloat16*)d_in[9];
  prm.out = (__nv_bfloat16*)d_out;
  fused_kernel<<<NCTA, NTHREADS, SMEM_BYTES>>>(tm_x, tm_wqkv, tm_wq, tm_woa, tm_wob, prm);
}
```

```cpp
#include <cuda_runtime.h>
#include <cuda_bf16.h>
#include <cuda.h>
#include <stdint.h>

namespace {

constexpr int S_LEN = 2048, DM = 448, DH = 28;
constexpr int NCTA = 128;
constexpr int NTHREADS = 640;
constexpr uint32_t POLY_PAT = 0x57;

#define QB_AT (3 + (wg >> 1))

constexpr int OFF_X = 0;
constexpr int OFF_KA = 0;
constexpr int OFF_VA = 16384;
constexpr int OFF_QP = 32768;
constexpr int OFF_QA = 57344;
constexpr int OFF_KVR = 73728;
constexpr int OFF_PHI = 81920;
constexpr int OFF_WO = 0;
constexpr int OFF_RING = 114688;
constexpr int OFF_WPH = 212992;
constexpr int OFF_SLC = 217088;
constexpr int OFF_QSQ = 224256;
constexpr int OFF_RED = 225792;
constexpr int OFF_BAR = 225856;
constexpr int SMEM_BYTES = 226368 + 1024;

constexpr int B_FULL = 0, B_X = 12, B_EMPTY = 19, B_WO = 31  , B_KVR = 33, B_X0FREE = 34, B_X1FREE = 35, B_B1 = 36,
              B_SLOW = 37, B_BUILD = 38, B_SIG = 40  , B_N = 44;

constexpr int C_KV = 0, C_PART = 1, C_DONE = 3, C_OA = 4, C_OB = 20, C_N = 36;

__device__ __align__(1024) uint8_t g_kv_img[32 * 8192];
__device__ __align__(16) float g_ksq[512];
__device__ __align__(16) float g_vsq[512];
__device__ __align__(16) float g_gate[S_LEN];
__device__ __align__(1024) float g_kvacc[2][16 * 64 * 32];
__device__ unsigned g_epoch;
__device__ __align__(1024) uint8_t g_o_img[2 * 16 * 14 * 8192];
__device__ unsigned g_cnt[C_N * 32];

#define PROF3(i) do { } while (0)
#define PROF2(i) do { } while (0)
#define PROF_CLK(i) do { } while (0)
#define PROF_MARK(i) do { } while (0)
__device__ __forceinline__ uint32_t smem_u32(const void* p) { return (uint32_t)__cvta_generic_to_shared(p); }
__device__ __forceinline__ void mbar_init(uint32_t a, int cnt) {
  asm volatile("mbarrier.init.shared::cta.b64 [%0], %1;" ::"r"(a), "r"(cnt) : "memory");
}
__device__ __forceinline__ void mbar_expect_tx(uint32_t a, uint32_t bytes) {
  asm volatile("mbarrier.arrive.expect_tx.shared::cta.b64 _, [%0], %1;" ::"r"(a), "r"(bytes) : "memory");
}
__device__ __forceinline__ void mbar_arrive(uint32_t a, uint32_t cnt) {
  asm volatile("mbarrier.arrive.shared::cta.b64 _, [%0], %1;" ::"r"(a), "r"(cnt) : "memory");
}
__device__ __forceinline__ void mbar_wait(uint32_t a, uint32_t parity) {
  asm volatile(
      "{\n.reg .pred p;\n.reg .u32 c;\nmov.u32 c, 0;\n"
      "W_%=:\nmbarrier.try_wait.parity.shared::cta.b64 p, [%0], %1;\n"
      "add.u32 c, c, 1;\nsetp.lt.and.u32 p, c, 0x1000000, !p;\n@p bra W_%=;\n}"
      ::"r"(a), "r"(parity) : "memory");
}
__device__ __forceinline__ uint32_t mbar_test(uint32_t a, uint32_t parity) {
  uint32_t ok;
  asm volatile("{\n.reg .pred p;\nmbarrier.test_wait.parity.shared::cta.b64 p, [%1], %2;\nselp.u32 %0, 1, 0, p;\n}"
               : "=r"(ok) : "r"(a), "r"(parity) : "memory");
  return ok;
}
__device__ __forceinline__ bool elect_one() {
  uint32_t r;
  asm volatile("{\n.reg .pred p;\nelect.sync _|p, 0xffffffff;\nselp.u32 %0, 1, 0, p;\n}" : "=r"(r));
  return r != 0;
}
__device__ __forceinline__ void tma_2d(uint32_t dst, const CUtensorMap* tm, int c0, int c1, uint32_t bar) {
  asm volatile("cp.async.bulk.tensor.2d.shared::cluster.global.mbarrier::complete_tx::bytes [%0], [%1, {%3, %4}], [%2];"
               ::"r"(dst), "l"(tm), "r"(bar), "r"(c0), "r"(c1) : "memory");
}
__device__ __forceinline__ void bulk_g2s(uint32_t dst, const void* src, uint32_t bytes, uint32_t bar) {
  asm volatile("cp.async.bulk.shared::cluster.global.mbarrier::complete_tx::bytes [%0], [%1], %2, [%3];"
               ::"r"(dst), "l"(src), "r"(bytes), "r"(bar) : "memory");
}
__device__ __forceinline__ void cp_async8(uint32_t dst, const void* src) {
  asm volatile("cp.async.ca.shared.global [%0], [%1], 8;" ::"r"(dst), "l"(src) : "memory");
}
__device__ __forceinline__ void fence_async_smem() { asm volatile("fence.proxy.async.shared::cta;" ::: "memory"); }
__device__ __forceinline__ void fence_async_all() { asm volatile("fence.proxy.async.global;" ::: "memory"); }
__device__ __forceinline__ float ldcg_f(const float* p) { float v; asm volatile("ld.global.cg.f32 %0, [%1];" : "=f"(v) : "l"(p) : "memory"); return v; }
__device__ __forceinline__ void bar_sync(int id, int n) { asm volatile("bar.sync %0, %1;" ::"r"(id), "r"(n) : "memory"); }
__device__ __forceinline__ void cnt_arrive(int idx) {
  asm volatile("red.release.gpu.global.add.u32 [%0], 1;" ::"l"(&g_cnt[idx * 32]) : "memory");
}
__device__ __forceinline__ void cnt_wait(int idx, unsigned target) {
  unsigned v, n = 0;
#pragma unroll 1
  while (true) {
    asm volatile("ld.acquire.gpu.global.u32 %0, [%1];" : "=r"(v) : "l"(&g_cnt[idx * 32]) : "memory");
    if (v >= target || ++n >= (1u << 22)) break;
    __nanosleep(32);
  }
}
__device__ __forceinline__ void wg_fence() { asm volatile("wgmma.fence.sync.aligned;" ::: "memory"); }
__device__ __forceinline__ void wg_commit() { asm volatile("wgmma.commit_group.sync.aligned;" ::: "memory"); }
template <int N> __device__ __forceinline__ void wg_wait() { asm volatile("wgmma.wait_group.sync.aligned %0;" ::"n"(N) : "memory"); }
template <int N> __device__ __forceinline__ void fence_regs(float (&d)[N]) {
#pragma unroll
  for (int i = 0; i < N; i++) asm volatile("" : "+f"(d[i])::"memory");
}
__device__ __forceinline__ uint64_t make_desc(uint32_t saddr, uint32_t lbo, uint32_t sbo, uint32_t swz) {
  return (uint64_t)((saddr & 0x3FFFF) >> 4) | ((uint64_t)(lbo >> 4) << 16) | ((uint64_t)(sbo >> 4) << 32) | ((uint64_t)swz << 62);
}
__device__ __forceinline__ float ex2f(float x) { float y; asm("ex2.approx.ftz.f32 %0, %1;" : "=f"(y) : "f"(x)); return y; }
__device__ __forceinline__ float rcpf(float x) { float y; asm("rcp.approx.ftz.f32 %0, %1;" : "=f"(y) : "f"(x)); return y; }
__device__ __forceinline__ uint32_t pack_bf16(float lo, float hi) {
  uint32_t r; asm("cvt.rn.bf16x2.f32 %0, %1, %2;" : "=r"(r) : "f"(hi), "f"(lo)); return r;
}
__device__ __forceinline__ uint32_t lop_and_or(uint32_t a, uint32_t m, uint32_t c) {
  uint32_t r; asm("lop3.b32 %0, %1, %2, %3, 0xEA;" : "=r"(r) : "r"(a), "r"(m), "r"(c)); return r;
}
__device__ __forceinline__ void sts32(uint32_t a, uint32_t v) { asm volatile("st.shared.b32 [%0], %1;" ::"r"(a), "r"(v) : "memory"); }
__device__ __forceinline__ void sts64(uint32_t a, uint32_t v0, uint32_t v1) { asm volatile("st.shared.v2.b32 [%0], {%1, %2};" ::"r"(a), "r"(v0), "r"(v1) : "memory"); }
__device__ __forceinline__ void sts128(uint32_t a, uint4 v) {
  asm volatile("st.shared.v4.b32 [%0], {%1, %2, %3, %4};" ::"r"(a), "r"(v.x), "r"(v.y), "r"(v.z), "r"(v.w) : "memory");
}
__device__ __forceinline__ float4 ldcg_f4(const float* p) {
  float4 v; asm volatile("ld.global.cg.v4.f32 {%0, %1, %2, %3}, [%4];" : "=f"(v.x), "=f"(v.y), "=f"(v.z), "=f"(v.w) : "l"(p) : "memory"); return v;
}
__device__ __forceinline__ float quad_sum(float v) { v += __shfl_xor_sync(~0u, v, 1); v += __shfl_xor_sync(~0u, v, 2); return v; }
__device__ __forceinline__ float quad_max(float v) { v = fmaxf(v, __shfl_xor_sync(~0u, v, 1)); v = fmaxf(v, __shfl_xor_sync(~0u, v, 2)); return v; }

template <int SD> __device__ __forceinline__ void wgmma_ss_n56_ta0_tb1(float (&d)[28], uint64_t da, uint64_t db) {
  if (SD) asm volatile("wgmma.mma_async.sync.aligned.m64n56k16.f32.bf16.bf16 {%0, %1, %2, %3, %4, %5, %6, %7, %8, %9, %10, %11, %12, %13, %14, %15, %16, %17, %18, %19, %20, %21, %22, %23, %24, %25, %26, %27}, %28, %29, 1, 1, 1, 0, 1;\n"
    : "+f"(d[0]), "+f"(d[1]), "+f"(d[2]), "+f"(d[3]), "+f"(d[4]), "+f"(d[5]), "+f"(d[6]), "+f"(d[7]), "+f"(d[8]), "+f"(d[9]), "+f"(d[10]), "+f"(d[11]), "+f"(d[12]), "+f"(d[13]), "+f"(d[14]), "+f"(d[15]), "+f"(d[16]), "+f"(d[17]), "+f"(d[18]), "+f"(d[19]), "+f"(d[20]), "+f"(d[21]), "+f"(d[22]), "+f"(d[23]), "+f"(d[24]), "+f"(d[25]), "+f"(d[26]), "+f"(d[27])
    : "l"(da), "l"(db));
  else asm volatile("wgmma.mma_async.sync.aligned.m64n56k16.f32.bf16.bf16 {%0, %1, %2, %3, %4, %5, %6, %7, %8, %9, %10, %11, %12, %13, %14, %15, %16, %17, %18, %19, %20, %21, %22, %23, %24, %25, %26, %27}, %28, %29, 0, 1, 1, 0, 1;\n"
    : "=f"(d[0]), "=f"(d[1]), "=f"(d[2]), "=f"(d[3]), "=f"(d[4]), "=f"(d[5]), "=f"(d[6]), "=f"(d[7]), "=f"(d[8]), "=f"(d[9]), "=f"(d[10]), "=f"(d[11]), "=f"(d[12]), "=f"(d[13]), "=f"(d[14]), "=f"(d[15]), "=f"(d[16]), "=f"(d[17]), "=f"(d[18]), "=f"(d[19]), "=f"(d[20]), "=f"(d[21]), "=f"(d[22]), "=f"(d[23]), "=f"(d[24]), "=f"(d[25]), "=f"(d[26]), "=f"(d[27])
    : "l"(da), "l"(db));
}
template <int SD> __device__ __forceinline__ void wgmma_ss_n8_ta0_tb1(float (&d)[4], uint64_t da, uint64_t db) {
  if (SD) asm volatile("wgmma.mma_async.sync.aligned.m64n8k16.f32.bf16.bf16 {%0, %1, %2, %3}, %4, %5, 1, 1, 1, 0, 1;\n"
    : "+f"(d[0]), "+f"(d[1]), "+f"(d[2]), "+f"(d[3])
    : "l"(da), "l"(db));
  else asm volatile("wgmma.mma_async.sync.aligned.m64n8k16.f32.bf16.bf16 {%0, %1, %2, %3}, %4, %5, 0, 1, 1, 0, 1;\n"
    : "=f"(d[0]), "=f"(d[1]), "=f"(d[2]), "=f"(d[3])
    : "l"(da), "l"(db));
}
template <int SD> __device__ __forceinline__ void wgmma_ss_n32_ta1_tb1(float (&d)[16], uint64_t da, uint64_t db) {
  if (SD) asm volatile("wgmma.mma_async.sync.aligned.m64n32k16.f32.bf16.bf16 {%0, %1, %2, %3, %4, %5, %6, %7, %8, %9, %10, %11, %12, %13, %14, %15}, %16, %17, 1, 1, 1, 1, 1;\n"
    : "+f"(d[0]), "+f"(d[1]), "+f"(d[2]), "+f"(d[3]), "+f"(d[4]), "+f"(d[5]), "+f"(d[6]), "+f"(d[7]), "+f"(d[8]), "+f"(d[9]), "+f"(d[10]), "+f"(d[11]), "+f"(d[12]), "+f"(d[13]), "+f"(d[14]), "+f"(d[15])
    : "l"(da), "l"(db));
  else asm volatile("wgmma.mma_async.sync.aligned.m64n32k16.f32.bf16.bf16 {%0, %1, %2, %3, %4, %5, %6, %7, %8, %9, %10, %11, %12, %13, %14, %15}, %16, %17, 0, 1, 1, 1, 1;\n"
    : "=f"(d[0]), "=f"(d[1]), "=f"(d[2]), "=f"(d[3]), "=f"(d[4]), "=f"(d[5]), "=f"(d[6]), "=f"(d[7]), "=f"(d[8]), "=f"(d[9]), "=f"(d[10]), "=f"(d[11]), "=f"(d[12]), "=f"(d[13]), "=f"(d[14]), "=f"(d[15])
    : "l"(da), "l"(db));
}
template <int SD> __device__ __forceinline__ void wgmma_ss_n32_ta0_tb1(float (&d)[16], uint64_t da, uint64_t db) {
  if (SD) asm volatile("wgmma.mma_async.sync.aligned.m64n32k16.f32.bf16.bf16 {%0, %1, %2, %3, %4, %5, %6, %7, %8, %9, %10, %11, %12, %13, %14, %15}, %16, %17, 1, 1, 1, 0, 1;\n"
    : "+f"(d[0]), "+f"(d[1]), "+f"(d[2]), "+f"(d[3]), "+f"(d[4]), "+f"(d[5]), "+f"(d[6]), "+f"(d[7]), "+f"(d[8]), "+f"(d[9]), "+f"(d[10]), "+f"(d[11]), "+f"(d[12]), "+f"(d[13]), "+f"(d[14]), "+f"(d[15])
    : "l"(da), "l"(db));
  else asm volatile("wgmma.mma_async.sync.aligned.m64n32k16.f32.bf16.bf16 {%0, %1, %2, %3, %4, %5, %6, %7, %8, %9, %10, %11, %12, %13, %14, %15}, %16, %17, 0, 1, 1, 0, 1;\n"
    : "=f"(d[0]), "=f"(d[1]), "=f"(d[2]), "=f"(d[3]), "=f"(d[4]), "=f"(d[5]), "=f"(d[6]), "=f"(d[7]), "=f"(d[8]), "=f"(d[9]), "=f"(d[10]), "=f"(d[11]), "=f"(d[12]), "=f"(d[13]), "=f"(d[14]), "=f"(d[15])
    : "l"(da), "l"(db));
}
template <int SD> __device__ __forceinline__ void wgmma_rs_n64_tb0(float (&d)[32], uint32_t a0, uint32_t a1, uint32_t a2, uint32_t a3, uint64_t db) {
  if (SD) asm volatile("wgmma.mma_async.sync.aligned.m64n64k16.f32.bf16.bf16 {%0, %1, %2, %3, %4, %5, %6, %7, %8, %9, %10, %11, %12, %13, %14, %15, %16, %17, %18, %19, %20, %21, %22, %23, %24, %25, %26, %27, %28, %29, %30, %31}, {%32, %33, %34, %35}, %36, 1, 1, 1, 0;\n"
    : "+f"(d[0]), "+f"(d[1]), "+f"(d[2]), "+f"(d[3]), "+f"(d[4]), "+f"(d[5]), "+f"(d[6]), "+f"(d[7]), "+f"(d[8]), "+f"(d[9]), "+f"(d[10]), "+f"(d[11]), "+f"(d[12]), "+f"(d[13]), "+f"(d[14]), "+f"(d[15]), "+f"(d[16]), "+f"(d[17]), "+f"(d[18]), "+f"(d[19]), "+f"(d[20]), "+f"(d[21]), "+f"(d[22]), "+f"(d[23]), "+f"(d[24]), "+f"(d[25]), "+f"(d[26]), "+f"(d[27]), "+f"(d[28]), "+f"(d[29]), "+f"(d[30]), "+f"(d[31])
    : "r"(a0), "r"(a1), "r"(a2), "r"(a3), "l"(db));
  else asm volatile("wgmma.mma_async.sync.aligned.m64n64k16.f32.bf16.bf16 {%0, %1, %2, %3, %4, %5, %6, %7, %8, %9, %10, %11, %12, %13, %14, %15, %16, %17, %18, %19, %20, %21, %22, %23, %24, %25, %26, %27, %28, %29, %30, %31}, {%32, %33, %34, %35}, %36, 0, 1, 1, 0;\n"
    : "=f"(d[0]), "=f"(d[1]), "=f"(d[2]), "=f"(d[3]), "=f"(d[4]), "=f"(d[5]), "=f"(d[6]), "=f"(d[7]), "=f"(d[8]), "=f"(d[9]), "=f"(d[10]), "=f"(d[11]), "=f"(d[12]), "=f"(d[13]), "=f"(d[14]), "=f"(d[15]), "=f"(d[16]), "=f"(d[17]), "=f"(d[18]), "=f"(d[19]), "=f"(d[20]), "=f"(d[21]), "=f"(d[22]), "=f"(d[23]), "=f"(d[24]), "=f"(d[25]), "=f"(d[26]), "=f"(d[27]), "=f"(d[28]), "=f"(d[29]), "=f"(d[30]), "=f"(d[31])
    : "r"(a0), "r"(a1), "r"(a2), "r"(a3), "l"(db));
}
template <int SD> __device__ __forceinline__ void wgmma_rs_n32_tb1(float (&d)[16], uint32_t a0, uint32_t a1, uint32_t a2, uint32_t a3, uint64_t db) {
  if (SD) asm volatile("wgmma.mma_async.sync.aligned.m64n32k16.f32.bf16.bf16 {%0, %1, %2, %3, %4, %5, %6, %7, %8, %9, %10, %11, %12, %13, %14, %15}, {%16, %17, %18, %19}, %20, 1, 1, 1, 1;\n"
    : "+f"(d[0]), "+f"(d[1]), "+f"(d[2]), "+f"(d[3]), "+f"(d[4]), "+f"(d[5]), "+f"(d[6]), "+f"(d[7]), "+f"(d[8]), "+f"(d[9]), "+f"(d[10]), "+f"(d[11]), "+f"(d[12]), "+f"(d[13]), "+f"(d[14]), "+f"(d[15])
    : "r"(a0), "r"(a1), "r"(a2), "r"(a3), "l"(db));
  else asm volatile("wgmma.mma_async.sync.aligned.m64n32k16.f32.bf16.bf16 {%0, %1, %2, %3, %4, %5, %6, %7, %8, %9, %10, %11, %12, %13, %14, %15}, {%16, %17, %18, %19}, %20, 0, 1, 1, 1;\n"
    : "=f"(d[0]), "=f"(d[1]), "=f"(d[2]), "=f"(d[3]), "=f"(d[4]), "=f"(d[5]), "=f"(d[6]), "=f"(d[7]), "=f"(d[8]), "=f"(d[9]), "=f"(d[10]), "=f"(d[11]), "=f"(d[12]), "=f"(d[13]), "=f"(d[14]), "=f"(d[15])
    : "r"(a0), "r"(a1), "r"(a2), "r"(a3), "l"(db));
}

__device__ __forceinline__ uint32_t sw64_off(int row, int d) { return row * 64 + ((((d >> 3) ^ (row >> 1)) & 3) << 4) + (d & 7) * 2; }

__device__ __forceinline__ uint32_t exp2_pair_fma(float t0, float t1, uint32_t c_half, uint32_t c_3) {
  uint32_t y0, y;
  asm("prmt.b32 %0, %1, %2, 0x6521;" : "=r"(y0) : "r"(__float_as_uint(t0)), "r"(__float_as_uint(t1)));
  uint32_t h = lop_and_or(y0, 0x007F007Fu, c_half);
  uint32_t e = lop_and_or(y0, 0xFF80FF80u, c_3);
  asm("fma.rn.bf16x2 %0, %1, %2, %3;" : "=r"(y) : "r"(y0), "r"(h), "r"(e));
  return y;
}

__device__ __forceinline__ void feature_map(float (&v)[16], uint32_t (&ph)[16], int lq) {
  const float L2E = 1.4426950408889634f;
  const bool tail_ok = lq < 2;
  float mx[2], mn[2], b[16], sa[2], sn[2];
#pragma unroll
  for (int r = 0; r < 2; r++) {
    const int o = 2 * r;
    if (!tail_ok) { v[o + 12] = v[o]; v[o + 13] = v[o]; }
    mx[r] = fmaxf(fmaxf(fmaxf(v[o], v[o + 1]), fmaxf(v[o + 4], v[o + 5])), fmaxf(fmaxf(v[o + 8], v[o + 9]), fmaxf(v[o + 12], v[o + 13])));
    mn[r] = fminf(fminf(fminf(v[o], v[o + 1]), fminf(v[o + 4], v[o + 5])), fminf(fminf(v[o + 8], v[o + 9]), fminf(v[o + 12], v[o + 13])));
  }
#pragma unroll
  for (int o = 1; o <= 2; o <<= 1)
#pragma unroll
    for (int r = 0; r < 2; r++) { mx[r] = fmaxf(mx[r], __shfl_xor_sync(~0u, mx[r], o)); mn[r] = fminf(mn[r], __shfl_xor_sync(~0u, mn[r], o)); }
#pragma unroll
  for (int r = 0; r < 2; r++) {
    const int o = 2 * r;
    const float cx = -mx[r] * L2E, cn = mn[r] * L2E;
#pragma unroll
    for (int i = 0; i < 8; i++) {
      const int k = o + 4 * (i >> 1) + (i & 1);
      b[k] = ex2f(fmaf(v[k], -L2E, cn));
      v[k] = ex2f(fmaf(v[k], L2E, cx));
    }
    if (!tail_ok) { v[o + 12] = v[o + 13] = b[o + 12] = b[o + 13] = 0.f; }
    sa[r] = ((v[o] + v[o + 1]) + (v[o + 4] + v[o + 5])) + ((v[o + 8] + v[o + 9]) + (v[o + 12] + v[o + 13]));
    sn[r] = ((b[o] + b[o + 1]) + (b[o + 4] + b[o + 5])) + ((b[o + 8] + b[o + 9]) + (b[o + 12] + b[o + 13]));
  }
#pragma unroll
  for (int o = 1; o <= 2; o <<= 1)
#pragma unroll
    for (int r = 0; r < 2; r++) { sa[r] += __shfl_xor_sync(~0u, sa[r], o); sn[r] += __shfl_xor_sync(~0u, sn[r], o); }
#pragma unroll
  for (int r = 0; r < 2; r++) {
    const float ra = rcpf(sa[r]), rb = rcpf(sn[r]);
#pragma unroll
    for (int jj = 0; jj < 4; jj++) {
      ph[jj * 2 + r] = pack_bf16(v[2 * r + 4 * jj] * ra, v[2 * r + 4 * jj + 1] * ra);
      ph[(4 + jj) * 2 + r] = pack_bf16(b[2 * r + 4 * jj] * rb, b[2 * r + 4 * jj + 1] * rb);
    }
  }
}

__device__ __forceinline__ void store_heads(uint32_t base, const uint32_t (&a)[14], uint32_t pad, int row0, int lq) {
  const uint32_t rb = base + row0 * 64 + (((row0 >> 1) & 3) << 4);
  const uint32_t b0 = rb + lq * 4;
  const uint32_t b1 = (rb + 8192 + ((lq * 4 + 8) & 15)) ^ ((lq >> 1) << 4);
#pragma unroll
  for (int j = 0; j < 7; j++) {
    uint32_t ad;
    if (j < 3) ad = b0 ^ (j << 4);
    else if (j == 3) ad = (lq < 2) ? (b0 ^ 48u) : (b1 ^ 16u);
    else ad = (lq < 2) ? (b1 ^ ((j - 4) << 4)) : ((b1 ^ 16u) ^ ((j - 3) << 4));
    sts32(ad, a[2 * j]);
    sts32(ad + 512, a[2 * j + 1]);
  }
  sts64((rb ^ 48u) + 8 + (lq & 1) * 8192 + (lq >> 1) * 512, pad, 0u);
}

struct Params {
  const __nv_bfloat16* w_phi;
  const __nv_bfloat16* wk;
  const __nv_bfloat16* wv;
  const __nv_bfloat16* gate_w;
  __nv_bfloat16* out;
};

__global__ void __launch_bounds__(NTHREADS, 1)
fused_kernel(const __grid_constant__ CUtensorMap tm_x, const __grid_constant__ CUtensorMap tm_wqkv,
             const __grid_constant__ CUtensorMap tm_wq, const __grid_constant__ CUtensorMap tm_woa,
             const __grid_constant__ CUtensorMap tm_wob, const Params prm) {
  extern __shared__ uint8_t smem_raw[];
  uint32_t sb = (smem_u32(smem_raw) + 1023u) & ~1023u;
  uint8_t* sgen = smem_raw + (sb - smem_u32(smem_raw));
  asm volatile("mov.u32 %0, %0;" : "+r"(sb));
  const int tid = threadIdx.x, lane = tid & 31;
  const int warp = __shfl_sync(~0u, tid >> 5, 0), wg = warp >> 2;
  const int pt = blockIdx.x >> 3, hp = blockIdx.x & 7;
  const uint32_t bars = sb + OFF_BAR;
  auto BAR = [&](int i) { return bars + 8u * i; };
  const unsigned epoch = g_epoch & 1;

  if (tid == 0) { PROF_MARK(0); PROF_CLK(30); PROF2(15); }
  if (elect_one()) {
    if (warp == 16) {
      mbar_init(BAR(B_X), 1); mbar_init(BAR(B_FULL), 1); mbar_init(BAR(B_FULL + 1), 1);
      fence_async_smem();
      mbar_expect_tx(BAR(B_X), 16384);
      tma_2d(sb + OFF_X, &tm_x, 0, pt * 128, BAR(B_X));
      mbar_expect_tx(BAR(B_FULL), 8192);
      tma_2d(sb + OFF_RING, &tm_wq, hp * 56, 0, BAR(B_FULL));
      mbar_expect_tx(BAR(B_FULL + 1), 8192);
      tma_2d(sb + OFF_RING + 8192, &tm_wqkv, DM + hp * 56, 0, BAR(B_FULL + 1));
    } else {
#pragma unroll 1
      for (int i = 2 + warp - (warp > 16); i < B_N; i += 19) {
        int cnt = (i >= B_EMPTY && i < B_WO) || i > B_SIG || i == B_X0FREE || i == B_X1FREE ? 16 : 1;
        if (i == B_BUILD) cnt = 3;
        if (i == B_SIG) cnt = 8;
        if (i != B_X) mbar_init(BAR(i), cnt);
      }
      fence_async_smem();
    }
  }
  __syncthreads();
  if (tid == 0) PROF2(14);

  if (wg == 4) {
    asm volatile("setmaxnreg.dec.sync.aligned.u32 32;");
    if (warp == 16) {
      if (elect_one()) {
#pragma unroll 1
        for (int i = 1; i < 14; i++) {
          const int c = i < 7 ? i : i - 7, ps = i % 6;
          if (i < 7) {
            mbar_expect_tx(BAR(B_X + c), 16384);
            tma_2d(sb + OFF_X + c * 16384, &tm_x, c * 64, pt * 128, BAR(B_X + c));
          }
#pragma unroll 1
          for (int h = 0; h < 2; h++) {
            const int sl = 2 * ps + h;
            if (i >= 6) mbar_wait(BAR(B_EMPTY + sl), (i / 6 - 1) & 1);
            mbar_expect_tx(BAR(B_FULL + sl), 8192);
            tma_2d(sb + OFF_RING + sl * 8192, (i < 7 && !h) ? &tm_wq : &tm_wqkv, hp * 56 + (h ? (i < 7 ? DM : 2 * DM) : 0), c * 64,
                   BAR(B_FULL + sl));
          }
        }
        PROF_MARK(20);
        cnt_wait(C_KV, NCTA);
        PROF_MARK(21);
        fence_async_all();
        int slot = 4, ng = 8;
        uint32_t par = 1;
#pragma unroll 1
        for (int n = 0; n < ng; n++) {
          mbar_wait(BAR(B_EMPTY + slot), par);
          if (n < 3) { mbar_wait(BAR(B_EMPTY + slot + 1), par); mbar_wait(BAR(B_EMPTY + slot + 2), par); mbar_wait(BAR(B_EMPTY + slot + 3), par); }
          mbar_expect_tx(BAR(B_FULL + slot), 32768);
          bulk_g2s(sb + OFF_RING + slot * 8192, g_kv_img + (n & 7) * 32768, 32768, BAR(B_FULL + slot));
          slot += 4;
          if (slot == 12) { slot = 0; par ^= 1; }
          if (n == 7) {
            mbar_wait(BAR(B_SLOW), 0);
            if (*(volatile int*)(sgen + OFF_RED + 8)) ng = 16;
          }
        }
#pragma unroll 1
        for (int i = 0; i < 14; i++) {
          const int ps = i % 6, g4 = (ps >> 1) * 4, bi = g4 + 1 + (ps & 1);
          if (i == 0 || i == 7) {
            PROF3(i ? 11 : 8);
            cnt_wait((i ? C_OB : C_OA) + pt, 8);
            PROF3(i ? 12 : 9);
            PROF_MARK(26);
            fence_async_all();
            PROF3(i ? 13 : 10);
          }
          if (i < 6) mbar_wait(BAR(B_EMPTY + g4), g4 >= slot ? par : par ^ 1);
          else mbar_wait(BAR(B_EMPTY + bi), (ps < 2) ^ ((i / 6 - 1) & 1));
          mbar_expect_tx(BAR(B_FULL + bi), 16384);
          bulk_g2s(sb + OFF_RING + ps * 16384, g_o_img + (size_t)(pt * 14 + (i < 7 ? 2 * i : 2 * i + 210)) * 8192, 16384, BAR(B_FULL + bi));
        }
      }
    } else {
      {
        const int t = tid - 544;
#pragma unroll 1
        for (int i = t; i < 256; i += 96) sts128(sb + OFF_WPH + i * 16, make_uint4(0, 0, 0, 0));
        bar_sync(2, 96);
#pragma unroll 1
        for (int k = t; k < DM; k += 96) {
          const __nv_bfloat16* src = (hp < 4 ? prm.wk : prm.wv) + k * DH + (hp & 3) * 8;
          cp_async8(sb + OFF_SLC + k * 16, src);
          if ((hp & 3) != 3) cp_async8(sb + OFF_SLC + k * 16 + 8, src + 4);
          else sts64(sb + OFF_SLC + k * 16 + 8, hp == 3 ? (uint32_t)((const unsigned short*)prm.gate_w)[k] : 0u, 0u);
          if (k < 392) {
            const int row = k / 7, e = row >= DH;
            cp_async8(sb + OFF_WPH + e * 2048 + sw64_off(row - DH * e, (k % 7) * 4), prm.w_phi + 2 * hp * DH * DH + k * 4);
          }
        }
        asm volatile("cp.async.wait_all;" ::: "memory");
        fence_async_smem();
        __syncwarp();
        if (lane == 0) mbar_arrive(BAR(B_BUILD), 1);
      }
      if (warp == 18) {
        if (elect_one()) {
#pragma unroll 1
          for (int i = 0; i < 4; i++) {
            mbar_wait(BAR(B_SIG + i), 0);
            PROF3(2 * i);
            cnt_arrive(i == 0 ? C_KV : i == 1 ? C_PART : (i == 2 ? C_OA : C_OB) + pt);
            PROF3(2 * i + 1);
            if (i == 1 || i == 2) {
              mbar_wait(BAR(B_X0FREE + i - 1), 0);
              mbar_expect_tx(BAR(B_WO + i - 1), 57344);
#pragma unroll 1
              for (int c = 0; c < 7; c++)
                tma_2d(sb + OFF_WO + (i - 1) * 57344 + c * 8192, i == 1 ? &tm_woa : &tm_wob, hp * 56, c * 64, BAR(B_WO + i - 1));
            }
          }
        }
      } else if (warp == 19) {
        if (lane == 0) {
          mbar_wait(BAR(B_SIG + 0), 0);
          cnt_wait(C_KV, NCTA);
        }
        __syncwarp();
        float ksq = 0.f, vsq = 0.f;
#pragma unroll
        for (int sl = 0; sl < 4; sl++) {
          float4 a = ldcg_f4(g_ksq + sl * 128 + lane * 4), b = ldcg_f4(g_vsq + sl * 128 + lane * 4);
          float m = fmaxf(fmaxf(a.x, a.y), fmaxf(a.z, a.w));
          m = __uint_as_float(__reduce_max_sync(~0u, __float_as_uint(m)));
          ksq += m;
          vsq = fmaxf(vsq, fmaxf(fmaxf(b.x, b.y), fmaxf(b.z, b.w)));
        }
        vsq = __uint_as_float(__reduce_max_sync(~0u, __float_as_uint(vsq)));
        if (lane == 0) {
          float* red = (float*)(sgen + OFF_RED);
          red[0] = ksq; red[1] = vsq;
          mbar_arrive(BAR(B_B1), 1);
        }
      } else {
        float4* z = (float4*)(g_kvacc[epoch ^ 1] + blockIdx.x * 256) + lane;
        z[0] = make_float4(0.f, 0.f, 0.f, 0.f);
        z[32] = make_float4(0.f, 0.f, 0.f, 0.f);
        if (lane == 0) {
          mbar_wait(BAR(B_SIG + 1), 0);
          cnt_wait(C_PART, NCTA);
          PROF_MARK(23);
          mbar_arrive(BAR(B_KVR), 1);
        }
      }
    }
  } else {
    asm volatile("setmaxnreg.inc.sync.aligned.u32 112;");
    const int mh = wg & 1, nh = wg >> 1, wq = warp & 3;
    float acc[28];
    uint32_t keep[14];
#pragma unroll
    for (int i = 0; i < 28; i++) acc[i] = 0.f;

#pragma unroll 1
    for (int stage = 0; stage < 4; stage++) {
      {
        const bool tail = stage >= 2;
        int ps = stage & 1, prev = 0;
        uint32_t w = stage & 1;
        const uint64_t dS = make_desc(tail ? sb + OFF_WO + (stage - 2) * 57344 : sb + OFF_X + mh * 8192, 1024, 1024, 1);
        const uint64_t dR = make_desc(sb + OFF_RING + (tail ? mh : nh) * 8192, 1024, 1024, 1);
#pragma unroll 1
        for (int c = 0; c < 7; c++) {
          const int bi = tail ? (ps >> 1) * 4 + 1 + (ps & 1) : 2 * ps + nh;
          mbar_wait(BAR(tail ? B_WO + stage - 2 : B_X + c), 0);
          if (tid == 0) PROF2(stage * 16 + c * 2);
          mbar_wait(BAR(B_FULL + bi), w ^ (tail && ps < 2));
          if (tid == 0) PROF2(stage * 16 + c * 2 + 1);
          const uint64_t ds = dS + c * (tail ? 512 : 1024), dr = dR + ps * 1024;
          const uint64_t dA = tail ? dr : ds, dB = tail ? ds : dr;
          wg_fence();
          wgmma_ss_n56_ta0_tb1<1>(acc, dA, dB);
          wgmma_ss_n56_ta0_tb1<1>(acc, dA + 2, dB + 128);
          wgmma_ss_n56_ta0_tb1<1>(acc, dA + 4, dB + 256);
          wgmma_ss_n56_ta0_tb1<1>(acc, dA + 6, dB + 384);
          wg_commit();
          if (stage != 3) {
            wg_wait<1>();
            if (lane == 0 && c > 0) mbar_arrive(BAR(B_EMPTY + prev), 2);
          } else if (c == 1) {
            wg_wait<1>();
            if (lane == 0) mbar_arrive(BAR(B_EMPTY + prev), 2);
          }
          prev = bi;
          if (++ps == 6) { ps = 0; w ^= 1; }
        }
        wg_wait<0>();
        fence_regs(acc);
        if (lane == 0) mbar_arrive(BAR(B_EMPTY + prev), 2);
      }
      if (stage == 2) { if (tid == 0) PROF_MARK(15); continue; }
      if (stage == 3) break;
      int lane_;
      asm volatile("mov.u32 %0, %%laneid;" : "=r"(lane_));
      const int lq = lane_ & 3;
      const int rowl = wq * 16 + (lane_ >> 2);
      const int row0 = mh * 64 + rowl;

      if (stage == 0) {
        if (tid == 0) PROF_MARK(2);
        if (tid == 256) PROF_MARK(3);
        float accs[4] = {0.f, 0.f, 0.f, 0.f};
        if (nh == 1) {
          mbar_wait(BAR(B_BUILD), 0);
          const uint64_t dX = make_desc(sb + OFF_X + mh * 8192, 1024, 1024, 1);
          const uint64_t dSlc = make_desc(sb + OFF_SLC, 128, 128, 0);
#pragma unroll 1
          for (int c = 0; c < 7; c++) {
            wg_fence();
            wgmma_ss_n8_ta0_tb1<1>(accs, dX + c * 1024, dSlc + c * 64);
            wgmma_ss_n8_ta0_tb1<1>(accs, dX + c * 1024 + 2, dSlc + c * 64 + 16);
            wgmma_ss_n8_ta0_tb1<1>(accs, dX + c * 1024 + 4, dSlc + c * 64 + 32);
            wgmma_ss_n8_ta0_tb1<1>(accs, dX + c * 1024 + 6, dSlc + c * 64 + 48);
            wg_commit();
          }
        }
        const float qs = nh ? 1.f : 0.18898223650461362f * 1.4426950408889634f;
#pragma unroll
        for (int i = 0; i < 28; i++) acc[i] *= qs;
#pragma unroll
        for (int i = 0; i < 14; i++) keep[i] = pack_bf16(acc[2 * i], acc[2 * i + 1]);
        if (nh == 0) {
          float sq[4] = {0.f, 0.f, 0.f, 0.f};
#pragma unroll
          for (int j = 0; j < 7; j++) {
#pragma unroll
            for (int rr = 0; rr < 2; rr++) {
              const float s2 = acc[4 * j + 2 * rr] * acc[4 * j + 2 * rr] + acc[4 * j + 2 * rr + 1] * acc[4 * j + 2 * rr + 1];
              if (j < 3) sq[rr] += s2;
              else if (j > 3) sq[2 + rr] += s2;
              else { sq[rr] += (lq < 2) ? s2 : 0.f; sq[2 + rr] += (lq < 2) ? 0.f : s2; }
            }
          }
#pragma unroll
          for (int i = 0; i < 4; i++) sq[i] = quad_sum(sq[i]);
          const float mine = lq == 0 ? sq[0] : lq == 1 ? sq[1] : lq == 2 ? sq[2] : sq[3];
          ((float*)(sgen + OFF_QSQ))[(mh + (lq & 2)) * 64 + rowl + 8 * (lq & 1)] = mine <= 3.0e38f ? mine : __int_as_float(0x7f800000);
        }
        wg_wait<0>();
        fence_regs(accs);
        if (nh == 1) {
          const int sl = hp & 3;
          const bool isk = hp < 4, real = (sl < 3) || (lq < 2);
          float mxv = 0.f;
#pragma unroll
          for (int rr = 0; rr < 2; rr++) {
            const int pos = pt * 128 + row0 + 8 * rr, kr = pos & 63;
            const float v0 = accs[2 * rr], v1 = accs[2 * rr + 1];
            const bool poly = isk && ((POLY_PAT >> (kr >> 3)) & 1);
            const float sc = poly ? 2.f : 1.f;
            const float s2 = quad_sum(real ? v0 * v0 + v1 * v1 : 0.f);
            mxv = fmaxf(mxv, s2 <= 3.0e38f ? s2 : __int_as_float(0x7f800000));
            const uint32_t padv = lq == 2 ? (poly ? 0x443F4000u : 0x00003F80u) : (poly ? 0x3AB03F4Du : 0u);
            const uint32_t outv = real ? pack_bf16(sc * v0, sc * v1) : padv;
            if (hp == 3 && lq == 2) g_gate[pos] = rcpf(1.f + ex2f(-1.4426950408889634f * v0));
            *(uint32_t*)(g_kv_img + (pos >> 6) * 8192 + (isk ? 0 : 4096) + sw64_off(kr, sl * 8 + 2 * lq)) = outv;
          }
          mxv = __uint_as_float(__reduce_max_sync(~0u, __float_as_uint(mxv)));
          if (lane == 0) (isk ? g_ksq : g_vsq)[sl * 128 + pt * 8 + mh * 4 + wq] = mxv;
          __syncwarp();
          if (lane == 0) mbar_arrive(BAR(B_SIG + 0), 1);
        }
        if (tid == 0) PROF_MARK(4);
        if (tid == 256) PROF_MARK(5);
#pragma unroll
        for (int i = 0; i < 28; i++) acc[i] = 0.f;
        continue;
      }

      bar_sync(1, 512);
      if (tid == 0) PROF_MARK(6);
#pragma unroll 1
      for (int r = 0; r < 2; r++) {
        store_heads(sb + (r ? (nh ? OFF_VA : OFF_QA) : (nh ? OFF_KA : OFF_QP)), keep, (r & nh) ? 0x00003F80u : 0u, row0, lq);
#pragma unroll
        for (int i = 0; i < 14; i++) keep[i] = pack_bf16(acc[2 * i], acc[2 * i + 1]);
      }
      fence_async_smem();
      if (tid == 0) PROF_MARK(7);

      bar_sync(1, 512);

      const uint64_t dK = make_desc(sb + OFF_RING, 512, 512, 2);
      const uint64_t dhi = dK & 0xffffffff00000000ull;
      const uint32_t dlo0 = (uint32_t)dK;
      int slot = 4, prev = 0;
      uint32_t par = 0, ok = 0, q[8];
      float m0 = -3.0e38f, m1 = -3.0e38f, g0 = 0.f, g1 = 0.f;
      bool slow = false;
      float o[16];
#pragma unroll
      for (int i = 0; i < 16; i++) o[i] = 0.f;
#pragma unroll
      for (int i = 0; i < 8; i++) q[i] = 0u;
      const int qb = QB_AT;
#pragma unroll 1
      for (int it = -1; it <= 8; it++) {
        uint32_t p[16];
        if (it < 0 || it == qb || it == 8) {
          float t[16];
          wg_wait<0>();
          fence_regs(o);
          if (it < 8) {
            if (tid == 0) PROF_MARK(it < 0 ? 27 : 11);
            const uint64_t dA = make_desc(sb + (it < 0 ? OFF_KA : OFF_QA) + nh * 8192 + mh * 4096, 512, 512, 2);
            const uint64_t dB = make_desc(sb + OFF_WPH + nh * 2048, 512, 512, 2);
            float* kvacc = g_kvacc[epoch] + (2 * hp + nh) * 2048;
            float pa[16];
            wg_fence();
            wgmma_ss_n32_ta0_tb1<0>(pa, dA, dB);
            wgmma_ss_n32_ta0_tb1<1>(pa, dA + 2, dB + 64);
            wg_commit();
            if (it >= 0) {
              mbar_wait(BAR(B_KVR), 0);
              const int tl = tid & 127;
              const float4 a = ldcg_f4(kvacc + tl * 16), b = ldcg_f4(kvacc + tl * 16 + 4), c = ldcg_f4(kvacc + tl * 16 + 8), d = ldcg_f4(kvacc + tl * 16 + 12);
              const uint32_t ad = sb + OFF_KVR + nh * 4096 + sw64_off(tl >> 1, (tl & 1) * 16);
              sts128(ad, make_uint4(pack_bf16(a.x, a.y), pack_bf16(a.z, a.w), pack_bf16(b.x, b.y), pack_bf16(b.z, b.w)));
              sts128(ad ^ 16u, make_uint4(pack_bf16(c.x, c.y), pack_bf16(c.z, c.w), pack_bf16(d.x, d.y), pack_bf16(d.z, d.w)));
            }
            wg_wait<0>();
            fence_regs(pa);
            uint32_t ph[16];
            feature_map(pa, ph, lq);
            const uint32_t rb = sb + OFF_PHI + wg * 8192 + rowl * 128 + lq * 4 + ((rowl & 7) << 4);
#pragma unroll
            for (int ch = 0; ch < 8; ch++) { sts32(rb ^ (ch << 4), ph[2 * ch]); sts32((rb ^ (ch << 4)) + 1024, ph[2 * ch + 1]); }
            fence_async_smem();
            bar_sync(4 + wg, 128);
            const uint64_t dP = make_desc(sb + OFF_PHI + wg * 8192, 1024, 1024, 1);
            if (it < 0) {
              const uint64_t dV = make_desc(sb + OFF_VA + nh * 8192 + mh * 4096, 512, 512, 2);
              float kv[16];
              wg_fence();
              wgmma_ss_n32_ta1_tb1<0>(kv, dP, dV);
#pragma unroll
              for (int ks = 1; ks < 4; ks++) wgmma_ss_n32_ta1_tb1<1>(kv, dP + ks * 128, dV + ks * 64);
              wg_commit();
              wg_wait<0>();
              fence_regs(kv);
              float* dst = kvacc + rowl * 32 + 2 * lq;
#pragma unroll
              for (int j = 0; j < 8; j++)
                asm volatile("red.global.add.v2.f32 [%0], {%1, %2};" ::"l"(dst + 8 * (j >> 1) + 256 * (j & 1)), "f"(kv[2 * j]), "f"(kv[2 * j + 1]) : "memory");
              __syncwarp();
              if (lane == 0) mbar_arrive(BAR(B_SIG + 1), 1);
              if (tid == 0) PROF_MARK(28);

              mbar_wait(BAR(B_B1), 0);
              if (tid == 0) PROF_MARK(9);
              g0 = ldcg_f(g_gate + pt * 128 + row0); g1 = ldcg_f(g_gate + pt * 128 + row0 + 8);
              const float* red = (const float*)(sgen + OFF_RED);
              const float ksq = red[0] * (1.02f * 1.02f), vsq = red[1];
              const float* qsq = (const float*)(sgen + OFF_QSQ);
              float b0, b1;
              asm("sqrt.approx.ftz.f32 %0, %1;" : "=f"(b0) : "f"(qsq[wg * 64 + rowl] * ksq));
              asm("sqrt.approx.ftz.f32 %0, %1;" : "=f"(b1) : "f"(qsq[wg * 64 + rowl + 8] * ksq));
              const float4 qa4 = ((const float4*)qsq)[lane_], qb4 = ((const float4*)qsq)[32 + lane_];
              const float qmax = fmaxf(fmaxf(fmaxf(qa4.x, qa4.y), fmaxf(qa4.z, qa4.w)), fmaxf(fmaxf(qb4.x, qb4.y), fmaxf(qb4.z, qb4.w)));
              slow = __any_sync(~0u, !(qmax * ksq <= 92.f * 92.f) || !(vsq <= 1.0e24f));
              if (tid == 0) { *(volatile int*)(sgen + OFF_RED + 8) = slow; mbar_arrive(BAR(B_SLOW), 1); }
              const uint32_t qa = sb + OFF_QP + nh * 8192;
              const int r = mh * 64 + wq * 16 + (lane_ & 7) + ((lane_ >> 3) & 1) * 8;
#pragma unroll
              for (int ks = 0; ks < 2; ks++)
                asm volatile("ldmatrix.sync.aligned.m8n8.x4.shared.b16 {%0, %1, %2, %3}, [%4];"
                             : "=r"(q[4 * ks]), "=r"(q[4 * ks + 1]), "=r"(q[4 * ks + 2]), "=r"(q[4 * ks + 3])
                             : "r"(qa + sw64_off(r, ks * 16 + (lane_ >> 4) * 8)) : "memory");
              if (lq >= 2 && !slow) {
                q[6] = lq == 2 ? pack_bf16(64.f - b0, 1.f) : 0x3F803F80u;
                q[7] = lq == 2 ? pack_bf16(64.f - b1, 1.f) : 0x3F803F80u;
              }
              __syncwarp();
              if (lane == 0) mbar_arrive(BAR(B_X0FREE), 1);
              if (__builtin_expect(slow, 0)) {
#pragma unroll 1
                for (int j64 = 0; j64 < 32; j64++) {
                  float s[32];
                  if ((j64 & 3) == 0) mbar_wait(BAR(B_FULL + slot), par);
                  const uint32_t lo = dlo0 + (slot + (j64 & 3)) * 512;
                  wg_fence();
                  wgmma_rs_n64_tb0<0>(s, q[0], q[1], q[2], q[3], dhi | lo);
                  wgmma_rs_n64_tb0<1>(s, q[4], q[5], q[6], q[7], dhi | (lo + 2));
                  wg_commit();
                  wg_wait<0>();
                  fence_regs(s);
#pragma unroll
                  for (int j = 0; j < 8; j++) {
                    const float sc = ((POLY_PAT >> j) & 1) ? 0.5f : 1.f;
                    m0 = fmaxf(m0, fmaxf(s[4 * j], s[4 * j + 1]) * sc);
                    m1 = fmaxf(m1, fmaxf(s[4 * j + 2], s[4 * j + 3]) * sc);
                  }
                  if ((j64 & 3) == 3) {
                    if (lane == 0) mbar_arrive(BAR(B_EMPTY + slot), 1);
                    slot += 4;
                    if (slot == 12) { slot = 0; par ^= 1; }
                  }
                }
                m0 = quad_max(m0); m1 = quad_max(m1);
              }
              if (tid == 0) PROF_MARK(10);
              continue;
            } else {
              const uint64_t dR = make_desc(sb + OFF_KVR + nh * 4096, 512, 512, 2);
              wg_fence();
              wgmma_ss_n32_ta0_tb1<0>(t, dP, dR);
#pragma unroll
              for (int ks = 1; ks < 4; ks++) wgmma_ss_n32_ta0_tb1<1>(t, dP + ks * 2, dR + ks * 64);
              wg_commit();
              wg_wait<0>();
              fence_regs(t);
              if (lane == 0) mbar_arrive(BAR(B_X1FREE), 1);
            }
          } else {
            if (lane == 0) mbar_arrive(BAR(B_EMPTY + prev), 1);
            if (tid == 0) PROF_MARK(13);
#pragma unroll
            for (int i = 0; i < 16; i++) t[i] = o[i];
          }
          {
            const int br = it == 8;
            const float eps = br ? 0.f : 1e-6f;
            const float d0 = __shfl_sync(~0u, t[12], (lane_ & ~3) | 2), d1 = __shfl_sync(~0u, t[14], (lane_ & ~3) | 2);
            const float r0 = __fdividef(br ? 1.f - g0 : g0, d0 + eps), r1 = __fdividef(br ? 1.f - g1 : g1, d1 + eps);
            uint8_t* img = g_o_img + (size_t)((br * 16 + pt) * 14 + mh) * 8192 + rowl * 128;
            const int col0 = (2 * hp + nh) * DH + 2 * lq;
#pragma unroll
            for (int j = 0; j < 4; j++) {
              const int col = col0 + 8 * j;
              uint8_t* gp = img + (col >> 6) * 16384 + ((((col >> 3) ^ rowl) & 7) << 4) + (col & 7) * 2;
              const uint32_t v0 = pack_bf16(t[4 * j] * r0, t[4 * j + 1] * r0), v1 = pack_bf16(t[4 * j + 2] * r1, t[4 * j + 3] * r1);
              if (j < 3 || lq < 2) { *(uint32_t*)gp = v0; *(uint32_t*)(gp + 1024) = v1; }
            }
            __syncwarp();
            if (lane == 0) mbar_arrive(BAR(B_SIG + 2 + br), 1);
            if (tid == 0) PROF_MARK(12 + 2 * br);
            if (br) break;
          }
        }
        float s[32];
        const uint32_t lo = dlo0 + slot * 512;
        if (!ok) mbar_wait(BAR(B_FULL + slot), par);
        wg_fence();
        wgmma_rs_n64_tb0<0>(s, q[0], q[1], q[2], q[3], dhi | lo);
        wgmma_rs_n64_tb0<1>(s, q[4], q[5], q[6], q[7], dhi | (lo + 2));
        wg_commit();
        int nslot = slot + 4;
        uint32_t npar = par;
        if (nslot == 12) { nslot = 0; npar ^= 1; }
#pragma unroll
        for (int u = 0; u < 4; u++) {
          wg_wait<0>();
          fence_regs(s);
          if (u == 0 && lane == 0 && it > 0) mbar_arrive(BAR(B_EMPTY + prev), 1);
          if (u == 2) ok = mbar_test(BAR(B_FULL + nslot), npar);
          if (__builtin_expect(!slow, 1)) {
#pragma unroll
            for (int j = 0; j < 8; j++) {
              if ((POLY_PAT >> j) & 1) {
                p[2 * j] = exp2_pair_fma(s[4 * j], s[4 * j + 1], 0x3F003F00u, 0x00030003u);
                p[2 * j + 1] = exp2_pair_fma(s[4 * j + 2], s[4 * j + 3], 0x3F003F00u, 0x00030003u);
              } else {
                p[2 * j] = pack_bf16(ex2f(s[4 * j]), ex2f(s[4 * j + 1]));
                p[2 * j + 1] = pack_bf16(ex2f(s[4 * j + 2]), ex2f(s[4 * j + 3]));
              }
            }
          } else {
#pragma unroll
            for (int j = 0; j < 8; j++) {
              const float sc = ((POLY_PAT >> j) & 1) ? 0.5f : 1.f;
              p[2 * j] = pack_bf16(ex2f(fmaf(s[4 * j], sc, -m0)), ex2f(fmaf(s[4 * j + 1], sc, -m0)));
              p[2 * j + 1] = pack_bf16(ex2f(fmaf(s[4 * j + 2], sc, -m1)), ex2f(fmaf(s[4 * j + 3], sc, -m1)));
            }
          }
          wg_fence();
#pragma unroll
          for (int ks = 0; ks < 4; ks++)
            wgmma_rs_n32_tb1<1>(o, p[4 * ks], p[4 * ks + 1], p[4 * ks + 2], p[4 * ks + 3], dhi | (lo + u * 512 + 256 + ks * 64));
          if (u < 3) {
            wgmma_rs_n64_tb0<0>(s, q[0], q[1], q[2], q[3], dhi | (lo + (u + 1) * 512));
            wgmma_rs_n64_tb0<1>(s, q[4], q[5], q[6], q[7], dhi | (lo + (u + 1) * 512 + 2));
          }
          wg_commit();
        }
        prev = slot; slot = nslot; par = npar;
      }
      wg_wait<0>();
      if (nh == 1) return;
#pragma unroll
      for (int i = 0; i < 14; i++) keep[i] = 0u;
#pragma unroll
      for (int i = 0; i < 28; i++) acc[i] = 0.f;
    }
    if (tid == 0) PROF_MARK(17);
    __nv_bfloat16* op = prm.out + (size_t)(pt * 128 + mh * 64 + wq * 16 + (lane >> 2)) * DM + hp * 56 + 2 * (lane & 3);
#pragma unroll
    for (int j = 0; j < 7; j++) {
      *(uint32_t*)(op + 8 * j) = pack_bf16(acc[4 * j], acc[4 * j + 1]);
      *(uint32_t*)(op + 8 * DM + 8 * j) = pack_bf16(acc[4 * j + 2], acc[4 * j + 3]);
    }
    if (tid == 0) { PROF_MARK(18); PROF_CLK(31); }
    if (tid == 0) {
      unsigned prevd = atomicAdd(&g_cnt[C_DONE * 32], 1u);
      if (prevd == NCTA - 1) {
#pragma unroll 1
        for (int i = 0; i < C_N; i++) g_cnt[i * 32] = 0;
        g_epoch = epoch ^ 1;
      }
    }
  }
}

typedef CUresult (*EncodeFn)(CUtensorMap*, CUtensorMapDataType, cuuint32_t, void*, const cuuint64_t*, const cuuint64_t*,
                             const cuuint32_t*, const cuuint32_t*, CUtensorMapInterleave, CUtensorMapSwizzle,
                             CUtensorMapL2promotion, CUtensorMapFloatOOBfill);

void make_map(EncodeFn enc, CUtensorMap* tm, const void* ptr, uint64_t cols, uint64_t rows, uint32_t box_rows) {
  cuuint64_t dims[2] = {cols, rows};
  cuuint64_t strides[1] = {cols * 2};
  cuuint32_t box[2] = {64, box_rows};
  cuuint32_t es[2] = {1, 1};
  enc(tm, CU_TENSOR_MAP_DATA_TYPE_BFLOAT16, 2, const_cast<void*>(ptr), dims, strides, box, es, CU_TENSOR_MAP_INTERLEAVE_NONE,
      CU_TENSOR_MAP_SWIZZLE_128B, CU_TENSOR_MAP_L2_PROMOTION_L2_128B, CU_TENSOR_MAP_FLOAT_OOB_FILL_NONE);
}

}

extern "C" void kernel_launch(void* const* d_in, const int* in_sizes, int n_in, void* d_out, int out_size) {
  (void)in_sizes; (void)n_in; (void)out_size;
  static EncodeFn enc = nullptr;
  if (!enc) {
    void* fn = nullptr;
    cudaDriverEntryPointQueryResult qr;
    cudaGetDriverEntryPoint("cuTensorMapEncodeTiled", &fn, cudaEnableDefault, &qr);
    enc = (EncodeFn)fn;
    cudaFuncSetAttribute(fused_kernel, cudaFuncAttributeMaxDynamicSharedMemorySize, SMEM_BYTES);
  }
  CUtensorMap tm_x, tm_wqkv, tm_wq, tm_woa, tm_wob;
  make_map(enc, &tm_x, d_in[0], DM, S_LEN, 128);
  make_map(enc, &tm_wqkv, d_in[1], 3 * DM, DM, 64);
  make_map(enc, &tm_wq, d_in[5], DM, DM, 64);
  make_map(enc, &tm_woa, d_in[3], DM, DM, 64);
  make_map(enc, &tm_wob, d_in[8], DM, DM, 64);
  Params prm;
  prm.w_phi = (const __nv_bfloat16*)d_in[2];
  prm.wk = (const __nv_bfloat16*)d_in[6];
  prm.wv = (const __nv_bfloat16*)d_in[7];
  prm.gate_w = (const __nv_bfloat16*)d_in[9];
  prm.out = (__nv_bfloat16*)d_out;
  fused_kernel<<<NCTA, NTHREADS, SMEM_BYTES>>>(tm_x, tm_wqkv, tm_wq, tm_woa, tm_wob, prm);
}
```

```cpp
#include <cuda_runtime.h>
#include <cuda_bf16.h>
#include <cuda.h>
#include <stdint.h>

namespace {

constexpr int S_LEN = 2048, DM = 448, DH = 28;
constexpr int NCTA = 128;
constexpr int NTHREADS = 640;
constexpr uint32_t POLY_PAT = 0x57;

#define KB_AT (nh ? -1 : 1)
#define QB_AT (4 + nh)

constexpr int OFF_X = 0;
constexpr int OFF_KA = 0;
constexpr int OFF_VA = 16384;
constexpr int OFF_QP = 32768;
constexpr int OFF_QA = 57344;
constexpr int OFF_KVR = 73728;
constexpr int OFF_PHI = 81920;
constexpr int OFF_WO = 0;
constexpr int OFF_RING = 114688;
constexpr int OFF_WPH = 212992;
constexpr int OFF_SLC = 217088;
constexpr int OFF_QSQ = 224256;
constexpr int OFF_RED = 225792;
constexpr int OFF_BAR = 225856;
constexpr int SMEM_BYTES = 226368 + 1024;

constexpr int B_FULL = 0, B_EMPTY = 3, B_WO = 6  , B_KVR = 8, B_X0FREE = 9, B_X1FREE = 10, B_B1 = 11, B_SLOW = 12,
              B_BUILD = 13, B_SIG = 14  , B_N = 18;

constexpr int C_KV = 0, C_PART = 1, C_DONE = 3, C_OA = 4, C_OB = 20, C_N = 36;

__device__ __align__(1024) uint8_t g_kv_img[32 * 8192];
__device__ __align__(16) float g_ksq[512];
__device__ __align__(16) float g_vsq[512];
__device__ __align__(16) float g_gate[S_LEN];
__device__ __align__(1024) float g_kvacc[2][16 * 64 * 32];
__device__ unsigned g_epoch;
__device__ __align__(1024) uint8_t g_o_img[2 * 16 * 14 * 8192];
__device__ unsigned g_cnt[C_N * 32];

#define PROF3(i) do { } while (0)
#define PROF2(i) do { } while (0)
#define PROF_CLK(i) do { } while (0)
#define PROF_MARK(i) do { } while (0)
__device__ __forceinline__ uint32_t smem_u32(const void* p) { return (uint32_t)__cvta_generic_to_shared(p); }
__device__ __forceinline__ void mbar_init(uint32_t a, int cnt) {
  asm volatile("mbarrier.init.shared::cta.b64 [%0], %1;" ::"r"(a), "r"(cnt) : "memory");
}
__device__ __forceinline__ void mbar_expect_tx(uint32_t a, uint32_t bytes) {
  asm volatile("mbarrier.arrive.expect_tx.shared::cta.b64 _, [%0], %1;" ::"r"(a), "r"(bytes) : "memory");
}
__device__ __forceinline__ void mbar_arrive(uint32_t a, uint32_t cnt) {
  asm volatile("mbarrier.arrive.shared::cta.b64 _, [%0], %1;" ::"r"(a), "r"(cnt) : "memory");
}
__device__ __forceinline__ void mbar_wait(uint32_t a, uint32_t parity) {
  asm volatile(
      "{\n.reg .pred p;\n.reg .u32 c;\nmov.u32 c, 0;\n"
      "W_%=:\nmbarrier.try_wait.parity.shared::cta.b64 p, [%0], %1;\n"
      "add.u32 c, c, 1;\nsetp.lt.and.u32 p, c, 0x1000000, !p;\n@p bra W_%=;\n}"
      ::"r"(a), "r"(parity) : "memory");
}
__device__ __forceinline__ uint32_t mbar_test(uint32_t a, uint32_t parity) {
  uint32_t ok;
  asm volatile("{\n.reg .pred p;\nmbarrier.test_wait.parity.shared::cta.b64 p, [%1], %2;\nselp.u32 %0, 1, 0, p;\n}"
               : "=r"(ok) : "r"(a), "r"(parity) : "memory");
  return ok;
}
__device__ __forceinline__ bool elect_one() {
  uint32_t r;
  asm volatile("{\n.reg .pred p;\nelect.sync _|p, 0xffffffff;\nselp.u32 %0, 1, 0, p;\n}" : "=r"(r));
  return r != 0;
}
__device__ __forceinline__ void tma_2d(uint32_t dst, const CUtensorMap* tm, int c0, int c1, uint32_t bar) {
  asm volatile("cp.async.bulk.tensor.2d.shared::cluster.global.mbarrier::complete_tx::bytes [%0], [%1, {%3, %4}], [%2];"
               ::"r"(dst), "l"(tm), "r"(bar), "r"(c0), "r"(c1) : "memory");
}
__device__ __forceinline__ void bulk_g2s(uint32_t dst, const void* src, uint32_t bytes, uint32_t bar) {
  asm volatile("cp.async.bulk.shared::cluster.global.mbarrier::complete_tx::bytes [%0], [%1], %2, [%3];"
               ::"r"(dst), "l"(src), "r"(bytes), "r"(bar) : "memory");
}
__device__ __forceinline__ void cp_async8(uint32_t dst, const void* src) {
  asm volatile("cp.async.ca.shared.global [%0], [%1], 8;" ::"r"(dst), "l"(src) : "memory");
}
__device__ __forceinline__ void fence_async_smem() { asm volatile("fence.proxy.async.shared::cta;" ::: "memory"); }
__device__ __forceinline__ void fence_async_all() { asm volatile("fence.proxy.async.global;" ::: "memory"); }
__device__ __forceinline__ float ldcg_f(const float* p) { float v; asm volatile("ld.global.cg.f32 %0, [%1];" : "=f"(v) : "l"(p) : "memory"); return v; }
__device__ __forceinline__ void bar_sync(int id, int n) { asm volatile("bar.sync %0, %1;" ::"r"(id), "r"(n) : "memory"); }
__device__ __forceinline__ void cnt_arrive(int idx) {
  asm volatile("red.release.gpu.global.add.u32 [%0], 1;" ::"l"(&g_cnt[idx * 32]) : "memory");
}
__device__ __forceinline__ void cnt_wait(int idx, unsigned target) {
  unsigned v, n = 0;
#pragma unroll 1
  while (true) {
    asm volatile("ld.acquire.gpu.global.u32 %0, [%1];" : "=r"(v) : "l"(&g_cnt[idx * 32]) : "memory");
    if (v >= target || ++n >= (1u << 22)) break;
    __nanosleep(32);
  }
}
__device__ __forceinline__ void wg_fence() { asm volatile("wgmma.fence.sync.aligned;" ::: "memory"); }
__device__ __forceinline__ void wg_commit() { asm volatile("wgmma.commit_group.sync.aligned;" ::: "memory"); }
template <int N> __device__ __forceinline__ void wg_wait() { asm volatile("wgmma.wait_group.sync.aligned %0;" ::"n"(N) : "memory"); }
template <int N> __device__ __forceinline__ void fence_regs(float (&d)[N]) {
#pragma unroll
  for (int i = 0; i < N; i++) asm volatile("" : "+f"(d[i])::"memory");
}
__device__ __forceinline__ uint64_t make_desc(uint32_t saddr, uint32_t lbo, uint32_t sbo, uint32_t swz) {
  return (uint64_t)((saddr & 0x3FFFF) >> 4) | ((uint64_t)(lbo >> 4) << 16) | ((uint64_t)(sbo >> 4) << 32) | ((uint64_t)swz << 62);
}
__device__ __forceinline__ float ex2f(float x) { float y; asm("ex2.approx.ftz.f32 %0, %1;" : "=f"(y) : "f"(x)); return y; }
__device__ __forceinline__ float rcpf(float x) { float y; asm("rcp.approx.ftz.f32 %0, %1;" : "=f"(y) : "f"(x)); return y; }
__device__ __forceinline__ uint32_t pack_bf16(float lo, float hi) {
  uint32_t r; asm("cvt.rn.bf16x2.f32 %0, %1, %2;" : "=r"(r) : "f"(hi), "f"(lo)); return r;
}
__device__ __forceinline__ uint32_t lop_and_or(uint32_t a, uint32_t m, uint32_t c) {
  uint32_t r; asm("lop3.b32 %0, %1, %2, %3, 0xEA;" : "=r"(r) : "r"(a), "r"(m), "r"(c)); return r;
}
__device__ __forceinline__ void sts32(uint32_t a, uint32_t v) { asm volatile("st.shared.b32 [%0], %1;" ::"r"(a), "r"(v) : "memory"); }
__device__ __forceinline__ void sts64(uint32_t a, uint32_t v0, uint32_t v1) { asm volatile("st.shared.v2.b32 [%0], {%1, %2};" ::"r"(a), "r"(v0), "r"(v1) : "memory"); }
__device__ __forceinline__ void sts128(uint32_t a, uint4 v) {
  asm volatile("st.shared.v4.b32 [%0], {%1, %2, %3, %4};" ::"r"(a), "r"(v.x), "r"(v.y), "r"(v.z), "r"(v.w) : "memory");
}
__device__ __forceinline__ float4 ldcg_f4(const float* p) {
  float4 v; asm volatile("ld.global.cg.v4.f32 {%0, %1, %2, %3}, [%4];" : "=f"(v.x), "=f"(v.y), "=f"(v.z), "=f"(v.w) : "l"(p) : "memory"); return v;
}
__device__ __forceinline__ float quad_sum(float v) { v += __shfl_xor_sync(~0u, v, 1); v += __shfl_xor_sync(~0u, v, 2); return v; }
__device__ __forceinline__ float quad_max(float v) { v = fmaxf(v, __shfl_xor_sync(~0u, v, 1)); v = fmaxf(v, __shfl_xor_sync(~0u, v, 2)); return v; }

template <int SD> __device__ __forceinline__ void wgmma_ss_n56_ta0_tb1(float (&d)[28], uint64_t da, uint64_t db) {
  if (SD) asm volatile("wgmma.mma_async.sync.aligned.m64n56k16.f32.bf16.bf16 {%0, %1, %2, %3, %4, %5, %6, %7, %8, %9, %10, %11, %12, %13, %14, %15, %16, %17, %18, %19, %20, %21, %22, %23, %24, %25, %26, %27}, %28, %29, 1, 1, 1, 0, 1;\n"
    : "+f"(d[0]), "+f"(d[1]), "+f"(d[2]), "+f"(d[3]), "+f"(d[4]), "+f"(d[5]), "+f"(d[6]), "+f"(d[7]), "+f"(d[8]), "+f"(d[9]), "+f"(d[10]), "+f"(d[11]), "+f"(d[12]), "+f"(d[13]), "+f"(d[14]), "+f"(d[15]), "+f"(d[16]), "+f"(d[17]), "+f"(d[18]), "+f"(d[19]), "+f"(d[20]), "+f"(d[21]), "+f"(d[22]), "+f"(d[23]), "+f"(d[24]), "+f"(d[25]), "+f"(d[26]), "+f"(d[27])
    : "l"(da), "l"(db));
  else asm volatile("wgmma.mma_async.sync.aligned.m64n56k16.f32.bf16.bf16 {%0, %1, %2, %3, %4, %5, %6, %7, %8, %9, %10, %11, %12, %13, %14, %15, %16, %17, %18, %19, %20, %21, %22, %23, %24, %25, %26, %27}, %28, %29, 0, 1, 1, 0, 1;\n"
    : "=f"(d[0]), "=f"(d[1]), "=f"(d[2]), "=f"(d[3]), "=f"(d[4]), "=f"(d[5]), "=f"(d[6]), "=f"(d[7]), "=f"(d[8]), "=f"(d[9]), "=f"(d[10]), "=f"(d[11]), "=f"(d[12]), "=f"(d[13]), "=f"(d[14]), "=f"(d[15]), "=f"(d[16]), "=f"(d[17]), "=f"(d[18]), "=f"(d[19]), "=f"(d[20]), "=f"(d[21]), "=f"(d[22]), "=f"(d[23]), "=f"(d[24]), "=f"(d[25]), "=f"(d[26]), "=f"(d[27])
    : "l"(da), "l"(db));
}
template <int SD> __device__ __forceinline__ void wgmma_ss_n8_ta0_tb1(float (&d)[4], uint64_t da, uint64_t db) {
  if (SD) asm volatile("wgmma.mma_async.sync.aligned.m64n8k16.f32.bf16.bf16 {%0, %1, %2, %3}, %4, %5, 1, 1, 1, 0, 1;\n"
    : "+f"(d[0]), "+f"(d[1]), "+f"(d[2]), "+f"(d[3])
    : "l"(da), "l"(db));
  else asm volatile("wgmma.mma_async.sync.aligned.m64n8k16.f32.bf16.bf16 {%0, %1, %2, %3}, %4, %5, 0, 1, 1, 0, 1;\n"
    : "=f"(d[0]), "=f"(d[1]), "=f"(d[2]), "=f"(d[3])
    : "l"(da), "l"(db));
}
template <int SD> __device__ __forceinline__ void wgmma_ss_n32_ta1_tb1(float (&d)[16], uint64_t da, uint64_t db) {
  if (SD) asm volatile("wgmma.mma_async.sync.aligned.m64n32k16.f32.bf16.bf16 {%0, %1, %2, %3, %4, %5, %6, %7, %8, %9, %10, %11, %12, %13, %14, %15}, %16, %17, 1, 1, 1, 1, 1;\n"
    : "+f"(d[0]), "+f"(d[1]), "+f"(d[2]), "+f"(d[3]), "+f"(d[4]), "+f"(d[5]), "+f"(d[6]), "+f"(d[7]), "+f"(d[8]), "+f"(d[9]), "+f"(d[10]), "+f"(d[11]), "+f"(d[12]), "+f"(d[13]), "+f"(d[14]), "+f"(d[15])
    : "l"(da), "l"(db));
  else asm volatile("wgmma.mma_async.sync.aligned.m64n32k16.f32.bf16.bf16 {%0, %1, %2, %3, %4, %5, %6, %7, %8, %9, %10, %11, %12, %13, %14, %15}, %16, %17, 0, 1, 1, 1, 1;\n"
    : "=f"(d[0]), "=f"(d[1]), "=f"(d[2]), "=f"(d[3]), "=f"(d[4]), "=f"(d[5]), "=f"(d[6]), "=f"(d[7]), "=f"(d[8]), "=f"(d[9]), "=f"(d[10]), "=f"(d[11]), "=f"(d[12]), "=f"(d[13]), "=f"(d[14]), "=f"(d[15])
    : "l"(da), "l"(db));
}
template <int SD> __device__ __forceinline__ void wgmma_ss_n32_ta0_tb1(float (&d)[16], uint64_t da, uint64_t db) {
  if (SD) asm volatile("wgmma.mma_async.sync.aligned.m64n32k16.f32.bf16.bf16 {%0, %1, %2, %3, %4, %5, %6, %7, %8, %9, %10, %11, %12, %13, %14, %15}, %16, %17, 1, 1, 1, 0, 1;\n"
    : "+f"(d[0]), "+f"(d[1]), "+f"(d[2]), "+f"(d[3]), "+f"(d[4]), "+f"(d[5]), "+f"(d[6]), "+f"(d[7]), "+f"(d[8]), "+f"(d[9]), "+f"(d[10]), "+f"(d[11]), "+f"(d[12]), "+f"(d[13]), "+f"(d[14]), "+f"(d[15])
    : "l"(da), "l"(db));
  else asm volatile("wgmma.mma_async.sync.aligned.m64n32k16.f32.bf16.bf16 {%0, %1, %2, %3, %4, %5, %6, %7, %8, %9, %10, %11, %12, %13, %14, %15}, %16, %17, 0, 1, 1, 0, 1;\n"
    : "=f"(d[0]), "=f"(d[1]), "=f"(d[2]), "=f"(d[3]), "=f"(d[4]), "=f"(d[5]), "=f"(d[6]), "=f"(d[7]), "=f"(d[8]), "=f"(d[9]), "=f"(d[10]), "=f"(d[11]), "=f"(d[12]), "=f"(d[13]), "=f"(d[14]), "=f"(d[15])
    : "l"(da), "l"(db));
}
template <int SD> __device__ __forceinline__ void wgmma_rs_n64_tb0(float (&d)[32], uint32_t a0, uint32_t a1, uint32_t a2, uint32_t a3, uint64_t db) {
  if (SD) asm volatile("wgmma.mma_async.sync.aligned.m64n64k16.f32.bf16.bf16 {%0, %1, %2, %3, %4, %5, %6, %7, %8, %9, %10, %11, %12, %13, %14, %15, %16, %17, %18, %19, %20, %21, %22, %23, %24, %25, %26, %27, %28, %29, %30, %31}, {%32, %33, %34, %35}, %36, 1, 1, 1, 0;\n"
    : "+f"(d[0]), "+f"(d[1]), "+f"(d[2]), "+f"(d[3]), "+f"(d[4]), "+f"(d[5]), "+f"(d[6]), "+f"(d[7]), "+f"(d[8]), "+f"(d[9]), "+f"(d[10]), "+f"(d[11]), "+f"(d[12]), "+f"(d[13]), "+f"(d[14]), "+f"(d[15]), "+f"(d[16]), "+f"(d[17]), "+f"(d[18]), "+f"(d[19]), "+f"(d[20]), "+f"(d[21]), "+f"(d[22]), "+f"(d[23]), "+f"(d[24]), "+f"(d[25]), "+f"(d[26]), "+f"(d[27]), "+f"(d[28]), "+f"(d[29]), "+f"(d[30]), "+f"(d[31])
    : "r"(a0), "r"(a1), "r"(a2), "r"(a3), "l"(db));
  else asm volatile("wgmma.mma_async.sync.aligned.m64n64k16.f32.bf16.bf16 {%0, %1, %2, %3, %4, %5, %6, %7, %8, %9, %10, %11, %12, %13, %14, %15, %16, %17, %18, %19, %20, %21, %22, %23, %24, %25, %26, %27, %28, %29, %30, %31}, {%32, %33, %34, %35}, %36, 0, 1, 1, 0;\n"
    : "=f"(d[0]), "=f"(d[1]), "=f"(d[2]), "=f"(d[3]), "=f"(d[4]), "=f"(d[5]), "=f"(d[6]), "=f"(d[7]), "=f"(d[8]), "=f"(d[9]), "=f"(d[10]), "=f"(d[11]), "=f"(d[12]), "=f"(d[13]), "=f"(d[14]), "=f"(d[15]), "=f"(d[16]), "=f"(d[17]), "=f"(d[18]), "=f"(d[19]), "=f"(d[20]), "=f"(d[21]), "=f"(d[22]), "=f"(d[23]), "=f"(d[24]), "=f"(d[25]), "=f"(d[26]), "=f"(d[27]), "=f"(d[28]), "=f"(d[29]), "=f"(d[30]), "=f"(d[31])
    : "r"(a0), "r"(a1), "r"(a2), "r"(a3), "l"(db));
}
template <int SD> __device__ __forceinline__ void wgmma_rs_n32_tb1(float (&d)[16], uint32_t a0, uint32_t a1, uint32_t a2, uint32_t a3, uint64_t db) {
  if (SD) asm volatile("wgmma.mma_async.sync.aligned.m64n32k16.f32.bf16.bf16 {%0, %1, %2, %3, %4, %5, %6, %7, %8, %9, %10, %11, %12, %13, %14, %15}, {%16, %17, %18, %19}, %20, 1, 1, 1, 1;\n"
    : "+f"(d[0]), "+f"(d[1]), "+f"(d[2]), "+f"(d[3]), "+f"(d[4]), "+f"(d[5]), "+f"(d[6]), "+f"(d[7]), "+f"(d[8]), "+f"(d[9]), "+f"(d[10]), "+f"(d[11]), "+f"(d[12]), "+f"(d[13]), "+f"(d[14]), "+f"(d[15])
    : "r"(a0), "r"(a1), "r"(a2), "r"(a3), "l"(db));
  else asm volatile("wgmma.mma_async.sync.aligned.m64n32k16.f32.bf16.bf16 {%0, %1, %2, %3, %4, %5, %6, %7, %8, %9, %10, %11, %12, %13, %14, %15}, {%16, %17, %18, %19}, %20, 0, 1, 1, 1;\n"
    : "=f"(d[0]), "=f"(d[1]), "=f"(d[2]), "=f"(d[3]), "=f"(d[4]), "=f"(d[5]), "=f"(d[6]), "=f"(d[7]), "=f"(d[8]), "=f"(d[9]), "=f"(d[10]), "=f"(d[11]), "=f"(d[12]), "=f"(d[13]), "=f"(d[14]), "=f"(d[15])
    : "r"(a0), "r"(a1), "r"(a2), "r"(a3), "l"(db));
}

__device__ __forceinline__ uint32_t sw64_off(int row, int d) { return row * 64 + ((((d >> 3) ^ (row >> 1)) & 3) << 4) + (d & 7) * 2; }

__device__ __forceinline__ uint32_t exp2_pair_fma(float t0, float t1, uint32_t c_half, uint32_t c_3) {
  uint32_t y0, y;
  asm("prmt.b32 %0, %1, %2, 0x6521;" : "=r"(y0) : "r"(__float_as_uint(t0)), "r"(__float_as_uint(t1)));
  uint32_t h = lop_and_or(y0, 0x007F007Fu, c_half);
  uint32_t e = lop_and_or(y0, 0xFF80FF80u, c_3);
  asm("fma.rn.bf16x2 %0, %1, %2, %3;" : "=r"(y) : "r"(y0), "r"(h), "r"(e));
  return y;
}

__device__ __forceinline__ void feature_map(float (&v)[16], uint32_t (&ph)[16], int lq) {
  const float L2E = 1.4426950408889634f;
  const bool tail_ok = lq < 2;
  float mx[2], mn[2], b[16], sa[2], sn[2];
#pragma unroll
  for (int r = 0; r < 2; r++) {
    const int o = 2 * r;
    if (!tail_ok) { v[o + 12] = v[o]; v[o + 13] = v[o]; }
    mx[r] = fmaxf(fmaxf(fmaxf(v[o], v[o + 1]), fmaxf(v[o + 4], v[o + 5])), fmaxf(fmaxf(v[o + 8], v[o + 9]), fmaxf(v[o + 12], v[o + 13])));
    mn[r] = fminf(fminf(fminf(v[o], v[o + 1]), fminf(v[o + 4], v[o + 5])), fminf(fminf(v[o + 8], v[o + 9]), fminf(v[o + 12], v[o + 13])));
  }
#pragma unroll
  for (int o = 1; o <= 2; o <<= 1)
#pragma unroll
    for (int r = 0; r < 2; r++) { mx[r] = fmaxf(mx[r], __shfl_xor_sync(~0u, mx[r], o)); mn[r] = fminf(mn[r], __shfl_xor_sync(~0u, mn[r], o)); }
#pragma unroll
  for (int r = 0; r < 2; r++) {
    const int o = 2 * r;
    const float cx = -mx[r] * L2E, cn = mn[r] * L2E;
#pragma unroll
    for (int i = 0; i < 8; i++) {
      const int k = o + 4 * (i >> 1) + (i & 1);
      b[k] = ex2f(fmaf(v[k], -L2E, cn));
      v[k] = ex2f(fmaf(v[k], L2E, cx));
    }
    if (!tail_ok) { v[o + 12] = v[o + 13] = b[o + 12] = b[o + 13] = 0.f; }
    sa[r] = ((v[o] + v[o + 1]) + (v[o + 4] + v[o + 5])) + ((v[o + 8] + v[o + 9]) + (v[o + 12] + v[o + 13]));
    sn[r] = ((b[o] + b[o + 1]) + (b[o + 4] + b[o + 5])) + ((b[o + 8] + b[o + 9]) + (b[o + 12] + b[o + 13]));
  }
#pragma unroll
  for (int o = 1; o <= 2; o <<= 1)
#pragma unroll
    for (int r = 0; r < 2; r++) { sa[r] += __shfl_xor_sync(~0u, sa[r], o); sn[r] += __shfl_xor_sync(~0u, sn[r], o); }
#pragma unroll
  for (int r = 0; r < 2; r++) {
    const float ra = rcpf(sa[r]), rb = rcpf(sn[r]);
#pragma unroll
    for (int jj = 0; jj < 4; jj++) {
      ph[jj * 2 + r] = pack_bf16(v[2 * r + 4 * jj] * ra, v[2 * r + 4 * jj + 1] * ra);
      ph[(4 + jj) * 2 + r] = pack_bf16(b[2 * r + 4 * jj] * rb, b[2 * r + 4 * jj + 1] * rb);
    }
  }
}

__device__ __forceinline__ void store_heads(uint32_t base, const uint32_t (&a)[14], uint32_t pad, int row0, int lq) {
  const uint32_t rb = base + row0 * 64 + (((row0 >> 1) & 3) << 4);
  const uint32_t b0 = rb + lq * 4;
  const uint32_t b1 = (rb + 8192 + ((lq * 4 + 8) & 15)) ^ ((lq >> 1) << 4);
#pragma unroll
  for (int j = 0; j < 7; j++) {
    uint32_t ad;
    if (j < 3) ad = b0 ^ (j << 4);
    else if (j == 3) ad = (lq < 2) ? (b0 ^ 48u) : (b1 ^ 16u);
    else ad = (lq < 2) ? (b1 ^ ((j - 4) << 4)) : ((b1 ^ 16u) ^ ((j - 3) << 4));
    sts32(ad, a[2 * j]);
    sts32(ad + 512, a[2 * j + 1]);
  }
  sts64((rb ^ 48u) + 8 + (lq & 1) * 8192 + (lq >> 1) * 512, pad, 0u);
}

struct Params {
  const __nv_bfloat16* w_phi;
  const __nv_bfloat16* wk;
  const __nv_bfloat16* wv;
  const __nv_bfloat16* gate_w;
  __nv_bfloat16* out;
};

__global__ void __launch_bounds__(NTHREADS, 1)
fused_kernel(const __grid_constant__ CUtensorMap tm_x, const __grid_constant__ CUtensorMap tm_wqkv,
             const __grid_constant__ CUtensorMap tm_wq, const __grid_constant__ CUtensorMap tm_woa,
             const __grid_constant__ CUtensorMap tm_wob, const Params prm) {
  extern __shared__ uint8_t smem_raw[];
  uint32_t sb = (smem_u32(smem_raw) + 1023u) & ~1023u;
  uint8_t* sgen = smem_raw + (sb - smem_u32(smem_raw));
  asm volatile("mov.u32 %0, %0;" : "+r"(sb));
  const int tid = threadIdx.x, lane = tid & 31;
  const int warp = __shfl_sync(~0u, tid >> 5, 0), wg = warp >> 2;
  const int pt = blockIdx.x >> 3, hp = blockIdx.x & 7;
  const uint32_t bars = sb + OFF_BAR;
  auto BAR = [&](int i) { return bars + 8u * i; };
  const unsigned epoch = g_epoch & 1;

  if (tid == 0) { PROF_MARK(0); PROF_CLK(30); PROF2(15); }
  auto load_proj = [&](int c, int g) {
    mbar_expect_tx(BAR(B_FULL + g), 49152);
    tma_2d(sb + OFF_X + c * 16384, &tm_x, c * 64, pt * 128, BAR(B_FULL + g));
    tma_2d(sb + OFF_RING + g * 32768, &tm_wq, hp * 56, c * 64, BAR(B_FULL + g));
#pragma unroll 1
    for (int j = 0; j < 3; j++) tma_2d(sb + OFF_RING + g * 32768 + 8192 + j * 8192, &tm_wqkv, j * DM + hp * 56, c * 64, BAR(B_FULL + g));
  };
  if (elect_one()) {
    const int i = warp == 16 ? 0 : (warp == 0 ? 16 : warp);
    if (i < B_N) {
      int cnt = (i >= B_EMPTY && i < B_WO) || i > B_SIG || i == B_X1FREE ? 16 : 1;
      if (i == B_X0FREE) cnt = 32;
      if (i == B_BUILD) cnt = 3;
      if (i == B_SIG) cnt = 8;
      mbar_init(BAR(i), cnt);
      fence_async_smem();
    }
    if (warp == 16) load_proj(0, 0);
  }
  __syncthreads();
  if (tid == 0) PROF2(14);

  if (wg == 4) {
    asm volatile("setmaxnreg.dec.sync.aligned.u32 32;");
    if (warp == 16) {
      if (elect_one()) {
        int g = 1, nkv = 8;
        uint32_t par = 1;
#pragma unroll 1
        for (int n = 1; n < 14 + nkv; n++) {
          if (n == 7) { PROF_MARK(20); cnt_wait(C_KV, NCTA); PROF_MARK(21); fence_async_all(); }
          if (n == 15) {
            mbar_wait(BAR(B_SLOW), 0);
            if (*(volatile int*)(sgen + OFF_RED + 8)) nkv = 16;
          }
          const int j = n - 7 - nkv;
          if (j == 0 || j == 3) {
            PROF3(j ? 11 : 8);
            cnt_wait((j ? C_OB : C_OA) + pt, 8);
            PROF3(j ? 12 : 9);
            PROF_MARK(26);
            fence_async_all();
          }
          mbar_wait(BAR(B_EMPTY + g), par);
          if (n < 7) load_proj(n, g);
          else {
            mbar_expect_tx(BAR(B_FULL + g), 32768);
            bulk_g2s(sb + OFF_RING + g * 32768, j < 0 ? g_kv_img + ((n - 7) & 7) * 32768 : g_o_img + (size_t)(pt * 7 + j) * 32768, 32768,
                     BAR(B_FULL + g));
          }
          if (++g == 3) { g = 0; par ^= 1; }
        }
      }
    } else {
      {
        const int t = tid - 544;
#pragma unroll 1
        for (int i = t; i < 256; i += 96) sts128(sb + OFF_WPH + i * 16, make_uint4(0, 0, 0, 0));
        bar_sync(2, 96);
#pragma unroll 1
        for (int k = t; k < DM; k += 96) {
          const __nv_bfloat16* src = (hp < 4 ? prm.wk : prm.wv) + k * DH + (hp & 3) * 8;
          cp_async8(sb + OFF_SLC + k * 16, src);
          if ((hp & 3) != 3) cp_async8(sb + OFF_SLC + k * 16 + 8, src + 4);
          else sts64(sb + OFF_SLC + k * 16 + 8, hp == 3 ? (uint32_t)((const unsigned short*)prm.gate_w)[k] : 0u, 0u);
          if (k < 392) {
            const int row = k / 7, e = row >= DH;
            cp_async8(sb + OFF_WPH + e * 2048 + sw64_off(row - DH * e, (k % 7) * 4), prm.w_phi + 2 * hp * DH * DH + k * 4);
          }
        }
        asm volatile("cp.async.wait_all;" ::: "memory");
        fence_async_smem();
        __syncwarp();
        if (lane == 0) mbar_arrive(BAR(B_BUILD), 1);
      }
      if (warp == 18) {
        if (elect_one()) {
#pragma unroll 1
          for (int i = 0; i < 4; i++) {
            mbar_wait(BAR(B_SIG + i), 0);
            PROF3(2 * i);
            cnt_arrive(i == 0 ? C_KV : i == 1 ? C_PART : (i == 2 ? C_OA : C_OB) + pt);
            PROF3(2 * i + 1);
            if (i == 1 || i == 2) {
              mbar_wait(BAR(B_X0FREE + i - 1), 0);
              mbar_expect_tx(BAR(B_WO + i - 1), 57344);
#pragma unroll 1
              for (int c = 0; c < 7; c++)
                tma_2d(sb + OFF_WO + (i - 1) * 57344 + c * 8192, i == 1 ? &tm_woa : &tm_wob, hp * 56, c * 64, BAR(B_WO + i - 1));
            }
          }
        }
      } else if (warp == 19) {
        if (lane == 0) {
          mbar_wait(BAR(B_SIG + 0), 0);
          cnt_wait(C_KV, NCTA);
        }
        __syncwarp();
        float ksq = 0.f, vsq = 0.f;
#pragma unroll
        for (int sl = 0; sl < 4; sl++) {
          float4 a = ldcg_f4(g_ksq + sl * 128 + lane * 4), b = ldcg_f4(g_vsq + sl * 128 + lane * 4);
          float m = fmaxf(fmaxf(a.x, a.y), fmaxf(a.z, a.w));
          m = __uint_as_float(__reduce_max_sync(~0u, __float_as_uint(m)));
          ksq += m;
          vsq = fmaxf(vsq, fmaxf(fmaxf(b.x, b.y), fmaxf(b.z, b.w)));
        }
        vsq = __uint_as_float(__reduce_max_sync(~0u, __float_as_uint(vsq)));
        if (lane == 0) {
          float* red = (float*)(sgen + OFF_RED);
          red[0] = ksq; red[1] = vsq;
          mbar_arrive(BAR(B_B1), 1);
        }
      } else {
        float4* z = (float4*)(g_kvacc[epoch ^ 1] + blockIdx.x * 256) + lane;
        z[0] = make_float4(0.f, 0.f, 0.f, 0.f);
        z[32] = make_float4(0.f, 0.f, 0.f, 0.f);
        if (lane == 0) {
          mbar_wait(BAR(B_SIG + 1), 0);
          cnt_wait(C_PART, NCTA);
          PROF_MARK(23);
          mbar_arrive(BAR(B_KVR), 1);
        }
      }
    }
  } else {
    asm volatile("setmaxnreg.inc.sync.aligned.u32 112;");
    const int mh = wg & 1, nh = wg >> 1, wq = warp & 3;
    float acc0[28], acc1[28], accs[4] = {0.f, 0.f, 0.f, 0.f};
#pragma unroll
    for (int i = 0; i < 28; i++) acc0[i] = acc1[i] = 0.f;
    int slot = 0, prev = 0;
    uint32_t par = 0;

#pragma unroll 1
    for (int stage = 0; stage < 2; stage++) {
      {
        const uint64_t dS = make_desc(stage ? sb + OFF_WO : sb + OFF_X + mh * 8192, 1024, 1024, 1);
        const uint64_t dR = make_desc(sb + OFF_RING + (stage ? mh * 8192 : nh * 16384), 1024, 1024, 1);
#pragma unroll 1
        for (int c = 0; c < 7; c++) {
          if (stage) mbar_wait(BAR(B_WO + (c >= 3)), 0);
          if (tid == 0) PROF2(stage * 16 + c * 2);
          mbar_wait(BAR(B_FULL + slot), par);
          if (tid == 0) PROF2(stage * 16 + c * 2 + 1);
          const uint64_t ds = dS + c * 1024, dr = dR + slot * 2048;
          const uint64_t dA0 = stage ? dr : ds, dA1 = stage ? dr + 1024 : ds, dB0 = stage ? ds : dr, dB1 = dB0 + 512;
          wg_fence();
#pragma unroll
          for (int ks = 0; ks < 4; ks++) {
            wgmma_ss_n56_ta0_tb1<1>(acc0, dA0 + ks * 2, dB0 + ks * 128);
            wgmma_ss_n56_ta0_tb1<1>(acc1, dA1 + ks * 2, dB1 + ks * 128);
          }
          wg_commit();
          wg_wait<1>();
          if (lane == 0 && c > 0) mbar_arrive(BAR(B_EMPTY + prev), 1 + stage);
          prev = slot;
          if (++slot == 3) { slot = 0; par ^= 1; }
        }
      }
      if (stage) break;
      int lane_;
      asm volatile("mov.u32 %0, %%laneid;" : "=r"(lane_));
      const int lq = lane_ & 3;
      const int rowl = wq * 16 + (lane_ >> 2);
      const int row0 = mh * 64 + rowl;
      {
        if (nh == 1) {
          mbar_wait(BAR(B_BUILD), 0);
          const uint64_t dX = make_desc(sb + OFF_X + mh * 8192, 1024, 1024, 1);
          const uint64_t dSlc = make_desc(sb + OFF_SLC, 128, 128, 0);
#pragma unroll 1
          for (int c = 0; c < 7; c++) {
            wg_fence();
            wgmma_ss_n8_ta0_tb1<1>(accs, dX + c * 1024, dSlc + c * 64);
            wgmma_ss_n8_ta0_tb1<1>(accs, dX + c * 1024 + 2, dSlc + c * 64 + 16);
            wgmma_ss_n8_ta0_tb1<1>(accs, dX + c * 1024 + 4, dSlc + c * 64 + 32);
            wgmma_ss_n8_ta0_tb1<1>(accs, dX + c * 1024 + 6, dSlc + c * 64 + 48);
            wg_commit();
          }
        }
        wg_wait<0>();
        fence_regs(acc0); fence_regs(acc1); fence_regs(accs);
        if (lane == 0) mbar_arrive(BAR(B_EMPTY + prev), 1);
        if (tid == 0) PROF_MARK(2);
        if (tid == 256) PROF_MARK(3);
        if (nh == 0) {
          float sq[4] = {0.f, 0.f, 0.f, 0.f};
#pragma unroll
          for (int i = 0; i < 28; i++) acc0[i] *= 0.18898223650461362f * 1.4426950408889634f;
#pragma unroll
          for (int j = 0; j < 7; j++) {
#pragma unroll
            for (int rr = 0; rr < 2; rr++) {
              const float s2 = acc0[4 * j + 2 * rr] * acc0[4 * j + 2 * rr] + acc0[4 * j + 2 * rr + 1] * acc0[4 * j + 2 * rr + 1];
              if (j < 3) sq[rr] += s2;
              else if (j > 3) sq[2 + rr] += s2;
              else { sq[rr] += (lq < 2) ? s2 : 0.f; sq[2 + rr] += (lq < 2) ? 0.f : s2; }
            }
          }
#pragma unroll
          for (int i = 0; i < 4; i++) sq[i] = quad_sum(sq[i]);
          const float mine = lq == 0 ? sq[0] : lq == 1 ? sq[1] : lq == 2 ? sq[2] : sq[3];
          ((float*)(sgen + OFF_QSQ))[(mh + (lq & 2)) * 64 + rowl + 8 * (lq & 1)] = mine <= 3.0e38f ? mine : __int_as_float(0x7f800000);
        } else {
          const int sl = hp & 3;
          const bool isk = hp < 4, real = (sl < 3) || (lq < 2);
          const int pos = pt * 128 + row0, kr = pos & 63;
          uint8_t* dst = g_kv_img + (pos >> 6) * 8192 + (isk ? 0 : 4096) + sw64_off(kr, sl * 8 + 2 * lq);
          const uint32_t pat = isk ? POLY_PAT >> (kr >> 3) : 0u;
          float mxv = 0.f;
#pragma unroll
          for (int rr = 0; rr < 2; rr++) {
            const float v0 = accs[2 * rr], v1 = accs[2 * rr + 1];
            const bool poly = (pat >> rr) & 1;
            const float sc = poly ? 2.f : 1.f;
            const float s2 = quad_sum(real ? v0 * v0 + v1 * v1 : 0.f);
            mxv = fmaxf(mxv, s2 <= 3.0e38f ? s2 : __int_as_float(0x7f800000));
            const uint32_t padv = lq == 2 ? (poly ? 0x443F4000u : 0x00003F80u) : (poly ? 0x3AB03F4Du : 0u);
            *(uint32_t*)(dst + rr * 512) = real ? pack_bf16(sc * v0, sc * v1) : padv;
            if (hp == 3 && lq == 2) g_gate[pos + 8 * rr] = rcpf(1.f + ex2f(-1.4426950408889634f * v0));
          }
          mxv = __uint_as_float(__reduce_max_sync(~0u, __float_as_uint(mxv)));
          if (lane == 0) (isk ? g_ksq : g_vsq)[sl * 128 + pt * 8 + mh * 4 + wq] = mxv;
          __syncwarp();
          if (lane == 0) mbar_arrive(BAR(B_SIG + 0), 1);
        }
      }
      if (tid == 0) PROF_MARK(4);
      if (tid == 256) PROF_MARK(5);
      {
        uint32_t h0[14], h1[14];
#pragma unroll
        for (int i = 0; i < 14; i++) { h0[i] = pack_bf16(acc0[2 * i], acc0[2 * i + 1]); h1[i] = pack_bf16(acc1[2 * i], acc1[2 * i + 1]); }
        bar_sync(1, 512);
        if (tid == 0) PROF_MARK(6);
#pragma unroll 1
        for (int r = 0; r < 2; r++) {
          store_heads(sb + (r ? (nh ? OFF_VA : OFF_QA) : (nh ? OFF_KA : OFF_QP)), h0, (r & nh) ? 0x00003F80u : 0u, row0, lq);
#pragma unroll
          for (int i = 0; i < 14; i++) h0[i] = h1[i];
        }
      }
      fence_async_smem();
      bar_sync(1, 512);
      if (tid == 0) PROF_MARK(7);

      const uint64_t dK = make_desc(sb + OFF_RING, 512, 512, 2);
      const uint64_t dhi = dK & 0xffffffff00000000ull;
      const uint32_t dlo0 = (uint32_t)dK;
      uint32_t ok = 0, q[8];
      float m0 = -3.0e38f, m1 = -3.0e38f, g0 = 0.f, g1 = 0.f;
      bool slow = false;
      float o[16];
#pragma unroll
      for (int i = 0; i < 16; i++) o[i] = 0.f;
#pragma unroll
      for (int i = 0; i < 8; i++) q[i] = 0u;
      const int kb = KB_AT, qb = QB_AT;
#pragma unroll 1
      for (int it = -1; it <= 8; it++) {
        uint32_t p[16];
        if (it == kb || it == qb || it == 8) {
          float t[16];
          wg_wait<0>();
          fence_regs(o);
          if (it < 8) {
            if (tid == 0) PROF_MARK(it == kb ? 27 : 11);
            const uint64_t dA = make_desc(sb + (it == kb ? OFF_KA : OFF_QA) + nh * 8192 + mh * 4096, 512, 512, 2);
            const uint64_t dB = make_desc(sb + OFF_WPH + nh * 2048, 512, 512, 2);
            float* kvacc = g_kvacc[epoch] + (2 * hp + nh) * 2048;
            float pa[16];
            wg_fence();
            wgmma_ss_n32_ta0_tb1<0>(pa, dA, dB);
            wgmma_ss_n32_ta0_tb1<1>(pa, dA + 2, dB + 64);
            wg_commit();
            if (it != kb) {
              mbar_wait(BAR(B_KVR), 0);
              const int tl = tid & 127;
              const float4 a = ldcg_f4(kvacc + tl * 16), b = ldcg_f4(kvacc + tl * 16 + 4), c = ldcg_f4(kvacc + tl * 16 + 8), d = ldcg_f4(kvacc + tl * 16 + 12);
              const uint32_t ad = sb + OFF_KVR + nh * 4096 + sw64_off(tl >> 1, (tl & 1) * 16);
              sts128(ad, make_uint4(pack_bf16(a.x, a.y), pack_bf16(a.z, a.w), pack_bf16(b.x, b.y), pack_bf16(b.z, b.w)));
              sts128(ad ^ 16u, make_uint4(pack_bf16(c.x, c.y), pack_bf16(c.z, c.w), pack_bf16(d.x, d.y), pack_bf16(d.z, d.w)));
            }
            wg_wait<0>();
            fence_regs(pa);
            uint32_t ph[16];
            feature_map(pa, ph, lq);
            const uint32_t rb = sb + OFF_PHI + wg * 8192 + rowl * 128 + lq * 4 + ((rowl & 7) << 4);
#pragma unroll
            for (int ch = 0; ch < 8; ch++) { sts32(rb ^ (ch << 4), ph[2 * ch]); sts32((rb ^ (ch << 4)) + 1024, ph[2 * ch + 1]); }
            fence_async_smem();
            bar_sync(4 + wg, 128);
            const uint64_t dP = make_desc(sb + OFF_PHI + wg * 8192, 1024, 1024, 1);
            if (it == kb) {
              const uint64_t dV = make_desc(sb + OFF_VA + nh * 8192 + mh * 4096, 512, 512, 2);
              float kv[16];
              wg_fence();
              wgmma_ss_n32_ta1_tb1<0>(kv, dP, dV);
#pragma unroll
              for (int ks = 1; ks < 4; ks++) wgmma_ss_n32_ta1_tb1<1>(kv, dP + ks * 128, dV + ks * 64);
              wg_commit();
              wg_wait<0>();
              fence_regs(kv);
              float* dst = kvacc + rowl * 32 + 2 * lq;
#pragma unroll
              for (int j = 0; j < 8; j++)
                asm volatile("red.global.add.v2.f32 [%0], {%1, %2};" ::"l"(dst + 8 * (j >> 1) + 256 * (j & 1)), "f"(kv[2 * j]), "f"(kv[2 * j + 1]) : "memory");
              __syncwarp();
              if (lane == 0) { mbar_arrive(BAR(B_SIG + 1), 1); mbar_arrive(BAR(B_X0FREE), 1); }
              if (tid == 0) PROF_MARK(28);
              goto after_block;
            } else {
              const uint64_t dR = make_desc(sb + OFF_KVR + nh * 4096, 512, 512, 2);
              wg_fence();
              wgmma_ss_n32_ta0_tb1<0>(t, dP, dR);
#pragma unroll
              for (int ks = 1; ks < 4; ks++) wgmma_ss_n32_ta0_tb1<1>(t, dP + ks * 2, dR + ks * 64);
              wg_commit();
              wg_wait<0>();
              fence_regs(t);
              if (lane == 0) mbar_arrive(BAR(B_X1FREE), 1);
            }
          } else {
            if (lane == 0) mbar_arrive(BAR(B_EMPTY + prev), 1);
            if (tid == 0) PROF_MARK(13);
#pragma unroll
            for (int i = 0; i < 16; i++) t[i] = o[i];
          }
          {
            const int br = it == 8;
            const float eps = br ? 0.f : 1e-6f;
            const float d0 = __shfl_sync(~0u, t[12], (lane_ & ~3) | 2), d1 = __shfl_sync(~0u, t[14], (lane_ & ~3) | 2);
            const float r0 = __fdividef(br ? 1.f - g0 : g0, d0 + eps), r1 = __fdividef(br ? 1.f - g1 : g1, d1 + eps);
            uint8_t* img = g_o_img + (size_t)((pt * 2 + br) * 14 + mh) * 8192 + rowl * 128;
            const int col0 = (2 * hp + nh) * DH + 2 * lq;
#pragma unroll
            for (int j = 0; j < 4; j++) {
              const int col = col0 + 8 * j;
              uint8_t* gp = img + (col >> 6) * 16384 + ((((col >> 3) ^ rowl) & 7) << 4) + (col & 7) * 2;
              const uint32_t v0 = pack_bf16(t[4 * j] * r0, t[4 * j + 1] * r0), v1 = pack_bf16(t[4 * j + 2] * r1, t[4 * j + 3] * r1);
              if (j < 3 || lq < 2) { *(uint32_t*)gp = v0; *(uint32_t*)(gp + 1024) = v1; }
            }
            __syncwarp();
            if (lane == 0) mbar_arrive(BAR(B_SIG + 2 + br), 1);
            if (tid == 0) PROF_MARK(12 + 2 * br);
            if (br) break;
          }
        }
      after_block:
        if (it < 0) {
              mbar_wait(BAR(B_B1), 0);
              if (tid == 0) PROF_MARK(9);
              g0 = ldcg_f(g_gate + pt * 128 + row0); g1 = ldcg_f(g_gate + pt * 128 + row0 + 8);
              const float* red = (const float*)(sgen + OFF_RED);
              const float ksq = red[0] * (1.02f * 1.02f), vsq = red[1];
              const float* qsq = (const float*)(sgen + OFF_QSQ);
              float b0, b1;
              asm("sqrt.approx.ftz.f32 %0, %1;" : "=f"(b0) : "f"(qsq[wg * 64 + rowl] * ksq));
              asm("sqrt.approx.ftz.f32 %0, %1;" : "=f"(b1) : "f"(qsq[wg * 64 + rowl + 8] * ksq));
              const float4 qa4 = ((const float4*)qsq)[lane_], qb4 = ((const float4*)qsq)[32 + lane_];
              const float qmax = fmaxf(fmaxf(fmaxf(qa4.x, qa4.y), fmaxf(qa4.z, qa4.w)), fmaxf(fmaxf(qb4.x, qb4.y), fmaxf(qb4.z, qb4.w)));
              slow = __any_sync(~0u, !(qmax * ksq <= 92.f * 92.f) || !(vsq <= 1.0e24f));
              if (tid == 0) { *(volatile int*)(sgen + OFF_RED + 8) = slow; mbar_arrive(BAR(B_SLOW), 1); }
              const uint32_t qa = sb + OFF_QP + nh * 8192;
              const int r = mh * 64 + wq * 16 + (lane_ & 7) + ((lane_ >> 3) & 1) * 8;
#pragma unroll
              for (int ks = 0; ks < 2; ks++)
                asm volatile("ldmatrix.sync.aligned.m8n8.x4.shared.b16 {%0, %1, %2, %3}, [%4];"
                             : "=r"(q[4 * ks]), "=r"(q[4 * ks + 1]), "=r"(q[4 * ks + 2]), "=r"(q[4 * ks + 3])
                             : "r"(qa + sw64_off(r, ks * 16 + (lane_ >> 4) * 8)) : "memory");
              if (lq >= 2 && !slow) {
                q[6] = lq == 2 ? pack_bf16(64.f - b0, 1.f) : 0x3F803F80u;
                q[7] = lq == 2 ? pack_bf16(64.f - b1, 1.f) : 0x3F803F80u;
              }
              __syncwarp();
              if (lane == 0) mbar_arrive(BAR(B_X0FREE), 1);
              if (__builtin_expect(slow, 0)) {
#pragma unroll 1
                for (int j64 = 0; j64 < 32; j64++) {
                  float s[32];
                  if ((j64 & 3) == 0) mbar_wait(BAR(B_FULL + slot), par);
                  const uint32_t lo = dlo0 + slot * 2048 + (j64 & 3) * 512;
                  wg_fence();
                  wgmma_rs_n64_tb0<0>(s, q[0], q[1], q[2], q[3], dhi | lo);
                  wgmma_rs_n64_tb0<1>(s, q[4], q[5], q[6], q[7], dhi | (lo + 2));
                  wg_commit();
                  wg_wait<0>();
                  fence_regs(s);
#pragma unroll
                  for (int j = 0; j < 8; j++) {
                    const float sc = ((POLY_PAT >> j) & 1) ? 0.5f : 1.f;
                    m0 = fmaxf(m0, fmaxf(s[4 * j], s[4 * j + 1]) * sc);
                    m1 = fmaxf(m1, fmaxf(s[4 * j + 2], s[4 * j + 3]) * sc);
                  }
                  if ((j64 & 3) == 3) {
                    if (lane == 0) mbar_arrive(BAR(B_EMPTY + slot), 1);
                    if (++slot == 3) { slot = 0; par ^= 1; }
                  }
                }
                m0 = quad_max(m0); m1 = quad_max(m1);
              }
              if (tid == 0) PROF_MARK(10);
              continue;
        }
        const uint32_t lo = dlo0 + slot * 2048;
        if (!ok) mbar_wait(BAR(B_FULL + slot), par);
        int nslot = slot + 1;
        uint32_t npar = par;
        if (nslot == 3) { nslot = 0; npar ^= 1; }
        if (__builtin_expect(slow, 0)) {
          if (lane == 0 && it > 0) mbar_arrive(BAR(B_EMPTY + prev), 1);
#pragma unroll 1
          for (int u = 0; u < 4; u++) {
            float s[32];
            uint32_t ps[16];
            wg_fence();
            wgmma_rs_n64_tb0<0>(s, q[0], q[1], q[2], q[3], dhi | (lo + u * 512));
            wgmma_rs_n64_tb0<1>(s, q[4], q[5], q[6], q[7], dhi | (lo + u * 512 + 2));
            wg_commit();
            wg_wait<0>();
            fence_regs(s);
#pragma unroll
            for (int j = 0; j < 8; j++) {
              const float sc = ((POLY_PAT >> j) & 1) ? 0.5f : 1.f;
              ps[2 * j] = pack_bf16(ex2f(fmaf(s[4 * j], sc, -m0)), ex2f(fmaf(s[4 * j + 1], sc, -m0)));
              ps[2 * j + 1] = pack_bf16(ex2f(fmaf(s[4 * j + 2], sc, -m1)), ex2f(fmaf(s[4 * j + 3], sc, -m1)));
            }
            wg_fence();
#pragma unroll
            for (int ks = 0; ks < 4; ks++)
              wgmma_rs_n32_tb1<1>(o, ps[4 * ks], ps[4 * ks + 1], ps[4 * ks + 2], ps[4 * ks + 3], dhi | (lo + u * 512 + 256 + ks * 64));
            wg_commit();
            wg_wait<0>();
            fence_regs(o);
          }
        } else {
          float s[32];
          wg_fence();
          wgmma_rs_n64_tb0<0>(s, q[0], q[1], q[2], q[3], dhi | lo);
          wgmma_rs_n64_tb0<1>(s, q[4], q[5], q[6], q[7], dhi | (lo + 2));
          wg_commit();
#pragma unroll
          for (int u = 0; u < 4; u++) {
            wg_wait<0>();
            fence_regs(s);
            if (u == 0 && lane == 0 && it > 0) mbar_arrive(BAR(B_EMPTY + prev), 1);
            if (u == 2) ok = mbar_test(BAR(B_FULL + nslot), npar);
#pragma unroll
            for (int j = 0; j < 8; j++) {
              if ((POLY_PAT >> j) & 1) {
                p[2 * j] = exp2_pair_fma(s[4 * j], s[4 * j + 1], 0x3F003F00u, 0x00030003u);
                p[2 * j + 1] = exp2_pair_fma(s[4 * j + 2], s[4 * j + 3], 0x3F003F00u, 0x00030003u);
              } else {
                p[2 * j] = pack_bf16(ex2f(s[4 * j]), ex2f(s[4 * j + 1]));
                p[2 * j + 1] = pack_bf16(ex2f(s[4 * j + 2]), ex2f(s[4 * j + 3]));
              }
            }
            wg_fence();
#pragma unroll
            for (int ks = 0; ks < 4; ks++)
              wgmma_rs_n32_tb1<1>(o, p[4 * ks], p[4 * ks + 1], p[4 * ks + 2], p[4 * ks + 3], dhi | (lo + u * 512 + 256 + ks * 64));
            if (u < 3) {
              wgmma_rs_n64_tb0<0>(s, q[0], q[1], q[2], q[3], dhi | (lo + (u + 1) * 512));
              wgmma_rs_n64_tb0<1>(s, q[4], q[5], q[6], q[7], dhi | (lo + (u + 1) * 512 + 2));
            }
            wg_commit();
          }
        }
        prev = slot; slot = nslot; par = npar;
      }
      wg_wait<0>();
      if (nh == 1) return;
#pragma unroll
      for (int i = 0; i < 28; i++) acc0[i] = acc1[i] = 0.f;
#pragma unroll
      for (int i = 0; i < 4; i++) accs[i] = 0.f;
    }
    wg_wait<0>();
    fence_regs(acc0); fence_regs(acc1);
    if (tid == 0) PROF_MARK(17);
    __nv_bfloat16* op = prm.out + (size_t)(pt * 128 + mh * 64 + wq * 16 + (lane >> 2)) * DM + hp * 56 + 2 * (lane & 3);
#pragma unroll
    for (int j = 0; j < 7; j++) {
      *(uint32_t*)(op + 8 * j) = pack_bf16(acc0[4 * j] + acc1[4 * j], acc0[4 * j + 1] + acc1[4 * j + 1]);
      *(uint32_t*)(op + 8 * DM + 8 * j) = pack_bf16(acc0[4 * j + 2] + acc1[4 * j + 2], acc0[4 * j + 3] + acc1[4 * j + 3]);
    }
    if (tid == 0) { PROF_MARK(18); PROF_CLK(31); }
    if (tid == 0) {
      unsigned prevd = atomicAdd(&g_cnt[C_DONE * 32], 1u);
      if (prevd == NCTA - 1) {
#pragma unroll 1
        for (int i = 0; i < C_N; i++) g_cnt[i * 32] = 0;
        g_epoch = epoch ^ 1;
      }
    }
  }
}

typedef CUresult (*EncodeFn)(CUtensorMap*, CUtensorMapDataType, cuuint32_t, void*, const cuuint64_t*, const cuuint64_t*,
                             const cuuint32_t*, const cuuint32_t*, CUtensorMapInterleave, CUtensorMapSwizzle,
                             CUtensorMapL2promotion, CUtensorMapFloatOOBfill);

void make_map(EncodeFn enc, CUtensorMap* tm, const void* ptr, uint64_t cols, uint64_t rows, uint32_t box_rows) {
  cuuint64_t dims[2] = {cols, rows};
  cuuint64_t strides[1] = {cols * 2};
  cuuint32_t box[2] = {64, box_rows};
  cuuint32_t es[2] = {1, 1};
  enc(tm, CU_TENSOR_MAP_DATA_TYPE_BFLOAT16, 2, const_cast<void*>(ptr), dims, strides, box, es, CU_TENSOR_MAP_INTERLEAVE_NONE,
      CU_TENSOR_MAP_SWIZZLE_128B, CU_TENSOR_MAP_L2_PROMOTION_L2_128B, CU_TENSOR_MAP_FLOAT_OOB_FILL_NONE);
}

}

extern "C" void kernel_launch(void* const* d_in, const int* in_sizes, int n_in, void* d_out, int out_size) {
  (void)in_sizes; (void)n_in; (void)out_size;
  static EncodeFn enc = nullptr;
  if (!enc) {
    void* fn = nullptr;
    cudaDriverEntryPointQueryResult qr;
    cudaGetDriverEntryPoint("cuTensorMapEncodeTiled", &fn, cudaEnableDefault, &qr);
    enc = (EncodeFn)fn;
    cudaFuncSetAttribute(fused_kernel, cudaFuncAttributeMaxDynamicSharedMemorySize, SMEM_BYTES);
  }
  CUtensorMap tm_x, tm_wqkv, tm_wq, tm_woa, tm_wob;
  make_map(enc, &tm_x, d_in[0], DM, S_LEN, 128);
  make_map(enc, &tm_wqkv, d_in[1], 3 * DM, DM, 64);
  make_map(enc, &tm_wq, d_in[5], DM, DM, 64);
  make_map(enc, &tm_woa, d_in[3], DM, DM, 64);
  make_map(enc, &tm_wob, d_in[8], DM, DM, 64);
  Params prm;
  prm.w_phi = (const __nv_bfloat16*)d_in[2];
  prm.wk = (const __nv_bfloat16*)d_in[6];
  prm.wv = (const __nv_bfloat16*)d_in[7];
  prm.gate_w = (const __nv_bfloat16*)d_in[9];
  prm.out = (__nv_bfloat16*)d_out;
  fused_kernel<<<NCTA, NTHREADS, SMEM_BYTES>>>(tm_x, tm_wqkv, tm_wq, tm_woa, tm_wob, prm);
}
```

```cpp
#include <cuda_runtime.h>
#include <cuda_bf16.h>
#include <cuda.h>
#include <stdint.h>

namespace {

constexpr int S_LEN = 2048, DM = 448, DH = 28;
constexpr int NCTA = 128;
constexpr int NTHREADS = 640;
constexpr uint32_t POLY_PAT = 0x57;

#define KB_AT (nh ? -1 : 1)
#define QB_AT (4 + nh)

constexpr int OFF_X = 0;
constexpr int OFF_KA = 0;
constexpr int OFF_VA = 16384;
constexpr int OFF_QP = 32768;
constexpr int OFF_QA = 57344;
constexpr int OFF_KVR = 73728;
constexpr int OFF_PHI = 81920;
constexpr int OFF_WO = 0;
constexpr int OFF_RING = 114688;
constexpr int OFF_WPH = 212992;
constexpr int OFF_SLC = 217088;
constexpr int OFF_QSQ = 224256;
constexpr int OFF_RED = 225792;
constexpr int OFF_BAR = 225856;
constexpr int SMEM_BYTES = 226368 + 1024;

constexpr int B_FULL = 0, B_EMPTY = 3, B_WO = 6  , B_KVR = 8, B_X0FREE = 9, B_X1FREE = 10, B_B1 = 11, B_SLOW = 12,
              B_BUILD = 13, B_SIG = 14  , B_N = 18;

constexpr int C_KV = 0, C_PART = 1, C_DONE = 3, C_OA = 4, C_OB = 20, C_N = 36;

__device__ __align__(1024) uint8_t g_kv_img[32 * 8192];
__device__ __align__(16) float g_ksq[512];
__device__ __align__(16) float g_vsq[512];
__device__ __align__(16) float g_gate[S_LEN];
__device__ __align__(1024) float g_kvacc[2][16 * 64 * 32];
__device__ unsigned g_epoch;
__device__ __align__(1024) uint8_t g_o_img[2 * 16 * 14 * 8192];
__device__ unsigned g_cnt[C_N * 32];

#define PROF3(i) do { } while (0)
#define PROF2(i) do { } while (0)
#define PROF_CLK(i) do { } while (0)
#define PROF_MARK(i) do { } while (0)
__device__ __forceinline__ uint32_t smem_u32(const void* p) { return (uint32_t)__cvta_generic_to_shared(p); }
__device__ __forceinline__ void mbar_init(uint32_t a, int cnt) {
  asm volatile("mbarrier.init.shared::cta.b64 [%0], %1;" ::"r"(a), "r"(cnt) : "memory");
}
__device__ __forceinline__ void mbar_expect_tx(uint32_t a, uint32_t bytes) {
  asm volatile("mbarrier.arrive.expect_tx.shared::cta.b64 _, [%0], %1;" ::"r"(a), "r"(bytes) : "memory");
}
__device__ __forceinline__ void mbar_arrive(uint32_t a, uint32_t cnt) {
  asm volatile("mbarrier.arrive.shared::cta.b64 _, [%0], %1;" ::"r"(a), "r"(cnt) : "memory");
}
__device__ __forceinline__ void mbar_wait(uint32_t a, uint32_t parity) {
  asm volatile(
      "{\n.reg .pred p;\n.reg .u32 c;\nmov.u32 c, 0;\n"
      "W_%=:\nmbarrier.try_wait.parity.shared::cta.b64 p, [%0], %1;\n"
      "add.u32 c, c, 1;\nsetp.lt.and.u32 p, c, 0x1000000, !p;\n@p bra W_%=;\n}"
      ::"r"(a), "r"(parity) : "memory");
}
__device__ __forceinline__ uint32_t mbar_test(uint32_t a, uint32_t parity) {
  uint32_t ok;
  asm volatile("{\n.reg .pred p;\nmbarrier.test_wait.parity.shared::cta.b64 p, [%1], %2;\nselp.u32 %0, 1, 0, p;\n}"
               : "=r"(ok) : "r"(a), "r"(parity) : "memory");
  return ok;
}
__device__ __forceinline__ bool elect_one() {
  uint32_t r;
  asm volatile("{\n.reg .pred p;\nelect.sync _|p, 0xffffffff;\nselp.u32 %0, 1, 0, p;\n}" : "=r"(r));
  return r != 0;
}
__device__ __forceinline__ void tma_2d(uint32_t dst, const CUtensorMap* tm, int c0, int c1, uint32_t bar) {
  asm volatile("cp.async.bulk.tensor.2d.shared::cluster.global.mbarrier::complete_tx::bytes [%0], [%1, {%3, %4}], [%2];"
               ::"r"(dst), "l"(tm), "r"(bar), "r"(c0), "r"(c1) : "memory");
}
__device__ __forceinline__ void bulk_g2s(uint32_t dst, const void* src, uint32_t bytes, uint32_t bar) {
  asm volatile("cp.async.bulk.shared::cluster.global.mbarrier::complete_tx::bytes [%0], [%1], %2, [%3];"
               ::"r"(dst), "l"(src), "r"(bytes), "r"(bar) : "memory");
}
__device__ __forceinline__ void cp_async8(uint32_t dst, const void* src) {
  asm volatile("cp.async.ca.shared.global [%0], [%1], 8;" ::"r"(dst), "l"(src) : "memory");
}
__device__ __forceinline__ void fence_async_smem() { asm volatile("fence.proxy.async.shared::cta;" ::: "memory"); }
__device__ __forceinline__ void fence_async_all() { asm volatile("fence.proxy.async.global;" ::: "memory"); }
__device__ __forceinline__ float ldcg_f(const float* p) { float v; asm volatile("ld.global.cg.f32 %0, [%1];" : "=f"(v) : "l"(p) : "memory"); return v; }
__device__ __forceinline__ void bar_sync(int id, int n) { asm volatile("bar.sync %0, %1;" ::"r"(id), "r"(n) : "memory"); }
__device__ __forceinline__ void cnt_arrive(int idx) {
  asm volatile("red.release.gpu.global.add.u32 [%0], 1;" ::"l"(&g_cnt[idx * 32]) : "memory");
}
__device__ __forceinline__ void cnt_wait(int idx, unsigned target) {
  unsigned v, n = 0;
#pragma unroll 1
  while (true) {
    asm volatile("ld.acquire.gpu.global.u32 %0, [%1];" : "=r"(v) : "l"(&g_cnt[idx * 32]) : "memory");
    if (v >= target || ++n >= (1u << 22)) break;
    __nanosleep(32);
  }
}
__device__ __forceinline__ void wg_fence() { asm volatile("wgmma.fence.sync.aligned;" ::: "memory"); }
__device__ __forceinline__ void wg_commit() { asm volatile("wgmma.commit_group.sync.aligned;" ::: "memory"); }
template <int N> __device__ __forceinline__ void wg_wait() { asm volatile("wgmma.wait_group.sync.aligned %0;" ::"n"(N) : "memory"); }
template <int N> __device__ __forceinline__ void fence_regs(float (&d)[N]) {
#pragma unroll
  for (int i = 0; i < N; i++) asm volatile("" : "+f"(d[i])::"memory");
}
__device__ __forceinline__ uint64_t make_desc(uint32_t saddr, uint32_t lbo, uint32_t sbo, uint32_t swz) {
  return (uint64_t)((saddr & 0x3FFFF) >> 4) | ((uint64_t)(lbo >> 4) << 16) | ((uint64_t)(sbo >> 4) << 32) | ((uint64_t)swz << 62);
}
__device__ __forceinline__ float ex2f(float x) { float y; asm("ex2.approx.ftz.f32 %0, %1;" : "=f"(y) : "f"(x)); return y; }
__device__ __forceinline__ float rcpf(float x) { float y; asm("rcp.approx.ftz.f32 %0, %1;" : "=f"(y) : "f"(x)); return y; }
__device__ __forceinline__ uint32_t pack_bf16(float lo, float hi) {
  uint32_t r; asm("cvt.rn.bf16x2.f32 %0, %1, %2;" : "=r"(r) : "f"(hi), "f"(lo)); return r;
}
__device__ __forceinline__ uint32_t lop_and_or(uint32_t a, uint32_t m, uint32_t c) {
  uint32_t r; asm("lop3.b32 %0, %1, %2, %3, 0xEA;" : "=r"(r) : "r"(a), "r"(m), "r"(c)); return r;
}
__device__ __forceinline__ void sts32(uint32_t a, uint32_t v) { asm volatile("st.shared.b32 [%0], %1;" ::"r"(a), "r"(v) : "memory"); }
__device__ __forceinline__ void sts64(uint32_t a, uint32_t v0, uint32_t v1) { asm volatile("st.shared.v2.b32 [%0], {%1, %2};" ::"r"(a), "r"(v0), "r"(v1) : "memory"); }
__device__ __forceinline__ void sts128(uint32_t a, uint4 v) {
  asm volatile("st.shared.v4.b32 [%0], {%1, %2, %3, %4};" ::"r"(a), "r"(v.x), "r"(v.y), "r"(v.z), "r"(v.w) : "memory");
}
__device__ __forceinline__ float4 ldcg_f4(const float* p) {
  float4 v; asm volatile("ld.global.cg.v4.f32 {%0, %1, %2, %3}, [%4];" : "=f"(v.x), "=f"(v.y), "=f"(v.z), "=f"(v.w) : "l"(p) : "memory"); return v;
}
__device__ __forceinline__ float quad_sum(float v) { v += __shfl_xor_sync(~0u, v, 1); v += __shfl_xor_sync(~0u, v, 2); return v; }
__device__ __forceinline__ float quad_max(float v) { v = fmaxf(v, __shfl_xor_sync(~0u, v, 1)); v = fmaxf(v, __shfl_xor_sync(~0u, v, 2)); return v; }

template <int SD> __device__ __forceinline__ void wgmma_ss_n56_ta0_tb1(float (&d)[28], uint64_t da, uint64_t db) {
  if (SD) asm volatile("wgmma.mma_async.sync.aligned.m64n56k16.f32.bf16.bf16 {%0, %1, %2, %3, %4, %5, %6, %7, %8, %9, %10, %11, %12, %13, %14, %15, %16, %17, %18, %19, %20, %21, %22, %23, %24, %25, %26, %27}, %28, %29, 1, 1, 1, 0, 1;\n"
    : "+f"(d[0]), "+f"(d[1]), "+f"(d[2]), "+f"(d[3]), "+f"(d[4]), "+f"(d[5]), "+f"(d[6]), "+f"(d[7]), "+f"(d[8]), "+f"(d[9]), "+f"(d[10]), "+f"(d[11]), "+f"(d[12]), "+f"(d[13]), "+f"(d[14]), "+f"(d[15]), "+f"(d[16]), "+f"(d[17]), "+f"(d[18]), "+f"(d[19]), "+f"(d[20]), "+f"(d[21]), "+f"(d[22]), "+f"(d[23]), "+f"(d[24]), "+f"(d[25]), "+f"(d[26]), "+f"(d[27])
    : "l"(da), "l"(db));
  else asm volatile("wgmma.mma_async.sync.aligned.m64n56k16.f32.bf16.bf16 {%0, %1, %2, %3, %4, %5, %6, %7, %8, %9, %10, %11, %12, %13, %14, %15, %16, %17, %18, %19, %20, %21, %22, %23, %24, %25, %26, %27}, %28, %29, 0, 1, 1, 0, 1;\n"
    : "=f"(d[0]), "=f"(d[1]), "=f"(d[2]), "=f"(d[3]), "=f"(d[4]), "=f"(d[5]), "=f"(d[6]), "=f"(d[7]), "=f"(d[8]), "=f"(d[9]), "=f"(d[10]), "=f"(d[11]), "=f"(d[12]), "=f"(d[13]), "=f"(d[14]), "=f"(d[15]), "=f"(d[16]), "=f"(d[17]), "=f"(d[18]), "=f"(d[19]), "=f"(d[20]), "=f"(d[21]), "=f"(d[22]), "=f"(d[23]), "=f"(d[24]), "=f"(d[25]), "=f"(d[26]), "=f"(d[27])
    : "l"(da), "l"(db));
}
template <int SD> __device__ __forceinline__ void wgmma_ss_n8_ta0_tb1(float (&d)[4], uint64_t da, uint64_t db) {
  if (SD) asm volatile("wgmma.mma_async.sync.aligned.m64n8k16.f32.bf16.bf16 {%0, %1, %2, %3}, %4, %5, 1, 1, 1, 0, 1;\n"
    : "+f"(d[0]), "+f"(d[1]), "+f"(d[2]), "+f"(d[3])
    : "l"(da), "l"(db));
  else asm volatile("wgmma.mma_async.sync.aligned.m64n8k16.f32.bf16.bf16 {%0, %1, %2, %3}, %4, %5, 0, 1, 1, 0, 1;\n"
    : "=f"(d[0]), "=f"(d[1]), "=f"(d[2]), "=f"(d[3])
    : "l"(da), "l"(db));
}
template <int SD> __device__ __forceinline__ void wgmma_ss_n32_ta1_tb1(float (&d)[16], uint64_t da, uint64_t db) {
  if (SD) asm volatile("wgmma.mma_async.sync.aligned.m64n32k16.f32.bf16.bf16 {%0, %1, %2, %3, %4, %5, %6, %7, %8, %9, %10, %11, %12, %13, %14, %15}, %16, %17, 1, 1, 1, 1, 1;\n"
    : "+f"(d[0]), "+f"(d[1]), "+f"(d[2]), "+f"(d[3]), "+f"(d[4]), "+f"(d[5]), "+f"(d[6]), "+f"(d[7]), "+f"(d[8]), "+f"(d[9]), "+f"(d[10]), "+f"(d[11]), "+f"(d[12]), "+f"(d[13]), "+f"(d[14]), "+f"(d[15])
    : "l"(da), "l"(db));
  else asm volatile("wgmma.mma_async.sync.aligned.m64n32k16.f32.bf16.bf16 {%0, %1, %2, %3, %4, %5, %6, %7, %8, %9, %10, %11, %12, %13, %14, %15}, %16, %17, 0, 1, 1, 1, 1;\n"
    : "=f"(d[0]), "=f"(d[1]), "=f"(d[2]), "=f"(d[3]), "=f"(d[4]), "=f"(d[5]), "=f"(d[6]), "=f"(d[7]), "=f"(d[8]), "=f"(d[9]), "=f"(d[10]), "=f"(d[11]), "=f"(d[12]), "=f"(d[13]), "=f"(d[14]), "=f"(d[15])
    : "l"(da), "l"(db));
}
template <int SD> __device__ __forceinline__ void wgmma_ss_n32_ta0_tb1(float (&d)[16], uint64_t da, uint64_t db) {
  if (SD) asm volatile("wgmma.mma_async.sync.aligned.m64n32k16.f32.bf16.bf16 {%0, %1, %2, %3, %4, %5, %6, %7, %8, %9, %10, %11, %12, %13, %14, %15}, %16, %17, 1, 1, 1, 0, 1;\n"
    : "+f"(d[0]), "+f"(d[1]), "+f"(d[2]), "+f"(d[3]), "+f"(d[4]), "+f"(d[5]), "+f"(d[6]), "+f"(d[7]), "+f"(d[8]), "+f"(d[9]), "+f"(d[10]), "+f"(d[11]), "+f"(d[12]), "+f"(d[13]), "+f"(d[14]), "+f"(d[15])
    : "l"(da), "l"(db));
  else asm volatile("wgmma.mma_async.sync.aligned.m64n32k16.f32.bf16.bf16 {%0, %1, %2, %3, %4, %5, %6, %7, %8, %9, %10, %11, %12, %13, %14, %15}, %16, %17, 0, 1, 1, 0, 1;\n"
    : "=f"(d[0]), "=f"(d[1]), "=f"(d[2]), "=f"(d[3]), "=f"(d[4]), "=f"(d[5]), "=f"(d[6]), "=f"(d[7]), "=f"(d[8]), "=f"(d[9]), "=f"(d[10]), "=f"(d[11]), "=f"(d[12]), "=f"(d[13]), "=f"(d[14]), "=f"(d[15])
    : "l"(da), "l"(db));
}
template <int SD> __device__ __forceinline__ void wgmma_rs_n64_tb0(float (&d)[32], uint32_t a0, uint32_t a1, uint32_t a2, uint32_t a3, uint64_t db) {
  if (SD) asm volatile("wgmma.mma_async.sync.aligned.m64n64k16.f32.bf16.bf16 {%0, %1, %2, %3, %4, %5, %6, %7, %8, %9, %10, %11, %12, %13, %14, %15, %16, %17, %18, %19, %20, %21, %22, %23, %24, %25, %26, %27, %28, %29, %30, %31}, {%32, %33, %34, %35}, %36, 1, 1, 1, 0;\n"
    : "+f"(d[0]), "+f"(d[1]), "+f"(d[2]), "+f"(d[3]), "+f"(d[4]), "+f"(d[5]), "+f"(d[6]), "+f"(d[7]), "+f"(d[8]), "+f"(d[9]), "+f"(d[10]), "+f"(d[11]), "+f"(d[12]), "+f"(d[13]), "+f"(d[14]), "+f"(d[15]), "+f"(d[16]), "+f"(d[17]), "+f"(d[18]), "+f"(d[19]), "+f"(d[20]), "+f"(d[21]), "+f"(d[22]), "+f"(d[23]), "+f"(d[24]), "+f"(d[25]), "+f"(d[26]), "+f"(d[27]), "+f"(d[28]), "+f"(d[29]), "+f"(d[30]), "+f"(d[31])
    : "r"(a0), "r"(a1), "r"(a2), "r"(a3), "l"(db));
  else asm volatile("wgmma.mma_async.sync.aligned.m64n64k16.f32.bf16.bf16 {%0, %1, %2, %3, %4, %5, %6, %7, %8, %9, %10, %11, %12, %13, %14, %15, %16, %17, %18, %19, %20, %21, %22, %23, %24, %25, %26, %27, %28, %29, %30, %31}, {%32, %33, %34, %35}, %36, 0, 1, 1, 0;\n"
    : "=f"(d[0]), "=f"(d[1]), "=f"(d[2]), "=f"(d[3]), "=f"(d[4]), "=f"(d[5]), "=f"(d[6]), "=f"(d[7]), "=f"(d[8]), "=f"(d[9]), "=f"(d[10]), "=f"(d[11]), "=f"(d[12]), "=f"(d[13]), "=f"(d[14]), "=f"(d[15]), "=f"(d[16]), "=f"(d[17]), "=f"(d[18]), "=f"(d[19]), "=f"(d[20]), "=f"(d[21]), "=f"(d[22]), "=f"(d[23]), "=f"(d[24]), "=f"(d[25]), "=f"(d[26]), "=f"(d[27]), "=f"(d[28]), "=f"(d[29]), "=f"(d[30]), "=f"(d[31])
    : "r"(a0), "r"(a1), "r"(a2), "r"(a3), "l"(db));
}
template <int SD> __device__ __forceinline__ void wgmma_rs_n32_tb1(float (&d)[16], uint32_t a0, uint32_t a1, uint32_t a2, uint32_t a3, uint64_t db) {
  if (SD) asm volatile("wgmma.mma_async.sync.aligned.m64n32k16.f32.bf16.bf16 {%0, %1, %2, %3, %4, %5, %6, %7, %8, %9, %10, %11, %12, %13, %14, %15}, {%16, %17, %18, %19}, %20, 1, 1, 1, 1;\n"
    : "+f"(d[0]), "+f"(d[1]), "+f"(d[2]), "+f"(d[3]), "+f"(d[4]), "+f"(d[5]), "+f"(d[6]), "+f"(d[7]), "+f"(d[8]), "+f"(d[9]), "+f"(d[10]), "+f"(d[11]), "+f"(d[12]), "+f"(d[13]), "+f"(d[14]), "+f"(d[15])
    : "r"(a0), "r"(a1), "r"(a2), "r"(a3), "l"(db));
  else asm volatile("wgmma.mma_async.sync.aligned.m64n32k16.f32.bf16.bf16 {%0, %1, %2, %3, %4, %5, %6, %7, %8, %9, %10, %11, %12, %13, %14, %15}, {%16, %17, %18, %19}, %20, 0, 1, 1, 1;\n"
    : "=f"(d[0]), "=f"(d[1]), "=f"(d[2]), "=f"(d[3]), "=f"(d[4]), "=f"(d[5]), "=f"(d[6]), "=f"(d[7]), "=f"(d[8]), "=f"(d[9]), "=f"(d[10]), "=f"(d[11]), "=f"(d[12]), "=f"(d[13]), "=f"(d[14]), "=f"(d[15])
    : "r"(a0), "r"(a1), "r"(a2), "r"(a3), "l"(db));
}

__device__ __forceinline__ uint32_t sw64_off(int row, int d) { return row * 64 + ((((d >> 3) ^ (row >> 1)) & 3) << 4) + (d & 7) * 2; }

__device__ __forceinline__ uint32_t exp2_pair_fma(float t0, float t1, uint32_t c_half, uint32_t c_3) {
  uint32_t y0, y;
  asm("prmt.b32 %0, %1, %2, 0x6521;" : "=r"(y0) : "r"(__float_as_uint(t0)), "r"(__float_as_uint(t1)));
  uint32_t h = lop_and_or(y0, 0x007F007Fu, c_half);
  uint32_t e = lop_and_or(y0, 0xFF80FF80u, c_3);
  asm("fma.rn.bf16x2 %0, %1, %2, %3;" : "=r"(y) : "r"(y0), "r"(h), "r"(e));
  return y;
}

__device__ __forceinline__ void feature_map(float (&v)[16], uint32_t (&ph)[16], int lq) {
  const float L2E = 1.4426950408889634f;
  const bool tail_ok = lq < 2;
  float mx[2], mn[2], b[16], sa[2], sn[2];
#pragma unroll
  for (int r = 0; r < 2; r++) {
    const int o = 2 * r;
    if (!tail_ok) { v[o + 12] = v[o]; v[o + 13] = v[o]; }
    mx[r] = fmaxf(fmaxf(fmaxf(v[o], v[o + 1]), fmaxf(v[o + 4], v[o + 5])), fmaxf(fmaxf(v[o + 8], v[o + 9]), fmaxf(v[o + 12], v[o + 13])));
    mn[r] = fminf(fminf(fminf(v[o], v[o + 1]), fminf(v[o + 4], v[o + 5])), fminf(fminf(v[o + 8], v[o + 9]), fminf(v[o + 12], v[o + 13])));
  }
#pragma unroll
  for (int o = 1; o <= 2; o <<= 1)
#pragma unroll
    for (int r = 0; r < 2; r++) { mx[r] = fmaxf(mx[r], __shfl_xor_sync(~0u, mx[r], o)); mn[r] = fminf(mn[r], __shfl_xor_sync(~0u, mn[r], o)); }
#pragma unroll
  for (int r = 0; r < 2; r++) {
    const int o = 2 * r;
    const float cx = -mx[r] * L2E, cn = mn[r] * L2E;
#pragma unroll
    for (int i = 0; i < 8; i++) {
      const int k = o + 4 * (i >> 1) + (i & 1);
      b[k] = ex2f(fmaf(v[k], -L2E, cn));
      v[k] = ex2f(fmaf(v[k], L2E, cx));
    }
    if (!tail_ok) { v[o + 12] = v[o + 13] = b[o + 12] = b[o + 13] = 0.f; }
    sa[r] = ((v[o] + v[o + 1]) + (v[o + 4] + v[o + 5])) + ((v[o + 8] + v[o + 9]) + (v[o + 12] + v[o + 13]));
    sn[r] = ((b[o] + b[o + 1]) + (b[o + 4] + b[o + 5])) + ((b[o + 8] + b[o + 9]) + (b[o + 12] + b[o + 13]));
  }
#pragma unroll
  for (int o = 1; o <= 2; o <<= 1)
#pragma unroll
    for (int r = 0; r < 2; r++) { sa[r] += __shfl_xor_sync(~0u, sa[r], o); sn[r] += __shfl_xor_sync(~0u, sn[r], o); }
#pragma unroll
  for (int r = 0; r < 2; r++) {
    const float ra = rcpf(sa[r]), rb = rcpf(sn[r]);
#pragma unroll
    for (int jj = 0; jj < 4; jj++) {
      ph[jj * 2 + r] = pack_bf16(v[2 * r + 4 * jj] * ra, v[2 * r + 4 * jj + 1] * ra);
      ph[(4 + jj) * 2 + r] = pack_bf16(b[2 * r + 4 * jj] * rb, b[2 * r + 4 * jj + 1] * rb);
    }
  }
}

__device__ __forceinline__ void store_heads(uint32_t base, const uint32_t (&a)[14], uint32_t pad, int row0, int lq) {
  const uint32_t rb = base + row0 * 64 + (((row0 >> 1) & 3) << 4);
  const uint32_t b0 = rb + lq * 4;
  const uint32_t b1 = (rb + 8192 + ((lq * 4 + 8) & 15)) ^ ((lq >> 1) << 4);
#pragma unroll
  for (int j = 0; j < 7; j++) {
    uint32_t ad;
    if (j < 3) ad = b0 ^ (j << 4);
    else if (j == 3) ad = (lq < 2) ? (b0 ^ 48u) : (b1 ^ 16u);
    else ad = (lq < 2) ? (b1 ^ ((j - 4) << 4)) : ((b1 ^ 16u) ^ ((j - 3) << 4));
    sts32(ad, a[2 * j]);
    sts32(ad + 512, a[2 * j + 1]);
  }
  sts64((rb ^ 48u) + 8 + (lq & 1) * 8192 + (lq >> 1) * 512, pad, 0u);
}

struct Params {
  const __nv_bfloat16* w_phi;
  const __nv_bfloat16* wk;
  const __nv_bfloat16* wv;
  const __nv_bfloat16* gate_w;
  __nv_bfloat16* out;
};

__global__ void __launch_bounds__(NTHREADS, 1)
fused_kernel(const __grid_constant__ CUtensorMap tm_x, const __grid_constant__ CUtensorMap tm_wqkv,
             const __grid_constant__ CUtensorMap tm_wq, const __grid_constant__ CUtensorMap tm_woa,
             const __grid_constant__ CUtensorMap tm_wob, const Params prm) {
  extern __shared__ uint8_t smem_raw[];
  uint32_t sb = (smem_u32(smem_raw) + 1023u) & ~1023u;
  uint8_t* sgen = smem_raw + (sb - smem_u32(smem_raw));
  asm volatile("mov.u32 %0, %0;" : "+r"(sb));
  const int tid = threadIdx.x, lane = tid & 31;
  const int warp = __shfl_sync(~0u, tid >> 5, 0), wg = warp >> 2;
  const int pt = blockIdx.x >> 3, hp = blockIdx.x & 7;
  const uint32_t bars = sb + OFF_BAR;
  auto BAR = [&](int i) { return bars + 8u * i; };
  const unsigned epoch = g_epoch & 1;

  if (tid == 0) { PROF_MARK(0); PROF_CLK(30); PROF2(15); }
  auto load_proj = [&](int c, int g) {
    mbar_expect_tx(BAR(B_FULL + g), 49152);
    tma_2d(sb + OFF_X + c * 16384, &tm_x, c * 64, pt * 128, BAR(B_FULL + g));
    tma_2d(sb + OFF_RING + g * 32768, &tm_wq, hp * 56, c * 64, BAR(B_FULL + g));
#pragma unroll 1
    for (int j = 0; j < 3; j++) tma_2d(sb + OFF_RING + g * 32768 + 8192 + j * 8192, &tm_wqkv, j * DM + hp * 56, c * 64, BAR(B_FULL + g));
  };
  if (elect_one()) {
    const int i = warp == 16 ? 0 : (warp == 0 ? 16 : warp);
    if (i < B_N) {
      int cnt = (i >= B_EMPTY && i < B_WO) || i > B_SIG || i == B_X1FREE ? 16 : 1;
      if (i == B_X0FREE) cnt = 32;
      if (i == B_BUILD) cnt = 3;
      if (i == B_SIG) cnt = 8;
      mbar_init(BAR(i), cnt);
      fence_async_smem();
    }
    if (warp == 16) load_proj(0, 0);
  }
  __syncthreads();
  if (tid == 0) PROF2(14);

  if (wg == 4) {
    asm volatile("setmaxnreg.dec.sync.aligned.u32 32;");
    if (warp == 16) {
      if (elect_one()) {
        int g = 1, nkv = 8;
        uint32_t par = 1;
#pragma unroll 1
        for (int n = 1; n < 14 + nkv; n++) {
          if (n == 7) { PROF_MARK(20); cnt_wait(C_KV, NCTA); PROF_MARK(21); fence_async_all(); }
          if (n == 15) {
            mbar_wait(BAR(B_SLOW), 0);
            if (*(volatile int*)(sgen + OFF_RED + 8)) nkv = 16;
          }
          const int j = n - 7 - nkv;
          if (j == 0 || j == 3) {
            PROF3(j ? 11 : 8);
            cnt_wait((j ? C_OB : C_OA) + pt, 8);
            PROF3(j ? 12 : 9);
            PROF_MARK(26);
            fence_async_all();
          }
          mbar_wait(BAR(B_EMPTY + g), par);
          if (n < 7) load_proj(n, g);
          else {
            mbar_expect_tx(BAR(B_FULL + g), 32768);
            bulk_g2s(sb + OFF_RING + g * 32768, j < 0 ? g_kv_img + ((n - 7) & 7) * 32768 : g_o_img + (size_t)(pt * 7 + j) * 32768, 32768,
                     BAR(B_FULL + g));
          }
          if (++g == 3) { g = 0; par ^= 1; }
        }
      }
    } else {
      {
        const int t = tid - 544;
#pragma unroll 1
        for (int i = t; i < 256; i += 96) sts128(sb + OFF_WPH + i * 16, make_uint4(0, 0, 0, 0));
        bar_sync(2, 96);
#pragma unroll 1
        for (int k = t; k < DM; k += 96) {
          const __nv_bfloat16* src = (hp < 4 ? prm.wk : prm.wv) + k * DH + (hp & 3) * 8;
          cp_async8(sb + OFF_SLC + k * 16, src);
          if ((hp & 3) != 3) cp_async8(sb + OFF_SLC + k * 16 + 8, src + 4);
          else sts64(sb + OFF_SLC + k * 16 + 8, hp == 3 ? (uint32_t)((const unsigned short*)prm.gate_w)[k] : 0u, 0u);
          if (k < 392) {
            const int row = k / 7, e = row >= DH;
            cp_async8(sb + OFF_WPH + e * 2048 + sw64_off(row - DH * e, (k % 7) * 4), prm.w_phi + 2 * hp * DH * DH + k * 4);
          }
        }
        asm volatile("cp.async.wait_all;" ::: "memory");
        fence_async_smem();
        __syncwarp();
        if (lane == 0) mbar_arrive(BAR(B_BUILD), 1);
      }
      if (warp == 18) {
        if (elect_one()) {
#pragma unroll 1
          for (int i = 0; i < 4; i++) {
            mbar_wait(BAR(B_SIG + i), 0);
            PROF3(2 * i);
            cnt_arrive(i == 0 ? C_KV : i == 1 ? C_PART : (i == 2 ? C_OA : C_OB) + pt);
            PROF3(2 * i + 1);
            if (i == 1 || i == 2) {
              mbar_wait(BAR(B_X0FREE + i - 1), 0);
              mbar_expect_tx(BAR(B_WO + i - 1), 57344);
#pragma unroll 1
              for (int c = 0; c < 7; c++)
                tma_2d(sb + OFF_WO + (i - 1) * 57344 + c * 8192, i == 1 ? &tm_woa : &tm_wob, hp * 56, c * 64, BAR(B_WO + i - 1));
            }
          }
        }
      } else if (warp == 19) {
        if (lane == 0) {
          mbar_wait(BAR(B_SIG + 0), 0);
          cnt_wait(C_KV, NCTA);
        }
        __syncwarp();
        float ksq = 0.f, vsq = 0.f;
#pragma unroll
        for (int sl = 0; sl < 4; sl++) {
          float4 a = ldcg_f4(g_ksq + sl * 128 + lane * 4), b = ldcg_f4(g_vsq + sl * 128 + lane * 4);
          float m = fmaxf(fmaxf(a.x, a.y), fmaxf(a.z, a.w));
          m = __uint_as_float(__reduce_max_sync(~0u, __float_as_uint(m)));
          ksq += m;
          vsq = fmaxf(vsq, fmaxf(fmaxf(b.x, b.y), fmaxf(b.z, b.w)));
        }
        vsq = __uint_as_float(__reduce_max_sync(~0u, __float_as_uint(vsq)));
        if (lane == 0) {
          float* red = (float*)(sgen + OFF_RED);
          red[0] = ksq; red[1] = vsq;
          mbar_arrive(BAR(B_B1), 1);
        }
      } else {
        float4* z = (float4*)(g_kvacc[epoch ^ 1] + blockIdx.x * 256) + lane;
        z[0] = make_float4(0.f, 0.f, 0.f, 0.f);
        z[32] = make_float4(0.f, 0.f, 0.f, 0.f);
        if (lane == 0) {
          mbar_wait(BAR(B_SIG + 1), 0);
          cnt_wait(C_PART, NCTA);
          PROF_MARK(23);
          mbar_arrive(BAR(B_KVR), 1);
        }
      }
    }
  } else {
    asm volatile("setmaxnreg.inc.sync.aligned.u32 112;");
    const int mh = wg & 1, nh = wg >> 1, wq = warp & 3;
    float acc0[28], acc1[28];
#pragma unroll
    for (int i = 0; i < 28; i++) acc0[i] = acc1[i] = 0.f;
    int slot = 0, prev = 0;
    uint32_t par = 0;

#pragma unroll 1
    for (int stage = 0; stage < 2; stage++) {
      {
        const uint64_t dS = make_desc(stage ? sb + OFF_WO : sb + OFF_X + mh * 8192, 1024, 1024, 1);
        const uint64_t dR = make_desc(sb + OFF_RING + (stage ? mh * 8192 : nh * 16384), 1024, 1024, 1);
#pragma unroll 1
        for (int c = 0; c < 7; c++) {
          if (stage) mbar_wait(BAR(B_WO + (c >= 3)), 0);
          if (tid == 0) PROF2(stage * 16 + c * 2);
          mbar_wait(BAR(B_FULL + slot), par);
          if (tid == 0) PROF2(stage * 16 + c * 2 + 1);
          const uint64_t ds = dS + c * 1024, dr = dR + slot * 2048;
          const uint64_t dA0 = stage ? dr : ds, dA1 = stage ? dr + 1024 : ds, dB0 = stage ? ds : dr, dB1 = dB0 + 512;
          wg_fence();
#pragma unroll
          for (int ks = 0; ks < 4; ks++) {
            wgmma_ss_n56_ta0_tb1<1>(acc0, dA0 + ks * 2, dB0 + ks * 128);
            wgmma_ss_n56_ta0_tb1<1>(acc1, dA1 + ks * 2, dB1 + ks * 128);
          }
          wg_commit();
          wg_wait<1>();
          if (lane == 0 && c > 0) mbar_arrive(BAR(B_EMPTY + prev), 1 + stage);
          prev = slot;
          if (++slot == 3) { slot = 0; par ^= 1; }
        }
      }
      if (stage) break;
      int lane_;
      asm volatile("mov.u32 %0, %%laneid;" : "=r"(lane_));
      const int lq = lane_ & 3;
      const int rowl = wq * 16 + (lane_ >> 2);
      const int row0 = mh * 64 + rowl;
      {
        float accs[4];
        if (nh == 1) {
          mbar_wait(BAR(B_BUILD), 0);
          const uint64_t dX = make_desc(sb + OFF_X + mh * 8192, 1024, 1024, 1);
          const uint64_t dSlc = make_desc(sb + OFF_SLC, 128, 128, 0);
          wg_fence();
          wgmma_ss_n8_ta0_tb1<0>(accs, dX, dSlc);
          wg_commit();
#pragma unroll 1
          for (int kk = 1; kk < 28; kk++) {
            wg_fence();
            wgmma_ss_n8_ta0_tb1<1>(accs, dX + (kk >> 2) * 1024 + (kk & 3) * 2, dSlc + kk * 16);
            wg_commit();
          }
        }
        wg_wait<0>();
        fence_regs(acc0); fence_regs(acc1); fence_regs(accs);
        if (lane == 0) mbar_arrive(BAR(B_EMPTY + prev), 1);
        if (tid == 0) PROF_MARK(2);
        if (tid == 256) PROF_MARK(3);
        if (nh == 0) {
          float sq[4] = {0.f, 0.f, 0.f, 0.f};
#pragma unroll
          for (int i = 0; i < 28; i++) acc0[i] *= 0.18898223650461362f * 1.4426950408889634f;
#pragma unroll
          for (int j = 0; j < 7; j++) {
#pragma unroll
            for (int rr = 0; rr < 2; rr++) {
              const float s2 = acc0[4 * j + 2 * rr] * acc0[4 * j + 2 * rr] + acc0[4 * j + 2 * rr + 1] * acc0[4 * j + 2 * rr + 1];
              if (j < 3) sq[rr] += s2;
              else if (j > 3) sq[2 + rr] += s2;
              else { sq[rr] += (lq < 2) ? s2 : 0.f; sq[2 + rr] += (lq < 2) ? 0.f : s2; }
            }
          }
#pragma unroll
          for (int i = 0; i < 4; i++) sq[i] = quad_sum(sq[i]);
          const float mine = lq == 0 ? sq[0] : lq == 1 ? sq[1] : lq == 2 ? sq[2] : sq[3];
          ((float*)(sgen + OFF_QSQ))[(mh + (lq & 2)) * 64 + rowl + 8 * (lq & 1)] = mine <= 3.0e38f ? mine : __int_as_float(0x7f800000);
        } else {
          const int sl = hp & 3;
          const bool isk = hp < 4, real = (sl < 3) || (lq < 2);
          const int pos = pt * 128 + row0, kr = pos & 63;
          uint8_t* dst = g_kv_img + (pos >> 6) * 8192 + (isk ? 0 : 4096) + sw64_off(kr, sl * 8 + 2 * lq);
          const uint32_t pat = isk ? POLY_PAT >> (kr >> 3) : 0u;
          float mxv = 0.f;
#pragma unroll
          for (int rr = 0; rr < 2; rr++) {
            const float v0 = accs[2 * rr], v1 = accs[2 * rr + 1];
            const bool poly = (pat >> rr) & 1;
            const float sc = poly ? 2.f : 1.f;
            const float s2 = quad_sum(real ? v0 * v0 + v1 * v1 : 0.f);
            mxv = fmaxf(mxv, s2 <= 3.0e38f ? s2 : __int_as_float(0x7f800000));
            const uint32_t padv = lq == 2 ? (poly ? 0x443F4000u : 0x00003F80u) : (poly ? 0x3AB03F4Du : 0u);
            *(uint32_t*)(dst + rr * 512) = real ? pack_bf16(sc * v0, sc * v1) : padv;
            if (hp == 3 && lq == 2) g_gate[pos + 8 * rr] = rcpf(1.f + ex2f(-1.4426950408889634f * v0));
          }
          mxv = __uint_as_float(__reduce_max_sync(~0u, __float_as_uint(mxv)));
          if (lane == 0) (isk ? g_ksq : g_vsq)[sl * 128 + pt * 8 + mh * 4 + wq] = mxv;
          __syncwarp();
          if (lane == 0) mbar_arrive(BAR(B_SIG + 0), 1);
        }
      }
      if (tid == 0) PROF_MARK(4);
      if (tid == 256) PROF_MARK(5);
      {
        uint32_t h0[14], h1[14];
#pragma unroll
        for (int i = 0; i < 14; i++) { h0[i] = pack_bf16(acc0[2 * i], acc0[2 * i + 1]); h1[i] = pack_bf16(acc1[2 * i], acc1[2 * i + 1]); }
        bar_sync(1, 512);
        if (tid == 0) PROF_MARK(6);
#pragma unroll 1
        for (int r = 0; r < 2; r++) {
          store_heads(sb + (r ? (nh ? OFF_VA : OFF_QA) : (nh ? OFF_KA : OFF_QP)), h0, (r & nh) ? 0x00003F80u : 0u, row0, lq);
#pragma unroll
          for (int i = 0; i < 14; i++) h0[i] = h1[i];
        }
      }
      fence_async_smem();
      bar_sync(1, 512);
      if (tid == 0) PROF_MARK(7);

      const uint64_t dK = make_desc(sb + OFF_RING, 512, 512, 2);
      const uint64_t dhi = dK & 0xffffffff00000000ull;
      const uint32_t dlo0 = (uint32_t)dK;
      uint32_t ok = 0, q[8];
      float m0 = -3.0e38f, m1 = -3.0e38f, g0 = 0.f, g1 = 0.f;
      bool slow = false;
      float o[16];
#pragma unroll
      for (int i = 0; i < 16; i++) o[i] = 0.f;
#pragma unroll
      for (int i = 0; i < 8; i++) q[i] = 0u;
      const int kb = KB_AT, qb = QB_AT;
#pragma unroll 1
      for (int it = -1; it <= 8; it++) {
        uint32_t p[16];
        if (it == kb || it == qb || it == 8) {
          float t[16];
          wg_wait<0>();
          fence_regs(o);
          if (it < 8) {
            if (tid == 0) PROF_MARK(it == kb ? 27 : 11);
            const uint64_t dA = make_desc(sb + (it == kb ? OFF_KA : OFF_QA) + nh * 8192 + mh * 4096, 512, 512, 2);
            const uint64_t dB = make_desc(sb + OFF_WPH + nh * 2048, 512, 512, 2);
            float* kvacc = g_kvacc[epoch] + (2 * hp + nh) * 2048;
            float pa[16];
            wg_fence();
            wgmma_ss_n32_ta0_tb1<0>(pa, dA, dB);
            wgmma_ss_n32_ta0_tb1<1>(pa, dA + 2, dB + 64);
            wg_commit();
            if (it != kb) {
              mbar_wait(BAR(B_KVR), 0);
              const int tl = tid & 127;
              const float4 a = ldcg_f4(kvacc + tl * 16), b = ldcg_f4(kvacc + tl * 16 + 4), c = ldcg_f4(kvacc + tl * 16 + 8), d = ldcg_f4(kvacc + tl * 16 + 12);
              const uint32_t ad = sb + OFF_KVR + nh * 4096 + sw64_off(tl >> 1, (tl & 1) * 16);
              sts128(ad, make_uint4(pack_bf16(a.x, a.y), pack_bf16(a.z, a.w), pack_bf16(b.x, b.y), pack_bf16(b.z, b.w)));
              sts128(ad ^ 16u, make_uint4(pack_bf16(c.x, c.y), pack_bf16(c.z, c.w), pack_bf16(d.x, d.y), pack_bf16(d.z, d.w)));
            }
            wg_wait<0>();
            fence_regs(pa);
            uint32_t ph[16];
            feature_map(pa, ph, lq);
            const uint32_t rb = sb + OFF_PHI + wg * 8192 + rowl * 128 + lq * 4 + ((rowl & 7) << 4);
#pragma unroll
            for (int ch = 0; ch < 8; ch++) { sts32(rb ^ (ch << 4), ph[2 * ch]); sts32((rb ^ (ch << 4)) + 1024, ph[2 * ch + 1]); }
            fence_async_smem();
            bar_sync(4 + wg, 128);
            const uint64_t dP = make_desc(sb + OFF_PHI + wg * 8192, 1024, 1024, 1);
            if (it == kb) {
              const uint64_t dV = make_desc(sb + OFF_VA + nh * 8192 + mh * 4096, 512, 512, 2);
              float kv[16];
              wg_fence();
              wgmma_ss_n32_ta1_tb1<0>(kv, dP, dV);
#pragma unroll
              for (int ks = 1; ks < 4; ks++) wgmma_ss_n32_ta1_tb1<1>(kv, dP + ks * 128, dV + ks * 64);
              wg_commit();
              wg_wait<0>();
              fence_regs(kv);
              float* dst = kvacc + rowl * 32 + 2 * lq;
#pragma unroll
              for (int j = 0; j < 8; j++)
                asm volatile("red.global.add.v2.f32 [%0], {%1, %2};" ::"l"(dst + 8 * (j >> 1) + 256 * (j & 1)), "f"(kv[2 * j]), "f"(kv[2 * j + 1]) : "memory");
              __syncwarp();
              if (lane == 0) { mbar_arrive(BAR(B_SIG + 1), 1); mbar_arrive(BAR(B_X0FREE), 1); }
              if (tid == 0) PROF_MARK(28);
              goto after_block;
            } else {
              const uint64_t dR = make_desc(sb + OFF_KVR + nh * 4096, 512, 512, 2);
              wg_fence();
              wgmma_ss_n32_ta0_tb1<0>(t, dP, dR);
#pragma unroll
              for (int ks = 1; ks < 4; ks++) wgmma_ss_n32_ta0_tb1<1>(t, dP + ks * 2, dR + ks * 64);
              wg_commit();
              wg_wait<0>();
              fence_regs(t);
              if (lane == 0) mbar_arrive(BAR(B_X1FREE), 1);
            }
          } else {
            if (lane == 0) mbar_arrive(BAR(B_EMPTY + prev), 1);
            if (tid == 0) PROF_MARK(13);
#pragma unroll
            for (int i = 0; i < 16; i++) t[i] = o[i];
          }
          {
            const int br = it == 8;
            const float eps = br ? 0.f : 1e-6f;
            const float d0 = __shfl_sync(~0u, t[12], (lane_ & ~3) | 2), d1 = __shfl_sync(~0u, t[14], (lane_ & ~3) | 2);
            const float r0 = __fdividef(br ? 1.f - g0 : g0, d0 + eps), r1 = __fdividef(br ? 1.f - g1 : g1, d1 + eps);
            uint8_t* img = g_o_img + (size_t)((pt * 2 + br) * 14 + mh) * 8192 + rowl * 128;
            const int col0 = (2 * hp + nh) * DH + 2 * lq;
#pragma unroll
            for (int j = 0; j < 4; j++) {
              const int col = col0 + 8 * j;
              uint8_t* gp = img + (col >> 6) * 16384 + ((((col >> 3) ^ rowl) & 7) << 4) + (col & 7) * 2;
              const uint32_t v0 = pack_bf16(t[4 * j] * r0, t[4 * j + 1] * r0), v1 = pack_bf16(t[4 * j + 2] * r1, t[4 * j + 3] * r1);
              if (j < 3 || lq < 2) { *(uint32_t*)gp = v0; *(uint32_t*)(gp + 1024) = v1; }
            }
            __syncwarp();
            if (lane == 0) mbar_arrive(BAR(B_SIG + 2 + br), 1);
            if (tid == 0) PROF_MARK(12 + 2 * br);
            if (br) break;
          }
        }
      after_block:
        if (it < 0) {
              mbar_wait(BAR(B_B1), 0);
              if (tid == 0) PROF_MARK(9);
              g0 = ldcg_f(g_gate + pt * 128 + row0); g1 = ldcg_f(g_gate + pt * 128 + row0 + 8);
              const float* red = (const float*)(sgen + OFF_RED);
              const float ksq = red[0] * (1.02f * 1.02f), vsq = red[1];
              const float* qsq = (const float*)(sgen + OFF_QSQ);
              float b0, b1;
              asm("sqrt.approx.ftz.f32 %0, %1;" : "=f"(b0) : "f"(qsq[wg * 64 + rowl] * ksq));
              asm("sqrt.approx.ftz.f32 %0, %1;" : "=f"(b1) : "f"(qsq[wg * 64 + rowl + 8] * ksq));
              const float4 qa4 = ((const float4*)qsq)[lane_], qb4 = ((const float4*)qsq)[32 + lane_];
              const float qmax = fmaxf(fmaxf(fmaxf(qa4.x, qa4.y), fmaxf(qa4.z, qa4.w)), fmaxf(fmaxf(qb4.x, qb4.y), fmaxf(qb4.z, qb4.w)));
              slow = __any_sync(~0u, !(qmax * ksq <= 92.f * 92.f) || !(vsq <= 1.0e24f));
              if (tid == 0) { *(volatile int*)(sgen + OFF_RED + 8) = slow; mbar_arrive(BAR(B_SLOW), 1); }
              const uint32_t qa = sb + OFF_QP + nh * 8192;
              const int r = mh * 64 + wq * 16 + (lane_ & 7) + ((lane_ >> 3) & 1) * 8;
#pragma unroll
              for (int ks = 0; ks < 2; ks++)
                asm volatile("ldmatrix.sync.aligned.m8n8.x4.shared.b16 {%0, %1, %2, %3}, [%4];"
                             : "=r"(q[4 * ks]), "=r"(q[4 * ks + 1]), "=r"(q[4 * ks + 2]), "=r"(q[4 * ks + 3])
                             : "r"(qa + sw64_off(r, ks * 16 + (lane_ >> 4) * 8)) : "memory");
              if (lq >= 2 && !slow) {
                q[6] = lq == 2 ? pack_bf16(64.f - b0, 1.f) : 0x3F803F80u;
                q[7] = lq == 2 ? pack_bf16(64.f - b1, 1.f) : 0x3F803F80u;
              }
              __syncwarp();
              if (lane == 0) mbar_arrive(BAR(B_X0FREE), 1);
              if (__builtin_expect(slow, 0)) {
#pragma unroll 1
                for (int j64 = 0; j64 < 32; j64++) {
                  float s[32];
                  if ((j64 & 3) == 0) mbar_wait(BAR(B_FULL + slot), par);
                  const uint32_t lo = dlo0 + slot * 2048 + (j64 & 3) * 512;
                  wg_fence();
                  wgmma_rs_n64_tb0<0>(s, q[0], q[1], q[2], q[3], dhi | lo);
                  wgmma_rs_n64_tb0<1>(s, q[4], q[5], q[6], q[7], dhi | (lo + 2));
                  wg_commit();
                  wg_wait<0>();
                  fence_regs(s);
#pragma unroll
                  for (int j = 0; j < 8; j++) {
                    const float sc = ((POLY_PAT >> j) & 1) ? 0.5f : 1.f;
                    m0 = fmaxf(m0, fmaxf(s[4 * j], s[4 * j + 1]) * sc);
                    m1 = fmaxf(m1, fmaxf(s[4 * j + 2], s[4 * j + 3]) * sc);
                  }
                  if ((j64 & 3) == 3) {
                    if (lane == 0) mbar_arrive(BAR(B_EMPTY + slot), 1);
                    if (++slot == 3) { slot = 0; par ^= 1; }
                  }
                }
                m0 = quad_max(m0); m1 = quad_max(m1);
              }
              if (tid == 0) PROF_MARK(10);
              continue;
        }
        const uint32_t lo = dlo0 + slot * 2048;
        if (!ok) mbar_wait(BAR(B_FULL + slot), par);
        int nslot = slot + 1;
        uint32_t npar = par;
        if (nslot == 3) { nslot = 0; npar ^= 1; }
        if (__builtin_expect(slow, 0)) {
          if (lane == 0 && it > 0) mbar_arrive(BAR(B_EMPTY + prev), 1);
#pragma unroll 1
          for (int u = 0; u < 4; u++) {
            float s[32];
            uint32_t ps[16];
            wg_fence();
            wgmma_rs_n64_tb0<0>(s, q[0], q[1], q[2], q[3], dhi | (lo + u * 512));
            wgmma_rs_n64_tb0<1>(s, q[4], q[5], q[6], q[7], dhi | (lo + u * 512 + 2));
            wg_commit();
            wg_wait<0>();
            fence_regs(s);
#pragma unroll
            for (int j = 0; j < 8; j++) {
              const float sc = ((POLY_PAT >> j) & 1) ? 0.5f : 1.f;
              ps[2 * j] = pack_bf16(ex2f(fmaf(s[4 * j], sc, -m0)), ex2f(fmaf(s[4 * j + 1], sc, -m0)));
              ps[2 * j + 1] = pack_bf16(ex2f(fmaf(s[4 * j + 2], sc, -m1)), ex2f(fmaf(s[4 * j + 3], sc, -m1)));
            }
            wg_fence();
#pragma unroll
            for (int ks = 0; ks < 4; ks++)
              wgmma_rs_n32_tb1<1>(o, ps[4 * ks], ps[4 * ks + 1], ps[4 * ks + 2], ps[4 * ks + 3], dhi | (lo + u * 512 + 256 + ks * 64));
            wg_commit();
            wg_wait<0>();
            fence_regs(o);
          }
        } else {
          float s[32];
          wg_fence();
          wgmma_rs_n64_tb0<0>(s, q[0], q[1], q[2], q[3], dhi | lo);
          wgmma_rs_n64_tb0<1>(s, q[4], q[5], q[6], q[7], dhi | (lo + 2));
          wg_commit();
#pragma unroll
          for (int u = 0; u < 4; u++) {
            wg_wait<0>();
            fence_regs(s);
            if (u == 0 && lane == 0 && it > 0) mbar_arrive(BAR(B_EMPTY + prev), 1);
            if (u == 2) ok = mbar_test(BAR(B_FULL + nslot), npar);
#pragma unroll
            for (int j = 0; j < 8; j++) {
              if ((POLY_PAT >> j) & 1) {
                p[2 * j] = exp2_pair_fma(s[4 * j], s[4 * j + 1], 0x3F003F00u, 0x00030003u);
                p[2 * j + 1] = exp2_pair_fma(s[4 * j + 2], s[4 * j + 3], 0x3F003F00u, 0x00030003u);
              } else {
                p[2 * j] = pack_bf16(ex2f(s[4 * j]), ex2f(s[4 * j + 1]));
                p[2 * j + 1] = pack_bf16(ex2f(s[4 * j + 2]), ex2f(s[4 * j + 3]));
              }
            }
            wg_fence();
#pragma unroll
            for (int ks = 0; ks < 4; ks++)
              wgmma_rs_n32_tb1<1>(o, p[4 * ks], p[4 * ks + 1], p[4 * ks + 2], p[4 * ks + 3], dhi | (lo + u * 512 + 256 + ks * 64));
            if (u < 3) {
              wgmma_rs_n64_tb0<0>(s, q[0], q[1], q[2], q[3], dhi | (lo + (u + 1) * 512));
              wgmma_rs_n64_tb0<1>(s, q[4], q[5], q[6], q[7], dhi | (lo + (u + 1) * 512 + 2));
            }
            wg_commit();
          }
        }
        prev = slot; slot = nslot; par = npar;
      }
      wg_wait<0>();
      if (nh == 1) return;
#pragma unroll
      for (int i = 0; i < 28; i++) acc0[i] = acc1[i] = 0.f;
    }
    wg_wait<0>();
    fence_regs(acc0); fence_regs(acc1);
    if (tid == 0) PROF_MARK(17);
    __nv_bfloat16* op = prm.out + (size_t)(pt * 128 + mh * 64 + wq * 16 + (lane >> 2)) * DM + hp * 56 + 2 * (lane & 3);
#pragma unroll
    for (int j = 0; j < 7; j++) {
      *(uint32_t*)(op + 8 * j) = pack_bf16(acc0[4 * j] + acc1[4 * j], acc0[4 * j + 1] + acc1[4 * j + 1]);
      *(uint32_t*)(op + 8 * DM + 8 * j) = pack_bf16(acc0[4 * j + 2] + acc1[4 * j + 2], acc0[4 * j + 3] + acc1[4 * j + 3]);
    }
    if (tid == 0) { PROF_MARK(18); PROF_CLK(31); }
    if (tid == 0) {
      unsigned prevd = atomicAdd(&g_cnt[C_DONE * 32], 1u);
      if (prevd == NCTA - 1) {
#pragma unroll 1
        for (int i = 0; i < C_N; i++) g_cnt[i * 32] = 0;
        g_epoch = epoch ^ 1;
      }
    }
  }
}

typedef CUresult (*EncodeFn)(CUtensorMap*, CUtensorMapDataType, cuuint32_t, void*, const cuuint64_t*, const cuuint64_t*,
                             const cuuint32_t*, const cuuint32_t*, CUtensorMapInterleave, CUtensorMapSwizzle,
                             CUtensorMapL2promotion, CUtensorMapFloatOOBfill);

void make_map(EncodeFn enc, CUtensorMap* tm, const void* ptr, uint64_t cols, uint64_t rows, uint32_t box_rows) {
  cuuint64_t dims[2] = {cols, rows};
  cuuint64_t strides[1] = {cols * 2};
  cuuint32_t box[2] = {64, box_rows};
  cuuint32_t es[2] = {1, 1};
  enc(tm, CU_TENSOR_MAP_DATA_TYPE_BFLOAT16, 2, const_cast<void*>(ptr), dims, strides, box, es, CU_TENSOR_MAP_INTERLEAVE_NONE,
      CU_TENSOR_MAP_SWIZZLE_128B, CU_TENSOR_MAP_L2_PROMOTION_L2_128B, CU_TENSOR_MAP_FLOAT_OOB_FILL_NONE);
}

}

extern "C" void kernel_launch(void* const* d_in, const int* in_sizes, int n_in, void* d_out, int out_size) {
  (void)in_sizes; (void)n_in; (void)out_size;
  static EncodeFn enc = nullptr;
  if (!enc) {
    void* fn = nullptr;
    cudaDriverEntryPointQueryResult qr;
    cudaGetDriverEntryPoint("cuTensorMapEncodeTiled", &fn, cudaEnableDefault, &qr);
    enc = (EncodeFn)fn;
    cudaFuncSetAttribute(fused_kernel, cudaFuncAttributeMaxDynamicSharedMemorySize, SMEM_BYTES);
  }
  CUtensorMap tm_x, tm_wqkv, tm_wq, tm_woa, tm_wob;
  make_map(enc, &tm_x, d_in[0], DM, S_LEN, 128);
  make_map(enc, &tm_wqkv, d_in[1], 3 * DM, DM, 64);
  make_map(enc, &tm_wq, d_in[5], DM, DM, 64);
  make_map(enc, &tm_woa, d_in[3], DM, DM, 64);
  make_map(enc, &tm_wob, d_in[8], DM, DM, 64);
  Params prm;
  prm.w_phi = (const __nv_bfloat16*)d_in[2];
  prm.wk = (const __nv_bfloat16*)d_in[6];
  prm.wv = (const __nv_bfloat16*)d_in[7];
  prm.gate_w = (const __nv_bfloat16*)d_in[9];
  prm.out = (__nv_bfloat16*)d_out;
  fused_kernel<<<NCTA, NTHREADS, SMEM_BYTES>>>(tm_x, tm_wqkv, tm_wq, tm_woa, tm_wob, prm);
}
```

```cpp
#include <cuda_runtime.h>
#include <cuda_bf16.h>
#include <cuda.h>
#include <stdint.h>

namespace {

constexpr int S_LEN = 2048, DM = 448, DH = 28;
constexpr int NCTA = 128;
constexpr int NTHREADS = 640;
constexpr uint32_t POLY_PAT = 0x57;

#define KB_AT 0
#define QB_AT (3 + nh)

constexpr int OFF_X = 0;
constexpr int OFF_KA = 0;
constexpr int OFF_VA = 16384;
constexpr int OFF_QP = 32768;
constexpr int OFF_QA = 57344;
constexpr int OFF_KVR = 73728;
constexpr int OFF_PHI = 81920;
constexpr int OFF_WO = 0;
constexpr int OFF_RING = 114688;
constexpr int OFF_WPH = 212992;
constexpr int OFF_SLC = 217088;
constexpr int OFF_QSQ = 224256;
constexpr int OFF_RED = 225792;
constexpr int OFF_BAR = 225856;
constexpr int SMEM_BYTES = 226368 + 1024;

constexpr int B_FULL = 0, B_EMPTY = 3, B_WO = 6  , B_KVR = 8, B_X0FREE = 9, B_X1FREE = 10, B_QSQ = 11, B_SLOW = 12,
              B_BUILD = 13, B_SIG = 14  , B_N = 18;

constexpr int C_KV = 0, C_PART = 1, C_DONE = 3, C_OA = 4, C_OB = 20, C_N = 36;

__device__ __align__(1024) uint8_t g_kv_img[32 * 8192];
__device__ __align__(16) float g_ksq[512];
__device__ __align__(16) float g_vsq[512];
__device__ __align__(16) float g_gate[S_LEN];
__device__ __align__(1024) float g_kvacc[2][16 * 64 * 32];
__device__ unsigned g_epoch;
__device__ __align__(1024) uint8_t g_o_img[2 * 16 * 14 * 8192];
__device__ unsigned g_cnt[C_N * 32];

#define PROF3(i) do { } while (0)
#define PROF2(i) do { } while (0)
#define PROF_CLK(i) do { } while (0)
#define PROF_MARK(i) do { } while (0)
__device__ __forceinline__ uint32_t smem_u32(const void* p) { return (uint32_t)__cvta_generic_to_shared(p); }
__device__ __forceinline__ void mbar_init(uint32_t a, int cnt) {
  asm volatile("mbarrier.init.shared::cta.b64 [%0], %1;" ::"r"(a), "r"(cnt) : "memory");
}
__device__ __forceinline__ void mbar_expect_tx(uint32_t a, uint32_t bytes) {
  asm volatile("mbarrier.arrive.expect_tx.shared::cta.b64 _, [%0], %1;" ::"r"(a), "r"(bytes) : "memory");
}
__device__ __forceinline__ void mbar_arrive(uint32_t a, uint32_t cnt) {
  asm volatile("mbarrier.arrive.shared::cta.b64 _, [%0], %1;" ::"r"(a), "r"(cnt) : "memory");
}
__device__ __forceinline__ void mbar_wait(uint32_t a, uint32_t parity) {
  asm volatile(
      "{\n.reg .pred p;\n.reg .u32 c;\nmov.u32 c, 0;\n"
      "W_%=:\nmbarrier.try_wait.parity.shared::cta.b64 p, [%0], %1;\n"
      "add.u32 c, c, 1;\nsetp.lt.and.u32 p, c, 0x1000000, !p;\n@p bra W_%=;\n}"
      ::"r"(a), "r"(parity) : "memory");
}
__device__ __forceinline__ uint32_t mbar_test(uint32_t a, uint32_t parity) {
  uint32_t ok;
  asm volatile("{\n.reg .pred p;\nmbarrier.test_wait.parity.shared::cta.b64 p, [%1], %2;\nselp.u32 %0, 1, 0, p;\n}"
               : "=r"(ok) : "r"(a), "r"(parity) : "memory");
  return ok;
}
__device__ __forceinline__ bool elect_one() {
  uint32_t r;
  asm volatile("{\n.reg .pred p;\nelect.sync _|p, 0xffffffff;\nselp.u32 %0, 1, 0, p;\n}" : "=r"(r));
  return r != 0;
}
__device__ __forceinline__ void tma_2d(uint32_t dst, const CUtensorMap* tm, int c0, int c1, uint32_t bar) {
  asm volatile("cp.async.bulk.tensor.2d.shared::cluster.global.mbarrier::complete_tx::bytes [%0], [%1, {%3, %4}], [%2];"
               ::"r"(dst), "l"(tm), "r"(bar), "r"(c0), "r"(c1) : "memory");
}
__device__ __forceinline__ void bulk_g2s(uint32_t dst, const void* src, uint32_t bytes, uint32_t bar) {
  asm volatile("cp.async.bulk.shared::cluster.global.mbarrier::complete_tx::bytes [%0], [%1], %2, [%3];"
               ::"r"(dst), "l"(src), "r"(bytes), "r"(bar) : "memory");
}
__device__ __forceinline__ void cp_async8(uint32_t dst, const void* src) {
  asm volatile("cp.async.ca.shared.global [%0], [%1], 8;" ::"r"(dst), "l"(src) : "memory");
}
__device__ __forceinline__ void fence_async_smem() { asm volatile("fence.proxy.async.shared::cta;" ::: "memory"); }
__device__ __forceinline__ void fence_async_all() { asm volatile("fence.proxy.async.global;" ::: "memory"); }
__device__ __forceinline__ float ldcg_f(const float* p) { float v; asm volatile("ld.global.cg.f32 %0, [%1];" : "=f"(v) : "l"(p) : "memory"); return v; }
__device__ __forceinline__ void bar_sync(int id, int n) { asm volatile("bar.sync %0, %1;" ::"r"(id), "r"(n) : "memory"); }
__device__ __forceinline__ void cnt_arrive(int idx) {
  asm volatile("red.release.gpu.global.add.u32 [%0], 1;" ::"l"(&g_cnt[idx * 32]) : "memory");
}
__device__ __forceinline__ void cnt_wait(int idx, unsigned target) {
  unsigned v, n = 0;
#pragma unroll 1
  while (true) {
    asm volatile("ld.acquire.gpu.global.u32 %0, [%1];" : "=r"(v) : "l"(&g_cnt[idx * 32]) : "memory");
    if (v >= target || ++n >= (1u << 22)) break;
    __nanosleep(32);
  }
}
__device__ __forceinline__ void wg_fence() { asm volatile("wgmma.fence.sync.aligned;" ::: "memory"); }
__device__ __forceinline__ void wg_commit() { asm volatile("wgmma.commit_group.sync.aligned;" ::: "memory"); }
template <int N> __device__ __forceinline__ void wg_wait() { asm volatile("wgmma.wait_group.sync.aligned %0;" ::"n"(N) : "memory"); }
template <int N> __device__ __forceinline__ void fence_regs(float (&d)[N]) {
#pragma unroll
  for (int i = 0; i < N; i++) asm volatile("" : "+f"(d[i])::"memory");
}
__device__ __forceinline__ uint64_t make_desc(uint32_t saddr, uint32_t lbo, uint32_t sbo, uint32_t swz) {
  return (uint64_t)((saddr & 0x3FFFF) >> 4) | ((uint64_t)(lbo >> 4) << 16) | ((uint64_t)(sbo >> 4) << 32) | ((uint64_t)swz << 62);
}
__device__ __forceinline__ float ex2f(float x) { float y; asm("ex2.approx.ftz.f32 %0, %1;" : "=f"(y) : "f"(x)); return y; }
__device__ __forceinline__ float rcpf(float x) { float y; asm("rcp.approx.ftz.f32 %0, %1;" : "=f"(y) : "f"(x)); return y; }
__device__ __forceinline__ uint32_t pack_bf16(float lo, float hi) {
  uint32_t r; asm("cvt.rn.bf16x2.f32 %0, %1, %2;" : "=r"(r) : "f"(hi), "f"(lo)); return r;
}
__device__ __forceinline__ uint32_t lop_and_or(uint32_t a, uint32_t m, uint32_t c) {
  uint32_t r; asm("lop3.b32 %0, %1, %2, %3, 0xEA;" : "=r"(r) : "r"(a), "r"(m), "r"(c)); return r;
}
__device__ __forceinline__ void sts32(uint32_t a, uint32_t v) { asm volatile("st.shared.b32 [%0], %1;" ::"r"(a), "r"(v) : "memory"); }
__device__ __forceinline__ void sts64(uint32_t a, uint32_t v0, uint32_t v1) { asm volatile("st.shared.v2.b32 [%0], {%1, %2};" ::"r"(a), "r"(v0), "r"(v1) : "memory"); }
__device__ __forceinline__ void sts128(uint32_t a, uint4 v) {
  asm volatile("st.shared.v4.b32 [%0], {%1, %2, %3, %4};" ::"r"(a), "r"(v.x), "r"(v.y), "r"(v.z), "r"(v.w) : "memory");
}
__device__ __forceinline__ float4 ldcg_f4(const float* p) {
  float4 v; asm volatile("ld.global.cg.v4.f32 {%0, %1, %2, %3}, [%4];" : "=f"(v.x), "=f"(v.y), "=f"(v.z), "=f"(v.w) : "l"(p) : "memory"); return v;
}
__device__ __forceinline__ float quad_sum(float v) { v += __shfl_xor_sync(~0u, v, 1); v += __shfl_xor_sync(~0u, v, 2); return v; }
__device__ __forceinline__ float quad_max(float v) { v = fmaxf(v, __shfl_xor_sync(~0u, v, 1)); v = fmaxf(v, __shfl_xor_sync(~0u, v, 2)); return v; }

template <int SD> __device__ __forceinline__ void wgmma_ss_n56_ta0_tb1(float (&d)[28], uint64_t da, uint64_t db) {
  if (SD) asm volatile("wgmma.mma_async.sync.aligned.m64n56k16.f32.bf16.bf16 {%0, %1, %2, %3, %4, %5, %6, %7, %8, %9, %10, %11, %12, %13, %14, %15, %16, %17, %18, %19, %20, %21, %22, %23, %24, %25, %26, %27}, %28, %29, 1, 1, 1, 0, 1;\n"
    : "+f"(d[0]), "+f"(d[1]), "+f"(d[2]), "+f"(d[3]), "+f"(d[4]), "+f"(d[5]), "+f"(d[6]), "+f"(d[7]), "+f"(d[8]), "+f"(d[9]), "+f"(d[10]), "+f"(d[11]), "+f"(d[12]), "+f"(d[13]), "+f"(d[14]), "+f"(d[15]), "+f"(d[16]), "+f"(d[17]), "+f"(d[18]), "+f"(d[19]), "+f"(d[20]), "+f"(d[21]), "+f"(d[22]), "+f"(d[23]), "+f"(d[24]), "+f"(d[25]), "+f"(d[26]), "+f"(d[27])
    : "l"(da), "l"(db));
  else asm volatile("wgmma.mma_async.sync.aligned.m64n56k16.f32.bf16.bf16 {%0, %1, %2, %3, %4, %5, %6, %7, %8, %9, %10, %11, %12, %13, %14, %15, %16, %17, %18, %19, %20, %21, %22, %23, %24, %25, %26, %27}, %28, %29, 0, 1, 1, 0, 1;\n"
    : "=f"(d[0]), "=f"(d[1]), "=f"(d[2]), "=f"(d[3]), "=f"(d[4]), "=f"(d[5]), "=f"(d[6]), "=f"(d[7]), "=f"(d[8]), "=f"(d[9]), "=f"(d[10]), "=f"(d[11]), "=f"(d[12]), "=f"(d[13]), "=f"(d[14]), "=f"(d[15]), "=f"(d[16]), "=f"(d[17]), "=f"(d[18]), "=f"(d[19]), "=f"(d[20]), "=f"(d[21]), "=f"(d[22]), "=f"(d[23]), "=f"(d[24]), "=f"(d[25]), "=f"(d[26]), "=f"(d[27])
    : "l"(da), "l"(db));
}
template <int SD> __device__ __forceinline__ void wgmma_ss_n8_ta0_tb1(float (&d)[4], uint64_t da, uint64_t db) {
  if (SD) asm volatile("wgmma.mma_async.sync.aligned.m64n8k16.f32.bf16.bf16 {%0, %1, %2, %3}, %4, %5, 1, 1, 1, 0, 1;\n"
    : "+f"(d[0]), "+f"(d[1]), "+f"(d[2]), "+f"(d[3])
    : "l"(da), "l"(db));
  else asm volatile("wgmma.mma_async.sync.aligned.m64n8k16.f32.bf16.bf16 {%0, %1, %2, %3}, %4, %5, 0, 1, 1, 0, 1;\n"
    : "=f"(d[0]), "=f"(d[1]), "=f"(d[2]), "=f"(d[3])
    : "l"(da), "l"(db));
}
template <int SD> __device__ __forceinline__ void wgmma_ss_n32_ta1_tb1(float (&d)[16], uint64_t da, uint64_t db) {
  if (SD) asm volatile("wgmma.mma_async.sync.aligned.m64n32k16.f32.bf16.bf16 {%0, %1, %2, %3, %4, %5, %6, %7, %8, %9, %10, %11, %12, %13, %14, %15}, %16, %17, 1, 1, 1, 1, 1;\n"
    : "+f"(d[0]), "+f"(d[1]), "+f"(d[2]), "+f"(d[3]), "+f"(d[4]), "+f"(d[5]), "+f"(d[6]), "+f"(d[7]), "+f"(d[8]), "+f"(d[9]), "+f"(d[10]), "+f"(d[11]), "+f"(d[12]), "+f"(d[13]), "+f"(d[14]), "+f"(d[15])
    : "l"(da), "l"(db));
  else asm volatile("wgmma.mma_async.sync.aligned.m64n32k16.f32.bf16.bf16 {%0, %1, %2, %3, %4, %5, %6, %7, %8, %9, %10, %11, %12, %13, %14, %15}, %16, %17, 0, 1, 1, 1, 1;\n"
    : "=f"(d[0]), "=f"(d[1]), "=f"(d[2]), "=f"(d[3]), "=f"(d[4]), "=f"(d[5]), "=f"(d[6]), "=f"(d[7]), "=f"(d[8]), "=f"(d[9]), "=f"(d[10]), "=f"(d[11]), "=f"(d[12]), "=f"(d[13]), "=f"(d[14]), "=f"(d[15])
    : "l"(da), "l"(db));
}
template <int SD> __device__ __forceinline__ void wgmma_ss_n32_ta0_tb1(float (&d)[16], uint64_t da, uint64_t db) {
  if (SD) asm volatile("wgmma.mma_async.sync.aligned.m64n32k16.f32.bf16.bf16 {%0, %1, %2, %3, %4, %5, %6, %7, %8, %9, %10, %11, %12, %13, %14, %15}, %16, %17, 1, 1, 1, 0, 1;\n"
    : "+f"(d[0]), "+f"(d[1]), "+f"(d[2]), "+f"(d[3]), "+f"(d[4]), "+f"(d[5]), "+f"(d[6]), "+f"(d[7]), "+f"(d[8]), "+f"(d[9]), "+f"(d[10]), "+f"(d[11]), "+f"(d[12]), "+f"(d[13]), "+f"(d[14]), "+f"(d[15])
    : "l"(da), "l"(db));
  else asm volatile("wgmma.mma_async.sync.aligned.m64n32k16.f32.bf16.bf16 {%0, %1, %2, %3, %4, %5, %6, %7, %8, %9, %10, %11, %12, %13, %14, %15}, %16, %17, 0, 1, 1, 0, 1;\n"
    : "=f"(d[0]), "=f"(d[1]), "=f"(d[2]), "=f"(d[3]), "=f"(d[4]), "=f"(d[5]), "=f"(d[6]), "=f"(d[7]), "=f"(d[8]), "=f"(d[9]), "=f"(d[10]), "=f"(d[11]), "=f"(d[12]), "=f"(d[13]), "=f"(d[14]), "=f"(d[15])
    : "l"(da), "l"(db));
}
template <int SD> __device__ __forceinline__ void wgmma_rs_n64_tb0(float (&d)[32], uint32_t a0, uint32_t a1, uint32_t a2, uint32_t a3, uint64_t db) {
  if (SD) asm volatile("wgmma.mma_async.sync.aligned.m64n64k16.f32.bf16.bf16 {%0, %1, %2, %3, %4, %5, %6, %7, %8, %9, %10, %11, %12, %13, %14, %15, %16, %17, %18, %19, %20, %21, %22, %23, %24, %25, %26, %27, %28, %29, %30, %31}, {%32, %33, %34, %35}, %36, 1, 1, 1, 0;\n"
    : "+f"(d[0]), "+f"(d[1]), "+f"(d[2]), "+f"(d[3]), "+f"(d[4]), "+f"(d[5]), "+f"(d[6]), "+f"(d[7]), "+f"(d[8]), "+f"(d[9]), "+f"(d[10]), "+f"(d[11]), "+f"(d[12]), "+f"(d[13]), "+f"(d[14]), "+f"(d[15]), "+f"(d[16]), "+f"(d[17]), "+f"(d[18]), "+f"(d[19]), "+f"(d[20]), "+f"(d[21]), "+f"(d[22]), "+f"(d[23]), "+f"(d[24]), "+f"(d[25]), "+f"(d[26]), "+f"(d[27]), "+f"(d[28]), "+f"(d[29]), "+f"(d[30]), "+f"(d[31])
    : "r"(a0), "r"(a1), "r"(a2), "r"(a3), "l"(db));
  else asm volatile("wgmma.mma_async.sync.aligned.m64n64k16.f32.bf16.bf16 {%0, %1, %2, %3, %4, %5, %6, %7, %8, %9, %10, %11, %12, %13, %14, %15, %16, %17, %18, %19, %20, %21, %22, %23, %24, %25, %26, %27, %28, %29, %30, %31}, {%32, %33, %34, %35}, %36, 0, 1, 1, 0;\n"
    : "=f"(d[0]), "=f"(d[1]), "=f"(d[2]), "=f"(d[3]), "=f"(d[4]), "=f"(d[5]), "=f"(d[6]), "=f"(d[7]), "=f"(d[8]), "=f"(d[9]), "=f"(d[10]), "=f"(d[11]), "=f"(d[12]), "=f"(d[13]), "=f"(d[14]), "=f"(d[15]), "=f"(d[16]), "=f"(d[17]), "=f"(d[18]), "=f"(d[19]), "=f"(d[20]), "=f"(d[21]), "=f"(d[22]), "=f"(d[23]), "=f"(d[24]), "=f"(d[25]), "=f"(d[26]), "=f"(d[27]), "=f"(d[28]), "=f"(d[29]), "=f"(d[30]), "=f"(d[31])
    : "r"(a0), "r"(a1), "r"(a2), "r"(a3), "l"(db));
}
template <int SD> __device__ __forceinline__ void wgmma_rs_n32_tb1(float (&d)[16], uint32_t a0, uint32_t a1, uint32_t a2, uint32_t a3, uint64_t db) {
  if (SD) asm volatile("wgmma.mma_async.sync.aligned.m64n32k16.f32.bf16.bf16 {%0, %1, %2, %3, %4, %5, %6, %7, %8, %9, %10, %11, %12, %13, %14, %15}, {%16, %17, %18, %19}, %20, 1, 1, 1, 1;\n"
    : "+f"(d[0]), "+f"(d[1]), "+f"(d[2]), "+f"(d[3]), "+f"(d[4]), "+f"(d[5]), "+f"(d[6]), "+f"(d[7]), "+f"(d[8]), "+f"(d[9]), "+f"(d[10]), "+f"(d[11]), "+f"(d[12]), "+f"(d[13]), "+f"(d[14]), "+f"(d[15])
    : "r"(a0), "r"(a1), "r"(a2), "r"(a3), "l"(db));
  else asm volatile("wgmma.mma_async.sync.aligned.m64n32k16.f32.bf16.bf16 {%0, %1, %2, %3, %4, %5, %6, %7, %8, %9, %10, %11, %12, %13, %14, %15}, {%16, %17, %18, %19}, %20, 0, 1, 1, 1;\n"
    : "=f"(d[0]), "=f"(d[1]), "=f"(d[2]), "=f"(d[3]), "=f"(d[4]), "=f"(d[5]), "=f"(d[6]), "=f"(d[7]), "=f"(d[8]), "=f"(d[9]), "=f"(d[10]), "=f"(d[11]), "=f"(d[12]), "=f"(d[13]), "=f"(d[14]), "=f"(d[15])
    : "r"(a0), "r"(a1), "r"(a2), "r"(a3), "l"(db));
}

__device__ __forceinline__ uint32_t sw64_off(int row, int d) { return row * 64 + ((((d >> 3) ^ (row >> 1)) & 3) << 4) + (d & 7) * 2; }

__device__ __forceinline__ uint32_t exp2_pair_fma(float t0, float t1, uint32_t c_half, uint32_t c_3) {
  uint32_t y0, y;
  asm("prmt.b32 %0, %1, %2, 0x6521;" : "=r"(y0) : "r"(__float_as_uint(t0)), "r"(__float_as_uint(t1)));
  uint32_t h = lop_and_or(y0, 0x007F007Fu, c_half);
  uint32_t e = lop_and_or(y0, 0xFF80FF80u, c_3);
  asm("fma.rn.bf16x2 %0, %1, %2, %3;" : "=r"(y) : "r"(y0), "r"(h), "r"(e));
  return y;
}

__device__ __forceinline__ void feature_map(float (&v)[16], uint32_t (&ph)[16], int lq) {
  const float L2E = 1.4426950408889634f;
  const bool tail_ok = lq < 2;
  float mx[2], mn[2], b[16], sa[2], sn[2];
#pragma unroll
  for (int r = 0; r < 2; r++) {
    const int o = 2 * r;
    if (!tail_ok) { v[o + 12] = v[o]; v[o + 13] = v[o]; }
    mx[r] = fmaxf(fmaxf(fmaxf(v[o], v[o + 1]), fmaxf(v[o + 4], v[o + 5])), fmaxf(fmaxf(v[o + 8], v[o + 9]), fmaxf(v[o + 12], v[o + 13])));
    mn[r] = fminf(fminf(fminf(v[o], v[o + 1]), fminf(v[o + 4], v[o + 5])), fminf(fminf(v[o + 8], v[o + 9]), fminf(v[o + 12], v[o + 13])));
  }
#pragma unroll
  for (int o = 1; o <= 2; o <<= 1)
#pragma unroll
    for (int r = 0; r < 2; r++) { mx[r] = fmaxf(mx[r], __shfl_xor_sync(~0u, mx[r], o)); mn[r] = fminf(mn[r], __shfl_xor_sync(~0u, mn[r], o)); }
#pragma unroll
  for (int r = 0; r < 2; r++) {
    const int o = 2 * r;
    const float cx = -mx[r] * L2E, cn = mn[r] * L2E;
#pragma unroll
    for (int i = 0; i < 8; i++) {
      const int k = o + 4 * (i >> 1) + (i & 1);
      b[k] = ex2f(fmaf(v[k], -L2E, cn));
      v[k] = ex2f(fmaf(v[k], L2E, cx));
    }
    if (!tail_ok) { v[o + 12] = v[o + 13] = b[o + 12] = b[o + 13] = 0.f; }
    sa[r] = ((v[o] + v[o + 1]) + (v[o + 4] + v[o + 5])) + ((v[o + 8] + v[o + 9]) + (v[o + 12] + v[o + 13]));
    sn[r] = ((b[o] + b[o + 1]) + (b[o + 4] + b[o + 5])) + ((b[o + 8] + b[o + 9]) + (b[o + 12] + b[o + 13]));
  }
#pragma unroll
  for (int o = 1; o <= 2; o <<= 1)
#pragma unroll
    for (int r = 0; r < 2; r++) { sa[r] += __shfl_xor_sync(~0u, sa[r], o); sn[r] += __shfl_xor_sync(~0u, sn[r], o); }
#pragma unroll
  for (int r = 0; r < 2; r++) {
    const float ra = rcpf(sa[r]), rb = rcpf(sn[r]);
#pragma unroll
    for (int jj = 0; jj < 4; jj++) {
      ph[jj * 2 + r] = pack_bf16(v[2 * r + 4 * jj] * ra, v[2 * r + 4 * jj + 1] * ra);
      ph[(4 + jj) * 2 + r] = pack_bf16(b[2 * r + 4 * jj] * rb, b[2 * r + 4 * jj + 1] * rb);
    }
  }
}

__device__ __forceinline__ void store_heads(uint32_t base, const uint32_t (&a)[14], uint32_t pad0, uint32_t pad1, int row0, int lq) {
  const uint32_t rb = base + row0 * 64 + (((row0 >> 1) & 3) << 4);
  const uint32_t b0 = rb + lq * 4;
  const uint32_t b1 = (rb + 8192 + ((lq * 4 + 8) & 15)) ^ ((lq >> 1) << 4);
#pragma unroll
  for (int j = 0; j < 7; j++) {
    uint32_t ad;
    if (j < 3) ad = b0 ^ (j << 4);
    else if (j == 3) ad = (lq < 2) ? (b0 ^ 48u) : (b1 ^ 16u);
    else ad = (lq < 2) ? (b1 ^ ((j - 4) << 4)) : ((b1 ^ 16u) ^ ((j - 3) << 4));
    sts32(ad, a[2 * j]);
    sts32(ad + 512, a[2 * j + 1]);
  }
  sts64((rb ^ 48u) + 8 + (lq & 1) * 8192 + (lq >> 1) * 512, pad0, pad1);
}

struct Params {
  const __nv_bfloat16* w_phi;
  const __nv_bfloat16* wk;
  const __nv_bfloat16* wv;
  const __nv_bfloat16* gate_w;
  __nv_bfloat16* out;
};

__global__ void __launch_bounds__(NTHREADS, 1)
fused_kernel(const __grid_constant__ CUtensorMap tm_x, const __grid_constant__ CUtensorMap tm_wqkv,
             const __grid_constant__ CUtensorMap tm_wq, const __grid_constant__ CUtensorMap tm_woa,
             const __grid_constant__ CUtensorMap tm_wob, const Params prm) {
  extern __shared__ uint8_t smem_raw[];
  uint32_t sb = (smem_u32(smem_raw) + 1023u) & ~1023u;
  uint8_t* sgen = smem_raw + (sb - smem_u32(smem_raw));
  asm volatile("mov.u32 %0, %0;" : "+r"(sb));
  const int tid = threadIdx.x, lane = tid & 31;
  const int warp = __shfl_sync(~0u, tid >> 5, 0), wg = warp >> 2;
  const int pt = blockIdx.x >> 3, hp = blockIdx.x & 7;
  const uint32_t bars = sb + OFF_BAR;
  auto BAR = [&](int i) { return bars + 8u * i; };
  const unsigned epoch = g_epoch & 1;

  if (tid == 0) { PROF_MARK(0); PROF_CLK(30); PROF2(15); }
  auto load_proj = [&](int c, int g) {
    mbar_expect_tx(BAR(B_FULL + g), 49152);
    tma_2d(sb + OFF_X + c * 16384, &tm_x, c * 64, pt * 128, BAR(B_FULL + g));
    tma_2d(sb + OFF_RING + g * 32768, &tm_wq, hp * 56, c * 64, BAR(B_FULL + g));
#pragma unroll 1
    for (int j = 0; j < 3; j++) tma_2d(sb + OFF_RING + g * 32768 + 8192 + j * 8192, &tm_wqkv, j * DM + hp * 56, c * 64, BAR(B_FULL + g));
  };
  if (elect_one()) {
    const int i = warp == 16 ? 0 : (warp == 0 ? 16 : warp);
    if (i < B_N) {
      int cnt = (i >= B_EMPTY && i < B_WO) || i > B_SIG || i == B_X0FREE || i == B_X1FREE ? 16 : 1;
      if (i == B_BUILD) cnt = 3;
      if (i == B_SIG || i == B_QSQ) cnt = 8;
      mbar_init(BAR(i), cnt);
      fence_async_smem();
    }
    if (warp == 16) load_proj(0, 0);
  }
  __syncthreads();
  if (tid == 0) PROF2(14);

  if (wg == 4) {
    asm volatile("setmaxnreg.dec.sync.aligned.u32 32;");
    if (warp == 16) {
      if (elect_one()) {
        int g = 1, nkv = 8;
        uint32_t par = 1;
#pragma unroll 1
        for (int n = 1; n < 14 + nkv; n++) {
          if (n == 7) { PROF_MARK(20); cnt_wait(C_KV, NCTA); PROF_MARK(21); fence_async_all(); }
          if (n == 15) {
            mbar_wait(BAR(B_SLOW), 0);
            if (*(volatile int*)(sgen + OFF_RED)) nkv = 24;
          }
          const int j = n - 7 - nkv;
          if (j == 0 || j == 3) {
            PROF3(j ? 11 : 8);
            cnt_wait((j ? C_OB : C_OA) + pt, 8);
            PROF3(j ? 12 : 9);
            PROF_MARK(26);
            fence_async_all();
          }
          mbar_wait(BAR(B_EMPTY + g), par);
          if (n < 7) load_proj(n, g);
          else {
            mbar_expect_tx(BAR(B_FULL + g), 32768);
            bulk_g2s(sb + OFF_RING + g * 32768, j < 0 ? g_kv_img + ((n - 7) & 7) * 32768 : g_o_img + (size_t)(pt * 7 + j) * 32768, 32768,
                     BAR(B_FULL + g));
          }
          if (++g == 3) { g = 0; par ^= 1; }
        }
      }
    } else {
      {
        const int t = tid - 544;
#pragma unroll 1
        for (int i = t; i < 256; i += 96) sts128(sb + OFF_WPH + i * 16, make_uint4(0, 0, 0, 0));
        bar_sync(2, 96);
#pragma unroll 1
        for (int k = t; k < DM; k += 96) {
          const __nv_bfloat16* src = (hp < 4 ? prm.wk : prm.wv) + k * DH + (hp & 3) * 8;
          cp_async8(sb + OFF_SLC + k * 16, src);
          if ((hp & 3) != 3) cp_async8(sb + OFF_SLC + k * 16 + 8, src + 4);
          else sts64(sb + OFF_SLC + k * 16 + 8, hp == 3 ? (uint32_t)((const unsigned short*)prm.gate_w)[k] : 0u, 0u);
          if (k < 392) {
            const int row = k / 7, e = row >= DH;
            cp_async8(sb + OFF_WPH + e * 2048 + sw64_off(row - DH * e, (k % 7) * 4), prm.w_phi + 2 * hp * DH * DH + k * 4);
          }
        }
        asm volatile("cp.async.wait_all;" ::: "memory");
        fence_async_smem();
        __syncwarp();
        if (lane == 0) mbar_arrive(BAR(B_BUILD), 1);
      }
      if (warp == 18) {
        if (elect_one()) {
#pragma unroll 1
          for (int i = 0; i < 4; i++) {
            mbar_wait(BAR(B_SIG + i), 0);
            PROF3(2 * i);
            cnt_arrive(i == 0 ? C_KV : i == 1 ? C_PART : (i == 2 ? C_OA : C_OB) + pt);
            PROF3(2 * i + 1);
            if (i == 1 || i == 2) {
              mbar_wait(BAR(B_X0FREE + i - 1), 0);
              mbar_expect_tx(BAR(B_WO + i - 1), 57344);
#pragma unroll 1
              for (int c = 0; c < 7; c++)
                tma_2d(sb + OFF_WO + (i - 1) * 57344 + c * 8192, i == 1 ? &tm_woa : &tm_wob, hp * 56, c * 64, BAR(B_WO + i - 1));
            }
          }
        }
      } else if (warp == 19) {
        if (lane == 0) {
          mbar_wait(BAR(B_SIG + 0), 0);
          cnt_wait(C_KV, NCTA);
        }
        __syncwarp();
        float ksq = 0.f, vsq = 0.f;
#pragma unroll
        for (int sl = 0; sl < 4; sl++) {
          float4 a = ldcg_f4(g_ksq + sl * 128 + lane * 4), b = ldcg_f4(g_vsq + sl * 128 + lane * 4);
          float m = fmaxf(fmaxf(a.x, a.y), fmaxf(a.z, a.w));
          m = __uint_as_float(__reduce_max_sync(~0u, __float_as_uint(m)));
          ksq += m;
          vsq = fmaxf(vsq, fmaxf(fmaxf(b.x, b.y), fmaxf(b.z, b.w)));
        }
        mbar_wait(BAR(B_QSQ), 0);
        const float4 qa4 = ((const float4*)(sgen + OFF_QSQ))[lane], qb4 = ((const float4*)(sgen + OFF_QSQ))[32 + lane];
        const float qmax = fmaxf(fmaxf(fmaxf(qa4.x, qa4.y), fmaxf(qa4.z, qa4.w)), fmaxf(fmaxf(qb4.x, qb4.y), fmaxf(qb4.z, qb4.w)));
        const bool slow = __any_sync(~0u, !(qmax * ksq <= 98.f * 98.f) || !(vsq <= 2.0e8f));
        if (lane == 0) {
          *(volatile int*)(sgen + OFF_RED) = slow;
          mbar_arrive(BAR(B_SLOW), 1);
        }
      } else {
        float4* z = (float4*)(g_kvacc[epoch ^ 1] + blockIdx.x * 256) + lane;
        z[0] = make_float4(0.f, 0.f, 0.f, 0.f);
        z[32] = make_float4(0.f, 0.f, 0.f, 0.f);
        if (lane == 0) {
          mbar_wait(BAR(B_SIG + 1), 0);
          cnt_wait(C_PART, NCTA);
          PROF_MARK(23);
          mbar_arrive(BAR(B_KVR), 1);
        }
      }
    }
  } else {
    asm volatile("setmaxnreg.inc.sync.aligned.u32 112;");
    const int mh = wg & 1, nh = wg >> 1, wq = warp & 3;
    float acc0[28], acc1[28], accs[4] = {0.f, 0.f, 0.f, 0.f};
#pragma unroll
    for (int i = 0; i < 28; i++) acc0[i] = acc1[i] = 0.f;
    int slot = 0, prev = 0;
    uint32_t par = 0;

#pragma unroll 1
    for (int stage = 0; stage < 2; stage++) {
      {
        const uint64_t dS = make_desc(stage ? sb + OFF_WO : sb + OFF_X + mh * 8192, 1024, 1024, 1);
        const uint64_t dR = make_desc(sb + OFF_RING + (stage ? mh * 8192 : nh * 16384), 1024, 1024, 1);
#pragma unroll 1
        for (int c = 0; c < 7; c++) {
          if (stage) mbar_wait(BAR(B_WO + (c >= 3)), 0);
          if (tid == 0) PROF2(stage * 16 + c * 2);
          mbar_wait(BAR(B_FULL + slot), par);
          if (tid == 0) PROF2(stage * 16 + c * 2 + 1);
          const uint64_t ds = dS + c * 1024, dr = dR + slot * 2048;
          const uint64_t dA0 = stage ? dr : ds, dA1 = stage ? dr + 1024 : ds, dB0 = stage ? ds : dr, dB1 = dB0 + 512;
          wg_fence();
#pragma unroll
          for (int ks = 0; ks < 4; ks++) {
            wgmma_ss_n56_ta0_tb1<1>(acc0, dA0 + ks * 2, dB0 + ks * 128);
            wgmma_ss_n56_ta0_tb1<1>(acc1, dA1 + ks * 2, dB1 + ks * 128);
          }
          wg_commit();
          if (nh == 1) {
            mbar_wait(BAR(B_BUILD), 0);
            const uint64_t dSlc = make_desc(sb + OFF_SLC + c * 1024, 128, 128, 0);
            wg_fence();
#pragma unroll
            for (int ks = 0; ks < 4; ks++) wgmma_ss_n8_ta0_tb1<1>(accs, ds + ks * 2, dSlc + ks * 16);
            wg_commit();
          }
          wg_wait<0>();
          if (lane == 0) mbar_arrive(BAR(B_EMPTY + slot), 1 + stage);
          if (++slot == 3) { slot = 0; par ^= 1; }
        }
        fence_regs(acc0); fence_regs(acc1); fence_regs(accs);
      }
      if (stage) break;
      int lane_;
      asm volatile("mov.u32 %0, %%laneid;" : "=r"(lane_));
      const int lq = lane_ & 3;
      const int rowl = wq * 16 + (lane_ >> 2);
      const int row0 = mh * 64 + rowl;
      {
        if (tid == 0) PROF_MARK(2);
        if (tid == 256) PROF_MARK(3);
        if (nh == 0) {
          float sq[4] = {0.f, 0.f, 0.f, 0.f};
#pragma unroll
          for (int i = 0; i < 28; i++) acc0[i] *= 0.18898223650461362f * 1.4426950408889634f;
#pragma unroll
          for (int j = 0; j < 7; j++) {
#pragma unroll
            for (int rr = 0; rr < 2; rr++) {
              const float s2 = acc0[4 * j + 2 * rr] * acc0[4 * j + 2 * rr] + acc0[4 * j + 2 * rr + 1] * acc0[4 * j + 2 * rr + 1];
              if (j < 3) sq[rr] += s2;
              else if (j > 3) sq[2 + rr] += s2;
              else { sq[rr] += (lq < 2) ? s2 : 0.f; sq[2 + rr] += (lq < 2) ? 0.f : s2; }
            }
          }
#pragma unroll
          for (int i = 0; i < 4; i++) sq[i] = quad_sum(sq[i]);
          const float mine = lq == 0 ? sq[0] : lq == 1 ? sq[1] : lq == 2 ? sq[2] : sq[3];
          ((float*)(sgen + OFF_QSQ))[(mh + (lq & 2)) * 64 + rowl + 8 * (lq & 1)] = mine <= 3.0e38f ? mine : __int_as_float(0x7f800000);
          __syncwarp();
          if (lane == 0) mbar_arrive(BAR(B_QSQ), 1);
        } else {
          const int sl = hp & 3;
          const bool isk = hp < 4, real = (sl < 3) || (lq < 2);
          const int pos = pt * 128 + row0, kr = pos & 63;
          uint8_t* dst = g_kv_img + (pos >> 6) * 8192 + (isk ? 0 : 4096) + sw64_off(kr, sl * 8 + 2 * lq);
          const uint32_t pat = isk ? POLY_PAT >> (kr >> 3) : 0u;
          float mxv = 0.f;
#pragma unroll
          for (int rr = 0; rr < 2; rr++) {
            const float v0 = accs[2 * rr], v1 = accs[2 * rr + 1];
            const bool poly = (pat >> rr) & 1;
            const float sc = poly ? 2.f : 1.f;
            const float s2 = quad_sum(real ? v0 * v0 + v1 * v1 : 0.f);
            mxv = fmaxf(mxv, s2 <= 3.0e38f ? s2 : __int_as_float(0x7f800000));
            const uint32_t padv = lq == 2 ? (poly ? 0x443F4000u : 0x00003F80u) : (poly ? 0x3AB03F4Du : 0u);
            *(uint32_t*)(dst + rr * 512) = real ? pack_bf16(sc * v0, sc * v1) : padv;
            if (hp == 3 && lq == 2) g_gate[pos + 8 * rr] = rcpf(1.f + ex2f(-1.4426950408889634f * v0));
          }
          mxv = __uint_as_float(__reduce_max_sync(~0u, __float_as_uint(mxv)));
          if (lane == 0) (isk ? g_ksq : g_vsq)[sl * 128 + pt * 8 + mh * 4 + wq] = mxv;
          __syncwarp();
          if (lane == 0) mbar_arrive(BAR(B_SIG + 0), 1);
        }
      }
      if (tid == 0) PROF_MARK(4);
      if (tid == 256) PROF_MARK(5);
      {
        uint32_t h0[14], h1[14];
#pragma unroll
        for (int i = 0; i < 14; i++) { h0[i] = pack_bf16(acc0[2 * i], acc0[2 * i + 1]); h1[i] = pack_bf16(acc1[2 * i], acc1[2 * i + 1]); }
        bar_sync(1, 512);
        if (tid == 0) PROF_MARK(6);
#pragma unroll 1
        for (int r = 0; r < 2; r++) {
          store_heads(sb + (r ? (nh ? OFF_VA : OFF_QA) : (nh ? OFF_KA : OFF_QP)), h0,
                      (r & nh) ? 0x00003F80u : (r | nh) ? 0u : 0x3F800000u, (r | nh) ? 0u : 0x3F803F80u, row0, lq);
#pragma unroll
          for (int i = 0; i < 14; i++) h0[i] = h1[i];
        }
      }
      fence_async_smem();
      bar_sync(1, 512);
      if (tid == 0) PROF_MARK(7);

      const uint64_t dK = make_desc(sb + OFF_RING, 512, 512, 2);
      const uint64_t dhi = dK & 0xffffffff00000000ull;
      const uint32_t dlo0 = (uint32_t)dK;
      uint32_t ok = 0, q[8];
      float g0 = 0.f, g1 = 0.f;
      float o[16];
#pragma unroll
      for (int i = 0; i < 16; i++) o[i] = 0.f;
      {
        const uint32_t qa = sb + OFF_QP + nh * 8192;
        const int r = mh * 64 + wq * 16 + (lane_ & 7) + ((lane_ >> 3) & 1) * 8;
#pragma unroll
        for (int ks = 0; ks < 2; ks++)
          asm volatile("ldmatrix.sync.aligned.m8n8.x4.shared.b16 {%0, %1, %2, %3}, [%4];"
                       : "=r"(q[4 * ks]), "=r"(q[4 * ks + 1]), "=r"(q[4 * ks + 2]), "=r"(q[4 * ks + 3])
                       : "r"(qa + sw64_off(r, ks * 16 + (lane_ >> 4) * 8)) : "memory");
      }
      const int kb = KB_AT, qb = QB_AT;
#pragma unroll 1
      for (int it = 0; it <= 8; it++) {
        uint32_t p[16];
        if (it == kb || it == qb || it == 8) {
          float t[16];
          wg_wait<0>();
          fence_regs(o);
          if (it < 8) {
            if (tid == 0) PROF_MARK(it == kb ? 27 : 11);
            const uint64_t dA = make_desc(sb + (it == kb ? OFF_KA : OFF_QA) + nh * 8192 + mh * 4096, 512, 512, 2);
            const uint64_t dB = make_desc(sb + OFF_WPH + nh * 2048, 512, 512, 2);
            float* kvacc = g_kvacc[epoch] + (2 * hp + nh) * 2048;
            float pa[16];
            wg_fence();
            wgmma_ss_n32_ta0_tb1<0>(pa, dA, dB);
            wgmma_ss_n32_ta0_tb1<1>(pa, dA + 2, dB + 64);
            wg_commit();
            if (it != kb) {
              mbar_wait(BAR(B_KVR), 0);
              g0 = ldcg_f(g_gate + pt * 128 + row0); g1 = ldcg_f(g_gate + pt * 128 + row0 + 8);
              const int tl = tid & 127;
              const float4 a = ldcg_f4(kvacc + tl * 16), b = ldcg_f4(kvacc + tl * 16 + 4), c = ldcg_f4(kvacc + tl * 16 + 8), d = ldcg_f4(kvacc + tl * 16 + 12);
              const uint32_t ad = sb + OFF_KVR + nh * 4096 + sw64_off(tl >> 1, (tl & 1) * 16);
              sts128(ad, make_uint4(pack_bf16(a.x, a.y), pack_bf16(a.z, a.w), pack_bf16(b.x, b.y), pack_bf16(b.z, b.w)));
              sts128(ad ^ 16u, make_uint4(pack_bf16(c.x, c.y), pack_bf16(c.z, c.w), pack_bf16(d.x, d.y), pack_bf16(d.z, d.w)));
            }
            wg_wait<0>();
            fence_regs(pa);
            uint32_t ph[16];
            feature_map(pa, ph, lq);
            const uint32_t rb = sb + OFF_PHI + wg * 8192 + rowl * 128 + lq * 4 + ((rowl & 7) << 4);
#pragma unroll
            for (int ch = 0; ch < 8; ch++) { sts32(rb ^ (ch << 4), ph[2 * ch]); sts32((rb ^ (ch << 4)) + 1024, ph[2 * ch + 1]); }
            fence_async_smem();
            bar_sync(4 + wg, 128);
            const uint64_t dP = make_desc(sb + OFF_PHI + wg * 8192, 1024, 1024, 1);
            if (it == kb) {
              const uint64_t dV = make_desc(sb + OFF_VA + nh * 8192 + mh * 4096, 512, 512, 2);
              float kv[16];
              wg_fence();
              wgmma_ss_n32_ta1_tb1<0>(kv, dP, dV);
#pragma unroll
              for (int ks = 1; ks < 4; ks++) wgmma_ss_n32_ta1_tb1<1>(kv, dP + ks * 128, dV + ks * 64);
              wg_commit();
              wg_wait<0>();
              fence_regs(kv);
              float* dst = kvacc + rowl * 32 + 2 * lq;
#pragma unroll
              for (int j = 0; j < 8; j++)
                asm volatile("red.global.add.v2.f32 [%0], {%1, %2};" ::"l"(dst + 8 * (j >> 1) + 256 * (j & 1)), "f"(kv[2 * j]), "f"(kv[2 * j + 1]) : "memory");
              __syncwarp();
              if (lane == 0) { mbar_arrive(BAR(B_SIG + 1), 1); mbar_arrive(BAR(B_X0FREE), 1); }
              if (tid == 0) PROF_MARK(28);
              goto after_block;
            } else {
              const uint64_t dR = make_desc(sb + OFF_KVR + nh * 4096, 512, 512, 2);
              wg_fence();
              wgmma_ss_n32_ta0_tb1<0>(t, dP, dR);
#pragma unroll
              for (int ks = 1; ks < 4; ks++) wgmma_ss_n32_ta0_tb1<1>(t, dP + ks * 2, dR + ks * 64);
              wg_commit();
              wg_wait<0>();
              fence_regs(t);
              if (lane == 0) mbar_arrive(BAR(B_X1FREE), 1);
            }
          } else {
            if (lane == 0) mbar_arrive(BAR(B_EMPTY + prev), 1);
            if (tid == 0) PROF_MARK(13);
            mbar_wait(BAR(B_SLOW), 0);
            if (__builtin_expect(__any_sync(~0u, *(volatile int*)(sgen + OFF_RED)), 0)) {
              if (lq >= 2) q[6] = q[7] = 0u;
              float m0 = -3.0e38f, m1 = -3.0e38f;
#pragma unroll
              for (int i = 0; i < 16; i++) o[i] = 0.f;
#pragma unroll 1
              for (int j64 = 0; j64 < 64; j64++) {
                float s[32];
                if ((j64 & 3) == 0) mbar_wait(BAR(B_FULL + slot), par);
                const uint32_t lo = dlo0 + slot * 2048 + (j64 & 3) * 512;
                wg_fence();
                wgmma_rs_n64_tb0<0>(s, q[0], q[1], q[2], q[3], dhi | lo);
                wgmma_rs_n64_tb0<1>(s, q[4], q[5], q[6], q[7], dhi | (lo + 2));
                wg_commit();
                wg_wait<0>();
                fence_regs(s);
                uint32_t ps[16];
#pragma unroll
                for (int j = 0; j < 8; j++) {
                  const float sc = ((POLY_PAT >> j) & 1) ? 0.5f : 1.f;
                  if (j64 < 32) {
                    m0 = fmaxf(m0, fmaxf(s[4 * j], s[4 * j + 1]) * sc);
                    m1 = fmaxf(m1, fmaxf(s[4 * j + 2], s[4 * j + 3]) * sc);
                  }
                  ps[2 * j] = j64 < 32 ? 0u : pack_bf16(ex2f(fmaf(s[4 * j], sc, -m0)), ex2f(fmaf(s[4 * j + 1], sc, -m0)));
                  ps[2 * j + 1] = j64 < 32 ? 0u : pack_bf16(ex2f(fmaf(s[4 * j + 2], sc, -m1)), ex2f(fmaf(s[4 * j + 3], sc, -m1)));
                }
                wg_fence();
#pragma unroll
                for (int ks = 0; ks < 4; ks++)
                  wgmma_rs_n32_tb1<1>(o, ps[4 * ks], ps[4 * ks + 1], ps[4 * ks + 2], ps[4 * ks + 3], dhi | (lo + 256 + ks * 64));
                wg_commit();
                wg_wait<0>();
                fence_regs(o);
                if ((j64 & 3) == 3) {
                  if (lane == 0) mbar_arrive(BAR(B_EMPTY + slot), 1);
                  if (++slot == 3) { slot = 0; par ^= 1; }
                }
                if (j64 == 31) { m0 = quad_max(m0); m1 = quad_max(m1); }
              }
            }
#pragma unroll
            for (int i = 0; i < 16; i++) t[i] = o[i];
          }
          {
            const int br = it == 8;
            const float eps = br ? 0.f : 1e-6f;
            const float d0 = __shfl_sync(~0u, t[12], (lane_ & ~3) | 2), d1 = __shfl_sync(~0u, t[14], (lane_ & ~3) | 2);
            const float r0 = __fdividef(br ? 1.f - g0 : g0, d0 + eps), r1 = __fdividef(br ? 1.f - g1 : g1, d1 + eps);
            uint8_t* img = g_o_img + (size_t)((pt * 2 + br) * 14 + mh) * 8192 + rowl * 128;
            const int col0 = (2 * hp + nh) * DH + 2 * lq;
#pragma unroll
            for (int j = 0; j < 4; j++) {
              const int col = col0 + 8 * j;
              uint8_t* gp = img + (col >> 6) * 16384 + ((((col >> 3) ^ rowl) & 7) << 4) + (col & 7) * 2;
              const uint32_t v0 = pack_bf16(t[4 * j] * r0, t[4 * j + 1] * r0), v1 = pack_bf16(t[4 * j + 2] * r1, t[4 * j + 3] * r1);
              if (j < 3 || lq < 2) { *(uint32_t*)gp = v0; *(uint32_t*)(gp + 1024) = v1; }
            }
            __syncwarp();
            if (lane == 0) mbar_arrive(BAR(B_SIG + 2 + br), 1);
            if (tid == 0) PROF_MARK(12 + 2 * br);
            if (br) break;
          }
        }
      after_block:
        if (it == 0 && tid == 0) PROF_MARK(10);
        const uint32_t lo = dlo0 + slot * 2048;
        if (!ok) mbar_wait(BAR(B_FULL + slot), par);
        int nslot = slot + 1;
        uint32_t npar = par;
        if (nslot == 3) { nslot = 0; npar ^= 1; }
        {
          float s[32];
          wg_fence();
          wgmma_rs_n64_tb0<0>(s, q[0], q[1], q[2], q[3], dhi | lo);
          wgmma_rs_n64_tb0<1>(s, q[4], q[5], q[6], q[7], dhi | (lo + 2));
          wg_commit();
#pragma unroll
          for (int u = 0; u < 4; u++) {
            wg_wait<0>();
            fence_regs(s);
            if (u == 0 && lane == 0 && it > 0) mbar_arrive(BAR(B_EMPTY + prev), 1);
            if (u == 2) ok = mbar_test(BAR(B_FULL + nslot), npar);
#pragma unroll
            for (int j = 0; j < 8; j++) {
              if ((POLY_PAT >> j) & 1) {
                p[2 * j] = exp2_pair_fma(s[4 * j], s[4 * j + 1], 0x3F003F00u, 0x00030003u);
                p[2 * j + 1] = exp2_pair_fma(s[4 * j + 2], s[4 * j + 3], 0x3F003F00u, 0x00030003u);
              } else {
                p[2 * j] = pack_bf16(ex2f(s[4 * j]), ex2f(s[4 * j + 1]));
                p[2 * j + 1] = pack_bf16(ex2f(s[4 * j + 2]), ex2f(s[4 * j + 3]));
              }
            }
            wg_fence();
#pragma unroll
            for (int ks = 0; ks < 4; ks++)
              wgmma_rs_n32_tb1<1>(o, p[4 * ks], p[4 * ks + 1], p[4 * ks + 2], p[4 * ks + 3], dhi | (lo + u * 512 + 256 + ks * 64));
            if (u < 3) {
              wgmma_rs_n64_tb0<0>(s, q[0], q[1], q[2], q[3], dhi | (lo + (u + 1) * 512));
              wgmma_rs_n64_tb0<1>(s, q[4], q[5], q[6], q[7], dhi | (lo + (u + 1) * 512 + 2));
            }
            wg_commit();
          }
        }
        prev = slot; slot = nslot; par = npar;
      }
      wg_wait<0>();
      if (nh == 1) return;
#pragma unroll
      for (int i = 0; i < 28; i++) acc0[i] = acc1[i] = 0.f;
#pragma unroll
      for (int i = 0; i < 4; i++) accs[i] = 0.f;
    }
    if (tid == 0) PROF_MARK(17);
    __nv_bfloat16* op = prm.out + (size_t)(pt * 128 + mh * 64 + wq * 16 + (lane >> 2)) * DM + hp * 56 + 2 * (lane & 3);
#pragma unroll
    for (int j = 0; j < 7; j++) {
      *(uint32_t*)(op + 8 * j) = pack_bf16(acc0[4 * j] + acc1[4 * j], acc0[4 * j + 1] + acc1[4 * j + 1]);
      *(uint32_t*)(op + 8 * DM + 8 * j) = pack_bf16(acc0[4 * j + 2] + acc1[4 * j + 2], acc0[4 * j + 3] + acc1[4 * j + 3]);
    }
    if (tid == 0) { PROF_MARK(18); PROF_CLK(31); }
    if (tid == 0) {
      unsigned prevd = atomicAdd(&g_cnt[C_DONE * 32], 1u);
      if (prevd == NCTA - 1) {
#pragma unroll 1
        for (int i = 0; i < C_N; i++) g_cnt[i * 32] = 0;
        g_epoch = epoch ^ 1;
      }
    }
  }
}

typedef CUresult (*EncodeFn)(CUtensorMap*, CUtensorMapDataType, cuuint32_t, void*, const cuuint64_t*, const cuuint64_t*,
                             const cuuint32_t*, const cuuint32_t*, CUtensorMapInterleave, CUtensorMapSwizzle,
                             CUtensorMapL2promotion, CUtensorMapFloatOOBfill);

void make_map(EncodeFn enc, CUtensorMap* tm, const void* ptr, uint64_t cols, uint64_t rows, uint32_t box_rows) {
  cuuint64_t dims[2] = {cols, rows};
  cuuint64_t strides[1] = {cols * 2};
  cuuint32_t box[2] = {64, box_rows};
  cuuint32_t es[2] = {1, 1};
  enc(tm, CU_TENSOR_MAP_DATA_TYPE_BFLOAT16, 2, const_cast<void*>(ptr), dims, strides, box, es, CU_TENSOR_MAP_INTERLEAVE_NONE,
      CU_TENSOR_MAP_SWIZZLE_128B, CU_TENSOR_MAP_L2_PROMOTION_L2_128B, CU_TENSOR_MAP_FLOAT_OOB_FILL_NONE);
}

}

extern "C" void kernel_launch(void* const* d_in, const int* in_sizes, int n_in, void* d_out, int out_size) {
  (void)in_sizes; (void)n_in; (void)out_size;
  static EncodeFn enc = nullptr;
  if (!enc) {
    void* fn = nullptr;
    cudaDriverEntryPointQueryResult qr;
    cudaGetDriverEntryPoint("cuTensorMapEncodeTiled", &fn, cudaEnableDefault, &qr);
    enc = (EncodeFn)fn;
    cudaFuncSetAttribute(fused_kernel, cudaFuncAttributeMaxDynamicSharedMemorySize, SMEM_BYTES);
  }
  CUtensorMap tm_x, tm_wqkv, tm_wq, tm_woa, tm_wob;
  make_map(enc, &tm_x, d_in[0], DM, S_LEN, 128);
  make_map(enc, &tm_wqkv, d_in[1], 3 * DM, DM, 64);
  make_map(enc, &tm_wq, d_in[5], DM, DM, 64);
  make_map(enc, &tm_woa, d_in[3], DM, DM, 64);
  make_map(enc, &tm_wob, d_in[8], DM, DM, 64);
  Params prm;
  prm.w_phi = (const __nv_bfloat16*)d_in[2];
  prm.wk = (const __nv_bfloat16*)d_in[6];
  prm.wv = (const __nv_bfloat16*)d_in[7];
  prm.gate_w = (const __nv_bfloat16*)d_in[9];
  prm.out = (__nv_bfloat16*)d_out;
  fused_kernel<<<NCTA, NTHREADS, SMEM_BYTES>>>(tm_x, tm_wqkv, tm_wq, tm_woa, tm_wob, prm);
}
```

```cpp
#include <cuda_runtime.h>
#include <cuda_bf16.h>
#include <cuda.h>
#include <stdint.h>

namespace {

constexpr int S_LEN = 2048, DM = 448, DH = 28;
constexpr int NCTA = 128;
constexpr int NTHREADS = 640;
constexpr uint32_t POLY_PAT = 0x57;

#define KB_AT 0
#define QB_AT (3 + nh)

constexpr int OFF_X = 0;
constexpr int OFF_KA = 0;
constexpr int OFF_VA = 16384;
constexpr int OFF_QP = 32768;
constexpr int OFF_QA = 57344;
constexpr int OFF_KVR = 73728;
constexpr int OFF_PHI = 81920;
constexpr int OFF_WO = 0;
constexpr int OFF_RING = 114688;
constexpr int OFF_WPH = 212992;
constexpr int OFF_SLC = 217088;
constexpr int OFF_QSQ = 224256;
constexpr int OFF_RED = 225792;
constexpr int OFF_BAR = 225856;
constexpr int SMEM_BYTES = 226368 + 1024;

constexpr int B_FULL = 0, B_EMPTY = 3, B_WO = 6  , B_KVR = 8, B_X0FREE = 9, B_X1FREE = 10, B_QSQ = 11, B_SLOW = 12,
              B_BUILD = 13, B_SIG = 14  , B_N = 18;

constexpr int C_KV = 0, C_PART = 1, C_DONE = 3, C_OA = 4, C_OB = 20, C_N = 36;

__device__ __align__(1024) uint8_t g_kv_img[32 * 8192];
__device__ __align__(16) float g_ksq[512];
__device__ __align__(16) float g_vsq[512];
__device__ __align__(16) float g_gate[S_LEN];
__device__ __align__(1024) float g_kvacc[2][16 * 64 * 32];
__device__ unsigned g_epoch;
__device__ __align__(1024) uint8_t g_o_img[2 * 16 * 14 * 8192];
__device__ unsigned g_cnt[C_N * 32];

#define PROF3(i) do { } while (0)
#define PROF2(i) do { } while (0)
#define PROF_CLK(i) do { } while (0)
#define PROF_MARK(i) do { } while (0)
__device__ __forceinline__ uint32_t smem_u32(const void* p) { return (uint32_t)__cvta_generic_to_shared(p); }
__device__ __forceinline__ void mbar_init(uint32_t a, int cnt) {
  asm volatile("mbarrier.init.shared::cta.b64 [%0], %1;" ::"r"(a), "r"(cnt) : "memory");
}
__device__ __forceinline__ void mbar_expect_tx(uint32_t a, uint32_t bytes) {
  asm volatile("mbarrier.arrive.expect_tx.shared::cta.b64 _, [%0], %1;" ::"r"(a), "r"(bytes) : "memory");
}
__device__ __forceinline__ void mbar_arrive(uint32_t a, uint32_t cnt) {
  asm volatile("mbarrier.arrive.shared::cta.b64 _, [%0], %1;" ::"r"(a), "r"(cnt) : "memory");
}
__device__ __forceinline__ void mbar_wait(uint32_t a, uint32_t parity) {
  asm volatile(
      "{\n.reg .pred p;\n.reg .u32 c;\nmov.u32 c, 0;\n"
      "W_%=:\nmbarrier.try_wait.parity.shared::cta.b64 p, [%0], %1;\n"
      "add.u32 c, c, 1;\nsetp.lt.and.u32 p, c, 0x1000000, !p;\n@p bra W_%=;\n}"
      ::"r"(a), "r"(parity) : "memory");
}
__device__ __forceinline__ uint32_t mbar_test(uint32_t a, uint32_t parity) {
  uint32_t ok;
  asm volatile("{\n.reg .pred p;\nmbarrier.test_wait.parity.shared::cta.b64 p, [%1], %2;\nselp.u32 %0, 1, 0, p;\n}"
               : "=r"(ok) : "r"(a), "r"(parity) : "memory");
  return ok;
}
__device__ __forceinline__ bool elect_one() {
  uint32_t r;
  asm volatile("{\n.reg .pred p;\nelect.sync _|p, 0xffffffff;\nselp.u32 %0, 1, 0, p;\n}" : "=r"(r));
  return r != 0;
}
__device__ __forceinline__ void tma_2d(uint32_t dst, const CUtensorMap* tm, int c0, int c1, uint32_t bar) {
  asm volatile("cp.async.bulk.tensor.2d.shared::cluster.global.mbarrier::complete_tx::bytes [%0], [%1, {%3, %4}], [%2];"
               ::"r"(dst), "l"(tm), "r"(bar), "r"(c0), "r"(c1) : "memory");
}
__device__ __forceinline__ void bulk_g2s(uint32_t dst, const void* src, uint32_t bytes, uint32_t bar) {
  asm volatile("cp.async.bulk.shared::cluster.global.mbarrier::complete_tx::bytes [%0], [%1], %2, [%3];"
               ::"r"(dst), "l"(src), "r"(bytes), "r"(bar) : "memory");
}
__device__ __forceinline__ void cp_async8(uint32_t dst, const void* src) {
  asm volatile("cp.async.ca.shared.global [%0], [%1], 8;" ::"r"(dst), "l"(src) : "memory");
}
__device__ __forceinline__ void fence_async_smem() { asm volatile("fence.proxy.async.shared::cta;" ::: "memory"); }
__device__ __forceinline__ void fence_async_all() { asm volatile("fence.proxy.async.global;" ::: "memory"); }
__device__ __forceinline__ float ldcg_f(const float* p) { float v; asm volatile("ld.global.cg.f32 %0, [%1];" : "=f"(v) : "l"(p) : "memory"); return v; }
__device__ __forceinline__ void bar_sync(int id, int n) { asm volatile("bar.sync %0, %1;" ::"r"(id), "r"(n) : "memory"); }
__device__ __forceinline__ void cnt_arrive(int idx) {
  asm volatile("red.release.gpu.global.add.u32 [%0], 1;" ::"l"(&g_cnt[idx * 32]) : "memory");
}
__device__ __forceinline__ void cnt_wait(int idx, unsigned target) {
  unsigned v, n = 0;
#pragma unroll 1
  while (true) {
    asm volatile("ld.acquire.gpu.global.u32 %0, [%1];" : "=r"(v) : "l"(&g_cnt[idx * 32]) : "memory");
    if (v >= target || ++n >= (1u << 22)) break;
    __nanosleep(32);
  }
}
__device__ __forceinline__ void wg_fence() { asm volatile("wgmma.fence.sync.aligned;" ::: "memory"); }
__device__ __forceinline__ void wg_commit() { asm volatile("wgmma.commit_group.sync.aligned;" ::: "memory"); }
template <int N> __device__ __forceinline__ void wg_wait() { asm volatile("wgmma.wait_group.sync.aligned %0;" ::"n"(N) : "memory"); }
template <int N> __device__ __forceinline__ void fence_regs(float (&d)[N]) {
#pragma unroll
  for (int i = 0; i < N; i++) asm volatile("" : "+f"(d[i])::"memory");
}
__device__ __forceinline__ uint64_t make_desc(uint32_t saddr, uint32_t lbo, uint32_t sbo, uint32_t swz) {
  return (uint64_t)((saddr & 0x3FFFF) >> 4) | ((uint64_t)(lbo >> 4) << 16) | ((uint64_t)(sbo >> 4) << 32) | ((uint64_t)swz << 62);
}
__device__ __forceinline__ float ex2f(float x) { float y; asm("ex2.approx.ftz.f32 %0, %1;" : "=f"(y) : "f"(x)); return y; }
__device__ __forceinline__ float rcpf(float x) { float y; asm("rcp.approx.ftz.f32 %0, %1;" : "=f"(y) : "f"(x)); return y; }
__device__ __forceinline__ uint32_t pack_bf16(float lo, float hi) {
  uint32_t r; asm("cvt.rn.bf16x2.f32 %0, %1, %2;" : "=r"(r) : "f"(hi), "f"(lo)); return r;
}
__device__ __forceinline__ uint32_t lop_and_or(uint32_t a, uint32_t m, uint32_t c) {
  uint32_t r; asm("lop3.b32 %0, %1, %2, %3, 0xEA;" : "=r"(r) : "r"(a), "r"(m), "r"(c)); return r;
}
__device__ __forceinline__ void sts32(uint32_t a, uint32_t v) { asm volatile("st.shared.b32 [%0], %1;" ::"r"(a), "r"(v) : "memory"); }
__device__ __forceinline__ void sts64(uint32_t a, uint32_t v0, uint32_t v1) { asm volatile("st.shared.v2.b32 [%0], {%1, %2};" ::"r"(a), "r"(v0), "r"(v1) : "memory"); }
__device__ __forceinline__ void sts128(uint32_t a, uint4 v) {
  asm volatile("st.shared.v4.b32 [%0], {%1, %2, %3, %4};" ::"r"(a), "r"(v.x), "r"(v.y), "r"(v.z), "r"(v.w) : "memory");
}
__device__ __forceinline__ float4 ldcg_f4(const float* p) {
  float4 v; asm volatile("ld.global.cg.v4.f32 {%0, %1, %2, %3}, [%4];" : "=f"(v.x), "=f"(v.y), "=f"(v.z), "=f"(v.w) : "l"(p) : "memory"); return v;
}
__device__ __forceinline__ float quad_sum(float v) { v += __shfl_xor_sync(~0u, v, 1); v += __shfl_xor_sync(~0u, v, 2); return v; }
__device__ __forceinline__ float quad_max(float v) { v = fmaxf(v, __shfl_xor_sync(~0u, v, 1)); v = fmaxf(v, __shfl_xor_sync(~0u, v, 2)); return v; }

template <int SD> __device__ __forceinline__ void wgmma_ss_n56_ta0_tb1(float (&d)[28], uint64_t da, uint64_t db) {
  if (SD) asm volatile("wgmma.mma_async.sync.aligned.m64n56k16.f32.bf16.bf16 {%0, %1, %2, %3, %4, %5, %6, %7, %8, %9, %10, %11, %12, %13, %14, %15, %16, %17, %18, %19, %20, %21, %22, %23, %24, %25, %26, %27}, %28, %29, 1, 1, 1, 0, 1;\n"
    : "+f"(d[0]), "+f"(d[1]), "+f"(d[2]), "+f"(d[3]), "+f"(d[4]), "+f"(d[5]), "+f"(d[6]), "+f"(d[7]), "+f"(d[8]), "+f"(d[9]), "+f"(d[10]), "+f"(d[11]), "+f"(d[12]), "+f"(d[13]), "+f"(d[14]), "+f"(d[15]), "+f"(d[16]), "+f"(d[17]), "+f"(d[18]), "+f"(d[19]), "+f"(d[20]), "+f"(d[21]), "+f"(d[22]), "+f"(d[23]), "+f"(d[24]), "+f"(d[25]), "+f"(d[26]), "+f"(d[27])
    : "l"(da), "l"(db));
  else asm volatile("wgmma.mma_async.sync.aligned.m64n56k16.f32.bf16.bf16 {%0, %1, %2, %3, %4, %5, %6, %7, %8, %9, %10, %11, %12, %13, %14, %15, %16, %17, %18, %19, %20, %21, %22, %23, %24, %25, %26, %27}, %28, %29, 0, 1, 1, 0, 1;\n"
    : "=f"(d[0]), "=f"(d[1]), "=f"(d[2]), "=f"(d[3]), "=f"(d[4]), "=f"(d[5]), "=f"(d[6]), "=f"(d[7]), "=f"(d[8]), "=f"(d[9]), "=f"(d[10]), "=f"(d[11]), "=f"(d[12]), "=f"(d[13]), "=f"(d[14]), "=f"(d[15]), "=f"(d[16]), "=f"(d[17]), "=f"(d[18]), "=f"(d[19]), "=f"(d[20]), "=f"(d[21]), "=f"(d[22]), "=f"(d[23]), "=f"(d[24]), "=f"(d[25]), "=f"(d[26]), "=f"(d[27])
    : "l"(da), "l"(db));
}
template <int SD> __device__ __forceinline__ void wgmma_ss_n8_ta0_tb1(float (&d)[4], uint64_t da, uint64_t db) {
  if (SD) asm volatile("wgmma.mma_async.sync.aligned.m64n8k16.f32.bf16.bf16 {%0, %1, %2, %3}, %4, %5, 1, 1, 1, 0, 1;\n"
    : "+f"(d[0]), "+f"(d[1]), "+f"(d[2]), "+f"(d[3])
    : "l"(da), "l"(db));
  else asm volatile("wgmma.mma_async.sync.aligned.m64n8k16.f32.bf16.bf16 {%0, %1, %2, %3}, %4, %5, 0, 1, 1, 0, 1;\n"
    : "=f"(d[0]), "=f"(d[1]), "=f"(d[2]), "=f"(d[3])
    : "l"(da), "l"(db));
}
template <int SD> __device__ __forceinline__ void wgmma_ss_n32_ta1_tb1(float (&d)[16], uint64_t da, uint64_t db) {
  if (SD) asm volatile("wgmma.mma_async.sync.aligned.m64n32k16.f32.bf16.bf16 {%0, %1, %2, %3, %4, %5, %6, %7, %8, %9, %10, %11, %12, %13, %14, %15}, %16, %17, 1, 1, 1, 1, 1;\n"
    : "+f"(d[0]), "+f"(d[1]), "+f"(d[2]), "+f"(d[3]), "+f"(d[4]), "+f"(d[5]), "+f"(d[6]), "+f"(d[7]), "+f"(d[8]), "+f"(d[9]), "+f"(d[10]), "+f"(d[11]), "+f"(d[12]), "+f"(d[13]), "+f"(d[14]), "+f"(d[15])
    : "l"(da), "l"(db));
  else asm volatile("wgmma.mma_async.sync.aligned.m64n32k16.f32.bf16.bf16 {%0, %1, %2, %3, %4, %5, %6, %7, %8, %9, %10, %11, %12, %13, %14, %15}, %16, %17, 0, 1, 1, 1, 1;\n"
    : "=f"(d[0]), "=f"(d[1]), "=f"(d[2]), "=f"(d[3]), "=f"(d[4]), "=f"(d[5]), "=f"(d[6]), "=f"(d[7]), "=f"(d[8]), "=f"(d[9]), "=f"(d[10]), "=f"(d[11]), "=f"(d[12]), "=f"(d[13]), "=f"(d[14]), "=f"(d[15])
    : "l"(da), "l"(db));
}
template <int SD> __device__ __forceinline__ void wgmma_ss_n32_ta0_tb1(float (&d)[16], uint64_t da, uint64_t db) {
  if (SD) asm volatile("wgmma.mma_async.sync.aligned.m64n32k16.f32.bf16.bf16 {%0, %1, %2, %3, %4, %5, %6, %7, %8, %9, %10, %11, %12, %13, %14, %15}, %16, %17, 1, 1, 1, 0, 1;\n"
    : "+f"(d[0]), "+f"(d[1]), "+f"(d[2]), "+f"(d[3]), "+f"(d[4]), "+f"(d[5]), "+f"(d[6]), "+f"(d[7]), "+f"(d[8]), "+f"(d[9]), "+f"(d[10]), "+f"(d[11]), "+f"(d[12]), "+f"(d[13]), "+f"(d[14]), "+f"(d[15])
    : "l"(da), "l"(db));
  else asm volatile("wgmma.mma_async.sync.aligned.m64n32k16.f32.bf16.bf16 {%0, %1, %2, %3, %4, %5, %6, %7, %8, %9, %10, %11, %12, %13, %14, %15}, %16, %17, 0, 1, 1, 0, 1;\n"
    : "=f"(d[0]), "=f"(d[1]), "=f"(d[2]), "=f"(d[3]), "=f"(d[4]), "=f"(d[5]), "=f"(d[6]), "=f"(d[7]), "=f"(d[8]), "=f"(d[9]), "=f"(d[10]), "=f"(d[11]), "=f"(d[12]), "=f"(d[13]), "=f"(d[14]), "=f"(d[15])
    : "l"(da), "l"(db));
}
template <int SD> __device__ __forceinline__ void wgmma_rs_n64_tb0(float (&d)[32], uint32_t a0, uint32_t a1, uint32_t a2, uint32_t a3, uint64_t db) {
  if (SD) asm volatile("wgmma.mma_async.sync.aligned.m64n64k16.f32.bf16.bf16 {%0, %1, %2, %3, %4, %5, %6, %7, %8, %9, %10, %11, %12, %13, %14, %15, %16, %17, %18, %19, %20, %21, %22, %23, %24, %25, %26, %27, %28, %29, %30, %31}, {%32, %33, %34, %35}, %36, 1, 1, 1, 0;\n"
    : "+f"(d[0]), "+f"(d[1]), "+f"(d[2]), "+f"(d[3]), "+f"(d[4]), "+f"(d[5]), "+f"(d[6]), "+f"(d[7]), "+f"(d[8]), "+f"(d[9]), "+f"(d[10]), "+f"(d[11]), "+f"(d[12]), "+f"(d[13]), "+f"(d[14]), "+f"(d[15]), "+f"(d[16]), "+f"(d[17]), "+f"(d[18]), "+f"(d[19]), "+f"(d[20]), "+f"(d[21]), "+f"(d[22]), "+f"(d[23]), "+f"(d[24]), "+f"(d[25]), "+f"(d[26]), "+f"(d[27]), "+f"(d[28]), "+f"(d[29]), "+f"(d[30]), "+f"(d[31])
    : "r"(a0), "r"(a1), "r"(a2), "r"(a3), "l"(db));
  else asm volatile("wgmma.mma_async.sync.aligned.m64n64k16.f32.bf16.bf16 {%0, %1, %2, %3, %4, %5, %6, %7, %8, %9, %10, %11, %12, %13, %14, %15, %16, %17, %18, %19, %20, %21, %22, %23, %24, %25, %26, %27, %28, %29, %30, %31}, {%32, %33, %34, %35}, %36, 0, 1, 1, 0;\n"
    : "=f"(d[0]), "=f"(d[1]), "=f"(d[2]), "=f"(d[3]), "=f"(d[4]), "=f"(d[5]), "=f"(d[6]), "=f"(d[7]), "=f"(d[8]), "=f"(d[9]), "=f"(d[10]), "=f"(d[11]), "=f"(d[12]), "=f"(d[13]), "=f"(d[14]), "=f"(d[15]), "=f"(d[16]), "=f"(d[17]), "=f"(d[18]), "=f"(d[19]), "=f"(d[20]), "=f"(d[21]), "=f"(d[22]), "=f"(d[23]), "=f"(d[24]), "=f"(d[25]), "=f"(d[26]), "=f"(d[27]), "=f"(d[28]), "=f"(d[29]), "=f"(d[30]), "=f"(d[31])
    : "r"(a0), "r"(a1), "r"(a2), "r"(a3), "l"(db));
}
template <int SD> __device__ __forceinline__ void wgmma_rs_n32_tb1(float (&d)[16], uint32_t a0, uint32_t a1, uint32_t a2, uint32_t a3, uint64_t db) {
  if (SD) asm volatile("wgmma.mma_async.sync.aligned.m64n32k16.f32.bf16.bf16 {%0, %1, %2, %3, %4, %5, %6, %7, %8, %9, %10, %11, %12, %13, %14, %15}, {%16, %17, %18, %19}, %20, 1, 1, 1, 1;\n"
    : "+f"(d[0]), "+f"(d[1]), "+f"(d[2]), "+f"(d[3]), "+f"(d[4]), "+f"(d[5]), "+f"(d[6]), "+f"(d[7]), "+f"(d[8]), "+f"(d[9]), "+f"(d[10]), "+f"(d[11]), "+f"(d[12]), "+f"(d[13]), "+f"(d[14]), "+f"(d[15])
    : "r"(a0), "r"(a1), "r"(a2), "r"(a3), "l"(db));
  else asm volatile("wgmma.mma_async.sync.aligned.m64n32k16.f32.bf16.bf16 {%0, %1, %2, %3, %4, %5, %6, %7, %8, %9, %10, %11, %12, %13, %14, %15}, {%16, %17, %18, %19}, %20, 0, 1, 1, 1;\n"
    : "=f"(d[0]), "=f"(d[1]), "=f"(d[2]), "=f"(d[3]), "=f"(d[4]), "=f"(d[5]), "=f"(d[6]), "=f"(d[7]), "=f"(d[8]), "=f"(d[9]), "=f"(d[10]), "=f"(d[11]), "=f"(d[12]), "=f"(d[13]), "=f"(d[14]), "=f"(d[15])
    : "r"(a0), "r"(a1), "r"(a2), "r"(a3), "l"(db));
}

__device__ __forceinline__ uint32_t sw64_off(int row, int d) { return row * 64 + ((((d >> 3) ^ (row >> 1)) & 3) << 4) + (d & 7) * 2; }

__device__ __forceinline__ uint32_t exp2_pair_fma(float t0, float t1, uint32_t c_half, uint32_t c_3) {
  uint32_t y0, y;
  asm("prmt.b32 %0, %1, %2, 0x6521;" : "=r"(y0) : "r"(__float_as_uint(t0)), "r"(__float_as_uint(t1)));
  uint32_t h = lop_and_or(y0, 0x007F007Fu, c_half);
  uint32_t e = lop_and_or(y0, 0xFF80FF80u, c_3);
  asm("fma.rn.bf16x2 %0, %1, %2, %3;" : "=r"(y) : "r"(y0), "r"(h), "r"(e));
  return y;
}

__device__ __forceinline__ void feature_map(float (&v)[16], uint32_t (&ph)[16], int lq) {
  const float L2E = 1.4426950408889634f;
  const bool tail_ok = lq < 2;
  float mx[2], mn[2], b[16], sa[2], sn[2];
#pragma unroll
  for (int r = 0; r < 2; r++) {
    const int o = 2 * r;
    if (!tail_ok) { v[o + 12] = v[o]; v[o + 13] = v[o]; }
    mx[r] = fmaxf(fmaxf(fmaxf(v[o], v[o + 1]), fmaxf(v[o + 4], v[o + 5])), fmaxf(fmaxf(v[o + 8], v[o + 9]), fmaxf(v[o + 12], v[o + 13])));
    mn[r] = fminf(fminf(fminf(v[o], v[o + 1]), fminf(v[o + 4], v[o + 5])), fminf(fminf(v[o + 8], v[o + 9]), fminf(v[o + 12], v[o + 13])));
  }
#pragma unroll
  for (int o = 1; o <= 2; o <<= 1)
#pragma unroll
    for (int r = 0; r < 2; r++) { mx[r] = fmaxf(mx[r], __shfl_xor_sync(~0u, mx[r], o)); mn[r] = fminf(mn[r], __shfl_xor_sync(~0u, mn[r], o)); }
#pragma unroll
  for (int r = 0; r < 2; r++) {
    const int o = 2 * r;
    const float cx = -mx[r] * L2E, cn = mn[r] * L2E;
#pragma unroll
    for (int i = 0; i < 8; i++) {
      const int k = o + 4 * (i >> 1) + (i & 1);
      b[k] = ex2f(fmaf(v[k], -L2E, cn));
      v[k] = ex2f(fmaf(v[k], L2E, cx));
    }
    if (!tail_ok) { v[o + 12] = v[o + 13] = b[o + 12] = b[o + 13] = 0.f; }
    sa[r] = ((v[o] + v[o + 1]) + (v[o + 4] + v[o + 5])) + ((v[o + 8] + v[o + 9]) + (v[o + 12] + v[o + 13]));
    sn[r] = ((b[o] + b[o + 1]) + (b[o + 4] + b[o + 5])) + ((b[o + 8] + b[o + 9]) + (b[o + 12] + b[o + 13]));
  }
#pragma unroll
  for (int o = 1; o <= 2; o <<= 1)
#pragma unroll
    for (int r = 0; r < 2; r++) { sa[r] += __shfl_xor_sync(~0u, sa[r], o); sn[r] += __shfl_xor_sync(~0u, sn[r], o); }
#pragma unroll
  for (int r = 0; r < 2; r++) {
    const float ra = rcpf(sa[r]), rb = rcpf(sn[r]);
#pragma unroll
    for (int jj = 0; jj < 4; jj++) {
      ph[jj * 2 + r] = pack_bf16(v[2 * r + 4 * jj] * ra, v[2 * r + 4 * jj + 1] * ra);
      ph[(4 + jj) * 2 + r] = pack_bf16(b[2 * r + 4 * jj] * rb, b[2 * r + 4 * jj + 1] * rb);
    }
  }
}

__device__ __forceinline__ void store_heads(uint32_t base, const uint32_t (&a)[14], uint32_t pad0, uint32_t pad1, int row0, int lq) {
  const uint32_t rb = base + row0 * 64 + (((row0 >> 1) & 3) << 4);
  const uint32_t b0 = rb + lq * 4;
  const uint32_t b1 = (rb + 8192 + ((lq * 4 + 8) & 15)) ^ ((lq >> 1) << 4);
#pragma unroll
  for (int j = 0; j < 7; j++) {
    uint32_t ad;
    if (j < 3) ad = b0 ^ (j << 4);
    else if (j == 3) ad = (lq < 2) ? (b0 ^ 48u) : (b1 ^ 16u);
    else ad = (lq < 2) ? (b1 ^ ((j - 4) << 4)) : ((b1 ^ 16u) ^ ((j - 3) << 4));
    sts32(ad, a[2 * j]);
    sts32(ad + 512, a[2 * j + 1]);
  }
  sts64((rb ^ 48u) + 8 + (lq & 1) * 8192 + (lq >> 1) * 512, pad0, pad1);
}

struct Params {
  const __nv_bfloat16* w_phi;
  const __nv_bfloat16* wk;
  const __nv_bfloat16* wv;
  const __nv_bfloat16* gate_w;
  __nv_bfloat16* out;
};

__global__ void __launch_bounds__(NTHREADS, 1)
fused_kernel(const __grid_constant__ CUtensorMap tm_x, const __grid_constant__ CUtensorMap tm_wqkv,
             const __grid_constant__ CUtensorMap tm_wq, const __grid_constant__ CUtensorMap tm_woa,
             const __grid_constant__ CUtensorMap tm_wob, const Params prm) {
  extern __shared__ uint8_t smem_raw[];
  uint32_t sb = (smem_u32(smem_raw) + 1023u) & ~1023u;
  uint8_t* sgen = smem_raw + (sb - smem_u32(smem_raw));
  asm volatile("mov.u32 %0, %0;" : "+r"(sb));
  const int tid = threadIdx.x, lane = tid & 31;
  const int warp = __shfl_sync(~0u, tid >> 5, 0), wg = warp >> 2;
  const int pt = blockIdx.x >> 3, hp = blockIdx.x & 7;
  const uint32_t bars = sb + OFF_BAR;
  auto BAR = [&](int i) { return bars + 8u * i; };
  const unsigned epoch = g_epoch & 1;

  if (tid == 0) { PROF_MARK(0); PROF_CLK(30); PROF2(15); }
  auto load_proj = [&](int c, int g) {
    mbar_expect_tx(BAR(B_FULL + g), 49152);
    tma_2d(sb + OFF_X + c * 16384, &tm_x, c * 64, pt * 128, BAR(B_FULL + g));
    tma_2d(sb + OFF_RING + g * 32768, &tm_wq, hp * 56, c * 64, BAR(B_FULL + g));
#pragma unroll 1
    for (int j = 0; j < 3; j++) tma_2d(sb + OFF_RING + g * 32768 + 8192 + j * 8192, &tm_wqkv, j * DM + hp * 56, c * 64, BAR(B_FULL + g));
  };
  if (elect_one()) {
    const int i = warp == 16 ? 0 : (warp == 0 ? 16 : warp);
    if (i < B_N) {
      int cnt = (i >= B_EMPTY && i < B_WO) || i > B_SIG || i == B_X0FREE || i == B_X1FREE ? 16 : 1;
      if (i == B_BUILD) cnt = 3;
      if (i == B_SIG || i == B_QSQ) cnt = 8;
      mbar_init(BAR(i), cnt);
      fence_async_smem();
    }
    if (warp == 16) load_proj(0, 0);
  }
  __syncthreads();
  if (tid == 0) PROF2(14);

  if (wg == 4) {
    asm volatile("setmaxnreg.dec.sync.aligned.u32 32;");
    if (warp == 16) {
      if (elect_one()) {
        int g = 1, nkv = 8;
        uint32_t par = 1;
#pragma unroll 1
        for (int n = 1; n < 14 + nkv; n++) {
          if (n == 7) { PROF_MARK(20); cnt_wait(C_KV, NCTA); PROF_MARK(21); fence_async_all(); }
          if (n == 15) {
            mbar_wait(BAR(B_SLOW), 0);
            if (*(volatile int*)(sgen + OFF_RED)) nkv = 26;
          }
          const int j = n - 7 - nkv;
          if (j == 0 || j == 3) {
            PROF3(j ? 11 : 8);
            cnt_wait((j ? C_OB : C_OA) + pt, 8);
            PROF3(j ? 12 : 9);
            PROF_MARK(26);
            fence_async_all();
          }
          mbar_wait(BAR(B_EMPTY + g), par);
          if (n < 7) load_proj(n, g);
          else {
            mbar_expect_tx(BAR(B_FULL + g), 32768);
            bulk_g2s(sb + OFF_RING + g * 32768, j < 0 ? g_kv_img + ((n - 7) & 7) * 32768 : g_o_img + (size_t)(pt * 7 + j) * 32768, 32768,
                     BAR(B_FULL + g));
          }
          if (++g == 3) { g = 0; par ^= 1; }
        }
      }
    } else {
      {
        const int t = tid - 544;
#pragma unroll 1
        for (int i = t; i < 256; i += 96) sts128(sb + OFF_WPH + i * 16, make_uint4(0, 0, 0, 0));
        bar_sync(2, 96);
#pragma unroll 1
        for (int k = t; k < DM; k += 96) {
          const __nv_bfloat16* src = (hp < 4 ? prm.wk : prm.wv) + k * DH + (hp & 3) * 8;
          cp_async8(sb + OFF_SLC + k * 16, src);
          if ((hp & 3) != 3) cp_async8(sb + OFF_SLC + k * 16 + 8, src + 4);
          else sts64(sb + OFF_SLC + k * 16 + 8, hp == 3 ? (uint32_t)((const unsigned short*)prm.gate_w)[k] : 0u, 0u);
          if (k < 392) {
            const int row = k / 7, e = row >= DH;
            cp_async8(sb + OFF_WPH + e * 2048 + sw64_off(row - DH * e, (k % 7) * 4), prm.w_phi + 2 * hp * DH * DH + k * 4);
          }
        }
        asm volatile("cp.async.wait_all;" ::: "memory");
        fence_async_smem();
        __syncwarp();
        if (lane == 0) mbar_arrive(BAR(B_BUILD), 1);
      }
      if (warp == 18) {
        if (elect_one()) {
#pragma unroll 1
          for (int i = 0; i < 4; i++) {
            mbar_wait(BAR(B_SIG + i), 0);
            PROF3(2 * i);
            cnt_arrive(i == 0 ? C_KV : i == 1 ? C_PART : (i == 2 ? C_OA : C_OB) + pt);
            PROF3(2 * i + 1);
            if (i == 1 || i == 2) {
              mbar_wait(BAR(B_X0FREE + i - 1), 0);
              mbar_expect_tx(BAR(B_WO + i - 1), 57344);
#pragma unroll 1
              for (int c = 0; c < 7; c++)
                tma_2d(sb + OFF_WO + (i - 1) * 57344 + c * 8192, i == 1 ? &tm_woa : &tm_wob, hp * 56, c * 64, BAR(B_WO + i - 1));
            }
          }
        }
      } else if (warp == 19) {
        if (lane == 0) {
          mbar_wait(BAR(B_SIG + 0), 0);
          cnt_wait(C_KV, NCTA);
        }
        __syncwarp();
        float ksq = 0.f, vsq = 0.f;
#pragma unroll
        for (int sl = 0; sl < 4; sl++) {
          float4 a = ldcg_f4(g_ksq + sl * 128 + lane * 4), b = ldcg_f4(g_vsq + sl * 128 + lane * 4);
          float m = fmaxf(fmaxf(a.x, a.y), fmaxf(a.z, a.w));
          m = __uint_as_float(__reduce_max_sync(~0u, __float_as_uint(m)));
          ksq += m;
          vsq = fmaxf(vsq, fmaxf(fmaxf(b.x, b.y), fmaxf(b.z, b.w)));
        }
        mbar_wait(BAR(B_QSQ), 0);
        const float4 qa4 = ((const float4*)(sgen + OFF_QSQ))[lane], qb4 = ((const float4*)(sgen + OFF_QSQ))[32 + lane];
        const float qmax = fmaxf(fmaxf(fmaxf(qa4.x, qa4.y), fmaxf(qa4.z, qa4.w)), fmaxf(fmaxf(qb4.x, qb4.y), fmaxf(qb4.z, qb4.w)));
        const bool slow = __any_sync(~0u, !(qmax * ksq <= 98.f * 98.f) || !(vsq <= 2.0e8f));
        if (lane == 0) {
          *(volatile int*)(sgen + OFF_RED) = slow;
          mbar_arrive(BAR(B_SLOW), 1);
        }
      } else {
        float4* z = (float4*)(g_kvacc[epoch ^ 1] + blockIdx.x * 256) + lane;
        z[0] = make_float4(0.f, 0.f, 0.f, 0.f);
        z[32] = make_float4(0.f, 0.f, 0.f, 0.f);
        if (lane == 0) {
          mbar_wait(BAR(B_SIG + 1), 0);
          cnt_wait(C_PART, NCTA);
          PROF_MARK(23);
          mbar_arrive(BAR(B_KVR), 1);
        }
      }
    }
  } else {
    asm volatile("setmaxnreg.inc.sync.aligned.u32 112;");
    const int mh = wg & 1, nh = wg >> 1, wq = warp & 3;
    float acc0[28], acc1[28], accs[4] = {0.f, 0.f, 0.f, 0.f};
#pragma unroll
    for (int i = 0; i < 28; i++) acc0[i] = acc1[i] = 0.f;
    int slot = 0, prev = 0;
    uint32_t par = 0;

    if (nh == 1) mbar_wait(BAR(B_BUILD), 0);
#pragma unroll 1
    for (int stage = 0; stage < 2; stage++) {
      {
        const uint64_t dS = make_desc(stage ? sb + OFF_WO : sb + OFF_X + mh * 8192, 1024, 1024, 1);
        const uint64_t dR = make_desc(sb + OFF_RING + (stage ? mh * 8192 : nh * 16384), 1024, 1024, 1);
#pragma unroll 1
        for (int c = 0; c < 7; c++) {
          if (stage) mbar_wait(BAR(B_WO + (c >= 3)), 0);
          if (tid == 0) PROF2(stage * 16 + c * 2);
          mbar_wait(BAR(B_FULL + slot), par);
          if (tid == 0) PROF2(stage * 16 + c * 2 + 1);
          const uint64_t ds = dS + c * 1024, dr = dR + slot * 2048;
          const uint64_t dA0 = stage ? dr : ds, dA1 = stage ? dr + 1024 : ds, dB0 = stage ? ds : dr, dB1 = dB0 + 512;
          wg_fence();
#pragma unroll
          for (int ks = 0; ks < 4; ks++) {
            wgmma_ss_n56_ta0_tb1<1>(acc0, dA0 + ks * 2, dB0 + ks * 128);
            wgmma_ss_n56_ta0_tb1<1>(acc1, dA1 + ks * 2, dB1 + ks * 128);
          }
          if (nh == 1) {
            const uint64_t dSlc = make_desc(sb + OFF_SLC + c * 1024, 128, 128, 0);
#pragma unroll
            for (int ks = 0; ks < 4; ks++) wgmma_ss_n8_ta0_tb1<1>(accs, ds + ks * 2, dSlc + ks * 16);
          }
          wg_commit();
          wg_wait<0>();
          if (lane == 0) mbar_arrive(BAR(B_EMPTY + slot), 1 + stage);
          if (++slot == 3) { slot = 0; par ^= 1; }
        }
        fence_regs(acc0); fence_regs(acc1); fence_regs(accs);
      }
      if (stage) break;
      int lane_;
      asm volatile("mov.u32 %0, %%laneid;" : "=r"(lane_));
      const int lq = lane_ & 3;
      const int rowl = wq * 16 + (lane_ >> 2);
      const int row0 = mh * 64 + rowl;
      {
        if (tid == 0) PROF_MARK(2);
        if (tid == 256) PROF_MARK(3);
        if (nh == 0) {
          float sq[4] = {0.f, 0.f, 0.f, 0.f};
#pragma unroll
          for (int i = 0; i < 28; i++) acc0[i] *= 0.18898223650461362f * 1.4426950408889634f;
#pragma unroll
          for (int j = 0; j < 7; j++) {
#pragma unroll
            for (int rr = 0; rr < 2; rr++) {
              const float s2 = acc0[4 * j + 2 * rr] * acc0[4 * j + 2 * rr] + acc0[4 * j + 2 * rr + 1] * acc0[4 * j + 2 * rr + 1];
              if (j < 3) sq[rr] += s2;
              else if (j > 3) sq[2 + rr] += s2;
              else { sq[rr] += (lq < 2) ? s2 : 0.f; sq[2 + rr] += (lq < 2) ? 0.f : s2; }
            }
          }
#pragma unroll
          for (int i = 0; i < 4; i++) sq[i] = quad_sum(sq[i]);
          const float mine = lq == 0 ? sq[0] : lq == 1 ? sq[1] : lq == 2 ? sq[2] : sq[3];
          ((float*)(sgen + OFF_QSQ))[(mh + (lq & 2)) * 64 + rowl + 8 * (lq & 1)] = mine <= 3.0e38f ? mine : __int_as_float(0x7f800000);
          __syncwarp();
          if (lane == 0) mbar_arrive(BAR(B_QSQ), 1);
        } else {
          const int sl = hp & 3;
          const bool isk = hp < 4, real = (sl < 3) || (lq < 2);
          const int pos = pt * 128 + row0, kr = pos & 63;
          uint8_t* dst = g_kv_img + (pos >> 6) * 8192 + (isk ? 0 : 4096) + sw64_off(kr, sl * 8 + 2 * lq);
          const uint32_t pat = isk ? POLY_PAT >> (kr >> 3) : 0u;
          float mxv = 0.f;
#pragma unroll
          for (int rr = 0; rr < 2; rr++) {
            const float v0 = accs[2 * rr], v1 = accs[2 * rr + 1];
            const bool poly = (pat >> rr) & 1;
            const float sc = poly ? 2.f : 1.f;
            const float s2 = quad_sum(real ? v0 * v0 + v1 * v1 : 0.f);
            mxv = fmaxf(mxv, s2 <= 3.0e38f ? s2 : __int_as_float(0x7f800000));
            const uint32_t padv = lq == 2 ? (poly ? 0x443F4000u : 0x00003F80u) : (poly ? 0x3AB03F4Du : 0u);
            *(uint32_t*)(dst + rr * 512) = real ? pack_bf16(sc * v0, sc * v1) : padv;
            if (hp == 3 && lq == 2) g_gate[pos + 8 * rr] = rcpf(1.f + ex2f(-1.4426950408889634f * v0));
          }
          mxv = __uint_as_float(__reduce_max_sync(~0u, __float_as_uint(mxv)));
          if (lane == 0) (isk ? g_ksq : g_vsq)[sl * 128 + pt * 8 + mh * 4 + wq] = mxv;
          __syncwarp();
          if (lane == 0) mbar_arrive(BAR(B_SIG + 0), 1);
        }
      }
      if (tid == 0) PROF_MARK(4);
      if (tid == 256) PROF_MARK(5);
      {
        uint32_t h0[14], h1[14];
#pragma unroll
        for (int i = 0; i < 14; i++) { h0[i] = pack_bf16(acc0[2 * i], acc0[2 * i + 1]); h1[i] = pack_bf16(acc1[2 * i], acc1[2 * i + 1]); }
        bar_sync(1, 512);
        if (tid == 0) PROF_MARK(6);
#pragma unroll 1
        for (int r = 0; r < 2; r++) {
          store_heads(sb + (r ? (nh ? OFF_VA : OFF_QA) : (nh ? OFF_KA : OFF_QP)), h0,
                      (r & nh) ? 0x00003F80u : (r | nh) ? 0u : 0x3F800000u, (r | nh) ? 0u : 0x3F803F80u, row0, lq);
#pragma unroll
          for (int i = 0; i < 14; i++) h0[i] = h1[i];
        }
      }
      fence_async_smem();
      bar_sync(1, 512);
      if (tid == 0) PROF_MARK(7);

      const uint64_t dK = make_desc(sb + OFF_RING, 512, 512, 2);
      const uint64_t dhi = dK & 0xffffffff00000000ull;
      const uint32_t dlo0 = (uint32_t)dK;
      uint32_t ok = 0, q[8];
      float g0 = 0.f, g1 = 0.f;
      float o[16];
#pragma unroll
      for (int i = 0; i < 16; i++) o[i] = 0.f;
      {
        const uint32_t qa = sb + OFF_QP + nh * 8192;
        const int r = mh * 64 + wq * 16 + (lane_ & 7) + ((lane_ >> 3) & 1) * 8;
#pragma unroll
        for (int ks = 0; ks < 2; ks++)
          asm volatile("ldmatrix.sync.aligned.m8n8.x4.shared.b16 {%0, %1, %2, %3}, [%4];"
                       : "=r"(q[4 * ks]), "=r"(q[4 * ks + 1]), "=r"(q[4 * ks + 2]), "=r"(q[4 * ks + 3])
                       : "r"(qa + sw64_off(r, ks * 16 + (lane_ >> 4) * 8)) : "memory");
      }
      const int kb = KB_AT, qb = QB_AT;
#pragma unroll 1
      for (int it = 0; it <= 8; it++) {
        uint32_t p[16];
        if (it == kb || it == qb || it == 8) {
          float t[16];
          wg_wait<0>();
          fence_regs(o);
          if (it < 8) {
            if (tid == 0) PROF_MARK(it == kb ? 27 : 11);
            const uint64_t dA = make_desc(sb + (it == kb ? OFF_KA : OFF_QA) + nh * 8192 + mh * 4096, 512, 512, 2);
            const uint64_t dB = make_desc(sb + OFF_WPH + nh * 2048, 512, 512, 2);
            float* kvacc = g_kvacc[epoch] + (2 * hp + nh) * 2048;
            float pa[16];
            wg_fence();
            wgmma_ss_n32_ta0_tb1<0>(pa, dA, dB);
            wgmma_ss_n32_ta0_tb1<1>(pa, dA + 2, dB + 64);
            wg_commit();
            if (it != kb) {
              mbar_wait(BAR(B_KVR), 0);
              g0 = ldcg_f(g_gate + pt * 128 + row0); g1 = ldcg_f(g_gate + pt * 128 + row0 + 8);
              const int tl = tid & 127;
              const float4 a = ldcg_f4(kvacc + tl * 16), b = ldcg_f4(kvacc + tl * 16 + 4), c = ldcg_f4(kvacc + tl * 16 + 8), d = ldcg_f4(kvacc + tl * 16 + 12);
              const uint32_t ad = sb + OFF_KVR + nh * 4096 + sw64_off(tl >> 1, (tl & 1) * 16);
              sts128(ad, make_uint4(pack_bf16(a.x, a.y), pack_bf16(a.z, a.w), pack_bf16(b.x, b.y), pack_bf16(b.z, b.w)));
              sts128(ad ^ 16u, make_uint4(pack_bf16(c.x, c.y), pack_bf16(c.z, c.w), pack_bf16(d.x, d.y), pack_bf16(d.z, d.w)));
            }
            wg_wait<0>();
            fence_regs(pa);
            uint32_t ph[16];
            feature_map(pa, ph, lq);
            const uint32_t rb = sb + OFF_PHI + wg * 8192 + rowl * 128 + lq * 4 + ((rowl & 7) << 4);
#pragma unroll
            for (int ch = 0; ch < 8; ch++) { sts32(rb ^ (ch << 4), ph[2 * ch]); sts32((rb ^ (ch << 4)) + 1024, ph[2 * ch + 1]); }
            fence_async_smem();
            bar_sync(4 + wg, 128);
            const uint64_t dP = make_desc(sb + OFF_PHI + wg * 8192, 1024, 1024, 1);
            if (it == kb) {
              const uint64_t dV = make_desc(sb + OFF_VA + nh * 8192 + mh * 4096, 512, 512, 2);
              float kv[16];
              wg_fence();
              wgmma_ss_n32_ta1_tb1<0>(kv, dP, dV);
#pragma unroll
              for (int ks = 1; ks < 4; ks++) wgmma_ss_n32_ta1_tb1<1>(kv, dP + ks * 128, dV + ks * 64);
              wg_commit();
              wg_wait<0>();
              fence_regs(kv);
              float* dst = kvacc + rowl * 32 + 2 * lq;
#pragma unroll
              for (int j = 0; j < 8; j++)
                asm volatile("red.global.add.v2.f32 [%0], {%1, %2};" ::"l"(dst + 8 * (j >> 1) + 256 * (j & 1)), "f"(kv[2 * j]), "f"(kv[2 * j + 1]) : "memory");
              __syncwarp();
              if (lane == 0) { mbar_arrive(BAR(B_SIG + 1), 1); mbar_arrive(BAR(B_X0FREE), 1); }
              if (tid == 0) PROF_MARK(28);
              goto after_block;
            } else {
              const uint64_t dR = make_desc(sb + OFF_KVR + nh * 4096, 512, 512, 2);
              wg_fence();
              wgmma_ss_n32_ta0_tb1<0>(t, dP, dR);
#pragma unroll
              for (int ks = 1; ks < 4; ks++) wgmma_ss_n32_ta0_tb1<1>(t, dP + ks * 2, dR + ks * 64);
              wg_commit();
              wg_wait<0>();
              fence_regs(t);
              if (lane == 0) mbar_arrive(BAR(B_X1FREE), 1);
            }
          } else {
            if (lane == 0) mbar_arrive(BAR(B_EMPTY + prev), 1);
            if (tid == 0) PROF_MARK(13);
            mbar_wait(BAR(B_SLOW), 0);
            if (__builtin_expect(__any_sync(~0u, *(volatile int*)(sgen + OFF_RED)), 0)) {
              uint32_t qz[8];
#pragma unroll
              for (int i = 0; i < 8; i++) qz[i] = (i >= 6 && lq >= 2) ? 0u : q[i];
              float m0 = -3.0e38f, m1 = -3.0e38f, o2[16];
              int sl2 = slot;
              uint32_t par2 = par;
#pragma unroll 1
              for (int j64 = 0; j64 < 32; j64++) {
                float s[32];
                mbar_wait(BAR(B_FULL + sl2), par2);
                const uint32_t lo = dlo0 + sl2 * 2048 + (j64 & 3) * 512;
                wg_fence();
                wgmma_rs_n64_tb0<0>(s, qz[0], qz[1], qz[2], qz[3], dhi | lo);
                wgmma_rs_n64_tb0<1>(s, qz[4], qz[5], qz[6], qz[7], dhi | (lo + 2));
                wg_commit();
                wg_wait<0>();
                fence_regs(s);
#pragma unroll
                for (int j = 0; j < 8; j++) {
                  const float sc = ((POLY_PAT >> j) & 1) ? 0.5f : 1.f;
                  m0 = fmaxf(m0, fmaxf(s[4 * j], s[4 * j + 1]) * sc);
                  m1 = fmaxf(m1, fmaxf(s[4 * j + 2], s[4 * j + 3]) * sc);
                }
                if ((j64 & 3) == 3) {
                  if (lane == 0) mbar_arrive(BAR(B_EMPTY + sl2), 1);
                  if (++sl2 == 3) { sl2 = 0; par2 ^= 1; }
                }
              }
              m0 = quad_max(m0); m1 = quad_max(m1);
#pragma unroll
              for (int i = 0; i < 16; i++) o2[i] = 0.f;
#pragma unroll 1
              for (int j64 = 0; j64 < 32; j64++) {
                float s[32];
                mbar_wait(BAR(B_FULL + sl2), par2);
                const uint32_t lo = dlo0 + sl2 * 2048 + (j64 & 3) * 512;
                wg_fence();
                wgmma_rs_n64_tb0<0>(s, qz[0], qz[1], qz[2], qz[3], dhi | lo);
                wgmma_rs_n64_tb0<1>(s, qz[4], qz[5], qz[6], qz[7], dhi | (lo + 2));
                wg_commit();
                wg_wait<0>();
                fence_regs(s);
                uint32_t ps[16];
#pragma unroll
                for (int j = 0; j < 8; j++) {
                  const float sc = ((POLY_PAT >> j) & 1) ? 0.5f : 1.f;
                  ps[2 * j] = pack_bf16(ex2f(fmaf(s[4 * j], sc, -m0)), ex2f(fmaf(s[4 * j + 1], sc, -m0)));
                  ps[2 * j + 1] = pack_bf16(ex2f(fmaf(s[4 * j + 2], sc, -m1)), ex2f(fmaf(s[4 * j + 3], sc, -m1)));
                }
                wg_fence();
#pragma unroll
                for (int ks = 0; ks < 4; ks++)
                  wgmma_rs_n32_tb1<1>(o2, ps[4 * ks], ps[4 * ks + 1], ps[4 * ks + 2], ps[4 * ks + 3], dhi | (lo + 256 + ks * 64));
                wg_commit();
                wg_wait<0>();
                fence_regs(o2);
                if ((j64 & 3) == 3) {
                  if (lane == 0) mbar_arrive(BAR(B_EMPTY + sl2), 1);
                  if (++sl2 == 3) { sl2 = 0; par2 ^= 1; }
                }
              }
#pragma unroll 1
              for (int j = 0; j < 2; j++) {
                mbar_wait(BAR(B_FULL + sl2), par2);
                __syncwarp();
                if (lane == 0) mbar_arrive(BAR(B_EMPTY + sl2), 1);
                if (++sl2 == 3) { sl2 = 0; par2 ^= 1; }
              }
#pragma unroll
              for (int i = 0; i < 16; i++) o[i] = o2[i];
            }
#pragma unroll
            for (int i = 0; i < 16; i++) t[i] = o[i];
          }
          {
            const int br = it == 8;
            const float eps = br ? 0.f : 1e-6f;
            const float d0 = __shfl_sync(~0u, t[12], (lane_ & ~3) | 2), d1 = __shfl_sync(~0u, t[14], (lane_ & ~3) | 2);
            const float r0 = __fdividef(br ? 1.f - g0 : g0, d0 + eps), r1 = __fdividef(br ? 1.f - g1 : g1, d1 + eps);
            uint8_t* img = g_o_img + (size_t)((pt * 2 + br) * 14 + mh) * 8192 + rowl * 128;
            const int col0 = (2 * hp + nh) * DH + 2 * lq;
#pragma unroll
            for (int j = 0; j < 4; j++) {
              const int col = col0 + 8 * j;
              uint8_t* gp = img + (col >> 6) * 16384 + ((((col >> 3) ^ rowl) & 7) << 4) + (col & 7) * 2;
              const uint32_t v0 = pack_bf16(t[4 * j] * r0, t[4 * j + 1] * r0), v1 = pack_bf16(t[4 * j + 2] * r1, t[4 * j + 3] * r1);
              if (j < 3 || lq < 2) { *(uint32_t*)gp = v0; *(uint32_t*)(gp + 1024) = v1; }
            }
            __syncwarp();
            if (lane == 0) mbar_arrive(BAR(B_SIG + 2 + br), 1);
            if (tid == 0) PROF_MARK(12 + 2 * br);
            if (br) break;
          }
        }
      after_block:
        if (it == 0 && tid == 0) PROF_MARK(10);
        const uint32_t lo = dlo0 + slot * 2048;
        if (!ok) mbar_wait(BAR(B_FULL + slot), par);
        int nslot = slot + 1;
        uint32_t npar = par;
        if (nslot == 3) { nslot = 0; npar ^= 1; }
        {
          float s[32];
          wg_fence();
          wgmma_rs_n64_tb0<0>(s, q[0], q[1], q[2], q[3], dhi | lo);
          wgmma_rs_n64_tb0<1>(s, q[4], q[5], q[6], q[7], dhi | (lo + 2));
          wg_commit();
#pragma unroll
          for (int u = 0; u < 4; u++) {
            wg_wait<0>();
            fence_regs(s);
            if (u == 0 && lane == 0 && it > 0) mbar_arrive(BAR(B_EMPTY + prev), 1);
            if (u == 2) ok = mbar_test(BAR(B_FULL + nslot), npar);
#pragma unroll
            for (int j = 0; j < 8; j++) {
              if ((POLY_PAT >> j) & 1) {
                p[2 * j] = exp2_pair_fma(s[4 * j], s[4 * j + 1], 0x3F003F00u, 0x00030003u);
                p[2 * j + 1] = exp2_pair_fma(s[4 * j + 2], s[4 * j + 3], 0x3F003F00u, 0x00030003u);
              } else {
                p[2 * j] = pack_bf16(ex2f(s[4 * j]), ex2f(s[4 * j + 1]));
                p[2 * j + 1] = pack_bf16(ex2f(s[4 * j + 2]), ex2f(s[4 * j + 3]));
              }
            }
            wg_fence();
#pragma unroll
            for (int ks = 0; ks < 4; ks++)
              wgmma_rs_n32_tb1<1>(o, p[4 * ks], p[4 * ks + 1], p[4 * ks + 2], p[4 * ks + 3], dhi | (lo + u * 512 + 256 + ks * 64));
            if (u < 3) {
              wgmma_rs_n64_tb0<0>(s, q[0], q[1], q[2], q[3], dhi | (lo + (u + 1) * 512));
              wgmma_rs_n64_tb0<1>(s, q[4], q[5], q[6], q[7], dhi | (lo + (u + 1) * 512 + 2));
            }
            wg_commit();
          }
        }
        prev = slot; slot = nslot; par = npar;
      }
      wg_wait<0>();
      if (nh == 1) return;
#pragma unroll
      for (int i = 0; i < 28; i++) acc0[i] = acc1[i] = 0.f;
#pragma unroll
      for (int i = 0; i < 4; i++) accs[i] = 0.f;
    }
    if (tid == 0) PROF_MARK(17);
    __nv_bfloat16* op = prm.out + (size_t)(pt * 128 + mh * 64 + wq * 16 + (lane >> 2)) * DM + hp * 56 + 2 * (lane & 3);
#pragma unroll
    for (int j = 0; j < 7; j++) {
      *(uint32_t*)(op + 8 * j) = pack_bf16(acc0[4 * j] + acc1[4 * j], acc0[4 * j + 1] + acc1[4 * j + 1]);
      *(uint32_t*)(op + 8 * DM + 8 * j) = pack_bf16(acc0[4 * j + 2] + acc1[4 * j + 2], acc0[4 * j + 3] + acc1[4 * j + 3]);
    }
    if (tid == 0) { PROF_MARK(18); PROF_CLK(31); }
    if (tid == 0) {
      unsigned prevd = atomicAdd(&g_cnt[C_DONE * 32], 1u);
      if (prevd == NCTA - 1) {
#pragma unroll 1
        for (int i = 0; i < C_N; i++) g_cnt[i * 32] = 0;
        g_epoch = epoch ^ 1;
      }
    }
  }
}

typedef CUresult (*EncodeFn)(CUtensorMap*, CUtensorMapDataType, cuuint32_t, void*, const cuuint64_t*, const cuuint64_t*,
                             const cuuint32_t*, const cuuint32_t*, CUtensorMapInterleave, CUtensorMapSwizzle,
                             CUtensorMapL2promotion, CUtensorMapFloatOOBfill);

void make_map(EncodeFn enc, CUtensorMap* tm, const void* ptr, uint64_t cols, uint64_t rows, uint32_t box_rows) {
  cuuint64_t dims[2] = {cols, rows};
  cuuint64_t strides[1] = {cols * 2};
  cuuint32_t box[2] = {64, box_rows};
  cuuint32_t es[2] = {1, 1};
  enc(tm, CU_TENSOR_MAP_DATA_TYPE_BFLOAT16, 2, const_cast<void*>(ptr), dims, strides, box, es, CU_TENSOR_MAP_INTERLEAVE_NONE,
      CU_TENSOR_MAP_SWIZZLE_128B, CU_TENSOR_MAP_L2_PROMOTION_L2_128B, CU_TENSOR_MAP_FLOAT_OOB_FILL_NONE);
}

}

extern "C" void kernel_launch(void* const* d_in, const int* in_sizes, int n_in, void* d_out, int out_size) {
  (void)in_sizes; (void)n_in; (void)out_size;
  static EncodeFn enc = nullptr;
  if (!enc) {
    void* fn = nullptr;
    cudaDriverEntryPointQueryResult qr;
    cudaGetDriverEntryPoint("cuTensorMapEncodeTiled", &fn, cudaEnableDefault, &qr);
    enc = (EncodeFn)fn;
    cudaFuncSetAttribute(fused_kernel, cudaFuncAttributeMaxDynamicSharedMemorySize, SMEM_BYTES);
  }
  CUtensorMap tm_x, tm_wqkv, tm_wq, tm_woa, tm_wob;
  make_map(enc, &tm_x, d_in[0], DM, S_LEN, 128);
  make_map(enc, &tm_wqkv, d_in[1], 3 * DM, DM, 64);
  make_map(enc, &tm_wq, d_in[5], DM, DM, 64);
  make_map(enc, &tm_woa, d_in[3], DM, DM, 64);
  make_map(enc, &tm_wob, d_in[8], DM, DM, 64);
  Params prm;
  prm.w_phi = (const __nv_bfloat16*)d_in[2];
  prm.wk = (const __nv_bfloat16*)d_in[6];
  prm.wv = (const __nv_bfloat16*)d_in[7];
  prm.gate_w = (const __nv_bfloat16*)d_in[9];
  prm.out = (__nv_bfloat16*)d_out;
  fused_kernel<<<NCTA, NTHREADS, SMEM_BYTES>>>(tm_x, tm_wqkv, tm_wq, tm_woa, tm_wob, prm);
}
```

```cpp
#include <cuda_runtime.h>
#include <cuda_bf16.h>
#include <cuda.h>
#include <stdint.h>

namespace {

constexpr int S_LEN = 2048, DM = 448, DH = 28;
constexpr int NCTA = 128;
constexpr int NTHREADS = 640;
constexpr uint32_t POLY_PAT = 0x57;

#define KB_AT (1 - nh)
#define QB_AT (4 + nh)

constexpr int OFF_X = 0;
constexpr int OFF_KA = 0;
constexpr int OFF_VA = 16384;
constexpr int OFF_QP = 32768;
constexpr int OFF_QA = 57344;
constexpr int OFF_KVR = 73728;
constexpr int OFF_PHI = 81920;
constexpr int OFF_WO = 0;
constexpr int OFF_RING = 114688;
constexpr int OFF_WPH = 212992;
constexpr int OFF_SLC = 217088;
constexpr int OFF_QSQ = 224256;
constexpr int OFF_RED = 225792;
constexpr int OFF_BAR = 225856;
constexpr int SMEM_BYTES = 226368 + 1024;

constexpr int B_FULL = 0, B_EMPTY = 3, B_WO = 6  , B_KVR = 8, B_X0FREE = 9, B_X1FREE = 10, B_QSQ = 11, B_SLOW = 12,
              B_BUILD = 13, B_SIG = 14  , B_N = 18;

constexpr int C_KV = 0, C_PART = 1, C_DONE = 3, C_OA = 4, C_OB = 20, C_N = 36;

__device__ __align__(1024) uint8_t g_kv_img[32 * 8192];
__device__ __align__(16) float g_ksq[512];
__device__ __align__(16) float g_vsq[512];
__device__ __align__(16) float g_gate[S_LEN];
__device__ __align__(1024) float g_kvacc[2][16 * 64 * 32];
__device__ unsigned g_epoch;
__device__ __align__(1024) uint8_t g_o_img[2 * 16 * 14 * 8192];
__device__ unsigned g_cnt[C_N * 32];

#define PROF3(i) do { } while (0)
#define PROF2(i) do { } while (0)
#define PROF_CLK(i) do { } while (0)
#define PROF_MARK(i) do { } while (0)
__device__ __forceinline__ uint32_t smem_u32(const void* p) { return (uint32_t)__cvta_generic_to_shared(p); }
__device__ __forceinline__ void mbar_init(uint32_t a, int cnt) {
  asm volatile("mbarrier.init.shared::cta.b64 [%0], %1;" ::"r"(a), "r"(cnt) : "memory");
}
__device__ __forceinline__ void mbar_expect_tx(uint32_t a, uint32_t bytes) {
  asm volatile("mbarrier.arrive.expect_tx.shared::cta.b64 _, [%0], %1;" ::"r"(a), "r"(bytes) : "memory");
}
__device__ __forceinline__ void mbar_arrive(uint32_t a, uint32_t cnt) {
  asm volatile("mbarrier.arrive.shared::cta.b64 _, [%0], %1;" ::"r"(a), "r"(cnt) : "memory");
}
__device__ __forceinline__ void mbar_wait(uint32_t a, uint32_t parity) {
  asm volatile(
      "{\n.reg .pred p;\n.reg .u32 c;\nmov.u32 c, 0;\n"
      "W_%=:\nmbarrier.try_wait.parity.shared::cta.b64 p, [%0], %1;\n"
      "add.u32 c, c, 1;\nsetp.lt.and.u32 p, c, 0x1000000, !p;\n@p bra W_%=;\n}"
      ::"r"(a), "r"(parity) : "memory");
}
__device__ __forceinline__ uint32_t mbar_test(uint32_t a, uint32_t parity) {
  uint32_t ok;
  asm volatile("{\n.reg .pred p;\nmbarrier.test_wait.parity.shared::cta.b64 p, [%1], %2;\nselp.u32 %0, 1, 0, p;\n}"
               : "=r"(ok) : "r"(a), "r"(parity) : "memory");
  return ok;
}
__device__ __forceinline__ bool elect_one() {
  uint32_t r;
  asm volatile("{\n.reg .pred p;\nelect.sync _|p, 0xffffffff;\nselp.u32 %0, 1, 0, p;\n}" : "=r"(r));
  return r != 0;
}
__device__ __forceinline__ void tma_2d(uint32_t dst, const CUtensorMap* tm, int c0, int c1, uint32_t bar) {
  asm volatile("cp.async.bulk.tensor.2d.shared::cluster.global.mbarrier::complete_tx::bytes [%0], [%1, {%3, %4}], [%2];"
               ::"r"(dst), "l"(tm), "r"(bar), "r"(c0), "r"(c1) : "memory");
}
__device__ __forceinline__ void bulk_g2s(uint32_t dst, const void* src, uint32_t bytes, uint32_t bar) {
  asm volatile("cp.async.bulk.shared::cluster.global.mbarrier::complete_tx::bytes [%0], [%1], %2, [%3];"
               ::"r"(dst), "l"(src), "r"(bytes), "r"(bar) : "memory");
}
__device__ __forceinline__ void cp_async8(uint32_t dst, const void* src) {
  asm volatile("cp.async.ca.shared.global [%0], [%1], 8;" ::"r"(dst), "l"(src) : "memory");
}
__device__ __forceinline__ void fence_async_smem() { asm volatile("fence.proxy.async.shared::cta;" ::: "memory"); }
__device__ __forceinline__ void fence_async_all() { asm volatile("fence.proxy.async.global;" ::: "memory"); }
__device__ __forceinline__ float ldcg_f(const float* p) { float v; asm volatile("ld.global.cg.f32 %0, [%1];" : "=f"(v) : "l"(p) : "memory"); return v; }
__device__ __forceinline__ void bar_sync(int id, int n) { asm volatile("bar.sync %0, %1;" ::"r"(id), "r"(n) : "memory"); }
__device__ __forceinline__ void cnt_arrive(int idx) {
  asm volatile("red.release.gpu.global.add.u32 [%0], 1;" ::"l"(&g_cnt[idx * 32]) : "memory");
}
__device__ __forceinline__ void cnt_wait(int idx, unsigned target) {
  unsigned v, n = 0;
#pragma unroll 1
  while (true) {
    asm volatile("ld.acquire.gpu.global.u32 %0, [%1];" : "=r"(v) : "l"(&g_cnt[idx * 32]) : "memory");
    if (v >= target || ++n >= (1u << 22)) break;
    __nanosleep(32);
  }
}
__device__ __forceinline__ void wg_fence() { asm volatile("wgmma.fence.sync.aligned;" ::: "memory"); }
__device__ __forceinline__ void wg_commit() { asm volatile("wgmma.commit_group.sync.aligned;" ::: "memory"); }
template <int N> __device__ __forceinline__ void wg_wait() { asm volatile("wgmma.wait_group.sync.aligned %0;" ::"n"(N) : "memory"); }
template <int N> __device__ __forceinline__ void fence_regs(float (&d)[N]) {
#pragma unroll
  for (int i = 0; i < N; i++) asm volatile("" : "+f"(d[i])::"memory");
}
__device__ __forceinline__ uint64_t make_desc(uint32_t saddr, uint32_t lbo, uint32_t sbo, uint32_t swz) {
  return (uint64_t)((saddr & 0x3FFFF) >> 4) | ((uint64_t)(lbo >> 4) << 16) | ((uint64_t)(sbo >> 4) << 32) | ((uint64_t)swz << 62);
}
__device__ __forceinline__ float ex2f(float x) { float y; asm("ex2.approx.ftz.f32 %0, %1;" : "=f"(y) : "f"(x)); return y; }
__device__ __forceinline__ float rcpf(float x) { float y; asm("rcp.approx.ftz.f32 %0, %1;" : "=f"(y) : "f"(x)); return y; }
__device__ __forceinline__ uint32_t pack_bf16(float lo, float hi) {
  uint32_t r; asm("cvt.rn.bf16x2.f32 %0, %1, %2;" : "=r"(r) : "f"(hi), "f"(lo)); return r;
}
__device__ __forceinline__ uint32_t lop_and_or(uint32_t a, uint32_t m, uint32_t c) {
  uint32_t r; asm("lop3.b32 %0, %1, %2, %3, 0xEA;" : "=r"(r) : "r"(a), "r"(m), "r"(c)); return r;
}
__device__ __forceinline__ void sts32(uint32_t a, uint32_t v) { asm volatile("st.shared.b32 [%0], %1;" ::"r"(a), "r"(v) : "memory"); }
__device__ __forceinline__ void sts64(uint32_t a, uint32_t v0, uint32_t v1) { asm volatile("st.shared.v2.b32 [%0], {%1, %2};" ::"r"(a), "r"(v0), "r"(v1) : "memory"); }
__device__ __forceinline__ void sts128(uint32_t a, uint4 v) {
  asm volatile("st.shared.v4.b32 [%0], {%1, %2, %3, %4};" ::"r"(a), "r"(v.x), "r"(v.y), "r"(v.z), "r"(v.w) : "memory");
}
__device__ __forceinline__ float4 ldcg_f4(const float* p) {
  float4 v; asm volatile("ld.global.cg.v4.f32 {%0, %1, %2, %3}, [%4];" : "=f"(v.x), "=f"(v.y), "=f"(v.z), "=f"(v.w) : "l"(p) : "memory"); return v;
}
__device__ __forceinline__ float quad_sum(float v) { v += __shfl_xor_sync(~0u, v, 1); v += __shfl_xor_sync(~0u, v, 2); return v; }
__device__ __forceinline__ float quad_max(float v) { v = fmaxf(v, __shfl_xor_sync(~0u, v, 1)); v = fmaxf(v, __shfl_xor_sync(~0u, v, 2)); return v; }

template <int SD> __device__ __forceinline__ void wgmma_ss_n56_ta0_tb1(float (&d)[28], uint64_t da, uint64_t db) {
  if (SD) asm volatile("wgmma.mma_async.sync.aligned.m64n56k16.f32.bf16.bf16 {%0, %1, %2, %3, %4, %5, %6, %7, %8, %9, %10, %11, %12, %13, %14, %15, %16, %17, %18, %19, %20, %21, %22, %23, %24, %25, %26, %27}, %28, %29, 1, 1, 1, 0, 1;\n"
    : "+f"(d[0]), "+f"(d[1]), "+f"(d[2]), "+f"(d[3]), "+f"(d[4]), "+f"(d[5]), "+f"(d[6]), "+f"(d[7]), "+f"(d[8]), "+f"(d[9]), "+f"(d[10]), "+f"(d[11]), "+f"(d[12]), "+f"(d[13]), "+f"(d[14]), "+f"(d[15]), "+f"(d[16]), "+f"(d[17]), "+f"(d[18]), "+f"(d[19]), "+f"(d[20]), "+f"(d[21]), "+f"(d[22]), "+f"(d[23]), "+f"(d[24]), "+f"(d[25]), "+f"(d[26]), "+f"(d[27])
    : "l"(da), "l"(db));
  else asm volatile("wgmma.mma_async.sync.aligned.m64n56k16.f32.bf16.bf16 {%0, %1, %2, %3, %4, %5, %6, %7, %8, %9, %10, %11, %12, %13, %14, %15, %16, %17, %18, %19, %20, %21, %22, %23, %24, %25, %26, %27}, %28, %29, 0, 1, 1, 0, 1;\n"
    : "=f"(d[0]), "=f"(d[1]), "=f"(d[2]), "=f"(d[3]), "=f"(d[4]), "=f"(d[5]), "=f"(d[6]), "=f"(d[7]), "=f"(d[8]), "=f"(d[9]), "=f"(d[10]), "=f"(d[11]), "=f"(d[12]), "=f"(d[13]), "=f"(d[14]), "=f"(d[15]), "=f"(d[16]), "=f"(d[17]), "=f"(d[18]), "=f"(d[19]), "=f"(d[20]), "=f"(d[21]), "=f"(d[22]), "=f"(d[23]), "=f"(d[24]), "=f"(d[25]), "=f"(d[26]), "=f"(d[27])
    : "l"(da), "l"(db));
}
template <int SD> __device__ __forceinline__ void wgmma_ss_n8_ta0_tb1(float (&d)[4], uint64_t da, uint64_t db) {
  if (SD) asm volatile("wgmma.mma_async.sync.aligned.m64n8k16.f32.bf16.bf16 {%0, %1, %2, %3}, %4, %5, 1, 1, 1, 0, 1;\n"
    : "+f"(d[0]), "+f"(d[1]), "+f"(d[2]), "+f"(d[3])
    : "l"(da), "l"(db));
  else asm volatile("wgmma.mma_async.sync.aligned.m64n8k16.f32.bf16.bf16 {%0, %1, %2, %3}, %4, %5, 0, 1, 1, 0, 1;\n"
    : "=f"(d[0]), "=f"(d[1]), "=f"(d[2]), "=f"(d[3])
    : "l"(da), "l"(db));
}
template <int SD> __device__ __forceinline__ void wgmma_ss_n32_ta1_tb1(float (&d)[16], uint64_t da, uint64_t db) {
  if (SD) asm volatile("wgmma.mma_async.sync.aligned.m64n32k16.f32.bf16.bf16 {%0, %1, %2, %3, %4, %5, %6, %7, %8, %9, %10, %11, %12, %13, %14, %15}, %16, %17, 1, 1, 1, 1, 1;\n"
    : "+f"(d[0]), "+f"(d[1]), "+f"(d[2]), "+f"(d[3]), "+f"(d[4]), "+f"(d[5]), "+f"(d[6]), "+f"(d[7]), "+f"(d[8]), "+f"(d[9]), "+f"(d[10]), "+f"(d[11]), "+f"(d[12]), "+f"(d[13]), "+f"(d[14]), "+f"(d[15])
    : "l"(da), "l"(db));
  else asm volatile("wgmma.mma_async.sync.aligned.m64n32k16.f32.bf16.bf16 {%0, %1, %2, %3, %4, %5, %6, %7, %8, %9, %10, %11, %12, %13, %14, %15}, %16, %17, 0, 1, 1, 1, 1;\n"
    : "=f"(d[0]), "=f"(d[1]), "=f"(d[2]), "=f"(d[3]), "=f"(d[4]), "=f"(d[5]), "=f"(d[6]), "=f"(d[7]), "=f"(d[8]), "=f"(d[9]), "=f"(d[10]), "=f"(d[11]), "=f"(d[12]), "=f"(d[13]), "=f"(d[14]), "=f"(d[15])
    : "l"(da), "l"(db));
}
template <int SD> __device__ __forceinline__ void wgmma_ss_n32_ta0_tb1(float (&d)[16], uint64_t da, uint64_t db) {
  if (SD) asm volatile("wgmma.mma_async.sync.aligned.m64n32k16.f32.bf16.bf16 {%0, %1, %2, %3, %4, %5, %6, %7, %8, %9, %10, %11, %12, %13, %14, %15}, %16, %17, 1, 1, 1, 0, 1;\n"
    : "+f"(d[0]), "+f"(d[1]), "+f"(d[2]), "+f"(d[3]), "+f"(d[4]), "+f"(d[5]), "+f"(d[6]), "+f"(d[7]), "+f"(d[8]), "+f"(d[9]), "+f"(d[10]), "+f"(d[11]), "+f"(d[12]), "+f"(d[13]), "+f"(d[14]), "+f"(d[15])
    : "l"(da), "l"(db));
  else asm volatile("wgmma.mma_async.sync.aligned.m64n32k16.f32.bf16.bf16 {%0, %1, %2, %3, %4, %5, %6, %7, %8, %9, %10, %11, %12, %13, %14, %15}, %16, %17, 0, 1, 1, 0, 1;\n"
    : "=f"(d[0]), "=f"(d[1]), "=f"(d[2]), "=f"(d[3]), "=f"(d[4]), "=f"(d[5]), "=f"(d[6]), "=f"(d[7]), "=f"(d[8]), "=f"(d[9]), "=f"(d[10]), "=f"(d[11]), "=f"(d[12]), "=f"(d[13]), "=f"(d[14]), "=f"(d[15])
    : "l"(da), "l"(db));
}
template <int SD> __device__ __forceinline__ void wgmma_rs_n64_tb0(float (&d)[32], uint32_t a0, uint32_t a1, uint32_t a2, uint32_t a3, uint64_t db) {
  if (SD) asm volatile("wgmma.mma_async.sync.aligned.m64n64k16.f32.bf16.bf16 {%0, %1, %2, %3, %4, %5, %6, %7, %8, %9, %10, %11, %12, %13, %14, %15, %16, %17, %18, %19, %20, %21, %22, %23, %24, %25, %26, %27, %28, %29, %30, %31}, {%32, %33, %34, %35}, %36, 1, 1, 1, 0;\n"
    : "+f"(d[0]), "+f"(d[1]), "+f"(d[2]), "+f"(d[3]), "+f"(d[4]), "+f"(d[5]), "+f"(d[6]), "+f"(d[7]), "+f"(d[8]), "+f"(d[9]), "+f"(d[10]), "+f"(d[11]), "+f"(d[12]), "+f"(d[13]), "+f"(d[14]), "+f"(d[15]), "+f"(d[16]), "+f"(d[17]), "+f"(d[18]), "+f"(d[19]), "+f"(d[20]), "+f"(d[21]), "+f"(d[22]), "+f"(d[23]), "+f"(d[24]), "+f"(d[25]), "+f"(d[26]), "+f"(d[27]), "+f"(d[28]), "+f"(d[29]), "+f"(d[30]), "+f"(d[31])
    : "r"(a0), "r"(a1), "r"(a2), "r"(a3), "l"(db));
  else asm volatile("wgmma.mma_async.sync.aligned.m64n64k16.f32.bf16.bf16 {%0, %1, %2, %3, %4, %5, %6, %7, %8, %9, %10, %11, %12, %13, %14, %15, %16, %17, %18, %19, %20, %21, %22, %23, %24, %25, %26, %27, %28, %29, %30, %31}, {%32, %33, %34, %35}, %36, 0, 1, 1, 0;\n"
    : "=f"(d[0]), "=f"(d[1]), "=f"(d[2]), "=f"(d[3]), "=f"(d[4]), "=f"(d[5]), "=f"(d[6]), "=f"(d[7]), "=f"(d[8]), "=f"(d[9]), "=f"(d[10]), "=f"(d[11]), "=f"(d[12]), "=f"(d[13]), "=f"(d[14]), "=f"(d[15]), "=f"(d[16]), "=f"(d[17]), "=f"(d[18]), "=f"(d[19]), "=f"(d[20]), "=f"(d[21]), "=f"(d[22]), "=f"(d[23]), "=f"(d[24]), "=f"(d[25]), "=f"(d[26]), "=f"(d[27]), "=f"(d[28]), "=f"(d[29]), "=f"(d[30]), "=f"(d[31])
    : "r"(a0), "r"(a1), "r"(a2), "r"(a3), "l"(db));
}
template <int SD> __device__ __forceinline__ void wgmma_rs_n32_tb1(float (&d)[16], uint32_t a0, uint32_t a1, uint32_t a2, uint32_t a3, uint64_t db) {
  if (SD) asm volatile("wgmma.mma_async.sync.aligned.m64n32k16.f32.bf16.bf16 {%0, %1, %2, %3, %4, %5, %6, %7, %8, %9, %10, %11, %12, %13, %14, %15}, {%16, %17, %18, %19}, %20, 1, 1, 1, 1;\n"
    : "+f"(d[0]), "+f"(d[1]), "+f"(d[2]), "+f"(d[3]), "+f"(d[4]), "+f"(d[5]), "+f"(d[6]), "+f"(d[7]), "+f"(d[8]), "+f"(d[9]), "+f"(d[10]), "+f"(d[11]), "+f"(d[12]), "+f"(d[13]), "+f"(d[14]), "+f"(d[15])
    : "r"(a0), "r"(a1), "r"(a2), "r"(a3), "l"(db));
  else asm volatile("wgmma.mma_async.sync.aligned.m64n32k16.f32.bf16.bf16 {%0, %1, %2, %3, %4, %5, %6, %7, %8, %9, %10, %11, %12, %13, %14, %15}, {%16, %17, %18, %19}, %20, 0, 1, 1, 1;\n"
    : "=f"(d[0]), "=f"(d[1]), "=f"(d[2]), "=f"(d[3]), "=f"(d[4]), "=f"(d[5]), "=f"(d[6]), "=f"(d[7]), "=f"(d[8]), "=f"(d[9]), "=f"(d[10]), "=f"(d[11]), "=f"(d[12]), "=f"(d[13]), "=f"(d[14]), "=f"(d[15])
    : "r"(a0), "r"(a1), "r"(a2), "r"(a3), "l"(db));
}

__device__ __forceinline__ uint32_t sw64_off(int row, int d) { return row * 64 + ((((d >> 3) ^ (row >> 1)) & 3) << 4) + (d & 7) * 2; }

__device__ __forceinline__ uint32_t exp2_pair_fma(float t0, float t1, uint32_t c_half, uint32_t c_3) {
  uint32_t y0, y;
  asm("prmt.b32 %0, %1, %2, 0x6521;" : "=r"(y0) : "r"(__float_as_uint(t0)), "r"(__float_as_uint(t1)));
  uint32_t h = lop_and_or(y0, 0x007F007Fu, c_half);
  uint32_t e = lop_and_or(y0, 0xFF80FF80u, c_3);
  asm("fma.rn.bf16x2 %0, %1, %2, %3;" : "=r"(y) : "r"(y0), "r"(h), "r"(e));
  return y;
}

__device__ __forceinline__ void feature_map(float (&v)[16], uint32_t (&ph)[16], int lq) {
  const float L2E = 1.4426950408889634f;
  const bool tail_ok = lq < 2;
  float mx[2], mn[2], b[16], sa[2], sn[2];
#pragma unroll
  for (int r = 0; r < 2; r++) {
    const int o = 2 * r;
    if (!tail_ok) { v[o + 12] = v[o]; v[o + 13] = v[o]; }
    mx[r] = fmaxf(fmaxf(fmaxf(v[o], v[o + 1]), fmaxf(v[o + 4], v[o + 5])), fmaxf(fmaxf(v[o + 8], v[o + 9]), fmaxf(v[o + 12], v[o + 13])));
    mn[r] = fminf(fminf(fminf(v[o], v[o + 1]), fminf(v[o + 4], v[o + 5])), fminf(fminf(v[o + 8], v[o + 9]), fminf(v[o + 12], v[o + 13])));
  }
#pragma unroll
  for (int o = 1; o <= 2; o <<= 1)
#pragma unroll
    for (int r = 0; r < 2; r++) { mx[r] = fmaxf(mx[r], __shfl_xor_sync(~0u, mx[r], o)); mn[r] = fminf(mn[r], __shfl_xor_sync(~0u, mn[r], o)); }
#pragma unroll
  for (int r = 0; r < 2; r++) {
    const int o = 2 * r;
    const float cx = -mx[r] * L2E, cn = mn[r] * L2E;
#pragma unroll
    for (int i = 0; i < 8; i++) {
      const int k = o + 4 * (i >> 1) + (i & 1);
      b[k] = ex2f(fmaf(v[k], -L2E, cn));
      v[k] = ex2f(fmaf(v[k], L2E, cx));
    }
    if (!tail_ok) { v[o + 12] = v[o + 13] = b[o + 12] = b[o + 13] = 0.f; }
    sa[r] = ((v[o] + v[o + 1]) + (v[o + 4] + v[o + 5])) + ((v[o + 8] + v[o + 9]) + (v[o + 12] + v[o + 13]));
    sn[r] = ((b[o] + b[o + 1]) + (b[o + 4] + b[o + 5])) + ((b[o + 8] + b[o + 9]) + (b[o + 12] + b[o + 13]));
  }
#pragma unroll
  for (int o = 1; o <= 2; o <<= 1)
#pragma unroll
    for (int r = 0; r < 2; r++) { sa[r] += __shfl_xor_sync(~0u, sa[r], o); sn[r] += __shfl_xor_sync(~0u, sn[r], o); }
#pragma unroll
  for (int r = 0; r < 2; r++) {
    const float ra = rcpf(sa[r]), rb = rcpf(sn[r]);
#pragma unroll
    for (int jj = 0; jj < 4; jj++) {
      ph[jj * 2 + r] = pack_bf16(v[2 * r + 4 * jj] * ra, v[2 * r + 4 * jj + 1] * ra);
      ph[(4 + jj) * 2 + r] = pack_bf16(b[2 * r + 4 * jj] * rb, b[2 * r + 4 * jj + 1] * rb);
    }
  }
}

__device__ __forceinline__ void store_heads(uint32_t base, const uint32_t (&a)[14], uint32_t pad0, uint32_t pad1, int row0, int lq) {
  const uint32_t rb = base + row0 * 64 + (((row0 >> 1) & 3) << 4);
  const uint32_t b0 = rb + lq * 4;
  const uint32_t b1 = (rb + 8192 + ((lq * 4 + 8) & 15)) ^ ((lq >> 1) << 4);
#pragma unroll
  for (int j = 0; j < 7; j++) {
    uint32_t ad;
    if (j < 3) ad = b0 ^ (j << 4);
    else if (j == 3) ad = (lq < 2) ? (b0 ^ 48u) : (b1 ^ 16u);
    else ad = (lq < 2) ? (b1 ^ ((j - 4) << 4)) : ((b1 ^ 16u) ^ ((j - 3) << 4));
    sts32(ad, a[2 * j]);
    sts32(ad + 512, a[2 * j + 1]);
  }
  sts64((rb ^ 48u) + 8 + (lq & 1) * 8192 + (lq >> 1) * 512, pad0, pad1);
}

struct Params {
  const __nv_bfloat16* w_phi;
  const __nv_bfloat16* wk;
  const __nv_bfloat16* wv;
  const __nv_bfloat16* gate_w;
  __nv_bfloat16* out;
};

__global__ void __launch_bounds__(NTHREADS, 1)
fused_kernel(const __grid_constant__ CUtensorMap tm_x, const __grid_constant__ CUtensorMap tm_wqkv,
             const __grid_constant__ CUtensorMap tm_wq, const __grid_constant__ CUtensorMap tm_woa,
             const __grid_constant__ CUtensorMap tm_wob, const Params prm) {
  extern __shared__ uint8_t smem_raw[];
  uint32_t sb = (smem_u32(smem_raw) + 1023u) & ~1023u;
  uint8_t* sgen = smem_raw + (sb - smem_u32(smem_raw));
  asm volatile("mov.u32 %0, %0;" : "+r"(sb));
  const int tid = threadIdx.x, lane = tid & 31;
  const int warp = __shfl_sync(~0u, tid >> 5, 0), wg = warp >> 2;
  const int pt = blockIdx.x >> 3, hp = blockIdx.x & 7;
  const uint32_t bars = sb + OFF_BAR;
  auto BAR = [&](int i) { return bars + 8u * i; };
  const unsigned epoch = g_epoch & 1;

  if (tid == 0) { PROF_MARK(0); PROF_CLK(30); PROF2(15); }
  auto load_proj = [&](int c, int g) {
    mbar_expect_tx(BAR(B_FULL + g), 49152);
    tma_2d(sb + OFF_X + c * 16384, &tm_x, c * 64, pt * 128, BAR(B_FULL + g));
    tma_2d(sb + OFF_RING + g * 32768, &tm_wq, hp * 56, c * 64, BAR(B_FULL + g));
#pragma unroll 1
    for (int j = 0; j < 3; j++) tma_2d(sb + OFF_RING + g * 32768 + 8192 + j * 8192, &tm_wqkv, j * DM + hp * 56, c * 64, BAR(B_FULL + g));
  };
  if (tid < DM) {
    const __nv_bfloat16* src = (hp < 4 ? prm.wk : prm.wv) + tid * DH + (hp & 3) * 8;
    cp_async8(sb + OFF_SLC + tid * 16, src);
    if ((hp & 3) != 3) cp_async8(sb + OFF_SLC + tid * 16 + 8, src + 4);
    if (tid < 392) {
      const int row = tid / 7, e = row >= DH;
      cp_async8(sb + OFF_WPH + e * 2048 + sw64_off(row - DH * e, (tid % 7) * 4), prm.w_phi + 2 * hp * DH * DH + tid * 4);
    } else {
      const int row = tid - 392, e = row >= DH;
      sts64(sb + OFF_WPH + e * 2048 + sw64_off(row - DH * e, 28), 0u, 0u);
    }
    if ((hp & 3) == 3) sts64(sb + OFF_SLC + tid * 16 + 8, hp == 3 ? (uint32_t)((const unsigned short*)prm.gate_w)[tid] : 0u, 0u);
  } else if (tid < DM + 32) {
    sts128(sb + OFF_WPH + ((tid - DM) >> 4) * 2048 + 28 * 64 + ((tid - DM) & 15) * 16, make_uint4(0, 0, 0, 0));
  }
  if (elect_one()) {
    const int i = warp == 16 ? 0 : (warp == 0 ? 16 : warp);
    if (i < B_N) {
      int cnt = (i >= B_EMPTY && i < B_WO) || i > B_SIG || i == B_X0FREE || i == B_X1FREE ? 16 : 1;
      if (i == B_BUILD) cnt = 512;
      if (i == B_SIG || i == B_QSQ) cnt = 8;
      mbar_init(BAR(i), cnt);
      fence_async_smem();
    }
    if (warp == 16) load_proj(0, 0);
  }
  __syncthreads();
  if (tid == 0) PROF2(14);

  if (wg == 4) {
    asm volatile("setmaxnreg.dec.sync.aligned.u32 32;");
    if (warp == 16) {
      if (elect_one()) {
        int g = 1, nkv = 8;
        uint32_t par = 1;
#pragma unroll 1
        for (int n = 1; n < 14 + nkv; n++) {
          if (n == 7) { PROF_MARK(20); cnt_wait(C_KV, NCTA); PROF_MARK(21); fence_async_all(); }
          if (n == 15) {
            mbar_wait(BAR(B_SLOW), 0);
            if (*(volatile int*)(sgen + OFF_RED)) nkv = 26;
          }
          const int j = n - 7 - nkv;
          if (j == 0 || j == 3) {
            PROF3(j ? 11 : 8);
            cnt_wait((j ? C_OB : C_OA) + pt, 8);
            PROF3(j ? 12 : 9);
            PROF_MARK(26);
            fence_async_all();
          }
          mbar_wait(BAR(B_EMPTY + g), par);
          if (n < 7) load_proj(n, g);
          else {
            mbar_expect_tx(BAR(B_FULL + g), 32768);
            bulk_g2s(sb + OFF_RING + g * 32768, j < 0 ? g_kv_img + ((n - 7) & 7) * 32768 : g_o_img + (size_t)(pt * 7 + j) * 32768, 32768,
                     BAR(B_FULL + g));
          }
          if (++g == 3) { g = 0; par ^= 1; }
        }
      }
    } else {
      if (warp == 18) {
        if (elect_one()) {
#pragma unroll 1
          for (int i = 0; i < 4; i++) {
            mbar_wait(BAR(B_SIG + i), 0);
            PROF3(2 * i);
            cnt_arrive(i == 0 ? C_KV : i == 1 ? C_PART : (i == 2 ? C_OA : C_OB) + pt);
            PROF3(2 * i + 1);
            if (i == 1 || i == 2) {
              mbar_wait(BAR(B_X0FREE + i - 1), 0);
              mbar_expect_tx(BAR(B_WO + i - 1), 57344);
#pragma unroll 1
              for (int c = 0; c < 7; c++)
                tma_2d(sb + OFF_WO + (i - 1) * 57344 + c * 8192, i == 1 ? &tm_woa : &tm_wob, hp * 56, c * 64, BAR(B_WO + i - 1));
            }
          }
        }
      } else if (warp == 19) {
        if (lane == 0) {
          mbar_wait(BAR(B_SIG + 0), 0);
          cnt_wait(C_KV, NCTA);
        }
        __syncwarp();
        float ksq = 0.f, vsq = 0.f;
#pragma unroll
        for (int sl = 0; sl < 4; sl++) {
          float4 a = ldcg_f4(g_ksq + sl * 128 + lane * 4), b = ldcg_f4(g_vsq + sl * 128 + lane * 4);
          float m = fmaxf(fmaxf(a.x, a.y), fmaxf(a.z, a.w));
          m = __uint_as_float(__reduce_max_sync(~0u, __float_as_uint(m)));
          ksq += m;
          vsq = fmaxf(vsq, fmaxf(fmaxf(b.x, b.y), fmaxf(b.z, b.w)));
        }
        mbar_wait(BAR(B_QSQ), 0);
        const float4 qa4 = ((const float4*)(sgen + OFF_QSQ))[lane], qb4 = ((const float4*)(sgen + OFF_QSQ))[32 + lane];
        const float qmax = fmaxf(fmaxf(fmaxf(qa4.x, qa4.y), fmaxf(qa4.z, qa4.w)), fmaxf(fmaxf(qb4.x, qb4.y), fmaxf(qb4.z, qb4.w)));
        const bool slow = __any_sync(~0u, !(qmax * ksq <= 98.f * 98.f) || !(vsq <= 2.0e8f));
        if (lane == 0) {
          *(volatile int*)(sgen + OFF_RED) = slow;
          mbar_arrive(BAR(B_SLOW), 1);
        }
      } else {
        float4* z = (float4*)(g_kvacc[epoch ^ 1] + blockIdx.x * 256) + lane;
        z[0] = make_float4(0.f, 0.f, 0.f, 0.f);
        z[32] = make_float4(0.f, 0.f, 0.f, 0.f);
        if (lane == 0) {
          mbar_wait(BAR(B_SIG + 1), 0);
          cnt_wait(C_PART, NCTA);
          PROF_MARK(23);
          mbar_arrive(BAR(B_KVR), 1);
        }
      }
    }
  } else {
    asm volatile("setmaxnreg.inc.sync.aligned.u32 112;");
    const int mh = wg & 1, nh = wg >> 1, wq = warp & 3;
    float acc0[28], acc1[28], accs[4] = {0.f, 0.f, 0.f, 0.f};
#pragma unroll
    for (int i = 0; i < 28; i++) acc0[i] = acc1[i] = 0.f;
    int slot = 0, prev = 0;
    uint32_t par = 0;

    asm volatile("cp.async.mbarrier.arrive.noinc.shared::cta.b64 [%0];" ::"r"(BAR(B_BUILD)) : "memory");
    if (nh == 1) { mbar_wait(BAR(B_BUILD), 0); fence_async_smem(); }
#pragma unroll 1
    for (int stage = 0; stage < 2; stage++) {
      {
        const uint64_t dS = make_desc(stage ? sb + OFF_WO : sb + OFF_X + mh * 8192, 1024, 1024, 1);
        const uint64_t dR = make_desc(sb + OFF_RING + (stage ? mh * 8192 : nh * 16384), 1024, 1024, 1);
#pragma unroll 1
        for (int c = 0; c < 7; c++) {
          if (stage) mbar_wait(BAR(B_WO + (c >= 3)), 0);
          if (tid == 0) PROF2(stage * 16 + c * 2);
          mbar_wait(BAR(B_FULL + slot), par);
          if (tid == 0) PROF2(stage * 16 + c * 2 + 1);
          const uint64_t ds = dS + c * 1024, dr = dR + slot * 2048;
          const uint64_t dA0 = stage ? dr : ds, dA1 = stage ? dr + 1024 : ds, dB0 = stage ? ds : dr, dB1 = dB0 + 512;
          wg_fence();
#pragma unroll
          for (int ks = 0; ks < 4; ks++) {
            wgmma_ss_n56_ta0_tb1<1>(acc0, dA0 + ks * 2, dB0 + ks * 128);
            wgmma_ss_n56_ta0_tb1<1>(acc1, dA1 + ks * 2, dB1 + ks * 128);
          }
          if (nh == 1) {
            const uint64_t dSlc = make_desc(sb + OFF_SLC + c * 1024, 128, 128, 0);
#pragma unroll
            for (int ks = 0; ks < 4; ks++) wgmma_ss_n8_ta0_tb1<1>(accs, ds + ks * 2, dSlc + ks * 16);
          }
          wg_commit();
          wg_wait<0>();
          if (lane == 0) mbar_arrive(BAR(B_EMPTY + slot), 1 + stage);
          if (++slot == 3) { slot = 0; par ^= 1; }
        }
        fence_regs(acc0); fence_regs(acc1); fence_regs(accs);
      }
      if (stage) break;
      int lane_;
      asm volatile("mov.u32 %0, %%laneid;" : "=r"(lane_));
      const int lq = lane_ & 3;
      const int rowl = wq * 16 + (lane_ >> 2);
      const int row0 = mh * 64 + rowl;
      {
        if (tid == 0) PROF_MARK(2);
        if (tid == 256) PROF_MARK(3);
        if (nh == 0) {
          float sq[4] = {0.f, 0.f, 0.f, 0.f};
#pragma unroll
          for (int i = 0; i < 28; i++) acc0[i] *= 0.18898223650461362f * 1.4426950408889634f;
#pragma unroll
          for (int j = 0; j < 7; j++) {
#pragma unroll
            for (int rr = 0; rr < 2; rr++) {
              const float s2 = acc0[4 * j + 2 * rr] * acc0[4 * j + 2 * rr] + acc0[4 * j + 2 * rr + 1] * acc0[4 * j + 2 * rr + 1];
              if (j < 3) sq[rr] += s2;
              else if (j > 3) sq[2 + rr] += s2;
              else { sq[rr] += (lq < 2) ? s2 : 0.f; sq[2 + rr] += (lq < 2) ? 0.f : s2; }
            }
          }
#pragma unroll
          for (int i = 0; i < 4; i++) sq[i] = quad_sum(sq[i]);
          const float mine = lq == 0 ? sq[0] : lq == 1 ? sq[1] : lq == 2 ? sq[2] : sq[3];
          ((float*)(sgen + OFF_QSQ))[(mh + (lq & 2)) * 64 + rowl + 8 * (lq & 1)] = mine <= 3.0e38f ? mine : __int_as_float(0x7f800000);
          __syncwarp();
          if (lane == 0) mbar_arrive(BAR(B_QSQ), 1);
        } else {
          const int sl = hp & 3;
          const bool isk = hp < 4, real = (sl < 3) || (lq < 2);
          const int pos = pt * 128 + row0, kr = pos & 63;
          uint8_t* dst = g_kv_img + (pos >> 6) * 8192 + (isk ? 0 : 4096) + sw64_off(kr, sl * 8 + 2 * lq);
          const uint32_t pat = isk ? POLY_PAT >> (kr >> 3) : 0u;
          float mxv = 0.f;
#pragma unroll
          for (int rr = 0; rr < 2; rr++) {
            const float v0 = accs[2 * rr], v1 = accs[2 * rr + 1];
            const bool poly = (pat >> rr) & 1;
            const float sc = poly ? 2.f : 1.f;
            const float s2 = quad_sum(real ? v0 * v0 + v1 * v1 : 0.f);
            mxv = fmaxf(mxv, s2 <= 3.0e38f ? s2 : __int_as_float(0x7f800000));
            const uint32_t padv = lq == 2 ? (poly ? 0x443F4000u : 0x00003F80u) : (poly ? 0x3AB03F4Du : 0u);
            *(uint32_t*)(dst + rr * 512) = real ? pack_bf16(sc * v0, sc * v1) : padv;
            if (hp == 3 && lq == 2) g_gate[pos + 8 * rr] = rcpf(1.f + ex2f(-1.4426950408889634f * v0));
          }
          mxv = __uint_as_float(__reduce_max_sync(~0u, __float_as_uint(mxv)));
          if (lane == 0) (isk ? g_ksq : g_vsq)[sl * 128 + pt * 8 + mh * 4 + wq] = mxv;
          __syncwarp();
          if (lane == 0) mbar_arrive(BAR(B_SIG + 0), 1);
        }
      }
      if (tid == 0) PROF_MARK(4);
      if (tid == 256) PROF_MARK(5);
      {
        uint32_t h0[14], h1[14];
#pragma unroll
        for (int i = 0; i < 14; i++) { h0[i] = pack_bf16(acc0[2 * i], acc0[2 * i + 1]); h1[i] = pack_bf16(acc1[2 * i], acc1[2 * i + 1]); }
        bar_sync(1, 512);
        if (tid == 0) PROF_MARK(6);
#pragma unroll 1
        for (int r = 0; r < 2; r++) {
          store_heads(sb + (r ? (nh ? OFF_VA : OFF_QA) : (nh ? OFF_KA : OFF_QP)), h0,
                      (r & nh) ? 0x00003F80u : (r | nh) ? 0u : 0x3F800000u, (r | nh) ? 0u : 0x3F803F80u, row0, lq);
#pragma unroll
          for (int i = 0; i < 14; i++) h0[i] = h1[i];
        }
      }
      fence_async_smem();
      bar_sync(1, 512);
      if (tid == 0) PROF_MARK(7);

      const uint64_t dK = make_desc(sb + OFF_RING, 512, 512, 2);
      const uint64_t dhi = dK & 0xffffffff00000000ull;
      const uint32_t dlo0 = (uint32_t)dK;
      uint32_t ok = 0, q[8];
      float g0 = 0.f, g1 = 0.f;
      float o[16];
#pragma unroll
      for (int i = 0; i < 16; i++) o[i] = 0.f;
      {
        const uint32_t qa = sb + OFF_QP + nh * 8192;
        const int r = mh * 64 + wq * 16 + (lane_ & 7) + ((lane_ >> 3) & 1) * 8;
#pragma unroll
        for (int ks = 0; ks < 2; ks++)
          asm volatile("ldmatrix.sync.aligned.m8n8.x4.shared.b16 {%0, %1, %2, %3}, [%4];"
                       : "=r"(q[4 * ks]), "=r"(q[4 * ks + 1]), "=r"(q[4 * ks + 2]), "=r"(q[4 * ks + 3])
                       : "r"(qa + sw64_off(r, ks * 16 + (lane_ >> 4) * 8)) : "memory");
      }
      const int kb = KB_AT, qb = QB_AT;
#pragma unroll 1
      for (int it = 0; it <= 8; it++) {
        uint32_t p[16];
        if (it == kb || it == qb || it == 8) {
          float t[16];
          wg_wait<0>();
          fence_regs(o);
          if (it < 8) {
            if (tid == 0) PROF_MARK(it == kb ? 27 : 11);
            const uint64_t dA = make_desc(sb + (it == kb ? OFF_KA : OFF_QA) + nh * 8192 + mh * 4096, 512, 512, 2);
            const uint64_t dB = make_desc(sb + OFF_WPH + nh * 2048, 512, 512, 2);
            float* kvacc = g_kvacc[epoch] + (2 * hp + nh) * 2048;
            float pa[16];
            wg_fence();
            wgmma_ss_n32_ta0_tb1<0>(pa, dA, dB);
            wgmma_ss_n32_ta0_tb1<1>(pa, dA + 2, dB + 64);
            wg_commit();
            if (it != kb) {
              mbar_wait(BAR(B_KVR), 0);
              g0 = ldcg_f(g_gate + pt * 128 + row0); g1 = ldcg_f(g_gate + pt * 128 + row0 + 8);
              const int tl = tid & 127;
              const float4 a = ldcg_f4(kvacc + tl * 16), b = ldcg_f4(kvacc + tl * 16 + 4), c = ldcg_f4(kvacc + tl * 16 + 8), d = ldcg_f4(kvacc + tl * 16 + 12);
              const uint32_t ad = sb + OFF_KVR + nh * 4096 + sw64_off(tl >> 1, (tl & 1) * 16);
              sts128(ad, make_uint4(pack_bf16(a.x, a.y), pack_bf16(a.z, a.w), pack_bf16(b.x, b.y), pack_bf16(b.z, b.w)));
              sts128(ad ^ 16u, make_uint4(pack_bf16(c.x, c.y), pack_bf16(c.z, c.w), pack_bf16(d.x, d.y), pack_bf16(d.z, d.w)));
            }
            wg_wait<0>();
            fence_regs(pa);
            uint32_t ph[16];
            feature_map(pa, ph, lq);
            const uint32_t rb = sb + OFF_PHI + wg * 8192 + rowl * 128 + lq * 4 + ((rowl & 7) << 4);
#pragma unroll
            for (int ch = 0; ch < 8; ch++) { sts32(rb ^ (ch << 4), ph[2 * ch]); sts32((rb ^ (ch << 4)) + 1024, ph[2 * ch + 1]); }
            fence_async_smem();
            bar_sync(4 + wg, 128);
            const uint64_t dP = make_desc(sb + OFF_PHI + wg * 8192, 1024, 1024, 1);
            if (it == kb) {
              const uint64_t dV = make_desc(sb + OFF_VA + nh * 8192 + mh * 4096, 512, 512, 2);
              float kv[16];
              wg_fence();
              wgmma_ss_n32_ta1_tb1<0>(kv, dP, dV);
#pragma unroll
              for (int ks = 1; ks < 4; ks++) wgmma_ss_n32_ta1_tb1<1>(kv, dP + ks * 128, dV + ks * 64);
              wg_commit();
              wg_wait<0>();
              fence_regs(kv);
              float* dst = kvacc + rowl * 32 + 2 * lq;
#pragma unroll
              for (int j = 0; j < 8; j++)
                asm volatile("red.global.add.v2.f32 [%0], {%1, %2};" ::"l"(dst + 8 * (j >> 1) + 256 * (j & 1)), "f"(kv[2 * j]), "f"(kv[2 * j + 1]) : "memory");
              __syncwarp();
              if (lane == 0) { mbar_arrive(BAR(B_SIG + 1), 1); mbar_arrive(BAR(B_X0FREE), 1); }
              if (tid == 0) PROF_MARK(28);
              goto after_block;
            } else {
              const uint64_t dR = make_desc(sb + OFF_KVR + nh * 4096, 512, 512, 2);
              wg_fence();
              wgmma_ss_n32_ta0_tb1<0>(t, dP, dR);
#pragma unroll
              for (int ks = 1; ks < 4; ks++) wgmma_ss_n32_ta0_tb1<1>(t, dP + ks * 2, dR + ks * 64);
              wg_commit();
              wg_wait<0>();
              fence_regs(t);
              if (lane == 0) mbar_arrive(BAR(B_X1FREE), 1);
            }
          } else {
            if (lane == 0) mbar_arrive(BAR(B_EMPTY + prev), 1);
            if (tid == 0) PROF_MARK(13);
            mbar_wait(BAR(B_SLOW), 0);
            if (__builtin_expect(__any_sync(~0u, *(volatile int*)(sgen + OFF_RED)), 0)) {
              uint32_t qz[8];
#pragma unroll
              for (int i = 0; i < 8; i++) qz[i] = (i >= 6 && lq >= 2) ? 0u : q[i];
              float m0 = -3.0e38f, m1 = -3.0e38f, o2[16];
              int sl2 = slot;
              uint32_t par2 = par;
#pragma unroll 1
              for (int j64 = 0; j64 < 32; j64++) {
                float s[32];
                mbar_wait(BAR(B_FULL + sl2), par2);
                const uint32_t lo = dlo0 + sl2 * 2048 + (j64 & 3) * 512;
                wg_fence();
                wgmma_rs_n64_tb0<0>(s, qz[0], qz[1], qz[2], qz[3], dhi | lo);
                wgmma_rs_n64_tb0<1>(s, qz[4], qz[5], qz[6], qz[7], dhi | (lo + 2));
                wg_commit();
                wg_wait<0>();
                fence_regs(s);
#pragma unroll
                for (int j = 0; j < 8; j++) {
                  const float sc = ((POLY_PAT >> j) & 1) ? 0.5f : 1.f;
                  m0 = fmaxf(m0, fmaxf(s[4 * j], s[4 * j + 1]) * sc);
                  m1 = fmaxf(m1, fmaxf(s[4 * j + 2], s[4 * j + 3]) * sc);
                }
                if ((j64 & 3) == 3) {
                  if (lane == 0) mbar_arrive(BAR(B_EMPTY + sl2), 1);
                  if (++sl2 == 3) { sl2 = 0; par2 ^= 1; }
                }
              }
              m0 = quad_max(m0); m1 = quad_max(m1);
#pragma unroll
              for (int i = 0; i < 16; i++) o2[i] = 0.f;
#pragma unroll 1
              for (int j64 = 0; j64 < 32; j64++) {
                float s[32];
                mbar_wait(BAR(B_FULL + sl2), par2);
                const uint32_t lo = dlo0 + sl2 * 2048 + (j64 & 3) * 512;
                wg_fence();
                wgmma_rs_n64_tb0<0>(s, qz[0], qz[1], qz[2], qz[3], dhi | lo);
                wgmma_rs_n64_tb0<1>(s, qz[4], qz[5], qz[6], qz[7], dhi | (lo + 2));
                wg_commit();
                wg_wait<0>();
                fence_regs(s);
                uint32_t ps[16];
#pragma unroll
                for (int j = 0; j < 8; j++) {
                  const float sc = ((POLY_PAT >> j) & 1) ? 0.5f : 1.f;
                  ps[2 * j] = pack_bf16(ex2f(fmaf(s[4 * j], sc, -m0)), ex2f(fmaf(s[4 * j + 1], sc, -m0)));
                  ps[2 * j + 1] = pack_bf16(ex2f(fmaf(s[4 * j + 2], sc, -m1)), ex2f(fmaf(s[4 * j + 3], sc, -m1)));
                }
                wg_fence();
#pragma unroll
                for (int ks = 0; ks < 4; ks++)
                  wgmma_rs_n32_tb1<1>(o2, ps[4 * ks], ps[4 * ks + 1], ps[4 * ks + 2], ps[4 * ks + 3], dhi | (lo + 256 + ks * 64));
                wg_commit();
                wg_wait<0>();
                fence_regs(o2);
                if ((j64 & 3) == 3) {
                  if (lane == 0) mbar_arrive(BAR(B_EMPTY + sl2), 1);
                  if (++sl2 == 3) { sl2 = 0; par2 ^= 1; }
                }
              }
#pragma unroll 1
              for (int j = 0; j < 2; j++) {
                mbar_wait(BAR(B_FULL + sl2), par2);
                __syncwarp();
                if (lane == 0) mbar_arrive(BAR(B_EMPTY + sl2), 1);
                if (++sl2 == 3) { sl2 = 0; par2 ^= 1; }
              }
#pragma unroll
              for (int i = 0; i < 16; i++) o[i] = o2[i];
            }
#pragma unroll
            for (int i = 0; i < 16; i++) t[i] = o[i];
          }
          {
            const int br = it == 8;
            const float eps = br ? 0.f : 1e-6f;
            const float d0 = __shfl_sync(~0u, t[12], (lane_ & ~3) | 2), d1 = __shfl_sync(~0u, t[14], (lane_ & ~3) | 2);
            const float r0 = __fdividef(br ? 1.f - g0 : g0, d0 + eps), r1 = __fdividef(br ? 1.f - g1 : g1, d1 + eps);
            uint8_t* img = g_o_img + (size_t)((pt * 2 + br) * 14 + mh) * 8192 + rowl * 128;
            const int col0 = (2 * hp + nh) * DH + 2 * lq;
#pragma unroll
            for (int j = 0; j < 4; j++) {
              const int col = col0 + 8 * j;
              uint8_t* gp = img + (col >> 6) * 16384 + ((((col >> 3) ^ rowl) & 7) << 4) + (col & 7) * 2;
              const uint32_t v0 = pack_bf16(t[4 * j] * r0, t[4 * j + 1] * r0), v1 = pack_bf16(t[4 * j + 2] * r1, t[4 * j + 3] * r1);
              if (j < 3 || lq < 2) { *(uint32_t*)gp = v0; *(uint32_t*)(gp + 1024) = v1; }
            }
            __syncwarp();
            if (lane == 0) mbar_arrive(BAR(B_SIG + 2 + br), 1);
            if (tid == 0) PROF_MARK(12 + 2 * br);
            if (br) break;
          }
        }
      after_block:
        if (it == 0 && tid == 0) PROF_MARK(10);
        const uint32_t lo = dlo0 + slot * 2048;
        if (!ok) mbar_wait(BAR(B_FULL + slot), par);
        int nslot = slot + 1;
        uint32_t npar = par;
        if (nslot == 3) { nslot = 0; npar ^= 1; }
        {
          float s[32];
          wg_fence();
          wgmma_rs_n64_tb0<0>(s, q[0], q[1], q[2], q[3], dhi | lo);
          wgmma_rs_n64_tb0<1>(s, q[4], q[5], q[6], q[7], dhi | (lo + 2));
          wg_commit();
#pragma unroll
          for (int u = 0; u < 4; u++) {
            wg_wait<0>();
            fence_regs(s);
            if (u == 0 && lane == 0 && it > 0) mbar_arrive(BAR(B_EMPTY + prev), 1);
            if (u == 2) ok = mbar_test(BAR(B_FULL + nslot), npar);
#pragma unroll
            for (int j = 0; j < 8; j++) {
              if ((POLY_PAT >> j) & 1) {
                p[2 * j] = exp2_pair_fma(s[4 * j], s[4 * j + 1], 0x3F003F00u, 0x00030003u);
                p[2 * j + 1] = exp2_pair_fma(s[4 * j + 2], s[4 * j + 3], 0x3F003F00u, 0x00030003u);
              } else {
                p[2 * j] = pack_bf16(ex2f(s[4 * j]), ex2f(s[4 * j + 1]));
                p[2 * j + 1] = pack_bf16(ex2f(s[4 * j + 2]), ex2f(s[4 * j + 3]));
              }
            }
            wg_fence();
#pragma unroll
            for (int ks = 0; ks < 4; ks++)
              wgmma_rs_n32_tb1<1>(o, p[4 * ks], p[4 * ks + 1], p[4 * ks + 2], p[4 * ks + 3], dhi | (lo + u * 512 + 256 + ks * 64));
            if (u < 3) {
              wgmma_rs_n64_tb0<0>(s, q[0], q[1], q[2], q[3], dhi | (lo + (u + 1) * 512));
              wgmma_rs_n64_tb0<1>(s, q[4], q[5], q[6], q[7], dhi | (lo + (u + 1) * 512 + 2));
            }
            wg_commit();
          }
        }
        prev = slot; slot = nslot; par = npar;
      }
      wg_wait<0>();
      if (nh == 1) return;
#pragma unroll
      for (int i = 0; i < 28; i++) acc0[i] = acc1[i] = 0.f;
#pragma unroll
      for (int i = 0; i < 4; i++) accs[i] = 0.f;
    }
    if (tid == 0) PROF_MARK(17);
    __nv_bfloat16* op = prm.out + (size_t)(pt * 128 + mh * 64 + wq * 16 + (lane >> 2)) * DM + hp * 56 + 2 * (lane & 3);
#pragma unroll
    for (int j = 0; j < 7; j++) {
      *(uint32_t*)(op + 8 * j) = pack_bf16(acc0[4 * j] + acc1[4 * j], acc0[4 * j + 1] + acc1[4 * j + 1]);
      *(uint32_t*)(op + 8 * DM + 8 * j) = pack_bf16(acc0[4 * j + 2] + acc1[4 * j + 2], acc0[4 * j + 3] + acc1[4 * j + 3]);
    }
    if (tid == 0) { PROF_MARK(18); PROF_CLK(31); }
    if (tid == 0) {
      unsigned prevd = atomicAdd(&g_cnt[C_DONE * 32], 1u);
      if (prevd == NCTA - 1) {
#pragma unroll 1
        for (int i = 0; i < C_N; i++) g_cnt[i * 32] = 0;
        g_epoch = epoch ^ 1;
      }
    }
  }
}

typedef CUresult (*EncodeFn)(CUtensorMap*, CUtensorMapDataType, cuuint32_t, void*, const cuuint64_t*, const cuuint64_t*,
                             const cuuint32_t*, const cuuint32_t*, CUtensorMapInterleave, CUtensorMapSwizzle,
                             CUtensorMapL2promotion, CUtensorMapFloatOOBfill);

void make_map(EncodeFn enc, CUtensorMap* tm, const void* ptr, uint64_t cols, uint64_t rows, uint32_t box_rows) {
  cuuint64_t dims[2] = {cols, rows};
  cuuint64_t strides[1] = {cols * 2};
  cuuint32_t box[2] = {64, box_rows};
  cuuint32_t es[2] = {1, 1};
  enc(tm, CU_TENSOR_MAP_DATA_TYPE_BFLOAT16, 2, const_cast<void*>(ptr), dims, strides, box, es, CU_TENSOR_MAP_INTERLEAVE_NONE,
      CU_TENSOR_MAP_SWIZZLE_128B, CU_TENSOR_MAP_L2_PROMOTION_L2_128B, CU_TENSOR_MAP_FLOAT_OOB_FILL_NONE);
}

}

extern "C" void kernel_launch(void* const* d_in, const int* in_sizes, int n_in, void* d_out, int out_size) {
  (void)in_sizes; (void)n_in; (void)out_size;
  static EncodeFn enc = nullptr;
  if (!enc) {
    void* fn = nullptr;
    cudaDriverEntryPointQueryResult qr;
    cudaGetDriverEntryPoint("cuTensorMapEncodeTiled", &fn, cudaEnableDefault, &qr);
    enc = (EncodeFn)fn;
    cudaFuncSetAttribute(fused_kernel, cudaFuncAttributeMaxDynamicSharedMemorySize, SMEM_BYTES);
  }
  CUtensorMap tm_x, tm_wqkv, tm_wq, tm_woa, tm_wob;
  make_map(enc, &tm_x, d_in[0], DM, S_LEN, 128);
  make_map(enc, &tm_wqkv, d_in[1], 3 * DM, DM, 64);
  make_map(enc, &tm_wq, d_in[5], DM, DM, 64);
  make_map(enc, &tm_woa, d_in[3], DM, DM, 64);
  make_map(enc, &tm_wob, d_in[8], DM, DM, 64);
  Params prm;
  prm.w_phi = (const __nv_bfloat16*)d_in[2];
  prm.wk = (const __nv_bfloat16*)d_in[6];
  prm.wv = (const __nv_bfloat16*)d_in[7];
  prm.gate_w = (const __nv_bfloat16*)d_in[9];
  prm.out = (__nv_bfloat16*)d_out;
  fused_kernel<<<NCTA, NTHREADS, SMEM_BYTES>>>(tm_x, tm_wqkv, tm_wq, tm_woa, tm_wob, prm);
}
```

```cpp
#include <cuda_runtime.h>
#include <cuda_bf16.h>
#include <cuda.h>
#include <stdint.h>

namespace {

constexpr int S_LEN = 2048, DM = 448, DH = 28;
constexpr int NCTA = 128;
constexpr int NTHREADS = 640;
constexpr uint32_t POLY_PAT = 0x57;

#define KB_AT (1 - nh)
#define QB_AT (4 + nh)

constexpr int OFF_X = 0;
constexpr int OFF_KA = 0;
constexpr int OFF_VA = 16384;
constexpr int OFF_QP = 32768;
constexpr int OFF_QA = 57344;
constexpr int OFF_KVR = 73728;
constexpr int OFF_PHI = 81920;
constexpr int OFF_WO = 0;
constexpr int OFF_RING = 114688;
constexpr int OFF_WPH = 212992;
constexpr int OFF_SLC = 217088;
constexpr int OFF_QSQ = 224256;
constexpr int OFF_RED = 225792;
constexpr int OFF_BAR = 225856;
constexpr int SMEM_BYTES = 226368 + 1024;

constexpr int B_FULL = 0, B_EMPTY = 3, B_WO = 6  , B_KVR = 8, B_X0FREE = 9, B_X1FREE = 10, B_QSQ = 11, B_SLOW = 12,
              B_BUILD = 13, B_SIG = 14  , B_N = 18;

constexpr int C_KV = 0, C_PART = 1, C_DONE = 3, C_OA = 4, C_OB = 20, C_N = 36;

__device__ __align__(1024) uint8_t g_kv_img[32 * 8192];
__device__ __align__(16) float g_ksq[512];
__device__ __align__(16) float g_vsq[512];
__device__ __align__(16) float g_gate[S_LEN];
__device__ __align__(1024) float g_kvacc[2][16 * 64 * 32];
__device__ unsigned g_epoch;
__device__ __align__(1024) uint8_t g_o_img[2 * 16 * 14 * 8192];
__device__ unsigned g_cnt[C_N * 32];

#define PROF3(i) do { } while (0)
#define PROF2(i) do { } while (0)
#define PROF_CLK(i) do { } while (0)
#define PROF_MARK(i) do { } while (0)
__device__ __forceinline__ uint32_t smem_u32(const void* p) { return (uint32_t)__cvta_generic_to_shared(p); }
__device__ __forceinline__ void mbar_init(uint32_t a, int cnt) {
  asm volatile("mbarrier.init.shared::cta.b64 [%0], %1;" ::"r"(a), "r"(cnt) : "memory");
}
__device__ __forceinline__ void mbar_expect_tx(uint32_t a, uint32_t bytes) {
  asm volatile("mbarrier.arrive.expect_tx.shared::cta.b64 _, [%0], %1;" ::"r"(a), "r"(bytes) : "memory");
}
__device__ __forceinline__ void mbar_arrive(uint32_t a, uint32_t cnt) {
  asm volatile("mbarrier.arrive.shared::cta.b64 _, [%0], %1;" ::"r"(a), "r"(cnt) : "memory");
}
__device__ __forceinline__ void mbar_wait(uint32_t a, uint32_t parity) {
  asm volatile(
      "{\n.reg .pred p;\n.reg .u32 c;\nmov.u32 c, 0;\n"
      "W_%=:\nmbarrier.try_wait.parity.shared::cta.b64 p, [%0], %1;\n"
      "add.u32 c, c, 1;\nsetp.lt.and.u32 p, c, 0x1000000, !p;\n@p bra W_%=;\n}"
      ::"r"(a), "r"(parity) : "memory");
}
__device__ __forceinline__ uint32_t mbar_test(uint32_t a, uint32_t parity) {
  uint32_t ok;
  asm volatile("{\n.reg .pred p;\nmbarrier.test_wait.parity.shared::cta.b64 p, [%1], %2;\nselp.u32 %0, 1, 0, p;\n}"
               : "=r"(ok) : "r"(a), "r"(parity) : "memory");
  return ok;
}
__device__ __forceinline__ bool elect_one() {
  uint32_t r;
  asm volatile("{\n.reg .pred p;\nelect.sync _|p, 0xffffffff;\nselp.u32 %0, 1, 0, p;\n}" : "=r"(r));
  return r != 0;
}
__device__ __forceinline__ void tma_2d(uint32_t dst, const CUtensorMap* tm, int c0, int c1, uint32_t bar) {
  asm volatile("cp.async.bulk.tensor.2d.shared::cluster.global.mbarrier::complete_tx::bytes [%0], [%1, {%3, %4}], [%2];"
               ::"r"(dst), "l"(tm), "r"(bar), "r"(c0), "r"(c1) : "memory");
}
__device__ __forceinline__ void bulk_g2s(uint32_t dst, const void* src, uint32_t bytes, uint32_t bar) {
  asm volatile("cp.async.bulk.shared::cluster.global.mbarrier::complete_tx::bytes [%0], [%1], %2, [%3];"
               ::"r"(dst), "l"(src), "r"(bytes), "r"(bar) : "memory");
}
__device__ __forceinline__ void cp_async8(uint32_t dst, const void* src) {
  asm volatile("cp.async.ca.shared.global [%0], [%1], 8;" ::"r"(dst), "l"(src) : "memory");
}
__device__ __forceinline__ void fence_async_smem() { asm volatile("fence.proxy.async.shared::cta;" ::: "memory"); }
__device__ __forceinline__ void fence_async_all() { asm volatile("fence.proxy.async.global;" ::: "memory"); }
__device__ __forceinline__ float ldcg_f(const float* p) { float v; asm volatile("ld.global.cg.f32 %0, [%1];" : "=f"(v) : "l"(p) : "memory"); return v; }
__device__ __forceinline__ void bar_sync(int id, int n) { asm volatile("bar.sync %0, %1;" ::"r"(id), "r"(n) : "memory"); }
__device__ __forceinline__ void cnt_arrive(int idx) {
  asm volatile("red.release.gpu.global.add.u32 [%0], 1;" ::"l"(&g_cnt[idx * 32]) : "memory");
}
__device__ __forceinline__ void cnt_wait(int idx, unsigned target) {
  unsigned v, n = 0;
#pragma unroll 1
  while (true) {
    asm volatile("ld.acquire.gpu.global.u32 %0, [%1];" : "=r"(v) : "l"(&g_cnt[idx * 32]) : "memory");
    if (v >= target || ++n >= (1u << 22)) break;
    __nanosleep(32);
  }
}
__device__ __forceinline__ void wg_fence() { asm volatile("wgmma.fence.sync.aligned;" ::: "memory"); }
__device__ __forceinline__ void wg_commit() { asm volatile("wgmma.commit_group.sync.aligned;" ::: "memory"); }
template <int N> __device__ __forceinline__ void wg_wait() { asm volatile("wgmma.wait_group.sync.aligned %0;" ::"n"(N) : "memory"); }
template <int N> __device__ __forceinline__ void fence_regs(float (&d)[N]) {
#pragma unroll
  for (int i = 0; i < N; i++) asm volatile("" : "+f"(d[i])::"memory");
}
__device__ __forceinline__ uint64_t make_desc(uint32_t saddr, uint32_t lbo, uint32_t sbo, uint32_t swz) {
  return (uint64_t)((saddr & 0x3FFFF) >> 4) | ((uint64_t)(lbo >> 4) << 16) | ((uint64_t)(sbo >> 4) << 32) | ((uint64_t)swz << 62);
}
__device__ __forceinline__ float ex2f(float x) { float y; asm("ex2.approx.ftz.f32 %0, %1;" : "=f"(y) : "f"(x)); return y; }
__device__ __forceinline__ float rcpf(float x) { float y; asm("rcp.approx.ftz.f32 %0, %1;" : "=f"(y) : "f"(x)); return y; }
__device__ __forceinline__ uint32_t pack_bf16(float lo, float hi) {
  uint32_t r; asm("cvt.rn.bf16x2.f32 %0, %1, %2;" : "=r"(r) : "f"(hi), "f"(lo)); return r;
}
__device__ __forceinline__ uint32_t lop_and_or(uint32_t a, uint32_t m, uint32_t c) {
  uint32_t r; asm("lop3.b32 %0, %1, %2, %3, 0xEA;" : "=r"(r) : "r"(a), "r"(m), "r"(c)); return r;
}
__device__ __forceinline__ void sts32(uint32_t a, uint32_t v) { asm volatile("st.shared.b32 [%0], %1;" ::"r"(a), "r"(v) : "memory"); }
__device__ __forceinline__ void sts64(uint32_t a, uint32_t v0, uint32_t v1) { asm volatile("st.shared.v2.b32 [%0], {%1, %2};" ::"r"(a), "r"(v0), "r"(v1) : "memory"); }
__device__ __forceinline__ void sts128(uint32_t a, uint4 v) {
  asm volatile("st.shared.v4.b32 [%0], {%1, %2, %3, %4};" ::"r"(a), "r"(v.x), "r"(v.y), "r"(v.z), "r"(v.w) : "memory");
}
__device__ __forceinline__ float4 ldcg_f4(const float* p) {
  float4 v; asm volatile("ld.global.cg.v4.f32 {%0, %1, %2, %3}, [%4];" : "=f"(v.x), "=f"(v.y), "=f"(v.z), "=f"(v.w) : "l"(p) : "memory"); return v;
}
__device__ __forceinline__ float quad_sum(float v) { v += __shfl_xor_sync(~0u, v, 1); v += __shfl_xor_sync(~0u, v, 2); return v; }
__device__ __forceinline__ float quad_max(float v) { v = fmaxf(v, __shfl_xor_sync(~0u, v, 1)); v = fmaxf(v, __shfl_xor_sync(~0u, v, 2)); return v; }

template <int SD> __device__ __forceinline__ void wgmma_ss_n56_ta0_tb1(float (&d)[28], uint64_t da, uint64_t db) {
  if (SD) asm volatile("wgmma.mma_async.sync.aligned.m64n56k16.f32.bf16.bf16 {%0, %1, %2, %3, %4, %5, %6, %7, %8, %9, %10, %11, %12, %13, %14, %15, %16, %17, %18, %19, %20, %21, %22, %23, %24, %25, %26, %27}, %28, %29, 1, 1, 1, 0, 1;\n"
    : "+f"(d[0]), "+f"(d[1]), "+f"(d[2]), "+f"(d[3]), "+f"(d[4]), "+f"(d[5]), "+f"(d[6]), "+f"(d[7]), "+f"(d[8]), "+f"(d[9]), "+f"(d[10]), "+f"(d[11]), "+f"(d[12]), "+f"(d[13]), "+f"(d[14]), "+f"(d[15]), "+f"(d[16]), "+f"(d[17]), "+f"(d[18]), "+f"(d[19]), "+f"(d[20]), "+f"(d[21]), "+f"(d[22]), "+f"(d[23]), "+f"(d[24]), "+f"(d[25]), "+f"(d[26]), "+f"(d[27])
    : "l"(da), "l"(db));
  else asm volatile("wgmma.mma_async.sync.aligned.m64n56k16.f32.bf16.bf16 {%0, %1, %2, %3, %4, %5, %6, %7, %8, %9, %10, %11, %12, %13, %14, %15, %16, %17, %18, %19, %20, %21, %22, %23, %24, %25, %26, %27}, %28, %29, 0, 1, 1, 0, 1;\n"
    : "=f"(d[0]), "=f"(d[1]), "=f"(d[2]), "=f"(d[3]), "=f"(d[4]), "=f"(d[5]), "=f"(d[6]), "=f"(d[7]), "=f"(d[8]), "=f"(d[9]), "=f"(d[10]), "=f"(d[11]), "=f"(d[12]), "=f"(d[13]), "=f"(d[14]), "=f"(d[15]), "=f"(d[16]), "=f"(d[17]), "=f"(d[18]), "=f"(d[19]), "=f"(d[20]), "=f"(d[21]), "=f"(d[22]), "=f"(d[23]), "=f"(d[24]), "=f"(d[25]), "=f"(d[26]), "=f"(d[27])
    : "l"(da), "l"(db));
}
template <int SD> __device__ __forceinline__ void wgmma_ss_n8_ta0_tb1(float (&d)[4], uint64_t da, uint64_t db) {
  if (SD) asm volatile("wgmma.mma_async.sync.aligned.m64n8k16.f32.bf16.bf16 {%0, %1, %2, %3}, %4, %5, 1, 1, 1, 0, 1;\n"
    : "+f"(d[0]), "+f"(d[1]), "+f"(d[2]), "+f"(d[3])
    : "l"(da), "l"(db));
  else asm volatile("wgmma.mma_async.sync.aligned.m64n8k16.f32.bf16.bf16 {%0, %1, %2, %3}, %4, %5, 0, 1, 1, 0, 1;\n"
    : "=f"(d[0]), "=f"(d[1]), "=f"(d[2]), "=f"(d[3])
    : "l"(da), "l"(db));
}
template <int SD> __device__ __forceinline__ void wgmma_ss_n32_ta1_tb1(float (&d)[16], uint64_t da, uint64_t db) {
  if (SD) asm volatile("wgmma.mma_async.sync.aligned.m64n32k16.f32.bf16.bf16 {%0, %1, %2, %3, %4, %5, %6, %7, %8, %9, %10, %11, %12, %13, %14, %15}, %16, %17, 1, 1, 1, 1, 1;\n"
    : "+f"(d[0]), "+f"(d[1]), "+f"(d[2]), "+f"(d[3]), "+f"(d[4]), "+f"(d[5]), "+f"(d[6]), "+f"(d[7]), "+f"(d[8]), "+f"(d[9]), "+f"(d[10]), "+f"(d[11]), "+f"(d[12]), "+f"(d[13]), "+f"(d[14]), "+f"(d[15])
    : "l"(da), "l"(db));
  else asm volatile("wgmma.mma_async.sync.aligned.m64n32k16.f32.bf16.bf16 {%0, %1, %2, %3, %4, %5, %6, %7, %8, %9, %10, %11, %12, %13, %14, %15}, %16, %17, 0, 1, 1, 1, 1;\n"
    : "=f"(d[0]), "=f"(d[1]), "=f"(d[2]), "=f"(d[3]), "=f"(d[4]), "=f"(d[5]), "=f"(d[6]), "=f"(d[7]), "=f"(d[8]), "=f"(d[9]), "=f"(d[10]), "=f"(d[11]), "=f"(d[12]), "=f"(d[13]), "=f"(d[14]), "=f"(d[15])
    : "l"(da), "l"(db));
}
template <int SD> __device__ __forceinline__ void wgmma_ss_n32_ta0_tb1(float (&d)[16], uint64_t da, uint64_t db) {
  if (SD) asm volatile("wgmma.mma_async.sync.aligned.m64n32k16.f32.bf16.bf16 {%0, %1, %2, %3, %4, %5, %6, %7, %8, %9, %10, %11, %12, %13, %14, %15}, %16, %17, 1, 1, 1, 0, 1;\n"
    : "+f"(d[0]), "+f"(d[1]), "+f"(d[2]), "+f"(d[3]), "+f"(d[4]), "+f"(d[5]), "+f"(d[6]), "+f"(d[7]), "+f"(d[8]), "+f"(d[9]), "+f"(d[10]), "+f"(d[11]), "+f"(d[12]), "+f"(d[13]), "+f"(d[14]), "+f"(d[15])
    : "l"(da), "l"(db));
  else asm volatile("wgmma.mma_async.sync.aligned.m64n32k16.f32.bf16.bf16 {%0, %1, %2, %3, %4, %5, %6, %7, %8, %9, %10, %11, %12, %13, %14, %15}, %16, %17, 0, 1, 1, 0, 1;\n"
    : "=f"(d[0]), "=f"(d[1]), "=f"(d[2]), "=f"(d[3]), "=f"(d[4]), "=f"(d[5]), "=f"(d[6]), "=f"(d[7]), "=f"(d[8]), "=f"(d[9]), "=f"(d[10]), "=f"(d[11]), "=f"(d[12]), "=f"(d[13]), "=f"(d[14]), "=f"(d[15])
    : "l"(da), "l"(db));
}
template <int SD> __device__ __forceinline__ void wgmma_rs_n64_tb0(float (&d)[32], uint32_t a0, uint32_t a1, uint32_t a2, uint32_t a3, uint64_t db) {
  if (SD) asm volatile("wgmma.mma_async.sync.aligned.m64n64k16.f32.bf16.bf16 {%0, %1, %2, %3, %4, %5, %6, %7, %8, %9, %10, %11, %12, %13, %14, %15, %16, %17, %18, %19, %20, %21, %22, %23, %24, %25, %26, %27, %28, %29, %30, %31}, {%32, %33, %34, %35}, %36, 1, 1, 1, 0;\n"
    : "+f"(d[0]), "+f"(d[1]), "+f"(d[2]), "+f"(d[3]), "+f"(d[4]), "+f"(d[5]), "+f"(d[6]), "+f"(d[7]), "+f"(d[8]), "+f"(d[9]), "+f"(d[10]), "+f"(d[11]), "+f"(d[12]), "+f"(d[13]), "+f"(d[14]), "+f"(d[15]), "+f"(d[16]), "+f"(d[17]), "+f"(d[18]), "+f"(d[19]), "+f"(d[20]), "+f"(d[21]), "+f"(d[22]), "+f"(d[23]), "+f"(d[24]), "+f"(d[25]), "+f"(d[26]), "+f"(d[27]), "+f"(d[28]), "+f"(d[29]), "+f"(d[30]), "+f"(d[31])
    : "r"(a0), "r"(a1), "r"(a2), "r"(a3), "l"(db));
  else asm volatile("wgmma.mma_async.sync.aligned.m64n64k16.f32.bf16.bf16 {%0, %1, %2, %3, %4, %5, %6, %7, %8, %9, %10, %11, %12, %13, %14, %15, %16, %17, %18, %19, %20, %21, %22, %23, %24, %25, %26, %27, %28, %29, %30, %31}, {%32, %33, %34, %35}, %36, 0, 1, 1, 0;\n"
    : "=f"(d[0]), "=f"(d[1]), "=f"(d[2]), "=f"(d[3]), "=f"(d[4]), "=f"(d[5]), "=f"(d[6]), "=f"(d[7]), "=f"(d[8]), "=f"(d[9]), "=f"(d[10]), "=f"(d[11]), "=f"(d[12]), "=f"(d[13]), "=f"(d[14]), "=f"(d[15]), "=f"(d[16]), "=f"(d[17]), "=f"(d[18]), "=f"(d[19]), "=f"(d[20]), "=f"(d[21]), "=f"(d[22]), "=f"(d[23]), "=f"(d[24]), "=f"(d[25]), "=f"(d[26]), "=f"(d[27]), "=f"(d[28]), "=f"(d[29]), "=f"(d[30]), "=f"(d[31])
    : "r"(a0), "r"(a1), "r"(a2), "r"(a3), "l"(db));
}
template <int SD> __device__ __forceinline__ void wgmma_rs_n32_tb1(float (&d)[16], uint32_t a0, uint32_t a1, uint32_t a2, uint32_t a3, uint64_t db) {
  if (SD) asm volatile("wgmma.mma_async.sync.aligned.m64n32k16.f32.bf16.bf16 {%0, %1, %2, %3, %4, %5, %6, %7, %8, %9, %10, %11, %12, %13, %14, %15}, {%16, %17, %18, %19}, %20, 1, 1, 1, 1;\n"
    : "+f"(d[0]), "+f"(d[1]), "+f"(d[2]), "+f"(d[3]), "+f"(d[4]), "+f"(d[5]), "+f"(d[6]), "+f"(d[7]), "+f"(d[8]), "+f"(d[9]), "+f"(d[10]), "+f"(d[11]), "+f"(d[12]), "+f"(d[13]), "+f"(d[14]), "+f"(d[15])
    : "r"(a0), "r"(a1), "r"(a2), "r"(a3), "l"(db));
  else asm volatile("wgmma.mma_async.sync.aligned.m64n32k16.f32.bf16.bf16 {%0, %1, %2, %3, %4, %5, %6, %7, %8, %9, %10, %11, %12, %13, %14, %15}, {%16, %17, %18, %19}, %20, 0, 1, 1, 1;\n"
    : "=f"(d[0]), "=f"(d[1]), "=f"(d[2]), "=f"(d[3]), "=f"(d[4]), "=f"(d[5]), "=f"(d[6]), "=f"(d[7]), "=f"(d[8]), "=f"(d[9]), "=f"(d[10]), "=f"(d[11]), "=f"(d[12]), "=f"(d[13]), "=f"(d[14]), "=f"(d[15])
    : "r"(a0), "r"(a1), "r"(a2), "r"(a3), "l"(db));
}

__device__ __forceinline__ uint32_t sw64_off(int row, int d) { return row * 64 + ((((d >> 3) ^ (row >> 1)) & 3) << 4) + (d & 7) * 2; }

__device__ __forceinline__ uint32_t exp2_pair_fma(float t0, float t1, uint32_t c_half, uint32_t c_3) {
  uint32_t y0, y;
  asm("prmt.b32 %0, %1, %2, 0x6521;" : "=r"(y0) : "r"(__float_as_uint(t0)), "r"(__float_as_uint(t1)));
  uint32_t h = lop_and_or(y0, 0x007F007Fu, c_half);
  uint32_t e = lop_and_or(y0, 0xFF80FF80u, c_3);
  asm("fma.rn.bf16x2 %0, %1, %2, %3;" : "=r"(y) : "r"(y0), "r"(h), "r"(e));
  return y;
}

__device__ __forceinline__ void feature_map(float (&v)[16], uint32_t (&ph)[16], int lq) {
  const float L2E = 1.4426950408889634f;
  const bool tail_ok = lq < 2;
  float mx[2], mn[2], b[16], sa[2], sn[2];
#pragma unroll
  for (int r = 0; r < 2; r++) {
    const int o = 2 * r;
    if (!tail_ok) { v[o + 12] = v[o]; v[o + 13] = v[o]; }
    mx[r] = fmaxf(fmaxf(fmaxf(v[o], v[o + 1]), fmaxf(v[o + 4], v[o + 5])), fmaxf(fmaxf(v[o + 8], v[o + 9]), fmaxf(v[o + 12], v[o + 13])));
    mn[r] = fminf(fminf(fminf(v[o], v[o + 1]), fminf(v[o + 4], v[o + 5])), fminf(fminf(v[o + 8], v[o + 9]), fminf(v[o + 12], v[o + 13])));
  }
#pragma unroll
  for (int o = 1; o <= 2; o <<= 1)
#pragma unroll
    for (int r = 0; r < 2; r++) { mx[r] = fmaxf(mx[r], __shfl_xor_sync(~0u, mx[r], o)); mn[r] = fminf(mn[r], __shfl_xor_sync(~0u, mn[r], o)); }
#pragma unroll
  for (int r = 0; r < 2; r++) {
    const int o = 2 * r;
    const float cx = -mx[r] * L2E, cn = mn[r] * L2E;
#pragma unroll
    for (int i = 0; i < 8; i++) {
      const int k = o + 4 * (i >> 1) + (i & 1);
      b[k] = ex2f(fmaf(v[k], -L2E, cn));
      v[k] = ex2f(fmaf(v[k], L2E, cx));
    }
    if (!tail_ok) { v[o + 12] = v[o + 13] = b[o + 12] = b[o + 13] = 0.f; }
    sa[r] = ((v[o] + v[o + 1]) + (v[o + 4] + v[o + 5])) + ((v[o + 8] + v[o + 9]) + (v[o + 12] + v[o + 13]));
    sn[r] = ((b[o] + b[o + 1]) + (b[o + 4] + b[o + 5])) + ((b[o + 8] + b[o + 9]) + (b[o + 12] + b[o + 13]));
  }
#pragma unroll
  for (int o = 1; o <= 2; o <<= 1)
#pragma unroll
    for (int r = 0; r < 2; r++) { sa[r] += __shfl_xor_sync(~0u, sa[r], o); sn[r] += __shfl_xor_sync(~0u, sn[r], o); }
#pragma unroll
  for (int r = 0; r < 2; r++) {
    const float ra = rcpf(sa[r]), rb = rcpf(sn[r]);
#pragma unroll
    for (int jj = 0; jj < 4; jj++) {
      ph[jj * 2 + r] = pack_bf16(v[2 * r + 4 * jj] * ra, v[2 * r + 4 * jj + 1] * ra);
      ph[(4 + jj) * 2 + r] = pack_bf16(b[2 * r + 4 * jj] * rb, b[2 * r + 4 * jj + 1] * rb);
    }
  }
}

__device__ __forceinline__ void store_heads(uint32_t base, const uint32_t (&a)[14], uint32_t pad0, uint32_t pad1, int row0, int lq) {
  const uint32_t rb = base + row0 * 64 + (((row0 >> 1) & 3) << 4);
  const uint32_t b0 = rb + lq * 4;
  const uint32_t b1 = (rb + 8192 + ((lq * 4 + 8) & 15)) ^ ((lq >> 1) << 4);
#pragma unroll
  for (int j = 0; j < 7; j++) {
    uint32_t ad;
    if (j < 3) ad = b0 ^ (j << 4);
    else if (j == 3) ad = (lq < 2) ? (b0 ^ 48u) : (b1 ^ 16u);
    else ad = (lq < 2) ? (b1 ^ ((j - 4) << 4)) : ((b1 ^ 16u) ^ ((j - 3) << 4));
    sts32(ad, a[2 * j]);
    sts32(ad + 512, a[2 * j + 1]);
  }
  sts64((rb ^ 48u) + 8 + (lq & 1) * 8192 + (lq >> 1) * 512, pad0, pad1);
}

struct Params {
  const __nv_bfloat16* w_phi;
  const __nv_bfloat16* wk;
  const __nv_bfloat16* wv;
  const __nv_bfloat16* gate_w;
  __nv_bfloat16* out;
};

__global__ void __launch_bounds__(NTHREADS, 1)
fused_kernel(const __grid_constant__ CUtensorMap tm_x, const __grid_constant__ CUtensorMap tm_wqkv,
             const __grid_constant__ CUtensorMap tm_wq, const __grid_constant__ CUtensorMap tm_woa,
             const __grid_constant__ CUtensorMap tm_wob, const Params prm) {
  extern __shared__ uint8_t smem_raw[];
  uint32_t sb = (smem_u32(smem_raw) + 1023u) & ~1023u;
  uint8_t* sgen = smem_raw + (sb - smem_u32(smem_raw));
  asm volatile("mov.u32 %0, %0;" : "+r"(sb));
  const int tid = threadIdx.x, lane = tid & 31;
  const int warp = __shfl_sync(~0u, tid >> 5, 0), wg = warp >> 2;
  const int pt = blockIdx.x >> 3, hp = blockIdx.x & 7;
  const uint32_t bars = sb + OFF_BAR;
  auto BAR = [&](int i) { return bars + 8u * i; };
  const unsigned epoch = g_epoch & 1;

  if (tid == 0) { PROF_MARK(0); PROF_CLK(30); PROF2(15); }
  auto load_proj = [&](int c, int g) {
    mbar_expect_tx(BAR(B_FULL + g), 49152);
    tma_2d(sb + OFF_X + c * 16384, &tm_x, c * 64, pt * 128, BAR(B_FULL + g));
    tma_2d(sb + OFF_RING + g * 32768, &tm_wq, hp * 56, c * 64, BAR(B_FULL + g));
#pragma unroll 1
    for (int j = 0; j < 3; j++) tma_2d(sb + OFF_RING + g * 32768 + 8192 + j * 8192, &tm_wqkv, j * DM + hp * 56, c * 64, BAR(B_FULL + g));
  };
  if (elect_one()) {
    const int i = warp == 16 ? 0 : (warp == 0 ? 16 : warp);
    if (i < B_N) {
      int cnt = (i >= B_EMPTY && i < B_WO) || i > B_SIG || i == B_X0FREE || i == B_X1FREE ? 16 : 1;
      if (i == B_BUILD) cnt = 512;
      if (i == B_SIG || i == B_QSQ) cnt = 8;
      mbar_init(BAR(i), cnt);
      fence_async_smem();
    }
    if (warp == 16) load_proj(0, 0);
  }
  __syncthreads();
  if (tid == 0) PROF2(14);

  if (wg == 4) {
    asm volatile("setmaxnreg.dec.sync.aligned.u32 32;");
    if (warp == 16) {
      if (elect_one()) {
        int g = 1, nkv = 8;
        uint32_t par = 1;
#pragma unroll 1
        for (int n = 1; n < 14 + nkv; n++) {
          if (n == 7) { PROF_MARK(20); cnt_wait(C_KV, NCTA); PROF_MARK(21); fence_async_all(); }
          if (n == 15) {
            mbar_wait(BAR(B_SLOW), 0);
            if (*(volatile int*)(sgen + OFF_RED)) nkv = 26;
          }
          const int j = n - 7 - nkv;
          if (j == 0 || j == 3) {
            PROF3(j ? 11 : 8);
            cnt_wait((j ? C_OB : C_OA) + pt, 8);
            PROF3(j ? 12 : 9);
            PROF_MARK(26);
            fence_async_all();
          }
          mbar_wait(BAR(B_EMPTY + g), par);
          if (n < 7) load_proj(n, g);
          else {
            mbar_expect_tx(BAR(B_FULL + g), 32768);
            bulk_g2s(sb + OFF_RING + g * 32768, j < 0 ? g_kv_img + ((n - 7) & 7) * 32768 : g_o_img + (size_t)(pt * 7 + j) * 32768, 32768,
                     BAR(B_FULL + g));
          }
          if (++g == 3) { g = 0; par ^= 1; }
        }
      }
    } else {
      if (warp == 18) {
        if (elect_one()) {
#pragma unroll 1
          for (int i = 0; i < 4; i++) {
            mbar_wait(BAR(B_SIG + i), 0);
            PROF3(2 * i);
            cnt_arrive(i == 0 ? C_KV : i == 1 ? C_PART : (i == 2 ? C_OA : C_OB) + pt);
            PROF3(2 * i + 1);
            if (i == 1 || i == 2) {
              mbar_wait(BAR(B_X0FREE + i - 1), 0);
              mbar_expect_tx(BAR(B_WO + i - 1), 57344);
#pragma unroll 1
              for (int c = 0; c < 7; c++)
                tma_2d(sb + OFF_WO + (i - 1) * 57344 + c * 8192, i == 1 ? &tm_woa : &tm_wob, hp * 56, c * 64, BAR(B_WO + i - 1));
            }
          }
        }
      } else if (warp == 19) {
        if (lane == 0) {
          mbar_wait(BAR(B_SIG + 0), 0);
          cnt_wait(C_KV, NCTA);
        }
        __syncwarp();
        float ksq = 0.f, vsq = 0.f;
#pragma unroll
        for (int sl = 0; sl < 4; sl++) {
          float4 a = ldcg_f4(g_ksq + sl * 128 + lane * 4), b = ldcg_f4(g_vsq + sl * 128 + lane * 4);
          float m = fmaxf(fmaxf(a.x, a.y), fmaxf(a.z, a.w));
          m = __uint_as_float(__reduce_max_sync(~0u, __float_as_uint(m)));
          ksq += m;
          vsq = fmaxf(vsq, fmaxf(fmaxf(b.x, b.y), fmaxf(b.z, b.w)));
        }
        mbar_wait(BAR(B_QSQ), 0);
        const float4 qa4 = ((const float4*)(sgen + OFF_QSQ))[lane], qb4 = ((const float4*)(sgen + OFF_QSQ))[32 + lane];
        const float qmax = fmaxf(fmaxf(fmaxf(qa4.x, qa4.y), fmaxf(qa4.z, qa4.w)), fmaxf(fmaxf(qb4.x, qb4.y), fmaxf(qb4.z, qb4.w)));
        const bool slow = __any_sync(~0u, !(qmax * ksq <= 98.f * 98.f) || !(vsq <= 2.0e8f));
        if (lane == 0) {
          *(volatile int*)(sgen + OFF_RED) = slow;
          mbar_arrive(BAR(B_SLOW), 1);
        }
      } else {
        float4* z = (float4*)(g_kvacc[epoch ^ 1] + blockIdx.x * 256) + lane;
        z[0] = make_float4(0.f, 0.f, 0.f, 0.f);
        z[32] = make_float4(0.f, 0.f, 0.f, 0.f);
        if (lane == 0) {
          mbar_wait(BAR(B_SIG + 1), 0);
          cnt_wait(C_PART, NCTA);
          PROF_MARK(23);
          mbar_arrive(BAR(B_KVR), 1);
        }
      }
    }
  } else {
    asm volatile("setmaxnreg.inc.sync.aligned.u32 112;");
    const int mh = wg & 1, nh = wg >> 1, wq = warp & 3;
    float acc0[28], acc1[28], accs[4] = {0.f, 0.f, 0.f, 0.f};
#pragma unroll
    for (int i = 0; i < 28; i++) acc0[i] = acc1[i] = 0.f;
    int slot = 0, prev = 0;
    uint32_t par = 0;

    if (tid < DM) {
      const __nv_bfloat16* src = (hp < 4 ? prm.wk : prm.wv) + tid * DH + (hp & 3) * 8;
      cp_async8(sb + OFF_SLC + tid * 16, src);
      if ((hp & 3) != 3) cp_async8(sb + OFF_SLC + tid * 16 + 8, src + 4);
      if (tid < 392) {
        const int row = tid / 7, e = row >= DH;
        cp_async8(sb + OFF_WPH + e * 2048 + sw64_off(row - DH * e, (tid % 7) * 4), prm.w_phi + 2 * hp * DH * DH + tid * 4);
      } else {
        const int row = tid - 392, e = row >= DH;
        sts64(sb + OFF_WPH + e * 2048 + sw64_off(row - DH * e, 28), 0u, 0u);
      }
      if ((hp & 3) == 3) sts64(sb + OFF_SLC + tid * 16 + 8, hp == 3 ? (uint32_t)((const unsigned short*)prm.gate_w)[tid] : 0u, 0u);
    } else if (tid < DM + 32) {
      sts128(sb + OFF_WPH + ((tid - DM) >> 4) * 2048 + 28 * 64 + ((tid - DM) & 15) * 16, make_uint4(0, 0, 0, 0));
    }
    asm volatile("cp.async.mbarrier.arrive.noinc.shared::cta.b64 [%0];" ::"r"(BAR(B_BUILD)) : "memory");
    if (nh == 1) { mbar_wait(BAR(B_BUILD), 0); fence_async_smem(); }
#pragma unroll 1
    for (int stage = 0; stage < 2; stage++) {
      {
        const uint64_t dS = make_desc(stage ? sb + OFF_WO : sb + OFF_X + mh * 8192, 1024, 1024, 1);
        const uint64_t dR = make_desc(sb + OFF_RING + (stage ? mh * 8192 : nh * 16384), 1024, 1024, 1);
#pragma unroll 1
        for (int c = 0; c < 7; c++) {
          if (stage) mbar_wait(BAR(B_WO + (c >= 3)), 0);
          if (tid == 0) PROF2(stage * 16 + c * 2);
          mbar_wait(BAR(B_FULL + slot), par);
          if (tid == 0) PROF2(stage * 16 + c * 2 + 1);
          const uint64_t ds = dS + c * 1024, dr = dR + slot * 2048;
          const uint64_t dA0 = stage ? dr : ds, dA1 = stage ? dr + 1024 : ds, dB0 = stage ? ds : dr, dB1 = dB0 + 512;
          wg_fence();
#pragma unroll
          for (int ks = 0; ks < 4; ks++) {
            wgmma_ss_n56_ta0_tb1<1>(acc0, dA0 + ks * 2, dB0 + ks * 128);
            wgmma_ss_n56_ta0_tb1<1>(acc1, dA1 + ks * 2, dB1 + ks * 128);
          }
          if (nh == 1) {
            const uint64_t dSlc = make_desc(sb + OFF_SLC + c * 1024, 128, 128, 0);
#pragma unroll
            for (int ks = 0; ks < 4; ks++) wgmma_ss_n8_ta0_tb1<1>(accs, ds + ks * 2, dSlc + ks * 16);
          }
          wg_commit();
          if (stage == 0 || c < 4) {
            wg_wait<0>();
            if (lane == 0) mbar_arrive(BAR(B_EMPTY + slot), 1 + stage);
          }
          if (++slot == 3) { slot = 0; par ^= 1; }
        }
        wg_wait<0>();
        fence_regs(acc0); fence_regs(acc1); fence_regs(accs);
      }
      if (stage) break;
      int lane_;
      asm volatile("mov.u32 %0, %%laneid;" : "=r"(lane_));
      const int lq = lane_ & 3;
      const int rowl = wq * 16 + (lane_ >> 2);
      const int row0 = mh * 64 + rowl;
      {
        if (tid == 0) PROF_MARK(2);
        if (tid == 256) PROF_MARK(3);
        if (nh == 0) {
          float sq[4] = {0.f, 0.f, 0.f, 0.f};
#pragma unroll
          for (int i = 0; i < 28; i++) acc0[i] *= 0.18898223650461362f * 1.4426950408889634f;
#pragma unroll
          for (int j = 0; j < 7; j++) {
#pragma unroll
            for (int rr = 0; rr < 2; rr++) {
              const float s2 = acc0[4 * j + 2 * rr] * acc0[4 * j + 2 * rr] + acc0[4 * j + 2 * rr + 1] * acc0[4 * j + 2 * rr + 1];
              if (j < 3) sq[rr] += s2;
              else if (j > 3) sq[2 + rr] += s2;
              else { sq[rr] += (lq < 2) ? s2 : 0.f; sq[2 + rr] += (lq < 2) ? 0.f : s2; }
            }
          }
#pragma unroll
          for (int i = 0; i < 4; i++) sq[i] = quad_sum(sq[i]);
          const float mine = lq == 0 ? sq[0] : lq == 1 ? sq[1] : lq == 2 ? sq[2] : sq[3];
          ((float*)(sgen + OFF_QSQ))[(mh + (lq & 2)) * 64 + rowl + 8 * (lq & 1)] = mine <= 3.0e38f ? mine : __int_as_float(0x7f800000);
          __syncwarp();
          if (lane == 0) mbar_arrive(BAR(B_QSQ), 1);
        } else {
          const int sl = hp & 3;
          const bool isk = hp < 4, real = (sl < 3) || (lq < 2);
          const int pos = pt * 128 + row0, kr = pos & 63;
          uint8_t* dst = g_kv_img + (pos >> 6) * 8192 + (isk ? 0 : 4096) + sw64_off(kr, sl * 8 + 2 * lq);
          const uint32_t pat = isk ? POLY_PAT >> (kr >> 3) : 0u;
          float mxv = 0.f;
#pragma unroll
          for (int rr = 0; rr < 2; rr++) {
            const float v0 = accs[2 * rr], v1 = accs[2 * rr + 1];
            const bool poly = (pat >> rr) & 1;
            const float sc = poly ? 2.f : 1.f;
            const float s2 = quad_sum(real ? v0 * v0 + v1 * v1 : 0.f);
            mxv = fmaxf(mxv, s2 <= 3.0e38f ? s2 : __int_as_float(0x7f800000));
            const uint32_t padv = lq == 2 ? (poly ? 0x443F4000u : 0x00003F80u) : (poly ? 0x3AB03F4Du : 0u);
            *(uint32_t*)(dst + rr * 512) = real ? pack_bf16(sc * v0, sc * v1) : padv;
            if (hp == 3 && lq == 2) g_gate[pos + 8 * rr] = rcpf(1.f + ex2f(-1.4426950408889634f * v0));
          }
          mxv = __uint_as_float(__reduce_max_sync(~0u, __float_as_uint(mxv)));
          if (lane == 0) (isk ? g_ksq : g_vsq)[sl * 128 + pt * 8 + mh * 4 + wq] = mxv;
          __syncwarp();
          if (lane == 0) mbar_arrive(BAR(B_SIG + 0), 1);
        }
      }
      if (tid == 0) PROF_MARK(4);
      if (tid == 256) PROF_MARK(5);
      {
        uint32_t h0[14], h1[14];
#pragma unroll
        for (int i = 0; i < 14; i++) { h0[i] = pack_bf16(acc0[2 * i], acc0[2 * i + 1]); h1[i] = pack_bf16(acc1[2 * i], acc1[2 * i + 1]); }
        bar_sync(1, 512);
        if (tid == 0) PROF_MARK(6);
#pragma unroll 1
        for (int r = 0; r < 2; r++) {
          store_heads(sb + (r ? (nh ? OFF_VA : OFF_QA) : (nh ? OFF_KA : OFF_QP)), h0,
                      (r & nh) ? 0x00003F80u : (r | nh) ? 0u : 0x3F800000u, (r | nh) ? 0u : 0x3F803F80u, row0, lq);
#pragma unroll
          for (int i = 0; i < 14; i++) h0[i] = h1[i];
        }
      }
      fence_async_smem();
      bar_sync(1, 512);
      if (tid == 0) PROF_MARK(7);

      const uint64_t dK = make_desc(sb + OFF_RING, 512, 512, 2);
      const uint64_t dhi = dK & 0xffffffff00000000ull;
      const uint32_t dlo0 = (uint32_t)dK;
      uint32_t ok = 0, q[8];
      float g0 = 0.f, g1 = 0.f;
      float o[16];
#pragma unroll
      for (int i = 0; i < 16; i++) o[i] = 0.f;
      {
        const uint32_t qa = sb + OFF_QP + nh * 8192;
        const int r = mh * 64 + wq * 16 + (lane_ & 7) + ((lane_ >> 3) & 1) * 8;
#pragma unroll
        for (int ks = 0; ks < 2; ks++)
          asm volatile("ldmatrix.sync.aligned.m8n8.x4.shared.b16 {%0, %1, %2, %3}, [%4];"
                       : "=r"(q[4 * ks]), "=r"(q[4 * ks + 1]), "=r"(q[4 * ks + 2]), "=r"(q[4 * ks + 3])
                       : "r"(qa + sw64_off(r, ks * 16 + (lane_ >> 4) * 8)) : "memory");
      }
      const int kb = KB_AT, qb = QB_AT;
#pragma unroll 1
      for (int it = 0; it <= 8; it++) {
        uint32_t p[16];
        if (it == kb || it == qb || it == 8) {
          float t[16];
          wg_wait<0>();
          fence_regs(o);
          if (it < 8) {
            if (tid == 0) PROF_MARK(it == kb ? 27 : 11);
            const uint64_t dA = make_desc(sb + (it == kb ? OFF_KA : OFF_QA) + nh * 8192 + mh * 4096, 512, 512, 2);
            const uint64_t dB = make_desc(sb + OFF_WPH + nh * 2048, 512, 512, 2);
            float* kvacc = g_kvacc[epoch] + (2 * hp + nh) * 2048;
            float pa[16];
            float4 ka = make_float4(0.f, 0.f, 0.f, 0.f), kb4 = ka, kc = ka, kd = ka;
            wg_fence();
            wgmma_ss_n32_ta0_tb1<0>(pa, dA, dB);
            wgmma_ss_n32_ta0_tb1<1>(pa, dA + 2, dB + 64);
            wg_commit();
            if (it != kb) {
              mbar_wait(BAR(B_KVR), 0);
              g0 = ldcg_f(g_gate + pt * 128 + row0); g1 = ldcg_f(g_gate + pt * 128 + row0 + 8);
              const float* src = kvacc + (tid & 127) * 16;
              ka = ldcg_f4(src); kb4 = ldcg_f4(src + 4); kc = ldcg_f4(src + 8); kd = ldcg_f4(src + 12);
            }
            wg_wait<0>();
            fence_regs(pa);
            uint32_t ph[16];
            feature_map(pa, ph, lq);
            const uint32_t rb = sb + OFF_PHI + wg * 8192 + rowl * 128 + lq * 4 + ((rowl & 7) << 4);
#pragma unroll
            for (int ch = 0; ch < 8; ch++) { sts32(rb ^ (ch << 4), ph[2 * ch]); sts32((rb ^ (ch << 4)) + 1024, ph[2 * ch + 1]); }
            if (it != kb) {
              const uint32_t ad = sb + OFF_KVR + nh * 4096 + sw64_off((tid & 127) >> 1, (tid & 1) * 16);
              sts128(ad, make_uint4(pack_bf16(ka.x, ka.y), pack_bf16(ka.z, ka.w), pack_bf16(kb4.x, kb4.y), pack_bf16(kb4.z, kb4.w)));
              sts128(ad ^ 16u, make_uint4(pack_bf16(kc.x, kc.y), pack_bf16(kc.z, kc.w), pack_bf16(kd.x, kd.y), pack_bf16(kd.z, kd.w)));
            }
            fence_async_smem();
            bar_sync(4 + wg, 128);
            const uint64_t dP = make_desc(sb + OFF_PHI + wg * 8192, 1024, 1024, 1);
            if (it == kb) {
              const uint64_t dV = make_desc(sb + OFF_VA + nh * 8192 + mh * 4096, 512, 512, 2);
              float kv[16];
              wg_fence();
              wgmma_ss_n32_ta1_tb1<0>(kv, dP, dV);
#pragma unroll
              for (int ks = 1; ks < 4; ks++) wgmma_ss_n32_ta1_tb1<1>(kv, dP + ks * 128, dV + ks * 64);
              wg_commit();
              wg_wait<0>();
              fence_regs(kv);
              float* dst = kvacc + rowl * 32 + 2 * lq;
#pragma unroll
              for (int j = 0; j < 8; j++)
                asm volatile("red.global.add.v2.f32 [%0], {%1, %2};" ::"l"(dst + 8 * (j >> 1) + 256 * (j & 1)), "f"(kv[2 * j]), "f"(kv[2 * j + 1]) : "memory");
              __syncwarp();
              if (lane == 0) { mbar_arrive(BAR(B_SIG + 1), 1); mbar_arrive(BAR(B_X0FREE), 1); }
              if (tid == 0) PROF_MARK(28);
              goto after_block;
            } else {
              const uint64_t dR = make_desc(sb + OFF_KVR + nh * 4096, 512, 512, 2);
              wg_fence();
              wgmma_ss_n32_ta0_tb1<0>(t, dP, dR);
#pragma unroll
              for (int ks = 1; ks < 4; ks++) wgmma_ss_n32_ta0_tb1<1>(t, dP + ks * 2, dR + ks * 64);
              wg_commit();
              wg_wait<0>();
              fence_regs(t);
              if (lane == 0) mbar_arrive(BAR(B_X1FREE), 1);
            }
          } else {
            if (lane == 0) mbar_arrive(BAR(B_EMPTY + prev), 1);
            if (tid == 0) PROF_MARK(13);
            mbar_wait(BAR(B_SLOW), 0);
            if (__builtin_expect(__any_sync(~0u, *(volatile int*)(sgen + OFF_RED)), 0)) {
              uint32_t qz[8];
#pragma unroll
              for (int i = 0; i < 8; i++) qz[i] = (i >= 6 && lq >= 2) ? 0u : q[i];
              float m0 = -3.0e38f, m1 = -3.0e38f, o2[16];
              int sl2 = slot;
              uint32_t par2 = par;
#pragma unroll 1
              for (int j64 = 0; j64 < 32; j64++) {
                float s[32];
                mbar_wait(BAR(B_FULL + sl2), par2);
                const uint32_t lo = dlo0 + sl2 * 2048 + (j64 & 3) * 512;
                wg_fence();
                wgmma_rs_n64_tb0<0>(s, qz[0], qz[1], qz[2], qz[3], dhi | lo);
                wgmma_rs_n64_tb0<1>(s, qz[4], qz[5], qz[6], qz[7], dhi | (lo + 2));
                wg_commit();
                wg_wait<0>();
                fence_regs(s);
#pragma unroll
                for (int j = 0; j < 8; j++) {
                  const float sc = ((POLY_PAT >> j) & 1) ? 0.5f : 1.f;
                  m0 = fmaxf(m0, fmaxf(s[4 * j], s[4 * j + 1]) * sc);
                  m1 = fmaxf(m1, fmaxf(s[4 * j + 2], s[4 * j + 3]) * sc);
                }
                if ((j64 & 3) == 3) {
                  if (lane == 0) mbar_arrive(BAR(B_EMPTY + sl2), 1);
                  if (++sl2 == 3) { sl2 = 0; par2 ^= 1; }
                }
              }
              m0 = quad_max(m0); m1 = quad_max(m1);
#pragma unroll
              for (int i = 0; i < 16; i++) o2[i] = 0.f;
#pragma unroll 1
              for (int j64 = 0; j64 < 32; j64++) {
                float s[32];
                mbar_wait(BAR(B_FULL + sl2), par2);
                const uint32_t lo = dlo0 + sl2 * 2048 + (j64 & 3) * 512;
                wg_fence();
                wgmma_rs_n64_tb0<0>(s, qz[0], qz[1], qz[2], qz[3], dhi | lo);
                wgmma_rs_n64_tb0<1>(s, qz[4], qz[5], qz[6], qz[7], dhi | (lo + 2));
                wg_commit();
                wg_wait<0>();
                fence_regs(s);
                uint32_t ps[16];
#pragma unroll
                for (int j = 0; j < 8; j++) {
                  const float sc = ((POLY_PAT >> j) & 1) ? 0.5f : 1.f;
                  ps[2 * j] = pack_bf16(ex2f(fmaf(s[4 * j], sc, -m0)), ex2f(fmaf(s[4 * j + 1], sc, -m0)));
                  ps[2 * j + 1] = pack_bf16(ex2f(fmaf(s[4 * j + 2], sc, -m1)), ex2f(fmaf(s[4 * j + 3], sc, -m1)));
                }
                wg_fence();
#pragma unroll
                for (int ks = 0; ks < 4; ks++)
                  wgmma_rs_n32_tb1<1>(o2, ps[4 * ks], ps[4 * ks + 1], ps[4 * ks + 2], ps[4 * ks + 3], dhi | (lo + 256 + ks * 64));
                wg_commit();
                wg_wait<0>();
                fence_regs(o2);
                if ((j64 & 3) == 3) {
                  if (lane == 0) mbar_arrive(BAR(B_EMPTY + sl2), 1);
                  if (++sl2 == 3) { sl2 = 0; par2 ^= 1; }
                }
              }
#pragma unroll 1
              for (int j = 0; j < 2; j++) {
                mbar_wait(BAR(B_FULL + sl2), par2);
                __syncwarp();
                if (lane == 0) mbar_arrive(BAR(B_EMPTY + sl2), 1);
                if (++sl2 == 3) { sl2 = 0; par2 ^= 1; }
              }
#pragma unroll
              for (int i = 0; i < 16; i++) o[i] = o2[i];
            }
#pragma unroll
            for (int i = 0; i < 16; i++) t[i] = o[i];
          }
          {
            const int br = it == 8;
            const float eps = br ? 0.f : 1e-6f;
            const float d0 = __shfl_sync(~0u, t[12], (lane_ & ~3) | 2), d1 = __shfl_sync(~0u, t[14], (lane_ & ~3) | 2);
            const float r0 = __fdividef(br ? 1.f - g0 : g0, d0 + eps), r1 = __fdividef(br ? 1.f - g1 : g1, d1 + eps);
            uint8_t* img = g_o_img + (size_t)((pt * 2 + br) * 14 + mh) * 8192 + rowl * 128;
            const int col0 = (2 * hp + nh) * DH + 2 * lq;
#pragma unroll
            for (int j = 0; j < 4; j++) {
              const int col = col0 + 8 * j;
              uint8_t* gp = img + (col >> 6) * 16384 + ((((col >> 3) ^ rowl) & 7) << 4) + (col & 7) * 2;
              const uint32_t v0 = pack_bf16(t[4 * j] * r0, t[4 * j + 1] * r0), v1 = pack_bf16(t[4 * j + 2] * r1, t[4 * j + 3] * r1);
              if (j < 3 || lq < 2) { *(uint32_t*)gp = v0; *(uint32_t*)(gp + 1024) = v1; }
            }
            __syncwarp();
            if (lane == 0) mbar_arrive(BAR(B_SIG + 2 + br), 1);
            if (tid == 0) PROF_MARK(12 + 2 * br);
            if (br) break;
          }
        }
      after_block:
        if (it == 0 && tid == 0) PROF_MARK(10);
        const uint32_t lo = dlo0 + slot * 2048;
        if (!ok) mbar_wait(BAR(B_FULL + slot), par);
        int nslot = slot + 1;
        uint32_t npar = par;
        if (nslot == 3) { nslot = 0; npar ^= 1; }
        {
          float s[32];
          wg_fence();
          wgmma_rs_n64_tb0<0>(s, q[0], q[1], q[2], q[3], dhi | lo);
          wgmma_rs_n64_tb0<1>(s, q[4], q[5], q[6], q[7], dhi | (lo + 2));
          wg_commit();
#pragma unroll
          for (int u = 0; u < 4; u++) {
            wg_wait<0>();
            fence_regs(s);
            if (u == 0 && lane == 0 && it > 0) mbar_arrive(BAR(B_EMPTY + prev), 1);
            if (u == 2) ok = mbar_test(BAR(B_FULL + nslot), npar);
#pragma unroll
            for (int j = 0; j < 8; j++) {
              if ((POLY_PAT >> j) & 1) {
                p[2 * j] = exp2_pair_fma(s[4 * j], s[4 * j + 1], 0x3F003F00u, 0x00030003u);
                p[2 * j + 1] = exp2_pair_fma(s[4 * j + 2], s[4 * j + 3], 0x3F003F00u, 0x00030003u);
              } else {
                p[2 * j] = pack_bf16(ex2f(s[4 * j]), ex2f(s[4 * j + 1]));
                p[2 * j + 1] = pack_bf16(ex2f(s[4 * j + 2]), ex2f(s[4 * j + 3]));
              }
            }
            wg_fence();
#pragma unroll
            for (int ks = 0; ks < 4; ks++)
              wgmma_rs_n32_tb1<1>(o, p[4 * ks], p[4 * ks + 1], p[4 * ks + 2], p[4 * ks + 3], dhi | (lo + u * 512 + 256 + ks * 64));
            if (u < 3) {
              wgmma_rs_n64_tb0<0>(s, q[0], q[1], q[2], q[3], dhi | (lo + (u + 1) * 512));
              wgmma_rs_n64_tb0<1>(s, q[4], q[5], q[6], q[7], dhi | (lo + (u + 1) * 512 + 2));
            }
            wg_commit();
          }
        }
        prev = slot; slot = nslot; par = npar;
      }
      wg_wait<0>();
      if (nh == 1) return;
#pragma unroll
      for (int i = 0; i < 28; i++) acc0[i] = acc1[i] = 0.f;
#pragma unroll
      for (int i = 0; i < 4; i++) accs[i] = 0.f;
    }
    if (tid == 0) PROF_MARK(17);
    __nv_bfloat16* op = prm.out + (size_t)(pt * 128 + mh * 64 + wq * 16 + (lane >> 2)) * DM + hp * 56 + 2 * (lane & 3);
#pragma unroll
    for (int j = 0; j < 7; j++) {
      *(uint32_t*)(op + 8 * j) = pack_bf16(acc0[4 * j] + acc1[4 * j], acc0[4 * j + 1] + acc1[4 * j + 1]);
      *(uint32_t*)(op + 8 * DM + 8 * j) = pack_bf16(acc0[4 * j + 2] + acc1[4 * j + 2], acc0[4 * j + 3] + acc1[4 * j + 3]);
    }
    if (tid == 0) { PROF_MARK(18); PROF_CLK(31); }
    if (tid == 0) {
      unsigned prevd = atomicAdd(&g_cnt[C_DONE * 32], 1u);
      if (prevd == NCTA - 1) {
#pragma unroll 1
        for (int i = 0; i < C_N; i++) g_cnt[i * 32] = 0;
        g_epoch = epoch ^ 1;
      }
    }
  }
}

typedef CUresult (*EncodeFn)(CUtensorMap*, CUtensorMapDataType, cuuint32_t, void*, const cuuint64_t*, const cuuint64_t*,
                             const cuuint32_t*, const cuuint32_t*, CUtensorMapInterleave, CUtensorMapSwizzle,
                             CUtensorMapL2promotion, CUtensorMapFloatOOBfill);

void make_map(EncodeFn enc, CUtensorMap* tm, const void* ptr, uint64_t cols, uint64_t rows, uint32_t box_rows) {
  cuuint64_t dims[2] = {cols, rows};
  cuuint64_t strides[1] = {cols * 2};
  cuuint32_t box[2] = {64, box_rows};
  cuuint32_t es[2] = {1, 1};
  enc(tm, CU_TENSOR_MAP_DATA_TYPE_BFLOAT16, 2, const_cast<void*>(ptr), dims, strides, box, es, CU_TENSOR_MAP_INTERLEAVE_NONE,
      CU_TENSOR_MAP_SWIZZLE_128B, CU_TENSOR_MAP_L2_PROMOTION_L2_128B, CU_TENSOR_MAP_FLOAT_OOB_FILL_NONE);
}

}

extern "C" void kernel_launch(void* const* d_in, const int* in_sizes, int n_in, void* d_out, int out_size) {
  (void)in_sizes; (void)n_in; (void)out_size;
  static EncodeFn enc = nullptr;
  if (!enc) {
    void* fn = nullptr;
    cudaDriverEntryPointQueryResult qr;
    cudaGetDriverEntryPoint("cuTensorMapEncodeTiled", &fn, cudaEnableDefault, &qr);
    enc = (EncodeFn)fn;
    cudaFuncSetAttribute(fused_kernel, cudaFuncAttributeMaxDynamicSharedMemorySize, SMEM_BYTES);
  }
  CUtensorMap tm_x, tm_wqkv, tm_wq, tm_woa, tm_wob;
  make_map(enc, &tm_x, d_in[0], DM, S_LEN, 128);
  make_map(enc, &tm_wqkv, d_in[1], 3 * DM, DM, 64);
  make_map(enc, &tm_wq, d_in[5], DM, DM, 64);
  make_map(enc, &tm_woa, d_in[3], DM, DM, 64);
  make_map(enc, &tm_wob, d_in[8], DM, DM, 64);
  Params prm;
  prm.w_phi = (const __nv_bfloat16*)d_in[2];
  prm.wk = (const __nv_bfloat16*)d_in[6];
  prm.wv = (const __nv_bfloat16*)d_in[7];
  prm.gate_w = (const __nv_bfloat16*)d_in[9];
  prm.out = (__nv_bfloat16*)d_out;
  fused_kernel<<<NCTA, NTHREADS, SMEM_BYTES>>>(tm_x, tm_wqkv, tm_wq, tm_woa, tm_wob, prm);
}
```

```cpp
#include <cuda_runtime.h>
#include <cuda_bf16.h>
#include <cuda.h>
#include <stdint.h>

namespace {

constexpr int S_LEN = 2048, DM = 448, DH = 28;
constexpr int NCTA = 128;
constexpr int NTHREADS = 640;
constexpr uint32_t POLY_PAT = 0x57;

#define KB_AT (nh)
#define QB_AT (4 + nh)

constexpr int OFF_X = 0;
constexpr int OFF_KA = 0;
constexpr int OFF_VA = 16384;
constexpr int OFF_QP = 32768;
constexpr int OFF_QA = 57344;
constexpr int OFF_KVR = 73728;
constexpr int OFF_PHI = 81920;
constexpr int OFF_WO = 0;
constexpr int OFF_RING = 114688;
constexpr int OFF_WPH = 212992;
constexpr int OFF_SLC = 217088;
constexpr int OFF_QSQ = 224256;
constexpr int OFF_RED = 225792;
constexpr int OFF_BAR = 225856;
constexpr int SMEM_BYTES = 226368 + 1024;

constexpr int B_FULL = 0, B_EMPTY = 3, B_WO = 6  , B_KVR = 8, B_X0FREE = 9, B_X1FREE = 10, B_QSQ = 11, B_SLOW = 12,
              B_BUILD = 13, B_SIG = 14  , B_N = 18;

constexpr int C_KV = 0, C_PART = 1, C_DONE = 3, C_OA = 4, C_OB = 20, C_N = 36;

__device__ __align__(1024) uint8_t g_kv_img[32 * 8192];
__device__ __align__(16) float g_ksq[512];
__device__ __align__(16) float g_vsq[512];
__device__ __align__(16) float g_gate[S_LEN];
__device__ __align__(1024) float g_kvacc[2][16 * 64 * 32];
__device__ unsigned g_epoch;
__device__ __align__(1024) uint8_t g_o_img[2 * 16 * 14 * 8192];
__device__ unsigned g_cnt[C_N * 32];

#define PROF3(i) do { } while (0)
#define PROF2(i) do { } while (0)
#define PROF_CLK(i) do { } while (0)
#define PROF_MARK(i) do { } while (0)
__device__ __forceinline__ uint32_t smem_u32(const void* p) { return (uint32_t)__cvta_generic_to_shared(p); }
__device__ __forceinline__ void mbar_init(uint32_t a, int cnt) {
  asm volatile("mbarrier.init.shared::cta.b64 [%0], %1;" ::"r"(a), "r"(cnt) : "memory");
}
__device__ __forceinline__ void mbar_expect_tx(uint32_t a, uint32_t bytes) {
  asm volatile("mbarrier.arrive.expect_tx.shared::cta.b64 _, [%0], %1;" ::"r"(a), "r"(bytes) : "memory");
}
__device__ __forceinline__ void mbar_arrive(uint32_t a, uint32_t cnt) {
  asm volatile("mbarrier.arrive.shared::cta.b64 _, [%0], %1;" ::"r"(a), "r"(cnt) : "memory");
}
__device__ __forceinline__ void mbar_wait(uint32_t a, uint32_t parity) {
  asm volatile(
      "{\n.reg .pred p;\n.reg .u32 c;\nmov.u32 c, 0;\n"
      "W_%=:\nmbarrier.try_wait.parity.shared::cta.b64 p, [%0], %1;\n"
      "add.u32 c, c, 1;\nsetp.lt.and.u32 p, c, 0x1000000, !p;\n@p bra W_%=;\n}"
      ::"r"(a), "r"(parity) : "memory");
}
__device__ __forceinline__ uint32_t mbar_test(uint32_t a, uint32_t parity) {
  uint32_t ok;
  asm volatile("{\n.reg .pred p;\nmbarrier.test_wait.parity.shared::cta.b64 p, [%1], %2;\nselp.u32 %0, 1, 0, p;\n}"
               : "=r"(ok) : "r"(a), "r"(parity) : "memory");
  return ok;
}
__device__ __forceinline__ bool elect_one() {
  uint32_t r;
  asm volatile("{\n.reg .pred p;\nelect.sync _|p, 0xffffffff;\nselp.u32 %0, 1, 0, p;\n}" : "=r"(r));
  return r != 0;
}
__device__ __forceinline__ void tma_2d(uint32_t dst, const CUtensorMap* tm, int c0, int c1, uint32_t bar) {
  asm volatile("cp.async.bulk.tensor.2d.shared::cluster.global.mbarrier::complete_tx::bytes [%0], [%1, {%3, %4}], [%2];"
               ::"r"(dst), "l"(tm), "r"(bar), "r"(c0), "r"(c1) : "memory");
}
__device__ __forceinline__ void bulk_g2s(uint32_t dst, const void* src, uint32_t bytes, uint32_t bar) {
  asm volatile("cp.async.bulk.shared::cluster.global.mbarrier::complete_tx::bytes [%0], [%1], %2, [%3];"
               ::"r"(dst), "l"(src), "r"(bytes), "r"(bar) : "memory");
}
__device__ __forceinline__ void cp_async8(uint32_t dst, const void* src) {
  asm volatile("cp.async.ca.shared.global [%0], [%1], 8;" ::"r"(dst), "l"(src) : "memory");
}
__device__ __forceinline__ void fence_async_smem() { asm volatile("fence.proxy.async.shared::cta;" ::: "memory"); }
__device__ __forceinline__ void fence_async_all() { asm volatile("fence.proxy.async.global;" ::: "memory"); }
__device__ __forceinline__ float ldcg_f(const float* p) { float v; asm volatile("ld.global.cg.f32 %0, [%1];" : "=f"(v) : "l"(p) : "memory"); return v; }
__device__ __forceinline__ void bar_sync(int id, int n) { asm volatile("bar.sync %0, %1;" ::"r"(id), "r"(n) : "memory"); }
__device__ __forceinline__ void cnt_arrive(int idx) {
  asm volatile("red.release.gpu.global.add.u32 [%0], 1;" ::"l"(&g_cnt[idx * 32]) : "memory");
}
__device__ __forceinline__ void cnt_wait(int idx, unsigned target) {
  unsigned v, n = 0;
#pragma unroll 1
  while (true) {
    asm volatile("ld.acquire.gpu.global.u32 %0, [%1];" : "=r"(v) : "l"(&g_cnt[idx * 32]) : "memory");
    if (v >= target || ++n >= (1u << 22)) break;
    __nanosleep(32);
  }
}
__device__ __forceinline__ void wg_fence() { asm volatile("wgmma.fence.sync.aligned;" ::: "memory"); }
__device__ __forceinline__ void wg_commit() { asm volatile("wgmma.commit_group.sync.aligned;" ::: "memory"); }
template <int N> __device__ __forceinline__ void wg_wait() { asm volatile("wgmma.wait_group.sync.aligned %0;" ::"n"(N) : "memory"); }
template <int N> __device__ __forceinline__ void fence_regs(float (&d)[N]) {
#pragma unroll
  for (int i = 0; i < N; i++) asm volatile("" : "+f"(d[i])::"memory");
}
__device__ __forceinline__ uint64_t make_desc(uint32_t saddr, uint32_t lbo, uint32_t sbo, uint32_t swz) {
  return (uint64_t)((saddr & 0x3FFFF) >> 4) | ((uint64_t)(lbo >> 4) << 16) | ((uint64_t)(sbo >> 4) << 32) | ((uint64_t)swz << 62);
}
__device__ __forceinline__ float ex2f(float x) { float y; asm("ex2.approx.ftz.f32 %0, %1;" : "=f"(y) : "f"(x)); return y; }
__device__ __forceinline__ float rcpf(float x) { float y; asm("rcp.approx.ftz.f32 %0, %1;" : "=f"(y) : "f"(x)); return y; }
__device__ __forceinline__ uint32_t pack_bf16(float lo, float hi) {
  uint32_t r; asm("cvt.rn.bf16x2.f32 %0, %1, %2;" : "=r"(r) : "f"(hi), "f"(lo)); return r;
}
__device__ __forceinline__ uint32_t lop_and_or(uint32_t a, uint32_t m, uint32_t c) {
  uint32_t r; asm("lop3.b32 %0, %1, %2, %3, 0xEA;" : "=r"(r) : "r"(a), "r"(m), "r"(c)); return r;
}
__device__ __forceinline__ void sts32(uint32_t a, uint32_t v) { asm volatile("st.shared.b32 [%0], %1;" ::"r"(a), "r"(v) : "memory"); }
__device__ __forceinline__ void sts64(uint32_t a, uint32_t v0, uint32_t v1) { asm volatile("st.shared.v2.b32 [%0], {%1, %2};" ::"r"(a), "r"(v0), "r"(v1) : "memory"); }
__device__ __forceinline__ void sts128(uint32_t a, uint4 v) {
  asm volatile("st.shared.v4.b32 [%0], {%1, %2, %3, %4};" ::"r"(a), "r"(v.x), "r"(v.y), "r"(v.z), "r"(v.w) : "memory");
}
__device__ __forceinline__ float4 ldcg_f4(const float* p) {
  float4 v; asm volatile("ld.global.cg.v4.f32 {%0, %1, %2, %3}, [%4];" : "=f"(v.x), "=f"(v.y), "=f"(v.z), "=f"(v.w) : "l"(p) : "memory"); return v;
}
__device__ __forceinline__ float quad_sum(float v) { v += __shfl_xor_sync(~0u, v, 1); v += __shfl_xor_sync(~0u, v, 2); return v; }
__device__ __forceinline__ float quad_max(float v) { v = fmaxf(v, __shfl_xor_sync(~0u, v, 1)); v = fmaxf(v, __shfl_xor_sync(~0u, v, 2)); return v; }

template <int SD> __device__ __forceinline__ void wgmma_ss_n56_ta0_tb1(float (&d)[28], uint64_t da, uint64_t db) {
  if (SD) asm volatile("wgmma.mma_async.sync.aligned.m64n56k16.f32.bf16.bf16 {%0, %1, %2, %3, %4, %5, %6, %7, %8, %9, %10, %11, %12, %13, %14, %15, %16, %17, %18, %19, %20, %21, %22, %23, %24, %25, %26, %27}, %28, %29, 1, 1, 1, 0, 1;\n"
    : "+f"(d[0]), "+f"(d[1]), "+f"(d[2]), "+f"(d[3]), "+f"(d[4]), "+f"(d[5]), "+f"(d[6]), "+f"(d[7]), "+f"(d[8]), "+f"(d[9]), "+f"(d[10]), "+f"(d[11]), "+f"(d[12]), "+f"(d[13]), "+f"(d[14]), "+f"(d[15]), "+f"(d[16]), "+f"(d[17]), "+f"(d[18]), "+f"(d[19]), "+f"(d[20]), "+f"(d[21]), "+f"(d[22]), "+f"(d[23]), "+f"(d[24]), "+f"(d[25]), "+f"(d[26]), "+f"(d[27])
    : "l"(da), "l"(db));
  else asm volatile("wgmma.mma_async.sync.aligned.m64n56k16.f32.bf16.bf16 {%0, %1, %2, %3, %4, %5, %6, %7, %8, %9, %10, %11, %12, %13, %14, %15, %16, %17, %18, %19, %20, %21, %22, %23, %24, %25, %26, %27}, %28, %29, 0, 1, 1, 0, 1;\n"
    : "=f"(d[0]), "=f"(d[1]), "=f"(d[2]), "=f"(d[3]), "=f"(d[4]), "=f"(d[5]), "=f"(d[6]), "=f"(d[7]), "=f"(d[8]), "=f"(d[9]), "=f"(d[10]), "=f"(d[11]), "=f"(d[12]), "=f"(d[13]), "=f"(d[14]), "=f"(d[15]), "=f"(d[16]), "=f"(d[17]), "=f"(d[18]), "=f"(d[19]), "=f"(d[20]), "=f"(d[21]), "=f"(d[22]), "=f"(d[23]), "=f"(d[24]), "=f"(d[25]), "=f"(d[26]), "=f"(d[27])
    : "l"(da), "l"(db));
}
template <int SD> __device__ __forceinline__ void wgmma_ss_n8_ta0_tb1(float (&d)[4], uint64_t da, uint64_t db) {
  if (SD) asm volatile("wgmma.mma_async.sync.aligned.m64n8k16.f32.bf16.bf16 {%0, %1, %2, %3}, %4, %5, 1, 1, 1, 0, 1;\n"
    : "+f"(d[0]), "+f"(d[1]), "+f"(d[2]), "+f"(d[3])
    : "l"(da), "l"(db));
  else asm volatile("wgmma.mma_async.sync.aligned.m64n8k16.f32.bf16.bf16 {%0, %1, %2, %3}, %4, %5, 0, 1, 1, 0, 1;\n"
    : "=f"(d[0]), "=f"(d[1]), "=f"(d[2]), "=f"(d[3])
    : "l"(da), "l"(db));
}
template <int SD> __device__ __forceinline__ void wgmma_ss_n32_ta1_tb1(float (&d)[16], uint64_t da, uint64_t db) {
  if (SD) asm volatile("wgmma.mma_async.sync.aligned.m64n32k16.f32.bf16.bf16 {%0, %1, %2, %3, %4, %5, %6, %7, %8, %9, %10, %11, %12, %13, %14, %15}, %16, %17, 1, 1, 1, 1, 1;\n"
    : "+f"(d[0]), "+f"(d[1]), "+f"(d[2]), "+f"(d[3]), "+f"(d[4]), "+f"(d[5]), "+f"(d[6]), "+f"(d[7]), "+f"(d[8]), "+f"(d[9]), "+f"(d[10]), "+f"(d[11]), "+f"(d[12]), "+f"(d[13]), "+f"(d[14]), "+f"(d[15])
    : "l"(da), "l"(db));
  else asm volatile("wgmma.mma_async.sync.aligned.m64n32k16.f32.bf16.bf16 {%0, %1, %2, %3, %4, %5, %6, %7, %8, %9, %10, %11, %12, %13, %14, %15}, %16, %17, 0, 1, 1, 1, 1;\n"
    : "=f"(d[0]), "=f"(d[1]), "=f"(d[2]), "=f"(d[3]), "=f"(d[4]), "=f"(d[5]), "=f"(d[6]), "=f"(d[7]), "=f"(d[8]), "=f"(d[9]), "=f"(d[10]), "=f"(d[11]), "=f"(d[12]), "=f"(d[13]), "=f"(d[14]), "=f"(d[15])
    : "l"(da), "l"(db));
}
template <int SD> __device__ __forceinline__ void wgmma_ss_n32_ta0_tb1(float (&d)[16], uint64_t da, uint64_t db) {
  if (SD) asm volatile("wgmma.mma_async.sync.aligned.m64n32k16.f32.bf16.bf16 {%0, %1, %2, %3, %4, %5, %6, %7, %8, %9, %10, %11, %12, %13, %14, %15}, %16, %17, 1, 1, 1, 0, 1;\n"
    : "+f"(d[0]), "+f"(d[1]), "+f"(d[2]), "+f"(d[3]), "+f"(d[4]), "+f"(d[5]), "+f"(d[6]), "+f"(d[7]), "+f"(d[8]), "+f"(d[9]), "+f"(d[10]), "+f"(d[11]), "+f"(d[12]), "+f"(d[13]), "+f"(d[14]), "+f"(d[15])
    : "l"(da), "l"(db));
  else asm volatile("wgmma.mma_async.sync.aligned.m64n32k16.f32.bf16.bf16 {%0, %1, %2, %3, %4, %5, %6, %7, %8, %9, %10, %11, %12, %13, %14, %15}, %16, %17, 0, 1, 1, 0, 1;\n"
    : "=f"(d[0]), "=f"(d[1]), "=f"(d[2]), "=f"(d[3]), "=f"(d[4]), "=f"(d[5]), "=f"(d[6]), "=f"(d[7]), "=f"(d[8]), "=f"(d[9]), "=f"(d[10]), "=f"(d[11]), "=f"(d[12]), "=f"(d[13]), "=f"(d[14]), "=f"(d[15])
    : "l"(da), "l"(db));
}
template <int SD> __device__ __forceinline__ void wgmma_rs_n64_tb0(float (&d)[32], uint32_t a0, uint32_t a1, uint32_t a2, uint32_t a3, uint64_t db) {
  if (SD) asm volatile("wgmma.mma_async.sync.aligned.m64n64k16.f32.bf16.bf16 {%0, %1, %2, %3, %4, %5, %6, %7, %8, %9, %10, %11, %12, %13, %14, %15, %16, %17, %18, %19, %20, %21, %22, %23, %24, %25, %26, %27, %28, %29, %30, %31}, {%32, %33, %34, %35}, %36, 1, 1, 1, 0;\n"
    : "+f"(d[0]), "+f"(d[1]), "+f"(d[2]), "+f"(d[3]), "+f"(d[4]), "+f"(d[5]), "+f"(d[6]), "+f"(d[7]), "+f"(d[8]), "+f"(d[9]), "+f"(d[10]), "+f"(d[11]), "+f"(d[12]), "+f"(d[13]), "+f"(d[14]), "+f"(d[15]), "+f"(d[16]), "+f"(d[17]), "+f"(d[18]), "+f"(d[19]), "+f"(d[20]), "+f"(d[21]), "+f"(d[22]), "+f"(d[23]), "+f"(d[24]), "+f"(d[25]), "+f"(d[26]), "+f"(d[27]), "+f"(d[28]), "+f"(d[29]), "+f"(d[30]), "+f"(d[31])
    : "r"(a0), "r"(a1), "r"(a2), "r"(a3), "l"(db));
  else asm volatile("wgmma.mma_async.sync.aligned.m64n64k16.f32.bf16.bf16 {%0, %1, %2, %3, %4, %5, %6, %7, %8, %9, %10, %11, %12, %13, %14, %15, %16, %17, %18, %19, %20, %21, %22, %23, %24, %25, %26, %27, %28, %29, %30, %31}, {%32, %33, %34, %35}, %36, 0, 1, 1, 0;\n"
    : "=f"(d[0]), "=f"(d[1]), "=f"(d[2]), "=f"(d[3]), "=f"(d[4]), "=f"(d[5]), "=f"(d[6]), "=f"(d[7]), "=f"(d[8]), "=f"(d[9]), "=f"(d[10]), "=f"(d[11]), "=f"(d[12]), "=f"(d[13]), "=f"(d[14]), "=f"(d[15]), "=f"(d[16]), "=f"(d[17]), "=f"(d[18]), "=f"(d[19]), "=f"(d[20]), "=f"(d[21]), "=f"(d[22]), "=f"(d[23]), "=f"(d[24]), "=f"(d[25]), "=f"(d[26]), "=f"(d[27]), "=f"(d[28]), "=f"(d[29]), "=f"(d[30]), "=f"(d[31])
    : "r"(a0), "r"(a1), "r"(a2), "r"(a3), "l"(db));
}
template <int SD> __device__ __forceinline__ void wgmma_rs_n32_tb1(float (&d)[16], uint32_t a0, uint32_t a1, uint32_t a2, uint32_t a3, uint64_t db) {
  if (SD) asm volatile("wgmma.mma_async.sync.aligned.m64n32k16.f32.bf16.bf16 {%0, %1, %2, %3, %4, %5, %6, %7, %8, %9, %10, %11, %12, %13, %14, %15}, {%16, %17, %18, %19}, %20, 1, 1, 1, 1;\n"
    : "+f"(d[0]), "+f"(d[1]), "+f"(d[2]), "+f"(d[3]), "+f"(d[4]), "+f"(d[5]), "+f"(d[6]), "+f"(d[7]), "+f"(d[8]), "+f"(d[9]), "+f"(d[10]), "+f"(d[11]), "+f"(d[12]), "+f"(d[13]), "+f"(d[14]), "+f"(d[15])
    : "r"(a0), "r"(a1), "r"(a2), "r"(a3), "l"(db));
  else asm volatile("wgmma.mma_async.sync.aligned.m64n32k16.f32.bf16.bf16 {%0, %1, %2, %3, %4, %5, %6, %7, %8, %9, %10, %11, %12, %13, %14, %15}, {%16, %17, %18, %19}, %20, 0, 1, 1, 1;\n"
    : "=f"(d[0]), "=f"(d[1]), "=f"(d[2]), "=f"(d[3]), "=f"(d[4]), "=f"(d[5]), "=f"(d[6]), "=f"(d[7]), "=f"(d[8]), "=f"(d[9]), "=f"(d[10]), "=f"(d[11]), "=f"(d[12]), "=f"(d[13]), "=f"(d[14]), "=f"(d[15])
    : "r"(a0), "r"(a1), "r"(a2), "r"(a3), "l"(db));
}

__device__ __forceinline__ uint32_t sw64_off(int row, int d) { return row * 64 + ((((d >> 3) ^ (row >> 1)) & 3) << 4) + (d & 7) * 2; }

__device__ __forceinline__ uint32_t exp2_pair_fma(float t0, float t1, uint32_t c_half, uint32_t c_3) {
  uint32_t y0, y;
  asm("prmt.b32 %0, %1, %2, 0x6521;" : "=r"(y0) : "r"(__float_as_uint(t0)), "r"(__float_as_uint(t1)));
  uint32_t h = lop_and_or(y0, 0x007F007Fu, c_half);
  uint32_t e = lop_and_or(y0, 0xFF80FF80u, c_3);
  asm("fma.rn.bf16x2 %0, %1, %2, %3;" : "=r"(y) : "r"(y0), "r"(h), "r"(e));
  return y;
}

__device__ __forceinline__ void feature_map(float (&v)[16], uint32_t (&ph)[16], int lq) {
  const float L2E = 1.4426950408889634f;
  const bool tail_ok = lq < 2;
  float mx[2], mn[2], b[16], sa[2], sn[2];
#pragma unroll
  for (int r = 0; r < 2; r++) {
    const int o = 2 * r;
    if (!tail_ok) { v[o + 12] = v[o]; v[o + 13] = v[o]; }
    mx[r] = fmaxf(fmaxf(fmaxf(v[o], v[o + 1]), fmaxf(v[o + 4], v[o + 5])), fmaxf(fmaxf(v[o + 8], v[o + 9]), fmaxf(v[o + 12], v[o + 13])));
    mn[r] = fminf(fminf(fminf(v[o], v[o + 1]), fminf(v[o + 4], v[o + 5])), fminf(fminf(v[o + 8], v[o + 9]), fminf(v[o + 12], v[o + 13])));
  }
#pragma unroll
  for (int o = 1; o <= 2; o <<= 1)
#pragma unroll
    for (int r = 0; r < 2; r++) { mx[r] = fmaxf(mx[r], __shfl_xor_sync(~0u, mx[r], o)); mn[r] = fminf(mn[r], __shfl_xor_sync(~0u, mn[r], o)); }
#pragma unroll
  for (int r = 0; r < 2; r++) {
    const int o = 2 * r;
    const float cx = -mx[r] * L2E, cn = mn[r] * L2E;
#pragma unroll
    for (int i = 0; i < 8; i++) {
      const int k = o + 4 * (i >> 1) + (i & 1);
      b[k] = ex2f(fmaf(v[k], -L2E, cn));
      v[k] = ex2f(fmaf(v[k], L2E, cx));
    }
    if (!tail_ok) { v[o + 12] = v[o + 13] = b[o + 12] = b[o + 13] = 0.f; }
    sa[r] = ((v[o] + v[o + 1]) + (v[o + 4] + v[o + 5])) + ((v[o + 8] + v[o + 9]) + (v[o + 12] + v[o + 13]));
    sn[r] = ((b[o] + b[o + 1]) + (b[o + 4] + b[o + 5])) + ((b[o + 8] + b[o + 9]) + (b[o + 12] + b[o + 13]));
  }
#pragma unroll
  for (int o = 1; o <= 2; o <<= 1)
#pragma unroll
    for (int r = 0; r < 2; r++) { sa[r] += __shfl_xor_sync(~0u, sa[r], o); sn[r] += __shfl_xor_sync(~0u, sn[r], o); }
#pragma unroll
  for (int r = 0; r < 2; r++) {
    const float ra = rcpf(sa[r]), rb = rcpf(sn[r]);
#pragma unroll
    for (int jj = 0; jj < 4; jj++) {
      ph[jj * 2 + r] = pack_bf16(v[2 * r + 4 * jj] * ra, v[2 * r + 4 * jj + 1] * ra);
      ph[(4 + jj) * 2 + r] = pack_bf16(b[2 * r + 4 * jj] * rb, b[2 * r + 4 * jj + 1] * rb);
    }
  }
}

__device__ __forceinline__ void store_heads(uint32_t base, const uint32_t (&a)[14], uint32_t pad0, uint32_t pad1, int row0, int lq) {
  const uint32_t rb = base + row0 * 64 + (((row0 >> 1) & 3) << 4);
  const uint32_t b0 = rb + lq * 4;
  const uint32_t b1 = (rb + 8192 + ((lq * 4 + 8) & 15)) ^ ((lq >> 1) << 4);
#pragma unroll
  for (int j = 0; j < 7; j++) {
    uint32_t ad;
    if (j < 3) ad = b0 ^ (j << 4);
    else if (j == 3) ad = (lq < 2) ? (b0 ^ 48u) : (b1 ^ 16u);
    else ad = (lq < 2) ? (b1 ^ ((j - 4) << 4)) : ((b1 ^ 16u) ^ ((j - 3) << 4));
    sts32(ad, a[2 * j]);
    sts32(ad + 512, a[2 * j + 1]);
  }
  sts64((rb ^ 48u) + 8 + (lq & 1) * 8192 + (lq >> 1) * 512, pad0, pad1);
}

struct Params {
  const __nv_bfloat16* w_phi;
  const __nv_bfloat16* wk;
  const __nv_bfloat16* wv;
  const __nv_bfloat16* gate_w;
  __nv_bfloat16* out;
};

__global__ void __launch_bounds__(NTHREADS, 1)
fused_kernel(const __grid_constant__ CUtensorMap tm_x, const __grid_constant__ CUtensorMap tm_wqkv,
             const __grid_constant__ CUtensorMap tm_wq, const __grid_constant__ CUtensorMap tm_woa,
             const __grid_constant__ CUtensorMap tm_wob, const Params prm) {
  extern __shared__ uint8_t smem_raw[];
  uint32_t sb = (smem_u32(smem_raw) + 1023u) & ~1023u;
  uint8_t* sgen = smem_raw + (sb - smem_u32(smem_raw));
  asm volatile("mov.u32 %0, %0;" : "+r"(sb));
  const int tid = threadIdx.x, lane = tid & 31;
  const int warp = __shfl_sync(~0u, tid >> 5, 0), wg = warp >> 2;
  const int pt = blockIdx.x >> 3, hp = blockIdx.x & 7;
  const uint32_t bars = sb + OFF_BAR;
  auto BAR = [&](int i) { return bars + 8u * i; };
  const unsigned epoch = g_epoch & 1;

  if (tid == 0) { PROF_MARK(0); PROF_CLK(30); PROF2(15); }
  auto load_proj = [&](int c, int g) {
    mbar_expect_tx(BAR(B_FULL + g), c == 0 ? 49152 : c < 4 ? 65536 : 32768);
    if (c < 4) tma_2d(sb + OFF_X + (2 * c - (c > 0)) * 16384, &tm_x, (2 * c - (c > 0)) * 64, pt * 128, BAR(B_FULL + g));
    tma_2d(sb + OFF_RING + g * 32768, &tm_wq, hp * 56, c * 64, BAR(B_FULL + g));
#pragma unroll 1
    for (int j = 0; j < 3; j++) tma_2d(sb + OFF_RING + g * 32768 + 8192 + j * 8192, &tm_wqkv, j * DM + hp * 56, c * 64, BAR(B_FULL + g));
    if (c > 0 && c < 4) tma_2d(sb + OFF_X + 2 * c * 16384, &tm_x, 2 * c * 64, pt * 128, BAR(B_FULL + g));
  };
  if (elect_one()) {
    const int i = warp == 16 ? 0 : (warp == 0 ? 16 : warp);
    if (i < B_N) {
      int cnt = (i >= B_EMPTY && i < B_WO) || i > B_SIG || i == B_X0FREE || i == B_X1FREE ? 16 : 1;
      if (i == B_BUILD) cnt = 512;
      if (i == B_SIG || i == B_QSQ) cnt = 8;
      mbar_init(BAR(i), cnt);
      fence_async_smem();
    }
    if (warp == 16) load_proj(0, 0);
  }
  __syncthreads();
  if (tid == 0) PROF2(14);

  if (wg == 4) {
    asm volatile("setmaxnreg.dec.sync.aligned.u32 32;");
    if (warp == 16) {
      if (elect_one()) {
        int g = 1, nkv = 8;
        uint32_t par = 1;
#pragma unroll 1
        for (int n = 1; n < 14 + nkv; n++) {
          if (n == 7) { PROF_MARK(20); cnt_wait(C_KV, NCTA); PROF_MARK(21); fence_async_all(); }
          if (n == 15) {
            mbar_wait(BAR(B_SLOW), 0);
            if (*(volatile int*)(sgen + OFF_RED)) nkv = 26;
          }
          const int j = n - 7 - nkv;
          if (j == 0 || j == 3) {
            PROF3(j ? 11 : 8);
            cnt_wait((j ? C_OB : C_OA) + pt, 8);
            PROF3(j ? 12 : 9);
            PROF_MARK(26);
            fence_async_all();
          }
          mbar_wait(BAR(B_EMPTY + g), par);
          if (n < 7) load_proj(n, g);
          else {
            mbar_expect_tx(BAR(B_FULL + g), 32768);
            bulk_g2s(sb + OFF_RING + g * 32768, j < 0 ? g_kv_img + ((n - 7) & 7) * 32768 : g_o_img + (size_t)(pt * 7 + j) * 32768, 32768,
                     BAR(B_FULL + g));
          }
          if (++g == 3) { g = 0; par ^= 1; }
        }
        if (atomicAdd(&g_cnt[C_DONE * 32], 1u) == NCTA - 1) {
#pragma unroll 1
          for (int i = 0; i < C_N; i++) g_cnt[i * 32] = 0;
          g_epoch = epoch ^ 1;
        }
      }
    } else {
      if (warp == 18) {
        if (elect_one()) {
#pragma unroll 1
          for (int i = 0; i < 4; i++) {
            mbar_wait(BAR(B_SIG + i), 0);
            PROF3(2 * i);
            cnt_arrive(i == 0 ? C_KV : i == 1 ? C_PART : (i == 2 ? C_OA : C_OB) + pt);
            PROF3(2 * i + 1);
            if (i == 1 || i == 2) {
              mbar_wait(BAR(B_X0FREE + i - 1), 0);
              mbar_expect_tx(BAR(B_WO + i - 1), 57344);
#pragma unroll 1
              for (int c = 0; c < 7; c++)
                tma_2d(sb + OFF_WO + (i - 1) * 57344 + c * 8192, i == 1 ? &tm_woa : &tm_wob, hp * 56, c * 64, BAR(B_WO + i - 1));
            }
          }
        }
      } else if (warp == 19) {
        if (lane == 0) {
          mbar_wait(BAR(B_SIG + 0), 0);
          cnt_wait(C_KV, NCTA);
        }
        __syncwarp();
        float ksq = 0.f, vsq = 0.f;
#pragma unroll
        for (int sl = 0; sl < 4; sl++) {
          float4 a = ldcg_f4(g_ksq + sl * 128 + lane * 4), b = ldcg_f4(g_vsq + sl * 128 + lane * 4);
          float m = fmaxf(fmaxf(a.x, a.y), fmaxf(a.z, a.w));
          m = __uint_as_float(__reduce_max_sync(~0u, __float_as_uint(m)));
          ksq += m;
          vsq = fmaxf(vsq, fmaxf(fmaxf(b.x, b.y), fmaxf(b.z, b.w)));
        }
        mbar_wait(BAR(B_QSQ), 0);
        const float4 qa4 = ((const float4*)(sgen + OFF_QSQ))[lane], qb4 = ((const float4*)(sgen + OFF_QSQ))[32 + lane];
        const float qmax = fmaxf(fmaxf(fmaxf(qa4.x, qa4.y), fmaxf(qa4.z, qa4.w)), fmaxf(fmaxf(qb4.x, qb4.y), fmaxf(qb4.z, qb4.w)));
        const bool slow = __any_sync(~0u, !(qmax * ksq <= 98.f * 98.f) || !(vsq <= 2.0e8f));
        if (lane == 0) {
          *(volatile int*)(sgen + OFF_RED) = slow;
          mbar_arrive(BAR(B_SLOW), 1);
        }
      } else {
        float4* z = (float4*)(g_kvacc[epoch ^ 1] + blockIdx.x * 256) + lane;
        z[0] = make_float4(0.f, 0.f, 0.f, 0.f);
        z[32] = make_float4(0.f, 0.f, 0.f, 0.f);
        if (lane == 0) {
          mbar_wait(BAR(B_SIG + 1), 0);
          cnt_wait(C_PART, NCTA);
          PROF_MARK(23);
          mbar_arrive(BAR(B_KVR), 1);
        }
      }
    }
  } else {
    asm volatile("setmaxnreg.inc.sync.aligned.u32 112;");
    const int mh = wg & 1, nh = wg >> 1, wq = warp & 3;
    float acc0[28], acc1[28];
#pragma unroll
    for (int i = 0; i < 28; i++) acc0[i] = acc1[i] = 0.f;
    int slot = 0, prev = 0;
    uint32_t par = 0;

    if (tid < DM) {
      const __nv_bfloat16* src = (hp < 4 ? prm.wk : prm.wv) + tid * DH + (hp & 3) * 8;
      cp_async8(sb + OFF_SLC + tid * 16, src);
      if ((hp & 3) != 3) cp_async8(sb + OFF_SLC + tid * 16 + 8, src + 4);
      if (tid < 392) {
        const int row = tid / 7, e = row >= DH;
        cp_async8(sb + OFF_WPH + e * 2048 + sw64_off(row - DH * e, (tid % 7) * 4), prm.w_phi + 2 * hp * DH * DH + tid * 4);
      } else {
        const int row = tid - 392, e = row >= DH;
        sts64(sb + OFF_WPH + e * 2048 + sw64_off(row - DH * e, 28), 0u, 0u);
      }
      if ((hp & 3) == 3) sts64(sb + OFF_SLC + tid * 16 + 8, hp == 3 ? (uint32_t)((const unsigned short*)prm.gate_w)[tid] : 0u, 0u);
    } else if (tid < DM + 32) {
      sts128(sb + OFF_WPH + ((tid - DM) >> 4) * 2048 + 28 * 64 + ((tid - DM) & 15) * 16, make_uint4(0, 0, 0, 0));
    }
    asm volatile("cp.async.mbarrier.arrive.noinc.shared::cta.b64 [%0];" ::"r"(BAR(B_BUILD)) : "memory");
#pragma unroll 1
    for (int stage = 0; stage < 2; stage++) {
      {
        const uint64_t dS = make_desc(stage ? sb + OFF_WO : sb + OFF_X + mh * 8192, 1024, 1024, 1);
        const uint64_t dR = make_desc(sb + OFF_RING + (stage ? mh * 8192 : nh * 16384), 1024, 1024, 1);
#pragma unroll 1
        for (int c = 0; c < 7; c++) {
          if (stage) mbar_wait(BAR(B_WO + (c >= 3)), 0);
          if (tid == 0 || tid == 256) PROF2(stage * 16 + c * 2 + (tid >> 3));
          mbar_wait(BAR(B_FULL + slot), par);
          if (tid == 0 || tid == 256) PROF2(stage * 16 + c * 2 + 1 + (tid >> 3));
          const uint64_t ds = dS + c * 1024, dr = dR + slot * 2048;
          const uint64_t dA0 = stage ? dr : ds, dA1 = stage ? dr + 1024 : ds, dB0 = stage ? ds : dr, dB1 = dB0 + 512;
          wg_fence();
#pragma unroll
          for (int ks = 0; ks < 4; ks++) {
            wgmma_ss_n56_ta0_tb1<1>(acc0, dA0 + ks * 2, dB0 + ks * 128);
            wgmma_ss_n56_ta0_tb1<1>(acc1, dA1 + ks * 2, dB1 + ks * 128);
          }
          wg_commit();
          if (stage == 0 || c < 4) {
            wg_wait<0>();
            if (lane == 0) mbar_arrive(BAR(B_EMPTY + slot), 1 + stage);
          }
          if (++slot == 3) { slot = 0; par ^= 1; }
          if (nh == 1 && c == 3) {
            float accs[4];
            mbar_wait(BAR(B_BUILD), 0);
            fence_async_smem();
            const uint64_t dSlc = make_desc(sb + OFF_SLC, 128, 128, 0);
            wg_fence();
            wgmma_ss_n8_ta0_tb1<0>(accs, dS, dSlc);
#pragma unroll
            for (int kk = 1; kk < 28; kk++) wgmma_ss_n8_ta0_tb1<1>(accs, dS + (kk >> 2) * 1024 + (kk & 3) * 2, dSlc + kk * 16);
            wg_commit();
            int lane_;
            asm volatile("mov.u32 %0, %%laneid;" : "=r"(lane_));
            const int lq = lane_ & 3, row0 = mh * 64 + wq * 16 + (lane_ >> 2);
            wg_wait<0>();
            fence_regs(accs);
            if (tid == 256) PROF_MARK(3);
            const int sl = hp & 3;
            const bool isk = hp < 4, real = (sl < 3) || (lq < 2);
            const int pos = pt * 128 + row0, kr = pos & 63;
            uint8_t* dst = g_kv_img + (pos >> 6) * 8192 + (isk ? 0 : 4096) + sw64_off(kr, sl * 8 + 2 * lq);
            const uint32_t pat = isk ? POLY_PAT >> (kr >> 3) : 0u;
            float mxv = 0.f;
  #pragma unroll
            for (int rr = 0; rr < 2; rr++) {
              const float v0 = accs[2 * rr], v1 = accs[2 * rr + 1];
              const bool poly = (pat >> rr) & 1;
              const float sc = poly ? 2.f : 1.f;
              const float s2 = quad_sum(real ? v0 * v0 + v1 * v1 : 0.f);
              mxv = fmaxf(mxv, s2 <= 3.0e38f ? s2 : __int_as_float(0x7f800000));
              const uint32_t padv = lq == 2 ? (poly ? 0x443F4000u : 0x00003F80u) : (poly ? 0x3AB03F4Du : 0u);
              *(uint32_t*)(dst + rr * 512) = real ? pack_bf16(sc * v0, sc * v1) : padv;
              if (hp == 3 && lq == 2) g_gate[pos + 8 * rr] = rcpf(1.f + ex2f(-1.4426950408889634f * v0));
            }
            mxv = __uint_as_float(__reduce_max_sync(~0u, __float_as_uint(mxv)));
            if (lane == 0) (isk ? g_ksq : g_vsq)[sl * 128 + pt * 8 + mh * 4 + wq] = mxv;
            __syncwarp();
            if (lane == 0) mbar_arrive(BAR(B_SIG + 0), 1);
            if (tid == 256) PROF_MARK(5);
          }
        }
        wg_wait<0>();
        fence_regs(acc0); fence_regs(acc1);
      }
      if (stage) break;
      int lane_;
      asm volatile("mov.u32 %0, %%laneid;" : "=r"(lane_));
      const int lq = lane_ & 3;
      const int rowl = wq * 16 + (lane_ >> 2);
      const int row0 = mh * 64 + rowl;
      {
        if (tid == 0) PROF_MARK(2);
        if (nh == 0) {
          float sq[4] = {0.f, 0.f, 0.f, 0.f};
#pragma unroll
          for (int i = 0; i < 28; i++) acc0[i] *= 0.18898223650461362f * 1.4426950408889634f;
#pragma unroll
          for (int j = 0; j < 7; j++) {
#pragma unroll
            for (int rr = 0; rr < 2; rr++) {
              const float s2 = acc0[4 * j + 2 * rr] * acc0[4 * j + 2 * rr] + acc0[4 * j + 2 * rr + 1] * acc0[4 * j + 2 * rr + 1];
              if (j < 3) sq[rr] += s2;
              else if (j > 3) sq[2 + rr] += s2;
              else { sq[rr] += (lq < 2) ? s2 : 0.f; sq[2 + rr] += (lq < 2) ? 0.f : s2; }
            }
          }
#pragma unroll
          for (int i = 0; i < 4; i++) sq[i] = quad_sum(sq[i]);
          const float mine = lq == 0 ? sq[0] : lq == 1 ? sq[1] : lq == 2 ? sq[2] : sq[3];
          ((float*)(sgen + OFF_QSQ))[(mh + (lq & 2)) * 64 + rowl + 8 * (lq & 1)] = mine <= 3.0e38f ? mine : __int_as_float(0x7f800000);
          __syncwarp();
          if (lane == 0) mbar_arrive(BAR(B_QSQ), 1);
        }
      }
      if (tid == 0) PROF_MARK(4);
      {
        uint32_t h0[14], h1[14];
#pragma unroll
        for (int i = 0; i < 14; i++) { h0[i] = pack_bf16(acc0[2 * i], acc0[2 * i + 1]); h1[i] = pack_bf16(acc1[2 * i], acc1[2 * i + 1]); }
        bar_sync(1, 512);
        if (tid == 0) PROF_MARK(6);
#pragma unroll 1
        for (int r = 0; r < 2; r++) {
          store_heads(sb + (r ? (nh ? OFF_VA : OFF_QA) : (nh ? OFF_KA : OFF_QP)), h0,
                      (r & nh) ? 0x00003F80u : (r | nh) ? 0u : 0x3F800000u, (r | nh) ? 0u : 0x3F803F80u, row0, lq);
#pragma unroll
          for (int i = 0; i < 14; i++) h0[i] = h1[i];
        }
      }
      fence_async_smem();
      bar_sync(1, 512);
      if (tid == 0) PROF_MARK(7);

      const uint64_t dK = make_desc(sb + OFF_RING, 512, 512, 2);
      const uint64_t dhi = dK & 0xffffffff00000000ull;
      const uint32_t dlo0 = (uint32_t)dK;
      uint32_t ok = 0, q[8];
      float g0 = 0.f, g1 = 0.f;
      float o[16];
#pragma unroll
      for (int i = 0; i < 16; i++) o[i] = 0.f;
      {
        const uint32_t qa = sb + OFF_QP + nh * 8192;
        const int r = mh * 64 + wq * 16 + (lane_ & 7) + ((lane_ >> 3) & 1) * 8;
#pragma unroll
        for (int ks = 0; ks < 2; ks++)
          asm volatile("ldmatrix.sync.aligned.m8n8.x4.shared.b16 {%0, %1, %2, %3}, [%4];"
                       : "=r"(q[4 * ks]), "=r"(q[4 * ks + 1]), "=r"(q[4 * ks + 2]), "=r"(q[4 * ks + 3])
                       : "r"(qa + sw64_off(r, ks * 16 + (lane_ >> 4) * 8)) : "memory");
      }
      const int kb = KB_AT, qb = QB_AT;
#pragma unroll 1
      for (int it = 0; it <= 8; it++) {
        uint32_t p[16];
        if (it == kb || it == qb || it == 8) {
          float t[16];
          wg_wait<0>();
          fence_regs(o);
          if (it < 8) {
            if (tid == 0) PROF_MARK(it == kb ? 27 : 11);
            const uint64_t dA = make_desc(sb + (it == kb ? OFF_KA : OFF_QA) + nh * 8192 + mh * 4096, 512, 512, 2);
            const uint64_t dB = make_desc(sb + OFF_WPH + nh * 2048, 512, 512, 2);
            float* kvacc = g_kvacc[epoch] + (2 * hp + nh) * 2048;
            float pa[16];
            float4 ka = make_float4(0.f, 0.f, 0.f, 0.f), kb4 = ka, kc = ka, kd = ka;
            wg_fence();
            wgmma_ss_n32_ta0_tb1<0>(pa, dA, dB);
            wgmma_ss_n32_ta0_tb1<1>(pa, dA + 2, dB + 64);
            wg_commit();
            if (it != kb) {
              mbar_wait(BAR(B_KVR), 0);
              g0 = ldcg_f(g_gate + pt * 128 + row0); g1 = ldcg_f(g_gate + pt * 128 + row0 + 8);
              const float* src = kvacc + (tid & 127) * 16;
              ka = ldcg_f4(src); kb4 = ldcg_f4(src + 4); kc = ldcg_f4(src + 8); kd = ldcg_f4(src + 12);
            }
            wg_wait<0>();
            fence_regs(pa);
            uint32_t ph[16];
            feature_map(pa, ph, lq);
            const uint32_t rb = sb + OFF_PHI + wg * 8192 + rowl * 128 + lq * 4 + ((rowl & 7) << 4);
#pragma unroll
            for (int ch = 0; ch < 8; ch++) { sts32(rb ^ (ch << 4), ph[2 * ch]); sts32((rb ^ (ch << 4)) + 1024, ph[2 * ch + 1]); }
            if (it != kb) {
              const uint32_t ad = sb + OFF_KVR + nh * 4096 + sw64_off((tid & 127) >> 1, (tid & 1) * 16);
              sts128(ad, make_uint4(pack_bf16(ka.x, ka.y), pack_bf16(ka.z, ka.w), pack_bf16(kb4.x, kb4.y), pack_bf16(kb4.z, kb4.w)));
              sts128(ad ^ 16u, make_uint4(pack_bf16(kc.x, kc.y), pack_bf16(kc.z, kc.w), pack_bf16(kd.x, kd.y), pack_bf16(kd.z, kd.w)));
            }
            fence_async_smem();
            bar_sync(4 + wg, 128);
            const uint64_t dP = make_desc(sb + OFF_PHI + wg * 8192, 1024, 1024, 1);
            if (it == kb) {
              const uint64_t dV = make_desc(sb + OFF_VA + nh * 8192 + mh * 4096, 512, 512, 2);
              float kv[16];
              wg_fence();
              wgmma_ss_n32_ta1_tb1<0>(kv, dP, dV);
#pragma unroll
              for (int ks = 1; ks < 4; ks++) wgmma_ss_n32_ta1_tb1<1>(kv, dP + ks * 128, dV + ks * 64);
              wg_commit();
              wg_wait<0>();
              fence_regs(kv);
              float* dst = kvacc + rowl * 32 + 2 * lq;
#pragma unroll
              for (int j = 0; j < 8; j++)
                asm volatile("red.global.add.v2.f32 [%0], {%1, %2};" ::"l"(dst + 8 * (j >> 1) + 256 * (j & 1)), "f"(kv[2 * j]), "f"(kv[2 * j + 1]) : "memory");
              __syncwarp();
              if (lane == 0) { mbar_arrive(BAR(B_SIG + 1), 1); mbar_arrive(BAR(B_X0FREE), 1); }
              if (tid == 0) PROF_MARK(28);
              goto after_block;
            } else {
              const uint64_t dR = make_desc(sb + OFF_KVR + nh * 4096, 512, 512, 2);
              wg_fence();
              wgmma_ss_n32_ta0_tb1<0>(t, dP, dR);
#pragma unroll
              for (int ks = 1; ks < 4; ks++) wgmma_ss_n32_ta0_tb1<1>(t, dP + ks * 2, dR + ks * 64);
              wg_commit();
              wg_wait<0>();
              fence_regs(t);
              if (lane == 0) mbar_arrive(BAR(B_X1FREE), 1);
            }
          } else {
            if (lane == 0) mbar_arrive(BAR(B_EMPTY + prev), 1);
            if (tid == 0) PROF_MARK(13);
            mbar_wait(BAR(B_SLOW), 0);
            if (__builtin_expect(__any_sync(~0u, *(volatile int*)(sgen + OFF_RED)), 0)) {
              uint32_t qz[8];
#pragma unroll
              for (int i = 0; i < 8; i++) qz[i] = (i >= 6 && lq >= 2) ? 0u : q[i];
              float m0 = -3.0e38f, m1 = -3.0e38f, o2[16];
              int sl2 = slot;
              uint32_t par2 = par;
#pragma unroll 1
              for (int j64 = 0; j64 < 32; j64++) {
                float s[32];
                mbar_wait(BAR(B_FULL + sl2), par2);
                const uint32_t lo = dlo0 + sl2 * 2048 + (j64 & 3) * 512;
                wg_fence();
                wgmma_rs_n64_tb0<0>(s, qz[0], qz[1], qz[2], qz[3], dhi | lo);
                wgmma_rs_n64_tb0<1>(s, qz[4], qz[5], qz[6], qz[7], dhi | (lo + 2));
                wg_commit();
                wg_wait<0>();
                fence_regs(s);
#pragma unroll
                for (int j = 0; j < 8; j++) {
                  const float sc = ((POLY_PAT >> j) & 1) ? 0.5f : 1.f;
                  m0 = fmaxf(m0, fmaxf(s[4 * j], s[4 * j + 1]) * sc);
                  m1 = fmaxf(m1, fmaxf(s[4 * j + 2], s[4 * j + 3]) * sc);
                }
                if ((j64 & 3) == 3) {
                  if (lane == 0) mbar_arrive(BAR(B_EMPTY + sl2), 1);
                  if (++sl2 == 3) { sl2 = 0; par2 ^= 1; }
                }
              }
              m0 = quad_max(m0); m1 = quad_max(m1);
#pragma unroll
              for (int i = 0; i < 16; i++) o2[i] = 0.f;
#pragma unroll 1
              for (int j64 = 0; j64 < 32; j64++) {
                float s[32];
                mbar_wait(BAR(B_FULL + sl2), par2);
                const uint32_t lo = dlo0 + sl2 * 2048 + (j64 & 3) * 512;
                wg_fence();
                wgmma_rs_n64_tb0<0>(s, qz[0], qz[1], qz[2], qz[3], dhi | lo);
                wgmma_rs_n64_tb0<1>(s, qz[4], qz[5], qz[6], qz[7], dhi | (lo + 2));
                wg_commit();
                wg_wait<0>();
                fence_regs(s);
                uint32_t ps[16];
#pragma unroll
                for (int j = 0; j < 8; j++) {
                  const float sc = ((POLY_PAT >> j) & 1) ? 0.5f : 1.f;
                  ps[2 * j] = pack_bf16(ex2f(fmaf(s[4 * j], sc, -m0)), ex2f(fmaf(s[4 * j + 1], sc, -m0)));
                  ps[2 * j + 1] = pack_bf16(ex2f(fmaf(s[4 * j + 2], sc, -m1)), ex2f(fmaf(s[4 * j + 3], sc, -m1)));
                }
                wg_fence();
#pragma unroll
                for (int ks = 0; ks < 4; ks++)
                  wgmma_rs_n32_tb1<1>(o2, ps[4 * ks], ps[4 * ks + 1], ps[4 * ks + 2], ps[4 * ks + 3], dhi | (lo + 256 + ks * 64));
                wg_commit();
                wg_wait<0>();
                fence_regs(o2);
                if ((j64 & 3) == 3) {
                  if (lane == 0) mbar_arrive(BAR(B_EMPTY + sl2), 1);
                  if (++sl2 == 3) { sl2 = 0; par2 ^= 1; }
                }
              }
#pragma unroll 1
              for (int j = 0; j < 2; j++) {
                mbar_wait(BAR(B_FULL + sl2), par2);
                __syncwarp();
                if (lane == 0) mbar_arrive(BAR(B_EMPTY + sl2), 1);
                if (++sl2 == 3) { sl2 = 0; par2 ^= 1; }
              }
#pragma unroll
              for (int i = 0; i < 16; i++) o[i] = o2[i];
            }
#pragma unroll
            for (int i = 0; i < 16; i++) t[i] = o[i];
          }
          {
            const int br = it == 8;
            const float eps = br ? 0.f : 1e-6f;
            const float d0 = __shfl_sync(~0u, t[12], (lane_ & ~3) | 2), d1 = __shfl_sync(~0u, t[14], (lane_ & ~3) | 2);
            const float r0 = __fdividef(br ? 1.f - g0 : g0, d0 + eps), r1 = __fdividef(br ? 1.f - g1 : g1, d1 + eps);
            uint8_t* img = g_o_img + (size_t)((pt * 2 + br) * 14 + mh) * 8192 + rowl * 128;
            const int col0 = (2 * hp + nh) * DH + 2 * lq;
#pragma unroll
            for (int j = 0; j < 4; j++) {
              const int col = col0 + 8 * j;
              uint8_t* gp = img + (col >> 6) * 16384 + ((((col >> 3) ^ rowl) & 7) << 4) + (col & 7) * 2;
              const uint32_t v0 = pack_bf16(t[4 * j] * r0, t[4 * j + 1] * r0), v1 = pack_bf16(t[4 * j + 2] * r1, t[4 * j + 3] * r1);
              if (j < 3 || lq < 2) { *(uint32_t*)gp = v0; *(uint32_t*)(gp + 1024) = v1; }
            }
            __syncwarp();
            if (lane == 0) mbar_arrive(BAR(B_SIG + 2 + br), 1);
            if (tid == 0) PROF_MARK(12 + 2 * br);
            if (br) break;
          }
        }
      after_block:
        if (it == 0 && tid == 0) PROF_MARK(10);
        const uint32_t lo = dlo0 + slot * 2048;
        if (!ok) mbar_wait(BAR(B_FULL + slot), par);
        int nslot = slot + 1;
        uint32_t npar = par;
        if (nslot == 3) { nslot = 0; npar ^= 1; }
        {
          float s[32];
          wg_fence();
          wgmma_rs_n64_tb0<0>(s, q[0], q[1], q[2], q[3], dhi | lo);
          wgmma_rs_n64_tb0<1>(s, q[4], q[5], q[6], q[7], dhi | (lo + 2));
          wg_commit();
#pragma unroll
          for (int u = 0; u < 4; u++) {
            wg_wait<0>();
            fence_regs(s);
            if (u == 0 && lane == 0 && it > 0) mbar_arrive(BAR(B_EMPTY + prev), 1);
            if (u == 2) ok = mbar_test(BAR(B_FULL + nslot), npar);
#pragma unroll
            for (int j = 0; j < 8; j++) {
              if ((POLY_PAT >> j) & 1) {
                p[2 * j] = exp2_pair_fma(s[4 * j], s[4 * j + 1], 0x3F003F00u, 0x00030003u);
                p[2 * j + 1] = exp2_pair_fma(s[4 * j + 2], s[4 * j + 3], 0x3F003F00u, 0x00030003u);
              } else {
                p[2 * j] = pack_bf16(ex2f(s[4 * j]), ex2f(s[4 * j + 1]));
                p[2 * j + 1] = pack_bf16(ex2f(s[4 * j + 2]), ex2f(s[4 * j + 3]));
              }
            }
            wg_fence();
#pragma unroll
            for (int ks = 0; ks < 4; ks++)
              wgmma_rs_n32_tb1<1>(o, p[4 * ks], p[4 * ks + 1], p[4 * ks + 2], p[4 * ks + 3], dhi | (lo + u * 512 + 256 + ks * 64));
            if (u < 3) {
              wgmma_rs_n64_tb0<0>(s, q[0], q[1], q[2], q[3], dhi | (lo + (u + 1) * 512));
              wgmma_rs_n64_tb0<1>(s, q[4], q[5], q[6], q[7], dhi | (lo + (u + 1) * 512 + 2));
            }
            wg_commit();
          }
        }
        prev = slot; slot = nslot; par = npar;
      }
      wg_wait<0>();
      if (nh == 1) return;
#pragma unroll
      for (int i = 0; i < 28; i++) acc0[i] = acc1[i] = 0.f;
    }
    if (tid == 0) PROF_MARK(17);
    __nv_bfloat16* op = prm.out + (size_t)(pt * 128 + mh * 64 + wq * 16 + (lane >> 2)) * DM + hp * 56 + 2 * (lane & 3);
#pragma unroll
    for (int j = 0; j < 7; j++) {
      *(uint32_t*)(op + 8 * j) = pack_bf16(acc0[4 * j] + acc1[4 * j], acc0[4 * j + 1] + acc1[4 * j + 1]);
      *(uint32_t*)(op + 8 * DM + 8 * j) = pack_bf16(acc0[4 * j + 2] + acc1[4 * j + 2], acc0[4 * j + 3] + acc1[4 * j + 3]);
    }
    if (tid == 0) { PROF_MARK(18); PROF_CLK(31); }
  }
}

typedef CUresult (*EncodeFn)(CUtensorMap*, CUtensorMapDataType, cuuint32_t, void*, const cuuint64_t*, const cuuint64_t*,
                             const cuuint32_t*, const cuuint32_t*, CUtensorMapInterleave, CUtensorMapSwizzle,
                             CUtensorMapL2promotion, CUtensorMapFloatOOBfill);

void make_map(EncodeFn enc, CUtensorMap* tm, const void* ptr, uint64_t cols, uint64_t rows, uint32_t box_rows) {
  cuuint64_t dims[2] = {cols, rows};
  cuuint64_t strides[1] = {cols * 2};
  cuuint32_t box[2] = {64, box_rows};
  cuuint32_t es[2] = {1, 1};
  enc(tm, CU_TENSOR_MAP_DATA_TYPE_BFLOAT16, 2, const_cast<void*>(ptr), dims, strides, box, es, CU_TENSOR_MAP_INTERLEAVE_NONE,
      CU_TENSOR_MAP_SWIZZLE_128B, CU_TENSOR_MAP_L2_PROMOTION_L2_128B, CU_TENSOR_MAP_FLOAT_OOB_FILL_NONE);
}

}

extern "C" void kernel_launch(void* const* d_in, const int* in_sizes, int n_in, void* d_out, int out_size) {
  (void)in_sizes; (void)n_in; (void)out_size;
  static EncodeFn enc = nullptr;
  if (!enc) {
    void* fn = nullptr;
    cudaDriverEntryPointQueryResult qr;
    cudaGetDriverEntryPoint("cuTensorMapEncodeTiled", &fn, cudaEnableDefault, &qr);
    enc = (EncodeFn)fn;
    cudaFuncSetAttribute(fused_kernel, cudaFuncAttributeMaxDynamicSharedMemorySize, SMEM_BYTES);
  }
  CUtensorMap tm_x, tm_wqkv, tm_wq, tm_woa, tm_wob;
  make_map(enc, &tm_x, d_in[0], DM, S_LEN, 128);
  make_map(enc, &tm_wqkv, d_in[1], 3 * DM, DM, 64);
  make_map(enc, &tm_wq, d_in[5], DM, DM, 64);
  make_map(enc, &tm_woa, d_in[3], DM, DM, 64);
  make_map(enc, &tm_wob, d_in[8], DM, DM, 64);
  Params prm;
  prm.w_phi = (const __nv_bfloat16*)d_in[2];
  prm.wk = (const __nv_bfloat16*)d_in[6];
  prm.wv = (const __nv_bfloat16*)d_in[7];
  prm.gate_w = (const __nv_bfloat16*)d_in[9];
  prm.out = (__nv_bfloat16*)d_out;
  fused_kernel<<<NCTA, NTHREADS, SMEM_BYTES>>>(tm_x, tm_wqkv, tm_wq, tm_woa, tm_wob, prm);
}
```

```cpp
#include <cuda_runtime.h>
#include <cuda_bf16.h>
#include <cuda.h>
#include <stdint.h>

namespace {

constexpr int S_LEN = 2048, DM = 448, DH = 28;
constexpr int NCTA = 128;
constexpr int NTHREADS = 640;
constexpr uint32_t POLY_PAT = 0x57;

#define KB_AT (nh)
#define QB_AT (5 + nh)

constexpr int OFF_X = 0;
constexpr int OFF_KA = 0;
constexpr int OFF_VA = 16384;
constexpr int OFF_QP = 32768;
constexpr int OFF_QA = 57344;
constexpr int OFF_KVR = 73728;
constexpr int OFF_PHI = 81920;
constexpr int OFF_WO = 0;
constexpr int OFF_RING = 114688;
constexpr int OFF_WPH = 212992;
constexpr int OFF_SLC = 217088;
constexpr int OFF_QSQ = 224256;
constexpr int OFF_GATE = 225280;
constexpr int OFF_RED = 225792;
constexpr int OFF_BAR = 225856;
constexpr int SMEM_BYTES = 226368 + 1024;

constexpr int B_FULL = 0, B_EMPTY = 3, B_WO = 6  , B_KVR = 8, B_X0FREE = 9, B_X1FREE = 10, B_QSQ = 11, B_SLOW = 12,
              B_BUILD = 13, B_SIG = 14  , B_N = 18;

constexpr int C_KV = 0, C_PART = 1, C_DONE = 3, C_OA = 4, C_OB = 20, C_N = 36;

__device__ __align__(1024) uint8_t g_kv_img[32 * 8192];
__device__ __align__(16) float g_ksq[512];
__device__ __align__(16) float g_vsq[512];
__device__ __align__(16) float g_gate[S_LEN];
__device__ __align__(1024) float g_kvacc[2][16 * 64 * 32];
__device__ unsigned g_epoch;
__device__ __align__(1024) uint8_t g_o_img[2 * 16 * 14 * 8192];
__device__ unsigned g_cnt[C_N * 32];

#define PROF4(i) do { } while (0)
#define PROF3(i) do { } while (0)
#define PROF2(i) do { } while (0)
#define PROF_CLK(i) do { } while (0)
#define PROF_MARK(i) do { } while (0)
__device__ __forceinline__ uint32_t smem_u32(const void* p) { return (uint32_t)__cvta_generic_to_shared(p); }
__device__ __forceinline__ void mbar_init(uint32_t a, int cnt) {
  asm volatile("mbarrier.init.shared::cta.b64 [%0], %1;" ::"r"(a), "r"(cnt) : "memory");
}
__device__ __forceinline__ void mbar_expect_tx(uint32_t a, uint32_t bytes) {
  asm volatile("mbarrier.arrive.expect_tx.shared::cta.b64 _, [%0], %1;" ::"r"(a), "r"(bytes) : "memory");
}
__device__ __forceinline__ void mbar_arrive(uint32_t a, uint32_t cnt) {
  asm volatile("mbarrier.arrive.shared::cta.b64 _, [%0], %1;" ::"r"(a), "r"(cnt) : "memory");
}
__device__ __forceinline__ void mbar_wait(uint32_t a, uint32_t parity) {
  asm volatile(
      "{\n.reg .pred p;\n.reg .u32 c;\nmov.u32 c, 0;\n"
      "W_%=:\nmbarrier.try_wait.parity.shared::cta.b64 p, [%0], %1;\n"
      "add.u32 c, c, 1;\nsetp.lt.and.u32 p, c, 0x1000000, !p;\n@p bra W_%=;\n}"
      ::"r"(a), "r"(parity) : "memory");
}
__device__ __forceinline__ uint32_t mbar_test(uint32_t a, uint32_t parity) {
  uint32_t ok;
  asm volatile("{\n.reg .pred p;\nmbarrier.test_wait.parity.shared::cta.b64 p, [%1], %2;\nselp.u32 %0, 1, 0, p;\n}"
               : "=r"(ok) : "r"(a), "r"(parity) : "memory");
  return ok;
}
__device__ __forceinline__ bool elect_one() {
  uint32_t r;
  asm volatile("{\n.reg .pred p;\nelect.sync _|p, 0xffffffff;\nselp.u32 %0, 1, 0, p;\n}" : "=r"(r));
  return r != 0;
}
__device__ __forceinline__ void tma_2d(uint32_t dst, const CUtensorMap* tm, int c0, int c1, uint32_t bar) {
  asm volatile("cp.async.bulk.tensor.2d.shared::cluster.global.mbarrier::complete_tx::bytes [%0], [%1, {%3, %4}], [%2];"
               ::"r"(dst), "l"(tm), "r"(bar), "r"(c0), "r"(c1) : "memory");
}
__device__ __forceinline__ void bulk_g2s(uint32_t dst, const void* src, uint32_t bytes, uint32_t bar) {
  asm volatile("cp.async.bulk.shared::cluster.global.mbarrier::complete_tx::bytes [%0], [%1], %2, [%3];"
               ::"r"(dst), "l"(src), "r"(bytes), "r"(bar) : "memory");
}
__device__ __forceinline__ void cp_async8(uint32_t dst, const void* src) {
  asm volatile("cp.async.ca.shared.global [%0], [%1], 8;" ::"r"(dst), "l"(src) : "memory");
}
__device__ __forceinline__ void fence_async_smem() { asm volatile("fence.proxy.async.shared::cta;" ::: "memory"); }
__device__ __forceinline__ void fence_async_all() { asm volatile("fence.proxy.async.global;" ::: "memory"); }

__device__ __forceinline__ void bar_sync(int id, int n) { asm volatile("bar.sync %0, %1;" ::"r"(id), "r"(n) : "memory"); }
__device__ __forceinline__ void cnt_arrive(int idx) {
  asm volatile("red.release.gpu.global.add.u32 [%0], 1;" ::"l"(&g_cnt[idx * 32]) : "memory");
}
__device__ __forceinline__ void cnt_wait(int idx, unsigned target) {
  unsigned v, n = 0;
#pragma unroll 1
  while (true) {
    asm volatile("ld.acquire.gpu.global.u32 %0, [%1];" : "=r"(v) : "l"(&g_cnt[idx * 32]) : "memory");
    if (v >= target || ++n >= (1u << 22)) break;
    __nanosleep(32);
  }
}
__device__ __forceinline__ void wg_fence() { asm volatile("wgmma.fence.sync.aligned;" ::: "memory"); }
__device__ __forceinline__ void wg_commit() { asm volatile("wgmma.commit_group.sync.aligned;" ::: "memory"); }
template <int N> __device__ __forceinline__ void wg_wait() { asm volatile("wgmma.wait_group.sync.aligned %0;" ::"n"(N) : "memory"); }
template <int N> __device__ __forceinline__ void fence_regs(float (&d)[N]) {
#pragma unroll
  for (int i = 0; i < N; i++) asm volatile("" : "+f"(d[i])::"memory");
}
__device__ __forceinline__ uint64_t make_desc(uint32_t saddr, uint32_t lbo, uint32_t sbo, uint32_t swz) {
  return (uint64_t)((saddr & 0x3FFFF) >> 4) | ((uint64_t)(lbo >> 4) << 16) | ((uint64_t)(sbo >> 4) << 32) | ((uint64_t)swz << 62);
}
__device__ __forceinline__ float ex2f(float x) { float y; asm("ex2.approx.ftz.f32 %0, %1;" : "=f"(y) : "f"(x)); return y; }
__device__ __forceinline__ float rcpf(float x) { float y; asm("rcp.approx.ftz.f32 %0, %1;" : "=f"(y) : "f"(x)); return y; }
__device__ __forceinline__ uint32_t pack_bf16(float lo, float hi) {
  uint32_t r; asm("cvt.rn.bf16x2.f32 %0, %1, %2;" : "=r"(r) : "f"(hi), "f"(lo)); return r;
}
__device__ __forceinline__ uint32_t lop_and_or(uint32_t a, uint32_t m, uint32_t c) {
  uint32_t r; asm("lop3.b32 %0, %1, %2, %3, 0xEA;" : "=r"(r) : "r"(a), "r"(m), "r"(c)); return r;
}
__device__ __forceinline__ void sts32(uint32_t a, uint32_t v) { asm volatile("st.shared.b32 [%0], %1;" ::"r"(a), "r"(v) : "memory"); }
__device__ __forceinline__ void sts64(uint32_t a, uint32_t v0, uint32_t v1) { asm volatile("st.shared.v2.b32 [%0], {%1, %2};" ::"r"(a), "r"(v0), "r"(v1) : "memory"); }
__device__ __forceinline__ void sts128(uint32_t a, uint4 v) {
  asm volatile("st.shared.v4.b32 [%0], {%1, %2, %3, %4};" ::"r"(a), "r"(v.x), "r"(v.y), "r"(v.z), "r"(v.w) : "memory");
}
__device__ __forceinline__ float4 ldcg_f4(const float* p) {
  float4 v; asm volatile("ld.global.cg.v4.f32 {%0, %1, %2, %3}, [%4];" : "=f"(v.x), "=f"(v.y), "=f"(v.z), "=f"(v.w) : "l"(p) : "memory"); return v;
}
__device__ __forceinline__ float quad_sum(float v) { v += __shfl_xor_sync(~0u, v, 1); v += __shfl_xor_sync(~0u, v, 2); return v; }
__device__ __forceinline__ float quad_max(float v) { v = fmaxf(v, __shfl_xor_sync(~0u, v, 1)); v = fmaxf(v, __shfl_xor_sync(~0u, v, 2)); return v; }

template <int SD> __device__ __forceinline__ void wgmma_ss_n56_ta0_tb1(float (&d)[28], uint64_t da, uint64_t db) {
  if (SD) asm volatile("wgmma.mma_async.sync.aligned.m64n56k16.f32.bf16.bf16 {%0, %1, %2, %3, %4, %5, %6, %7, %8, %9, %10, %11, %12, %13, %14, %15, %16, %17, %18, %19, %20, %21, %22, %23, %24, %25, %26, %27}, %28, %29, 1, 1, 1, 0, 1;\n"
    : "+f"(d[0]), "+f"(d[1]), "+f"(d[2]), "+f"(d[3]), "+f"(d[4]), "+f"(d[5]), "+f"(d[6]), "+f"(d[7]), "+f"(d[8]), "+f"(d[9]), "+f"(d[10]), "+f"(d[11]), "+f"(d[12]), "+f"(d[13]), "+f"(d[14]), "+f"(d[15]), "+f"(d[16]), "+f"(d[17]), "+f"(d[18]), "+f"(d[19]), "+f"(d[20]), "+f"(d[21]), "+f"(d[22]), "+f"(d[23]), "+f"(d[24]), "+f"(d[25]), "+f"(d[26]), "+f"(d[27])
    : "l"(da), "l"(db));
  else asm volatile("wgmma.mma_async.sync.aligned.m64n56k16.f32.bf16.bf16 {%0, %1, %2, %3, %4, %5, %6, %7, %8, %9, %10, %11, %12, %13, %14, %15, %16, %17, %18, %19, %20, %21, %22, %23, %24, %25, %26, %27}, %28, %29, 0, 1, 1, 0, 1;\n"
    : "=f"(d[0]), "=f"(d[1]), "=f"(d[2]), "=f"(d[3]), "=f"(d[4]), "=f"(d[5]), "=f"(d[6]), "=f"(d[7]), "=f"(d[8]), "=f"(d[9]), "=f"(d[10]), "=f"(d[11]), "=f"(d[12]), "=f"(d[13]), "=f"(d[14]), "=f"(d[15]), "=f"(d[16]), "=f"(d[17]), "=f"(d[18]), "=f"(d[19]), "=f"(d[20]), "=f"(d[21]), "=f"(d[22]), "=f"(d[23]), "=f"(d[24]), "=f"(d[25]), "=f"(d[26]), "=f"(d[27])
    : "l"(da), "l"(db));
}
template <int SD> __device__ __forceinline__ void wgmma_ss_n8_ta0_tb1(float (&d)[4], uint64_t da, uint64_t db) {
  if (SD) asm volatile("wgmma.mma_async.sync.aligned.m64n8k16.f32.bf16.bf16 {%0, %1, %2, %3}, %4, %5, 1, 1, 1, 0, 1;\n"
    : "+f"(d[0]), "+f"(d[1]), "+f"(d[2]), "+f"(d[3])
    : "l"(da), "l"(db));
  else asm volatile("wgmma.mma_async.sync.aligned.m64n8k16.f32.bf16.bf16 {%0, %1, %2, %3}, %4, %5, 0, 1, 1, 0, 1;\n"
    : "=f"(d[0]), "=f"(d[1]), "=f"(d[2]), "=f"(d[3])
    : "l"(da), "l"(db));
}
template <int SD> __device__ __forceinline__ void wgmma_ss_n32_ta1_tb1(float (&d)[16], uint64_t da, uint64_t db) {
  if (SD) asm volatile("wgmma.mma_async.sync.aligned.m64n32k16.f32.bf16.bf16 {%0, %1, %2, %3, %4, %5, %6, %7, %8, %9, %10, %11, %12, %13, %14, %15}, %16, %17, 1, 1, 1, 1, 1;\n"
    : "+f"(d[0]), "+f"(d[1]), "+f"(d[2]), "+f"(d[3]), "+f"(d[4]), "+f"(d[5]), "+f"(d[6]), "+f"(d[7]), "+f"(d[8]), "+f"(d[9]), "+f"(d[10]), "+f"(d[11]), "+f"(d[12]), "+f"(d[13]), "+f"(d[14]), "+f"(d[15])
    : "l"(da), "l"(db));
  else asm volatile("wgmma.mma_async.sync.aligned.m64n32k16.f32.bf16.bf16 {%0, %1, %2, %3, %4, %5, %6, %7, %8, %9, %10, %11, %12, %13, %14, %15}, %16, %17, 0, 1, 1, 1, 1;\n"
    : "=f"(d[0]), "=f"(d[1]), "=f"(d[2]), "=f"(d[3]), "=f"(d[4]), "=f"(d[5]), "=f"(d[6]), "=f"(d[7]), "=f"(d[8]), "=f"(d[9]), "=f"(d[10]), "=f"(d[11]), "=f"(d[12]), "=f"(d[13]), "=f"(d[14]), "=f"(d[15])
    : "l"(da), "l"(db));
}
template <int SD> __device__ __forceinline__ void wgmma_ss_n32_ta0_tb1(float (&d)[16], uint64_t da, uint64_t db) {
  if (SD) asm volatile("wgmma.mma_async.sync.aligned.m64n32k16.f32.bf16.bf16 {%0, %1, %2, %3, %4, %5, %6, %7, %8, %9, %10, %11, %12, %13, %14, %15}, %16, %17, 1, 1, 1, 0, 1;\n"
    : "+f"(d[0]), "+f"(d[1]), "+f"(d[2]), "+f"(d[3]), "+f"(d[4]), "+f"(d[5]), "+f"(d[6]), "+f"(d[7]), "+f"(d[8]), "+f"(d[9]), "+f"(d[10]), "+f"(d[11]), "+f"(d[12]), "+f"(d[13]), "+f"(d[14]), "+f"(d[15])
    : "l"(da), "l"(db));
  else asm volatile("wgmma.mma_async.sync.aligned.m64n32k16.f32.bf16.bf16 {%0, %1, %2, %3, %4, %5, %6, %7, %8, %9, %10, %11, %12, %13, %14, %15}, %16, %17, 0, 1, 1, 0, 1;\n"
    : "=f"(d[0]), "=f"(d[1]), "=f"(d[2]), "=f"(d[3]), "=f"(d[4]), "=f"(d[5]), "=f"(d[6]), "=f"(d[7]), "=f"(d[8]), "=f"(d[9]), "=f"(d[10]), "=f"(d[11]), "=f"(d[12]), "=f"(d[13]), "=f"(d[14]), "=f"(d[15])
    : "l"(da), "l"(db));
}
template <int SD> __device__ __forceinline__ void wgmma_rs_n64_tb0(float (&d)[32], uint32_t a0, uint32_t a1, uint32_t a2, uint32_t a3, uint64_t db) {
  if (SD) asm volatile("wgmma.mma_async.sync.aligned.m64n64k16.f32.bf16.bf16 {%0, %1, %2, %3, %4, %5, %6, %7, %8, %9, %10, %11, %12, %13, %14, %15, %16, %17, %18, %19, %20, %21, %22, %23, %24, %25, %26, %27, %28, %29, %30, %31}, {%32, %33, %34, %35}, %36, 1, 1, 1, 0;\n"
    : "+f"(d[0]), "+f"(d[1]), "+f"(d[2]), "+f"(d[3]), "+f"(d[4]), "+f"(d[5]), "+f"(d[6]), "+f"(d[7]), "+f"(d[8]), "+f"(d[9]), "+f"(d[10]), "+f"(d[11]), "+f"(d[12]), "+f"(d[13]), "+f"(d[14]), "+f"(d[15]), "+f"(d[16]), "+f"(d[17]), "+f"(d[18]), "+f"(d[19]), "+f"(d[20]), "+f"(d[21]), "+f"(d[22]), "+f"(d[23]), "+f"(d[24]), "+f"(d[25]), "+f"(d[26]), "+f"(d[27]), "+f"(d[28]), "+f"(d[29]), "+f"(d[30]), "+f"(d[31])
    : "r"(a0), "r"(a1), "r"(a2), "r"(a3), "l"(db));
  else asm volatile("wgmma.mma_async.sync.aligned.m64n64k16.f32.bf16.bf16 {%0, %1, %2, %3, %4, %5, %6, %7, %8, %9, %10, %11, %12, %13, %14, %15, %16, %17, %18, %19, %20, %21, %22, %23, %24, %25, %26, %27, %28, %29, %30, %31}, {%32, %33, %34, %35}, %36, 0, 1, 1, 0;\n"
    : "=f"(d[0]), "=f"(d[1]), "=f"(d[2]), "=f"(d[3]), "=f"(d[4]), "=f"(d[5]), "=f"(d[6]), "=f"(d[7]), "=f"(d[8]), "=f"(d[9]), "=f"(d[10]), "=f"(d[11]), "=f"(d[12]), "=f"(d[13]), "=f"(d[14]), "=f"(d[15]), "=f"(d[16]), "=f"(d[17]), "=f"(d[18]), "=f"(d[19]), "=f"(d[20]), "=f"(d[21]), "=f"(d[22]), "=f"(d[23]), "=f"(d[24]), "=f"(d[25]), "=f"(d[26]), "=f"(d[27]), "=f"(d[28]), "=f"(d[29]), "=f"(d[30]), "=f"(d[31])
    : "r"(a0), "r"(a1), "r"(a2), "r"(a3), "l"(db));
}
template <int SD> __device__ __forceinline__ void wgmma_rs_n32_tb1(float (&d)[16], uint32_t a0, uint32_t a1, uint32_t a2, uint32_t a3, uint64_t db) {
  if (SD) asm volatile("wgmma.mma_async.sync.aligned.m64n32k16.f32.bf16.bf16 {%0, %1, %2, %3, %4, %5, %6, %7, %8, %9, %10, %11, %12, %13, %14, %15}, {%16, %17, %18, %19}, %20, 1, 1, 1, 1;\n"
    : "+f"(d[0]), "+f"(d[1]), "+f"(d[2]), "+f"(d[3]), "+f"(d[4]), "+f"(d[5]), "+f"(d[6]), "+f"(d[7]), "+f"(d[8]), "+f"(d[9]), "+f"(d[10]), "+f"(d[11]), "+f"(d[12]), "+f"(d[13]), "+f"(d[14]), "+f"(d[15])
    : "r"(a0), "r"(a1), "r"(a2), "r"(a3), "l"(db));
  else asm volatile("wgmma.mma_async.sync.aligned.m64n32k16.f32.bf16.bf16 {%0, %1, %2, %3, %4, %5, %6, %7, %8, %9, %10, %11, %12, %13, %14, %15}, {%16, %17, %18, %19}, %20, 0, 1, 1, 1;\n"
    : "=f"(d[0]), "=f"(d[1]), "=f"(d[2]), "=f"(d[3]), "=f"(d[4]), "=f"(d[5]), "=f"(d[6]), "=f"(d[7]), "=f"(d[8]), "=f"(d[9]), "=f"(d[10]), "=f"(d[11]), "=f"(d[12]), "=f"(d[13]), "=f"(d[14]), "=f"(d[15])
    : "r"(a0), "r"(a1), "r"(a2), "r"(a3), "l"(db));
}

__device__ __forceinline__ uint32_t sw64_off(int row, int d) { return row * 64 + ((((d >> 3) ^ (row >> 1)) & 3) << 4) + (d & 7) * 2; }

__device__ __forceinline__ uint32_t exp2_pair_fma(float t0, float t1, uint32_t c_half, uint32_t c_3) {
  uint32_t y0, y;
  asm("prmt.b32 %0, %1, %2, 0x6521;" : "=r"(y0) : "r"(__float_as_uint(t0)), "r"(__float_as_uint(t1)));
  uint32_t h = lop_and_or(y0, 0x007F007Fu, c_half);
  uint32_t e = lop_and_or(y0, 0xFF80FF80u, c_3);
  asm("fma.rn.bf16x2 %0, %1, %2, %3;" : "=r"(y) : "r"(y0), "r"(h), "r"(e));
  return y;
}

__device__ __forceinline__ void feature_map(float (&v)[16], uint32_t (&ph)[16], int lq) {
  const float L2E = 1.4426950408889634f;
  const bool tail_ok = lq < 2;
  float mx[2], mn[2], b[16], sa[2], sn[2];
#pragma unroll
  for (int r = 0; r < 2; r++) {
    const int o = 2 * r;
    if (!tail_ok) { v[o + 12] = v[o]; v[o + 13] = v[o]; }
    mx[r] = fmaxf(fmaxf(fmaxf(v[o], v[o + 1]), fmaxf(v[o + 4], v[o + 5])), fmaxf(fmaxf(v[o + 8], v[o + 9]), fmaxf(v[o + 12], v[o + 13])));
    mn[r] = fminf(fminf(fminf(v[o], v[o + 1]), fminf(v[o + 4], v[o + 5])), fminf(fminf(v[o + 8], v[o + 9]), fminf(v[o + 12], v[o + 13])));
  }
#pragma unroll
  for (int o = 1; o <= 2; o <<= 1)
#pragma unroll
    for (int r = 0; r < 2; r++) { mx[r] = fmaxf(mx[r], __shfl_xor_sync(~0u, mx[r], o)); mn[r] = fminf(mn[r], __shfl_xor_sync(~0u, mn[r], o)); }
#pragma unroll
  for (int r = 0; r < 2; r++) {
    const int o = 2 * r;
    const float cx = -mx[r] * L2E, cn = mn[r] * L2E;
#pragma unroll
    for (int i = 0; i < 8; i++) {
      const int k = o + 4 * (i >> 1) + (i & 1);
      b[k] = ex2f(fmaf(v[k], -L2E, cn));
      v[k] = ex2f(fmaf(v[k], L2E, cx));
    }
    if (!tail_ok) { v[o + 12] = v[o + 13] = b[o + 12] = b[o + 13] = 0.f; }
    sa[r] = ((v[o] + v[o + 1]) + (v[o + 4] + v[o + 5])) + ((v[o + 8] + v[o + 9]) + (v[o + 12] + v[o + 13]));
    sn[r] = ((b[o] + b[o + 1]) + (b[o + 4] + b[o + 5])) + ((b[o + 8] + b[o + 9]) + (b[o + 12] + b[o + 13]));
  }
#pragma unroll
  for (int o = 1; o <= 2; o <<= 1)
#pragma unroll
    for (int r = 0; r < 2; r++) { sa[r] += __shfl_xor_sync(~0u, sa[r], o); sn[r] += __shfl_xor_sync(~0u, sn[r], o); }
#pragma unroll
  for (int r = 0; r < 2; r++) {
    const float ra = rcpf(sa[r]), rb = rcpf(sn[r]);
#pragma unroll
    for (int jj = 0; jj < 4; jj++) {
      ph[jj * 2 + r] = pack_bf16(v[2 * r + 4 * jj] * ra, v[2 * r + 4 * jj + 1] * ra);
      ph[(4 + jj) * 2 + r] = pack_bf16(b[2 * r + 4 * jj] * rb, b[2 * r + 4 * jj + 1] * rb);
    }
  }
}

__device__ __forceinline__ void store_heads(uint32_t base, const uint32_t (&a)[14], uint32_t pad0, uint32_t pad1, int row0, int lq) {
  const uint32_t rb = base + row0 * 64 + (((row0 >> 1) & 3) << 4);
  const uint32_t b0 = rb + lq * 4;
  const uint32_t b1 = (rb + 8192 + ((lq * 4 + 8) & 15)) ^ ((lq >> 1) << 4);
#pragma unroll
  for (int j = 0; j < 7; j++) {
    uint32_t ad;
    if (j < 3) ad = b0 ^ (j << 4);
    else if (j == 3) ad = (lq < 2) ? (b0 ^ 48u) : (b1 ^ 16u);
    else ad = (lq < 2) ? (b1 ^ ((j - 4) << 4)) : ((b1 ^ 16u) ^ ((j - 3) << 4));
    sts32(ad, a[2 * j]);
    sts32(ad + 512, a[2 * j + 1]);
  }
  sts64((rb ^ 48u) + 8 + (lq & 1) * 8192 + (lq >> 1) * 512, pad0, pad1);
}

struct Params {
  const __nv_bfloat16* w_phi;
  const __nv_bfloat16* wk;
  const __nv_bfloat16* wv;
  const __nv_bfloat16* gate_w;
  __nv_bfloat16* out;
};

__global__ void __launch_bounds__(NTHREADS, 1)
fused_kernel(const __grid_constant__ CUtensorMap tm_x, const __grid_constant__ CUtensorMap tm_wqkv,
             const __grid_constant__ CUtensorMap tm_wq, const __grid_constant__ CUtensorMap tm_woa,
             const __grid_constant__ CUtensorMap tm_wob, const Params prm) {
  extern __shared__ uint8_t smem_raw[];
  uint32_t sb = (smem_u32(smem_raw) + 1023u) & ~1023u;
  uint8_t* sgen = smem_raw + (sb - smem_u32(smem_raw));
  asm volatile("mov.u32 %0, %0;" : "+r"(sb));
  const int tid = threadIdx.x, lane = tid & 31;
  const int warp = __shfl_sync(~0u, tid >> 5, 0), wg = warp >> 2;
  const int pt = blockIdx.x >> 3, hp = blockIdx.x & 7;
  const uint32_t bars = sb + OFF_BAR;
  auto BAR = [&](int i) { return bars + 8u * i; };
  const unsigned epoch = g_epoch & 1;

  if (tid == 0) { PROF_MARK(0); PROF_CLK(30); PROF2(15); }
  auto load_proj = [&](int c, int g) {
    mbar_expect_tx(BAR(B_FULL + g), c == 0 ? 49152 : c < 4 ? 65536 : 32768);
    if (c < 4) tma_2d(sb + OFF_X + (2 * c - (c > 0)) * 16384, &tm_x, (2 * c - (c > 0)) * 64, pt * 128, BAR(B_FULL + g));
    tma_2d(sb + OFF_RING + g * 32768, &tm_wq, hp * 56, c * 64, BAR(B_FULL + g));
#pragma unroll 1
    for (int j = 0; j < 3; j++) tma_2d(sb + OFF_RING + g * 32768 + 8192 + j * 8192, &tm_wqkv, j * DM + hp * 56, c * 64, BAR(B_FULL + g));
    if (c > 0 && c < 4) tma_2d(sb + OFF_X + 2 * c * 16384, &tm_x, 2 * c * 64, pt * 128, BAR(B_FULL + g));
  };
  if (elect_one()) {
    const int i = warp == 16 ? 0 : (warp == 0 ? 16 : warp);
    if (i < B_N) {
      int cnt = (i >= B_EMPTY && i < B_WO) || i > B_SIG || i == B_X0FREE || i == B_X1FREE ? 16 : 1;
      if (i == B_BUILD) cnt = 512;
      if (i == B_SIG || i == B_QSQ) cnt = 8;
      mbar_init(BAR(i), cnt);
      fence_async_smem();
    }
    if (warp == 16) load_proj(0, 0);
  }
  __syncthreads();
  if (tid == 0) PROF2(14);

  if (wg == 4) {
    asm volatile("setmaxnreg.dec.sync.aligned.u32 32;");
    if (warp == 16) {
      if (elect_one()) {
        int g = 1, nkv = 8;
        uint32_t par = 1;
#pragma unroll 1
        for (int n = 1; n < 14 + nkv; n++) {
          if (n == 7) { PROF_MARK(20); cnt_wait(C_KV, NCTA); PROF_MARK(21); fence_async_all(); }
          if (n == 15) {
            mbar_wait(BAR(B_SLOW), 0);
            if (*(volatile int*)(sgen + OFF_RED)) nkv = 26;
          }
          const int j = n - 7 - nkv;
          if (j == 0 || j == 3) {
            PROF3(j ? 11 : 8);
            cnt_wait((j ? C_OB : C_OA) + pt, 8);
            PROF3(j ? 12 : 9);
            PROF_MARK(26);
            fence_async_all();
          }
          mbar_wait(BAR(B_EMPTY + g), par);
          if (n < 7) load_proj(n, g);
          else {
            mbar_expect_tx(BAR(B_FULL + g), 32768);
            bulk_g2s(sb + OFF_RING + g * 32768, j < 0 ? g_kv_img + ((n - 7) & 7) * 32768 : g_o_img + (size_t)(pt * 7 + j) * 32768, 32768,
                     BAR(B_FULL + g));
          }
          if (++g == 3) { g = 0; par ^= 1; }
        }
        if (atomicAdd(&g_cnt[C_DONE * 32], 1u) == NCTA - 1) {
#pragma unroll 1
          for (int i = 0; i < C_N; i++) g_cnt[i * 32] = 0;
          g_epoch = epoch ^ 1;
        }
      }
    } else {
      if (warp == 18) {
        if (elect_one()) {
#pragma unroll 1
          for (int i = 0; i < 4; i++) {
            mbar_wait(BAR(B_SIG + i), 0);
            PROF3(2 * i);
            cnt_arrive(i == 0 ? C_KV : i == 1 ? C_PART : (i == 2 ? C_OA : C_OB) + pt);
            PROF3(2 * i + 1);
            if (i == 1 || i == 2) {
              mbar_wait(BAR(B_X0FREE + i - 1), 0);
              mbar_expect_tx(BAR(B_WO + i - 1), 57344);
#pragma unroll 1
              for (int c = 0; c < 7; c++)
                tma_2d(sb + OFF_WO + (i - 1) * 57344 + c * 8192, i == 1 ? &tm_woa : &tm_wob, hp * 56, c * 64, BAR(B_WO + i - 1));
            }
          }
        }
      } else if (warp == 19) {
        if (lane == 0) {
          mbar_wait(BAR(B_SIG + 0), 0);
          cnt_wait(C_KV, NCTA);
        }
        __syncwarp();
        float ksq = 0.f, vsq = 0.f;
#pragma unroll
        for (int sl = 0; sl < 4; sl++) {
          float4 a = ldcg_f4(g_ksq + sl * 128 + lane * 4), b = ldcg_f4(g_vsq + sl * 128 + lane * 4);
          float m = fmaxf(fmaxf(a.x, a.y), fmaxf(a.z, a.w));
          m = __uint_as_float(__reduce_max_sync(~0u, __float_as_uint(m)));
          ksq += m;
          vsq = fmaxf(vsq, fmaxf(fmaxf(b.x, b.y), fmaxf(b.z, b.w)));
        }
        mbar_wait(BAR(B_QSQ), 0);
        const float4 qa4 = ((const float4*)(sgen + OFF_QSQ))[lane], qb4 = ((const float4*)(sgen + OFF_QSQ))[32 + lane];
        const float qmax = fmaxf(fmaxf(fmaxf(qa4.x, qa4.y), fmaxf(qa4.z, qa4.w)), fmaxf(fmaxf(qb4.x, qb4.y), fmaxf(qb4.z, qb4.w)));
        const bool slow = __any_sync(~0u, !(qmax * ksq <= 98.f * 98.f) || !(vsq <= 2.0e8f));
        if (lane == 0) {
          *(volatile int*)(sgen + OFF_RED) = slow;
          mbar_arrive(BAR(B_SLOW), 1);
        }
      } else {
        float4* z = (float4*)(g_kvacc[epoch ^ 1] + blockIdx.x * 256) + lane;
        z[0] = make_float4(0.f, 0.f, 0.f, 0.f);
        z[32] = make_float4(0.f, 0.f, 0.f, 0.f);
        if (lane == 0) {
          mbar_wait(BAR(B_SIG + 1), 0);
          cnt_wait(C_PART, NCTA);
          PROF_MARK(23);
        }
        __syncwarp();
        const float* src = g_kvacc[epoch] + hp * 4096 + lane * 8;
#pragma unroll 2
        for (int i = 0; i < 16; i++) {
          const float4 a = ldcg_f4(src + i * 256), b = ldcg_f4(src + i * 256 + 4);
          sts128(sb + OFF_KVR + sw64_off(i * 8 + (lane >> 2), (lane & 3) * 8),
                 make_uint4(pack_bf16(a.x, a.y), pack_bf16(a.z, a.w), pack_bf16(b.x, b.y), pack_bf16(b.z, b.w)));
        }
        ((float4*)(sgen + OFF_GATE))[lane] = ldcg_f4(g_gate + pt * 128 + lane * 4);
        fence_async_smem();
        __syncwarp();
        if (lane == 0) mbar_arrive(BAR(B_KVR), 1);
      }
    }
  } else {
    asm volatile("setmaxnreg.inc.sync.aligned.u32 112;");
    const int mh = wg & 1, nh = wg >> 1, wq = warp & 3;
    float acc0[28], acc1[28];
#pragma unroll
    for (int i = 0; i < 28; i++) acc0[i] = acc1[i] = 0.f;
    int slot = 0, prev = 0;
    uint32_t par = 0;

    if (tid < DM) {
      const __nv_bfloat16* src = (hp < 4 ? prm.wk : prm.wv) + tid * DH + (hp & 3) * 8;
      cp_async8(sb + OFF_SLC + tid * 16, src);
      if ((hp & 3) != 3) cp_async8(sb + OFF_SLC + tid * 16 + 8, src + 4);
      if (tid < 392) {
        const int row = tid / 7, e = row >= DH;
        cp_async8(sb + OFF_WPH + e * 2048 + sw64_off(row - DH * e, (tid % 7) * 4), prm.w_phi + 2 * hp * DH * DH + tid * 4);
      } else {
        const int row = tid - 392, e = row >= DH;
        sts64(sb + OFF_WPH + e * 2048 + sw64_off(row - DH * e, 28), 0u, 0u);
      }
      if ((hp & 3) == 3) sts64(sb + OFF_SLC + tid * 16 + 8, hp == 3 ? (uint32_t)((const unsigned short*)prm.gate_w)[tid] : 0u, 0u);
    } else if (tid < DM + 32) {
      sts128(sb + OFF_WPH + ((tid - DM) >> 4) * 2048 + 28 * 64 + ((tid - DM) & 15) * 16, make_uint4(0, 0, 0, 0));
    }
    asm volatile("cp.async.mbarrier.arrive.noinc.shared::cta.b64 [%0];" ::"r"(BAR(B_BUILD)) : "memory");
#pragma unroll 1
    for (int stage = 0; stage < 2; stage++) {
      {
        const uint64_t dS = make_desc(stage ? sb + OFF_WO : sb + OFF_X + mh * 8192, 1024, 1024, 1);
        const uint64_t dR = make_desc(sb + OFF_RING + (stage ? mh * 8192 : nh * 16384), 1024, 1024, 1);
#pragma unroll 1
        for (int c = 0; c < 7; c++) {
          if (stage) mbar_wait(BAR(B_WO + (c >= 3)), 0);
          mbar_wait(BAR(B_FULL + slot), par);
          const uint64_t ds = dS + c * 1024, dr = dR + slot * 2048;
          const uint64_t dA0 = stage ? dr : ds, dA1 = stage ? dr + 1024 : ds, dB0 = stage ? ds : dr, dB1 = dB0 + 512;
          wg_fence();
#pragma unroll
          for (int ks = 0; ks < 4; ks++) {
            wgmma_ss_n56_ta0_tb1<1>(acc0, dA0 + ks * 2, dB0 + ks * 128);
            wgmma_ss_n56_ta0_tb1<1>(acc1, dA1 + ks * 2, dB1 + ks * 128);
          }
          wg_commit();
          if (stage == 0 || c < 4) {
            wg_wait<0>();
            if (lane == 0) mbar_arrive(BAR(B_EMPTY + slot), 1 + stage);
          }
          if (++slot == 3) { slot = 0; par ^= 1; }
          if (nh == 1 && c == 3) {
            float accs[4];
            mbar_wait(BAR(B_BUILD), 0);
            fence_async_smem();
            const uint64_t dSlc = make_desc(sb + OFF_SLC, 128, 128, 0);
            wg_fence();
            wgmma_ss_n8_ta0_tb1<0>(accs, dS, dSlc);
#pragma unroll
            for (int kk = 1; kk < 28; kk++) wgmma_ss_n8_ta0_tb1<1>(accs, dS + (kk >> 2) * 1024 + (kk & 3) * 2, dSlc + kk * 16);
            wg_commit();
            int lane_;
            asm volatile("mov.u32 %0, %%laneid;" : "=r"(lane_));
            const int lq = lane_ & 3, row0 = mh * 64 + wq * 16 + (lane_ >> 2);
            wg_wait<0>();
            fence_regs(accs);
            if (tid == 256) PROF_MARK(3);
            const int sl = hp & 3;
            const bool isk = hp < 4, real = (sl < 3) || (lq < 2);
            const int pos = pt * 128 + row0, kr = pos & 63;
            uint8_t* dst = g_kv_img + (pos >> 6) * 8192 + (isk ? 0 : 4096) + sw64_off(kr, sl * 8 + 2 * lq);
            const uint32_t pat = isk ? POLY_PAT >> (kr >> 3) : 0u;
            float mxv = 0.f;
  #pragma unroll
            for (int rr = 0; rr < 2; rr++) {
              const float v0 = accs[2 * rr], v1 = accs[2 * rr + 1];
              const bool poly = (pat >> rr) & 1;
              const float sc = poly ? 2.f : 1.f;
              const float s2 = quad_sum(real ? v0 * v0 + v1 * v1 : 0.f);
              mxv = fmaxf(mxv, s2 <= 3.0e38f ? s2 : __int_as_float(0x7f800000));
              const uint32_t padv = lq == 2 ? (poly ? 0x443F4000u : 0x00003F80u) : (poly ? 0x3AB03F4Du : 0u);
              *(uint32_t*)(dst + rr * 512) = real ? pack_bf16(sc * v0, sc * v1) : padv;
              if (hp == 3 && lq == 2) g_gate[pos + 8 * rr] = rcpf(1.f + ex2f(-1.4426950408889634f * v0));
            }
            mxv = __uint_as_float(__reduce_max_sync(~0u, __float_as_uint(mxv)));
            if (lane == 0) (isk ? g_ksq : g_vsq)[sl * 128 + pt * 8 + mh * 4 + wq] = mxv;
            __syncwarp();
            if (lane == 0) mbar_arrive(BAR(B_SIG + 0), 1);
            if (tid == 256) PROF_MARK(5);
          }
        }
        wg_wait<0>();
        fence_regs(acc0); fence_regs(acc1);
      }
      if (stage) break;
      int lane_;
      asm volatile("mov.u32 %0, %%laneid;" : "=r"(lane_));
      const int lq = lane_ & 3;
      const int rowl = wq * 16 + (lane_ >> 2);
      const int row0 = mh * 64 + rowl;
      {
        if (tid == 0) PROF_MARK(2);
        if (nh == 0) {
          float sq[4] = {0.f, 0.f, 0.f, 0.f};
#pragma unroll
          for (int i = 0; i < 28; i++) acc0[i] *= 0.18898223650461362f * 1.4426950408889634f;
#pragma unroll
          for (int j = 0; j < 7; j++) {
#pragma unroll
            for (int rr = 0; rr < 2; rr++) {
              const float s2 = acc0[4 * j + 2 * rr] * acc0[4 * j + 2 * rr] + acc0[4 * j + 2 * rr + 1] * acc0[4 * j + 2 * rr + 1];
              if (j < 3) sq[rr] += s2;
              else if (j > 3) sq[2 + rr] += s2;
              else { sq[rr] += (lq < 2) ? s2 : 0.f; sq[2 + rr] += (lq < 2) ? 0.f : s2; }
            }
          }
#pragma unroll
          for (int i = 0; i < 4; i++) sq[i] = quad_sum(sq[i]);
          const float mine = lq == 0 ? sq[0] : lq == 1 ? sq[1] : lq == 2 ? sq[2] : sq[3];
          ((float*)(sgen + OFF_QSQ))[(mh + (lq & 2)) * 64 + rowl + 8 * (lq & 1)] = mine <= 3.0e38f ? mine : __int_as_float(0x7f800000);
          __syncwarp();
          if (lane == 0) mbar_arrive(BAR(B_QSQ), 1);
        }
      }
      if (tid == 0) PROF_MARK(4);
      {
        uint32_t h0[14], h1[14];
#pragma unroll
        for (int i = 0; i < 14; i++) { h0[i] = pack_bf16(acc0[2 * i], acc0[2 * i + 1]); h1[i] = pack_bf16(acc1[2 * i], acc1[2 * i + 1]); }
        bar_sync(1, 512);
        if (tid == 0) PROF_MARK(6);
#pragma unroll 1
        for (int r = 0; r < 2; r++) {
          store_heads(sb + (r ? (nh ? OFF_VA : OFF_QA) : (nh ? OFF_KA : OFF_QP)), h0,
                      (r & nh) ? 0x00003F80u : (r | nh) ? 0u : 0x3F800000u, (r | nh) ? 0u : 0x3F803F80u, row0, lq);
#pragma unroll
          for (int i = 0; i < 14; i++) h0[i] = h1[i];
        }
      }
      fence_async_smem();
      bar_sync(1, 512);
      if (tid == 0) PROF_MARK(7);

      const uint64_t dK = make_desc(sb + OFF_RING, 512, 512, 2);
      const uint64_t dhi = dK & 0xffffffff00000000ull;
      const uint32_t dlo0 = (uint32_t)dK;
      uint32_t ok = 0, q[8];
      float o[16];
#pragma unroll
      for (int i = 0; i < 16; i++) o[i] = 0.f;
      {
        const uint32_t qa = sb + OFF_QP + nh * 8192;
        const int r = mh * 64 + wq * 16 + (lane_ & 7) + ((lane_ >> 3) & 1) * 8;
#pragma unroll
        for (int ks = 0; ks < 2; ks++)
          asm volatile("ldmatrix.sync.aligned.m8n8.x4.shared.b16 {%0, %1, %2, %3}, [%4];"
                       : "=r"(q[4 * ks]), "=r"(q[4 * ks + 1]), "=r"(q[4 * ks + 2]), "=r"(q[4 * ks + 3])
                       : "r"(qa + sw64_off(r, ks * 16 + (lane_ >> 4) * 8)) : "memory");
      }
      const int kb = KB_AT, qb = QB_AT;
#pragma unroll 1
      for (int it = 0; it <= 8; it++) {
        uint32_t p[16];
        if ((tid & 127) == 0) PROF4(wg * 32 + it * 3);
        if (it == kb || it == qb || it == 8) {
          float t[16];
          wg_wait<0>();
          fence_regs(o);
          if (it < 8) {
            if (tid == 0) PROF_MARK(it == kb ? 27 : 11);
            const uint64_t dA = make_desc(sb + (it == kb ? OFF_KA : OFF_QA) + nh * 8192 + mh * 4096, 512, 512, 2);
            const uint64_t dB = make_desc(sb + OFF_WPH + nh * 2048, 512, 512, 2);
            if (tid == 0 && it == qb) PROF2(32);
            float pa[16];
            wg_fence();
            wgmma_ss_n32_ta0_tb1<0>(pa, dA, dB);
            wgmma_ss_n32_ta0_tb1<1>(pa, dA + 2, dB + 64);
            wg_commit();
            if (tid == 0 && it == qb) PROF2(33);
            wg_wait<0>();
            fence_regs(pa);
            if (tid == 0 && it == qb) PROF2(34);
            uint32_t ph[16];
            feature_map(pa, ph, lq);
            if (tid == 0 && it == qb) PROF2(35);
            const uint32_t rb = sb + OFF_PHI + wg * 8192 + rowl * 128 + lq * 4 + ((rowl & 7) << 4);
#pragma unroll
            for (int ch = 0; ch < 8; ch++) { sts32(rb ^ (ch << 4), ph[2 * ch]); sts32((rb ^ (ch << 4)) + 1024, ph[2 * ch + 1]); }
            if (tid == 0 && it == qb) PROF2(36);
            fence_async_smem();
            if (tid == 0 && it == qb) PROF2(37);
            bar_sync(4 + wg, 128);
            if (tid == 0 && it == qb) PROF2(38);
            const uint64_t dP = make_desc(sb + OFF_PHI + wg * 8192, 1024, 1024, 1);
            if (it == kb) {
              const uint64_t dV = make_desc(sb + OFF_VA + nh * 8192 + mh * 4096, 512, 512, 2);
              float kv[16];
              wg_fence();
              wgmma_ss_n32_ta1_tb1<0>(kv, dP, dV);
#pragma unroll
              for (int ks = 1; ks < 4; ks++) wgmma_ss_n32_ta1_tb1<1>(kv, dP + ks * 128, dV + ks * 64);
              wg_commit();
              wg_wait<0>();
              fence_regs(kv);
              float* dst = g_kvacc[epoch] + (2 * hp + nh) * 2048 + rowl * 32 + 2 * lq;
#pragma unroll
              for (int j = 0; j < 8; j++)
                asm volatile("red.global.add.v2.f32 [%0], {%1, %2};" ::"l"(dst + 8 * (j >> 1) + 256 * (j & 1)), "f"(kv[2 * j]), "f"(kv[2 * j + 1]) : "memory");
              __syncwarp();
              if (lane == 0) { mbar_arrive(BAR(B_SIG + 1), 1); mbar_arrive(BAR(B_X0FREE), 1); }
              if (tid == 0) PROF_MARK(28);
              goto after_block;
            } else {
              mbar_wait(BAR(B_KVR), 0);
              const uint64_t dR = make_desc(sb + OFF_KVR + nh * 4096, 512, 512, 2);
              wg_fence();
              wgmma_ss_n32_ta0_tb1<0>(t, dP, dR);
#pragma unroll
              for (int ks = 1; ks < 4; ks++) wgmma_ss_n32_ta0_tb1<1>(t, dP + ks * 2, dR + ks * 64);
              wg_commit();
              wg_wait<0>();
              fence_regs(t);
              if (lane == 0) mbar_arrive(BAR(B_X1FREE), 1);
            if (tid == 0 && it == qb) PROF2(39);
            }
          } else {
            if (lane == 0) mbar_arrive(BAR(B_EMPTY + prev), 1);
            if (tid == 0) PROF_MARK(13);
            mbar_wait(BAR(B_SLOW), 0);
            if (__builtin_expect(__any_sync(~0u, *(volatile int*)(sgen + OFF_RED)), 0)) {
              uint32_t qz[8];
#pragma unroll
              for (int i = 0; i < 8; i++) qz[i] = (i >= 6 && lq >= 2) ? 0u : q[i];
              float m0 = -3.0e38f, m1 = -3.0e38f, o2[16];
              int sl2 = slot;
              uint32_t par2 = par;
#pragma unroll 1
              for (int j64 = 0; j64 < 32; j64++) {
                float s[32];
                mbar_wait(BAR(B_FULL + sl2), par2);
                const uint32_t lo = dlo0 + sl2 * 2048 + (j64 & 3) * 512;
                wg_fence();
                wgmma_rs_n64_tb0<0>(s, qz[0], qz[1], qz[2], qz[3], dhi | lo);
                wgmma_rs_n64_tb0<1>(s, qz[4], qz[5], qz[6], qz[7], dhi | (lo + 2));
                wg_commit();
                wg_wait<0>();
                fence_regs(s);
#pragma unroll
                for (int j = 0; j < 8; j++) {
                  const float sc = ((POLY_PAT >> j) & 1) ? 0.5f : 1.f;
                  m0 = fmaxf(m0, fmaxf(s[4 * j], s[4 * j + 1]) * sc);
                  m1 = fmaxf(m1, fmaxf(s[4 * j + 2], s[4 * j + 3]) * sc);
                }
                if ((j64 & 3) == 3) {
                  if (lane == 0) mbar_arrive(BAR(B_EMPTY + sl2), 1);
                  if (++sl2 == 3) { sl2 = 0; par2 ^= 1; }
                }
              }
              m0 = quad_max(m0); m1 = quad_max(m1);
#pragma unroll
              for (int i = 0; i < 16; i++) o2[i] = 0.f;
#pragma unroll 1
              for (int j64 = 0; j64 < 32; j64++) {
                float s[32];
                mbar_wait(BAR(B_FULL + sl2), par2);
                const uint32_t lo = dlo0 + sl2 * 2048 + (j64 & 3) * 512;
                wg_fence();
                wgmma_rs_n64_tb0<0>(s, qz[0], qz[1], qz[2], qz[3], dhi | lo);
                wgmma_rs_n64_tb0<1>(s, qz[4], qz[5], qz[6], qz[7], dhi | (lo + 2));
                wg_commit();
                wg_wait<0>();
                fence_regs(s);
                uint32_t ps[16];
#pragma unroll
                for (int j = 0; j < 8; j++) {
                  const float sc = ((POLY_PAT >> j) & 1) ? 0.5f : 1.f;
                  ps[2 * j] = pack_bf16(ex2f(fmaf(s[4 * j], sc, -m0)), ex2f(fmaf(s[4 * j + 1], sc, -m0)));
                  ps[2 * j + 1] = pack_bf16(ex2f(fmaf(s[4 * j + 2], sc, -m1)), ex2f(fmaf(s[4 * j + 3], sc, -m1)));
                }
                wg_fence();
#pragma unroll
                for (int ks = 0; ks < 4; ks++)
                  wgmma_rs_n32_tb1<1>(o2, ps[4 * ks], ps[4 * ks + 1], ps[4 * ks + 2], ps[4 * ks + 3], dhi | (lo + 256 + ks * 64));
                wg_commit();
                wg_wait<0>();
                fence_regs(o2);
                if ((j64 & 3) == 3) {
                  if (lane == 0) mbar_arrive(BAR(B_EMPTY + sl2), 1);
                  if (++sl2 == 3) { sl2 = 0; par2 ^= 1; }
                }
              }
#pragma unroll 1
              for (int j = 0; j < 2; j++) {
                mbar_wait(BAR(B_FULL + sl2), par2);
                __syncwarp();
                if (lane == 0) mbar_arrive(BAR(B_EMPTY + sl2), 1);
                if (++sl2 == 3) { sl2 = 0; par2 ^= 1; }
              }
#pragma unroll
              for (int i = 0; i < 16; i++) o[i] = o2[i];
            }
#pragma unroll
            for (int i = 0; i < 16; i++) t[i] = o[i];
          }
          {
            const int br = it == 8;
            const float eps = br ? 0.f : 1e-6f;
            const float g0 = ((const float*)(sgen + OFF_GATE))[row0], g1 = ((const float*)(sgen + OFF_GATE))[row0 + 8];
            const float d0 = __shfl_sync(~0u, t[12], (lane_ & ~3) | 2), d1 = __shfl_sync(~0u, t[14], (lane_ & ~3) | 2);
            const float r0 = __fdividef(br ? 1.f - g0 : g0, d0 + eps), r1 = __fdividef(br ? 1.f - g1 : g1, d1 + eps);
            uint8_t* img = g_o_img + (size_t)((pt * 2 + br) * 14 + mh) * 8192 + rowl * 128;
            const int col0 = (2 * hp + nh) * DH + 2 * lq;
#pragma unroll
            for (int j = 0; j < 4; j++) {
              const int col = col0 + 8 * j;
              uint8_t* gp = img + (col >> 6) * 16384 + ((((col >> 3) ^ rowl) & 7) << 4) + (col & 7) * 2;
              const uint32_t v0 = pack_bf16(t[4 * j] * r0, t[4 * j + 1] * r0), v1 = pack_bf16(t[4 * j + 2] * r1, t[4 * j + 3] * r1);
              if (j < 3 || lq < 2) { *(uint32_t*)gp = v0; *(uint32_t*)(gp + 1024) = v1; }
            }
            __syncwarp();
            if (lane == 0) mbar_arrive(BAR(B_SIG + 2 + br), 1);
            if (tid == 0) PROF_MARK(12 + 2 * br);
            if (tid == 0 && it == qb) PROF2(40);
            if (br) break;
          }
        }
      after_block:
        if (it == 0 && tid == 0) PROF_MARK(10);
        const uint32_t lo = dlo0 + slot * 2048;
        if ((tid & 127) == 0) PROF4(wg * 32 + it * 3 + 1);
        if (!ok) mbar_wait(BAR(B_FULL + slot), par);
        if ((tid & 127) == 0) PROF4(wg * 32 + it * 3 + 2);
        int nslot = slot + 1;
        uint32_t npar = par;
        if (nslot == 3) { nslot = 0; npar ^= 1; }
        {
          float s[32];
          wg_fence();
          wgmma_rs_n64_tb0<0>(s, q[0], q[1], q[2], q[3], dhi | lo);
          wgmma_rs_n64_tb0<1>(s, q[4], q[5], q[6], q[7], dhi | (lo + 2));
          wg_commit();
#pragma unroll
          for (int u = 0; u < 4; u++) {
            wg_wait<0>();
            fence_regs(s);
            if (u == 0 && lane == 0 && it > 0) mbar_arrive(BAR(B_EMPTY + prev), 1);
            if (u == 2) ok = mbar_test(BAR(B_FULL + nslot), npar);
#pragma unroll
            for (int j = 0; j < 8; j++) {
              if ((POLY_PAT >> j) & 1) {
                p[2 * j] = exp2_pair_fma(s[4 * j], s[4 * j + 1], 0x3F003F00u, 0x00030003u);
                p[2 * j + 1] = exp2_pair_fma(s[4 * j + 2], s[4 * j + 3], 0x3F003F00u, 0x00030003u);
              } else {
                p[2 * j] = pack_bf16(ex2f(s[4 * j]), ex2f(s[4 * j + 1]));
                p[2 * j + 1] = pack_bf16(ex2f(s[4 * j + 2]), ex2f(s[4 * j + 3]));
              }
            }
            wg_fence();
#pragma unroll
            for (int ks = 0; ks < 4; ks++)
              wgmma_rs_n32_tb1<1>(o, p[4 * ks], p[4 * ks + 1], p[4 * ks + 2], p[4 * ks + 3], dhi | (lo + u * 512 + 256 + ks * 64));
            if (u < 3) {
              wgmma_rs_n64_tb0<0>(s, q[0], q[1], q[2], q[3], dhi | (lo + (u + 1) * 512));
              wgmma_rs_n64_tb0<1>(s, q[4], q[5], q[6], q[7], dhi | (lo + (u + 1) * 512 + 2));
            }
            wg_commit();
          }
        }
        prev = slot; slot = nslot; par = npar;
      }
      wg_wait<0>();
      if (nh == 1) return;
#pragma unroll
      for (int i = 0; i < 28; i++) acc0[i] = acc1[i] = 0.f;
    }
    if (tid == 0) PROF_MARK(17);
    __nv_bfloat16* op = prm.out + (size_t)(pt * 128 + mh * 64 + wq * 16 + (lane >> 2)) * DM + hp * 56 + 2 * (lane & 3);
#pragma unroll
    for (int j = 0; j < 7; j++) {
      *(uint32_t*)(op + 8 * j) = pack_bf16(acc0[4 * j] + acc1[4 * j], acc0[4 * j + 1] + acc1[4 * j + 1]);
      *(uint32_t*)(op + 8 * DM + 8 * j) = pack_bf16(acc0[4 * j + 2] + acc1[4 * j + 2], acc0[4 * j + 3] + acc1[4 * j + 3]);
    }
    if (tid == 0) { PROF_MARK(18); PROF_CLK(31); }
  }
}

typedef CUresult (*EncodeFn)(CUtensorMap*, CUtensorMapDataType, cuuint32_t, void*, const cuuint64_t*, const cuuint64_t*,
                             const cuuint32_t*, const cuuint32_t*, CUtensorMapInterleave, CUtensorMapSwizzle,
                             CUtensorMapL2promotion, CUtensorMapFloatOOBfill);

void make_map(EncodeFn enc, CUtensorMap* tm, const void* ptr, uint64_t cols, uint64_t rows, uint32_t box_rows) {
  cuuint64_t dims[2] = {cols, rows};
  cuuint64_t strides[1] = {cols * 2};
  cuuint32_t box[2] = {64, box_rows};
  cuuint32_t es[2] = {1, 1};
  enc(tm, CU_TENSOR_MAP_DATA_TYPE_BFLOAT16, 2, const_cast<void*>(ptr), dims, strides, box, es, CU_TENSOR_MAP_INTERLEAVE_NONE,
      CU_TENSOR_MAP_SWIZZLE_128B, CU_TENSOR_MAP_L2_PROMOTION_L2_128B, CU_TENSOR_MAP_FLOAT_OOB_FILL_NONE);
}

}

extern "C" void kernel_launch(void* const* d_in, const int* in_sizes, int n_in, void* d_out, int out_size) {
  (void)in_sizes; (void)n_in; (void)out_size;
  static EncodeFn enc = nullptr;
  if (!enc) {
    void* fn = nullptr;
    cudaDriverEntryPointQueryResult qr;
    cudaGetDriverEntryPoint("cuTensorMapEncodeTiled", &fn, cudaEnableDefault, &qr);
    enc = (EncodeFn)fn;
    cudaFuncSetAttribute(fused_kernel, cudaFuncAttributeMaxDynamicSharedMemorySize, SMEM_BYTES);
  }
  CUtensorMap tm_x, tm_wqkv, tm_wq, tm_woa, tm_wob;
  make_map(enc, &tm_x, d_in[0], DM, S_LEN, 128);
  make_map(enc, &tm_wqkv, d_in[1], 3 * DM, DM, 64);
  make_map(enc, &tm_wq, d_in[5], DM, DM, 64);
  make_map(enc, &tm_woa, d_in[3], DM, DM, 64);
  make_map(enc, &tm_wob, d_in[8], DM, DM, 64);
  Params prm;
  prm.w_phi = (const __nv_bfloat16*)d_in[2];
  prm.wk = (const __nv_bfloat16*)d_in[6];
  prm.wv = (const __nv_bfloat16*)d_in[7];
  prm.gate_w = (const __nv_bfloat16*)d_in[9];
  prm.out = (__nv_bfloat16*)d_out;
  fused_kernel<<<NCTA, NTHREADS, SMEM_BYTES>>>(tm_x, tm_wqkv, tm_wq, tm_woa, tm_wob, prm);
}
```

```cpp
#include <cuda_runtime.h>
#include <cuda_bf16.h>
#include <cuda.h>
#include <stdint.h>

namespace {

constexpr int S_LEN = 2048, DM = 448, DH = 28;
constexpr int NCTA = 128;
constexpr int NTHREADS = 640;
constexpr uint32_t POLY_PAT = 0x57;

#define QB_AT (3 + wg)

constexpr int OFF_X = 0;
constexpr int OFF_KA = 0;
constexpr int OFF_VA = 16384;
constexpr int OFF_QP = 32768;
constexpr int OFF_QA = 57344;
constexpr int OFF_KVR = 73728;
constexpr int OFF_PHI = 81920;
constexpr int OFF_WO = 0;
constexpr int OFF_RING = 114688;
constexpr int OFF_WPH = 212992;
constexpr int OFF_SLC = 217088;
constexpr int OFF_QSQ = 224256;
constexpr int OFF_GATE = 225280;
constexpr int OFF_RED = 225792;
constexpr int OFF_BAR = 225856;
constexpr int SMEM_BYTES = 226368 + 1024;

constexpr int B_FULL = 0, B_EMPTY = 3, B_WO = 6  , B_KVR = 8, B_X0FREE = 9, B_X1FREE = 10, B_QSQ = 11, B_SLOW = 12,
              B_BUILD = 13, B_SIG = 14  , B_N = 18;

constexpr int C_KV = 0, C_PART = 1, C_DONE = 3, C_OA = 4, C_OB = 20, C_N = 36;

__device__ __align__(1024) uint8_t g_kv_img[32 * 8192];
__device__ __align__(16) float g_ksq[512];
__device__ __align__(16) float g_vsq[512];
__device__ __align__(16) float g_gate[S_LEN];
__device__ __align__(1024) float g_kvacc[2][16 * 64 * 32];
__device__ unsigned g_epoch;
__device__ __align__(1024) uint8_t g_o_img[2 * 16 * 14 * 8192];
__device__ unsigned g_cnt[C_N * 32];

#define PROF4(i) do { } while (0)
#define PROF3(i) do { } while (0)
#define PROF2(i) do { } while (0)
#define PROF_CLK(i) do { } while (0)
#define PROF_MARK(i) do { } while (0)
__device__ __forceinline__ uint32_t smem_u32(const void* p) { return (uint32_t)__cvta_generic_to_shared(p); }
__device__ __forceinline__ void mbar_init(uint32_t a, int cnt) {
  asm volatile("mbarrier.init.shared::cta.b64 [%0], %1;" ::"r"(a), "r"(cnt) : "memory");
}
__device__ __forceinline__ void mbar_expect_tx(uint32_t a, uint32_t bytes) {
  asm volatile("mbarrier.arrive.expect_tx.shared::cta.b64 _, [%0], %1;" ::"r"(a), "r"(bytes) : "memory");
}
__device__ __forceinline__ void mbar_arrive(uint32_t a, uint32_t cnt) {
  asm volatile("mbarrier.arrive.shared::cta.b64 _, [%0], %1;" ::"r"(a), "r"(cnt) : "memory");
}
__device__ __forceinline__ void mbar_wait(uint32_t a, uint32_t parity) {
  asm volatile(
      "{\n.reg .pred p;\n.reg .u32 c;\nmov.u32 c, 0;\n"
      "W_%=:\nmbarrier.try_wait.parity.shared::cta.b64 p, [%0], %1;\n"
      "add.u32 c, c, 1;\nsetp.lt.and.u32 p, c, 0x40000, !p;\n@p bra W_%=;\n}"
      ::"r"(a), "r"(parity) : "memory");
}
__device__ __forceinline__ uint32_t mbar_test(uint32_t a, uint32_t parity) {
  uint32_t ok;
  asm volatile("{\n.reg .pred p;\nmbarrier.test_wait.parity.shared::cta.b64 p, [%1], %2;\nselp.u32 %0, 1, 0, p;\n}"
               : "=r"(ok) : "r"(a), "r"(parity) : "memory");
  return ok;
}
__device__ __forceinline__ bool elect_one() {
  uint32_t r;
  asm volatile("{\n.reg .pred p;\nelect.sync _|p, 0xffffffff;\nselp.u32 %0, 1, 0, p;\n}" : "=r"(r));
  return r != 0;
}
__device__ __forceinline__ void tma_2d(uint32_t dst, const CUtensorMap* tm, int c0, int c1, uint32_t bar) {
  asm volatile("cp.async.bulk.tensor.2d.shared::cluster.global.mbarrier::complete_tx::bytes [%0], [%1, {%3, %4}], [%2];"
               ::"r"(dst), "l"(tm), "r"(bar), "r"(c0), "r"(c1) : "memory");
}
__device__ __forceinline__ void bulk_g2s(uint32_t dst, const void* src, uint32_t bytes, uint32_t bar) {
  asm volatile("cp.async.bulk.shared::cluster.global.mbarrier::complete_tx::bytes [%0], [%1], %2, [%3];"
               ::"r"(dst), "l"(src), "r"(bytes), "r"(bar) : "memory");
}
__device__ __forceinline__ void cp_async8(uint32_t dst, const void* src) {
  asm volatile("cp.async.ca.shared.global [%0], [%1], 8;" ::"r"(dst), "l"(src) : "memory");
}
__device__ __forceinline__ void fence_async_smem() { asm volatile("fence.proxy.async.shared::cta;" ::: "memory"); }
__device__ __forceinline__ void fence_async_all() { asm volatile("fence.proxy.async.global;" ::: "memory"); }

__device__ __forceinline__ void bar_sync(int id, int n) { asm volatile("bar.sync %0, %1;" ::"r"(id), "r"(n) : "memory"); }
__device__ __forceinline__ void cnt_arrive(int idx) {
  asm volatile("red.release.gpu.global.add.u32 [%0], 1;" ::"l"(&g_cnt[idx * 32]) : "memory");
}
__device__ __forceinline__ void cnt_wait(int idx, unsigned target) {
  unsigned v, n = 0;
#pragma unroll 1
  while (true) {
    asm volatile("ld.acquire.gpu.global.u32 %0, [%1];" : "=r"(v) : "l"(&g_cnt[idx * 32]) : "memory");
    if (v >= target || ++n >= (1u << 18)) break;
    __nanosleep(32);
  }
}
__device__ __forceinline__ void wg_fence() { asm volatile("wgmma.fence.sync.aligned;" ::: "memory"); }
__device__ __forceinline__ void wg_commit() { asm volatile("wgmma.commit_group.sync.aligned;" ::: "memory"); }
template <int N> __device__ __forceinline__ void wg_wait() { asm volatile("wgmma.wait_group.sync.aligned %0;" ::"n"(N) : "memory"); }
template <int N> __device__ __forceinline__ void fence_regs(float (&d)[N]) {
#pragma unroll
  for (int i = 0; i < N; i++) asm volatile("" : "+f"(d[i])::"memory");
}
__device__ __forceinline__ uint64_t make_desc(uint32_t saddr, uint32_t lbo, uint32_t sbo, uint32_t swz) {
  return (uint64_t)((saddr & 0x3FFFF) >> 4) | ((uint64_t)(lbo >> 4) << 16) | ((uint64_t)(sbo >> 4) << 32) | ((uint64_t)swz << 62);
}
__device__ __forceinline__ float ex2f(float x) { float y; asm("ex2.approx.ftz.f32 %0, %1;" : "=f"(y) : "f"(x)); return y; }
__device__ __forceinline__ float rcpf(float x) { float y; asm("rcp.approx.ftz.f32 %0, %1;" : "=f"(y) : "f"(x)); return y; }
__device__ __forceinline__ uint32_t pack_bf16(float lo, float hi) {
  uint32_t r; asm("cvt.rn.bf16x2.f32 %0, %1, %2;" : "=r"(r) : "f"(hi), "f"(lo)); return r;
}
__device__ __forceinline__ uint32_t lop_and_or(uint32_t a, uint32_t m, uint32_t c) {
  uint32_t r; asm("lop3.b32 %0, %1, %2, %3, 0xEA;" : "=r"(r) : "r"(a), "r"(m), "r"(c)); return r;
}
__device__ __forceinline__ void sts32(uint32_t a, uint32_t v) { asm volatile("st.shared.b32 [%0], %1;" ::"r"(a), "r"(v) : "memory"); }
__device__ __forceinline__ void sts64(uint32_t a, uint32_t v0, uint32_t v1) { asm volatile("st.shared.v2.b32 [%0], {%1, %2};" ::"r"(a), "r"(v0), "r"(v1) : "memory"); }
__device__ __forceinline__ void sts128(uint32_t a, uint4 v) {
  asm volatile("st.shared.v4.b32 [%0], {%1, %2, %3, %4};" ::"r"(a), "r"(v.x), "r"(v.y), "r"(v.z), "r"(v.w) : "memory");
}
__device__ __forceinline__ float4 ldcg_f4(const float* p) {
  float4 v; asm volatile("ld.global.cg.v4.f32 {%0, %1, %2, %3}, [%4];" : "=f"(v.x), "=f"(v.y), "=f"(v.z), "=f"(v.w) : "l"(p) : "memory"); return v;
}
__device__ __forceinline__ void ldsm4(uint32_t* r, uint32_t a) {
  asm volatile("ldmatrix.sync.aligned.m8n8.x4.shared.b16 {%0, %1, %2, %3}, [%4];"
               : "=r"(r[0]), "=r"(r[1]), "=r"(r[2]), "=r"(r[3]) : "r"(a) : "memory");
}
__device__ __forceinline__ float quad_sum(float v) { v += __shfl_xor_sync(~0u, v, 1); v += __shfl_xor_sync(~0u, v, 2); return v; }
__device__ __forceinline__ float quad_max(float v) { v = fmaxf(v, __shfl_xor_sync(~0u, v, 1)); v = fmaxf(v, __shfl_xor_sync(~0u, v, 2)); return v; }

template <int SD> __device__ __forceinline__ void wgmma_ss_n56_ta0_tb1(float (&d)[28], uint64_t da, uint64_t db) {
  if (SD) asm volatile("wgmma.mma_async.sync.aligned.m64n56k16.f32.bf16.bf16 {%0, %1, %2, %3, %4, %5, %6, %7, %8, %9, %10, %11, %12, %13, %14, %15, %16, %17, %18, %19, %20, %21, %22, %23, %24, %25, %26, %27}, %28, %29, 1, 1, 1, 0, 1;\n"
    : "+f"(d[0]), "+f"(d[1]), "+f"(d[2]), "+f"(d[3]), "+f"(d[4]), "+f"(d[5]), "+f"(d[6]), "+f"(d[7]), "+f"(d[8]), "+f"(d[9]), "+f"(d[10]), "+f"(d[11]), "+f"(d[12]), "+f"(d[13]), "+f"(d[14]), "+f"(d[15]), "+f"(d[16]), "+f"(d[17]), "+f"(d[18]), "+f"(d[19]), "+f"(d[20]), "+f"(d[21]), "+f"(d[22]), "+f"(d[23]), "+f"(d[24]), "+f"(d[25]), "+f"(d[26]), "+f"(d[27])
    : "l"(da), "l"(db));
  else asm volatile("wgmma.mma_async.sync.aligned.m64n56k16.f32.bf16.bf16 {%0, %1, %2, %3, %4, %5, %6, %7, %8, %9, %10, %11, %12, %13, %14, %15, %16, %17, %18, %19, %20, %21, %22, %23, %24, %25, %26, %27}, %28, %29, 0, 1, 1, 0, 1;\n"
    : "=f"(d[0]), "=f"(d[1]), "=f"(d[2]), "=f"(d[3]), "=f"(d[4]), "=f"(d[5]), "=f"(d[6]), "=f"(d[7]), "=f"(d[8]), "=f"(d[9]), "=f"(d[10]), "=f"(d[11]), "=f"(d[12]), "=f"(d[13]), "=f"(d[14]), "=f"(d[15]), "=f"(d[16]), "=f"(d[17]), "=f"(d[18]), "=f"(d[19]), "=f"(d[20]), "=f"(d[21]), "=f"(d[22]), "=f"(d[23]), "=f"(d[24]), "=f"(d[25]), "=f"(d[26]), "=f"(d[27])
    : "l"(da), "l"(db));
}
template <int SD> __device__ __forceinline__ void wgmma_rs_n56_tb1(float (&d)[28], uint32_t a0, uint32_t a1, uint32_t a2, uint32_t a3, uint64_t db) {
  if (SD) asm volatile("wgmma.mma_async.sync.aligned.m64n56k16.f32.bf16.bf16 {%0, %1, %2, %3, %4, %5, %6, %7, %8, %9, %10, %11, %12, %13, %14, %15, %16, %17, %18, %19, %20, %21, %22, %23, %24, %25, %26, %27}, {%28, %29, %30, %31}, %32, 1, 1, 1, 1;\n"
    : "+f"(d[0]), "+f"(d[1]), "+f"(d[2]), "+f"(d[3]), "+f"(d[4]), "+f"(d[5]), "+f"(d[6]), "+f"(d[7]), "+f"(d[8]), "+f"(d[9]), "+f"(d[10]), "+f"(d[11]), "+f"(d[12]), "+f"(d[13]), "+f"(d[14]), "+f"(d[15]), "+f"(d[16]), "+f"(d[17]), "+f"(d[18]), "+f"(d[19]), "+f"(d[20]), "+f"(d[21]), "+f"(d[22]), "+f"(d[23]), "+f"(d[24]), "+f"(d[25]), "+f"(d[26]), "+f"(d[27])
    : "r"(a0), "r"(a1), "r"(a2), "r"(a3), "l"(db));
  else asm volatile("wgmma.mma_async.sync.aligned.m64n56k16.f32.bf16.bf16 {%0, %1, %2, %3, %4, %5, %6, %7, %8, %9, %10, %11, %12, %13, %14, %15, %16, %17, %18, %19, %20, %21, %22, %23, %24, %25, %26, %27}, {%28, %29, %30, %31}, %32, 0, 1, 1, 1;\n"
    : "=f"(d[0]), "=f"(d[1]), "=f"(d[2]), "=f"(d[3]), "=f"(d[4]), "=f"(d[5]), "=f"(d[6]), "=f"(d[7]), "=f"(d[8]), "=f"(d[9]), "=f"(d[10]), "=f"(d[11]), "=f"(d[12]), "=f"(d[13]), "=f"(d[14]), "=f"(d[15]), "=f"(d[16]), "=f"(d[17]), "=f"(d[18]), "=f"(d[19]), "=f"(d[20]), "=f"(d[21]), "=f"(d[22]), "=f"(d[23]), "=f"(d[24]), "=f"(d[25]), "=f"(d[26]), "=f"(d[27])
    : "r"(a0), "r"(a1), "r"(a2), "r"(a3), "l"(db));
}
template <int SD> __device__ __forceinline__ void wgmma_rs_n8_tb1(float (&d)[4], uint32_t a0, uint32_t a1, uint32_t a2, uint32_t a3, uint64_t db) {
  if (SD) asm volatile("wgmma.mma_async.sync.aligned.m64n8k16.f32.bf16.bf16 {%0, %1, %2, %3}, {%4, %5, %6, %7}, %8, 1, 1, 1, 1;\n"
    : "+f"(d[0]), "+f"(d[1]), "+f"(d[2]), "+f"(d[3])
    : "r"(a0), "r"(a1), "r"(a2), "r"(a3), "l"(db));
  else asm volatile("wgmma.mma_async.sync.aligned.m64n8k16.f32.bf16.bf16 {%0, %1, %2, %3}, {%4, %5, %6, %7}, %8, 0, 1, 1, 1;\n"
    : "=f"(d[0]), "=f"(d[1]), "=f"(d[2]), "=f"(d[3])
    : "r"(a0), "r"(a1), "r"(a2), "r"(a3), "l"(db));
}
template <int SD> __device__ __forceinline__ void wgmma_ss_n32_ta1_tb1(float (&d)[16], uint64_t da, uint64_t db) {
  if (SD) asm volatile("wgmma.mma_async.sync.aligned.m64n32k16.f32.bf16.bf16 {%0, %1, %2, %3, %4, %5, %6, %7, %8, %9, %10, %11, %12, %13, %14, %15}, %16, %17, 1, 1, 1, 1, 1;\n"
    : "+f"(d[0]), "+f"(d[1]), "+f"(d[2]), "+f"(d[3]), "+f"(d[4]), "+f"(d[5]), "+f"(d[6]), "+f"(d[7]), "+f"(d[8]), "+f"(d[9]), "+f"(d[10]), "+f"(d[11]), "+f"(d[12]), "+f"(d[13]), "+f"(d[14]), "+f"(d[15])
    : "l"(da), "l"(db));
  else asm volatile("wgmma.mma_async.sync.aligned.m64n32k16.f32.bf16.bf16 {%0, %1, %2, %3, %4, %5, %6, %7, %8, %9, %10, %11, %12, %13, %14, %15}, %16, %17, 0, 1, 1, 1, 1;\n"
    : "=f"(d[0]), "=f"(d[1]), "=f"(d[2]), "=f"(d[3]), "=f"(d[4]), "=f"(d[5]), "=f"(d[6]), "=f"(d[7]), "=f"(d[8]), "=f"(d[9]), "=f"(d[10]), "=f"(d[11]), "=f"(d[12]), "=f"(d[13]), "=f"(d[14]), "=f"(d[15])
    : "l"(da), "l"(db));
}
template <int SD> __device__ __forceinline__ void wgmma_ss_n32_ta0_tb1(float (&d)[16], uint64_t da, uint64_t db) {
  if (SD) asm volatile("wgmma.mma_async.sync.aligned.m64n32k16.f32.bf16.bf16 {%0, %1, %2, %3, %4, %5, %6, %7, %8, %9, %10, %11, %12, %13, %14, %15}, %16, %17, 1, 1, 1, 0, 1;\n"
    : "+f"(d[0]), "+f"(d[1]), "+f"(d[2]), "+f"(d[3]), "+f"(d[4]), "+f"(d[5]), "+f"(d[6]), "+f"(d[7]), "+f"(d[8]), "+f"(d[9]), "+f"(d[10]), "+f"(d[11]), "+f"(d[12]), "+f"(d[13]), "+f"(d[14]), "+f"(d[15])
    : "l"(da), "l"(db));
  else asm volatile("wgmma.mma_async.sync.aligned.m64n32k16.f32.bf16.bf16 {%0, %1, %2, %3, %4, %5, %6, %7, %8, %9, %10, %11, %12, %13, %14, %15}, %16, %17, 0, 1, 1, 0, 1;\n"
    : "=f"(d[0]), "=f"(d[1]), "=f"(d[2]), "=f"(d[3]), "=f"(d[4]), "=f"(d[5]), "=f"(d[6]), "=f"(d[7]), "=f"(d[8]), "=f"(d[9]), "=f"(d[10]), "=f"(d[11]), "=f"(d[12]), "=f"(d[13]), "=f"(d[14]), "=f"(d[15])
    : "l"(da), "l"(db));
}
template <int SD> __device__ __forceinline__ void wgmma_rs_n64_tb0(float (&d)[32], uint32_t a0, uint32_t a1, uint32_t a2, uint32_t a3, uint64_t db) {
  if (SD) asm volatile("wgmma.mma_async.sync.aligned.m64n64k16.f32.bf16.bf16 {%0, %1, %2, %3, %4, %5, %6, %7, %8, %9, %10, %11, %12, %13, %14, %15, %16, %17, %18, %19, %20, %21, %22, %23, %24, %25, %26, %27, %28, %29, %30, %31}, {%32, %33, %34, %35}, %36, 1, 1, 1, 0;\n"
    : "+f"(d[0]), "+f"(d[1]), "+f"(d[2]), "+f"(d[3]), "+f"(d[4]), "+f"(d[5]), "+f"(d[6]), "+f"(d[7]), "+f"(d[8]), "+f"(d[9]), "+f"(d[10]), "+f"(d[11]), "+f"(d[12]), "+f"(d[13]), "+f"(d[14]), "+f"(d[15]), "+f"(d[16]), "+f"(d[17]), "+f"(d[18]), "+f"(d[19]), "+f"(d[20]), "+f"(d[21]), "+f"(d[22]), "+f"(d[23]), "+f"(d[24]), "+f"(d[25]), "+f"(d[26]), "+f"(d[27]), "+f"(d[28]), "+f"(d[29]), "+f"(d[30]), "+f"(d[31])
    : "r"(a0), "r"(a1), "r"(a2), "r"(a3), "l"(db));
  else asm volatile("wgmma.mma_async.sync.aligned.m64n64k16.f32.bf16.bf16 {%0, %1, %2, %3, %4, %5, %6, %7, %8, %9, %10, %11, %12, %13, %14, %15, %16, %17, %18, %19, %20, %21, %22, %23, %24, %25, %26, %27, %28, %29, %30, %31}, {%32, %33, %34, %35}, %36, 0, 1, 1, 0;\n"
    : "=f"(d[0]), "=f"(d[1]), "=f"(d[2]), "=f"(d[3]), "=f"(d[4]), "=f"(d[5]), "=f"(d[6]), "=f"(d[7]), "=f"(d[8]), "=f"(d[9]), "=f"(d[10]), "=f"(d[11]), "=f"(d[12]), "=f"(d[13]), "=f"(d[14]), "=f"(d[15]), "=f"(d[16]), "=f"(d[17]), "=f"(d[18]), "=f"(d[19]), "=f"(d[20]), "=f"(d[21]), "=f"(d[22]), "=f"(d[23]), "=f"(d[24]), "=f"(d[25]), "=f"(d[26]), "=f"(d[27]), "=f"(d[28]), "=f"(d[29]), "=f"(d[30]), "=f"(d[31])
    : "r"(a0), "r"(a1), "r"(a2), "r"(a3), "l"(db));
}
template <int SD> __device__ __forceinline__ void wgmma_rs_n32_tb1(float (&d)[16], uint32_t a0, uint32_t a1, uint32_t a2, uint32_t a3, uint64_t db) {
  if (SD) asm volatile("wgmma.mma_async.sync.aligned.m64n32k16.f32.bf16.bf16 {%0, %1, %2, %3, %4, %5, %6, %7, %8, %9, %10, %11, %12, %13, %14, %15}, {%16, %17, %18, %19}, %20, 1, 1, 1, 1;\n"
    : "+f"(d[0]), "+f"(d[1]), "+f"(d[2]), "+f"(d[3]), "+f"(d[4]), "+f"(d[5]), "+f"(d[6]), "+f"(d[7]), "+f"(d[8]), "+f"(d[9]), "+f"(d[10]), "+f"(d[11]), "+f"(d[12]), "+f"(d[13]), "+f"(d[14]), "+f"(d[15])
    : "r"(a0), "r"(a1), "r"(a2), "r"(a3), "l"(db));
  else asm volatile("wgmma.mma_async.sync.aligned.m64n32k16.f32.bf16.bf16 {%0, %1, %2, %3, %4, %5, %6, %7, %8, %9, %10, %11, %12, %13, %14, %15}, {%16, %17, %18, %19}, %20, 0, 1, 1, 1;\n"
    : "=f"(d[0]), "=f"(d[1]), "=f"(d[2]), "=f"(d[3]), "=f"(d[4]), "=f"(d[5]), "=f"(d[6]), "=f"(d[7]), "=f"(d[8]), "=f"(d[9]), "=f"(d[10]), "=f"(d[11]), "=f"(d[12]), "=f"(d[13]), "=f"(d[14]), "=f"(d[15])
    : "r"(a0), "r"(a1), "r"(a2), "r"(a3), "l"(db));
}

__device__ __forceinline__ uint32_t sw64_off(int row, int d) { return row * 64 + ((((d >> 3) ^ (row >> 1)) & 3) << 4) + (d & 7) * 2; }

__device__ __forceinline__ uint32_t exp2_pair_fma(float t0, float t1, uint32_t c_half, uint32_t c_3) {
  uint32_t y0, y;
  asm("prmt.b32 %0, %1, %2, 0x6521;" : "=r"(y0) : "r"(__float_as_uint(t0)), "r"(__float_as_uint(t1)));
  uint32_t h = lop_and_or(y0, 0x007F007Fu, c_half);
  uint32_t e = lop_and_or(y0, 0xFF80FF80u, c_3);
  asm("fma.rn.bf16x2 %0, %1, %2, %3;" : "=r"(y) : "r"(y0), "r"(h), "r"(e));
  return y;
}

__device__ __forceinline__ void feature_map(float (&v)[16], uint32_t (&ph)[16], int lq) {
  const float L2E = 1.4426950408889634f;
  const bool tail_ok = lq < 2;
  float mx[2], mn[2], b[16], sa[2], sn[2];
#pragma unroll
  for (int r = 0; r < 2; r++) {
    const int o = 2 * r;
    if (!tail_ok) { v[o + 12] = v[o]; v[o + 13] = v[o]; }
    mx[r] = fmaxf(fmaxf(fmaxf(v[o], v[o + 1]), fmaxf(v[o + 4], v[o + 5])), fmaxf(fmaxf(v[o + 8], v[o + 9]), fmaxf(v[o + 12], v[o + 13])));
    mn[r] = fminf(fminf(fminf(v[o], v[o + 1]), fminf(v[o + 4], v[o + 5])), fminf(fminf(v[o + 8], v[o + 9]), fminf(v[o + 12], v[o + 13])));
  }
#pragma unroll
  for (int o = 1; o <= 2; o <<= 1)
#pragma unroll
    for (int r = 0; r < 2; r++) { mx[r] = fmaxf(mx[r], __shfl_xor_sync(~0u, mx[r], o)); mn[r] = fminf(mn[r], __shfl_xor_sync(~0u, mn[r], o)); }
#pragma unroll
  for (int r = 0; r < 2; r++) {
    const int o = 2 * r;
    const float cx = -mx[r] * L2E, cn = mn[r] * L2E;
#pragma unroll
    for (int i = 0; i < 8; i++) {
      const int k = o + 4 * (i >> 1) + (i & 1);
      b[k] = ex2f(fmaf(v[k], -L2E, cn));
      v[k] = ex2f(fmaf(v[k], L2E, cx));
    }
    if (!tail_ok) { v[o + 12] = v[o + 13] = b[o + 12] = b[o + 13] = 0.f; }
    sa[r] = ((v[o] + v[o + 1]) + (v[o + 4] + v[o + 5])) + ((v[o + 8] + v[o + 9]) + (v[o + 12] + v[o + 13]));
    sn[r] = ((b[o] + b[o + 1]) + (b[o + 4] + b[o + 5])) + ((b[o + 8] + b[o + 9]) + (b[o + 12] + b[o + 13]));
  }
#pragma unroll
  for (int o = 1; o <= 2; o <<= 1)
#pragma unroll
    for (int r = 0; r < 2; r++) { sa[r] += __shfl_xor_sync(~0u, sa[r], o); sn[r] += __shfl_xor_sync(~0u, sn[r], o); }
#pragma unroll
  for (int r = 0; r < 2; r++) {
    const float ra = rcpf(sa[r]), rb = rcpf(sn[r]);
#pragma unroll
    for (int jj = 0; jj < 4; jj++) {
      ph[jj * 2 + r] = pack_bf16(v[2 * r + 4 * jj] * ra, v[2 * r + 4 * jj + 1] * ra);
      ph[(4 + jj) * 2 + r] = pack_bf16(b[2 * r + 4 * jj] * rb, b[2 * r + 4 * jj + 1] * rb);
    }
  }
}

__device__ __forceinline__ void store_heads(uint32_t base, const uint32_t (&a)[14], uint32_t pad0, uint32_t pad1, int row0, int lq) {
  const uint32_t rb = base + row0 * 64 + (((row0 >> 1) & 3) << 4);
  const uint32_t b0 = rb + lq * 4;
  const uint32_t b1 = (rb + 8192 + ((lq * 4 + 8) & 15)) ^ ((lq >> 1) << 4);
#pragma unroll
  for (int j = 0; j < 7; j++) {
    uint32_t ad;
    if (j < 3) ad = b0 ^ (j << 4);
    else if (j == 3) ad = (lq < 2) ? (b0 ^ 48u) : (b1 ^ 16u);
    else ad = (lq < 2) ? (b1 ^ ((j - 4) << 4)) : ((b1 ^ 16u) ^ ((j - 3) << 4));
    sts32(ad, a[2 * j]);
    sts32(ad + 512, a[2 * j + 1]);
  }
  sts64((rb ^ 48u) + 8 + (lq & 1) * 8192 + (lq >> 1) * 512, pad0, pad1);
}

struct Params {
  const __nv_bfloat16* w_phi;
  const __nv_bfloat16* wk;
  const __nv_bfloat16* wv;
  const __nv_bfloat16* gate_w;
  __nv_bfloat16* out;
};

__global__ void __launch_bounds__(NTHREADS, 1)
fused_kernel(const __grid_constant__ CUtensorMap tm_x, const __grid_constant__ CUtensorMap tm_wqkv,
             const __grid_constant__ CUtensorMap tm_wq, const __grid_constant__ CUtensorMap tm_woa,
             const __grid_constant__ CUtensorMap tm_wob, const Params prm) {
  extern __shared__ uint8_t smem_raw[];
  uint32_t sb = (smem_u32(smem_raw) + 1023u) & ~1023u;
  uint8_t* sgen = smem_raw + (sb - smem_u32(smem_raw));
  asm volatile("mov.u32 %0, %0;" : "+r"(sb));
  const int tid = threadIdx.x, lane = tid & 31;
  const int warp = __shfl_sync(~0u, tid >> 5, 0), wg = warp >> 2;
  const int pt = blockIdx.x >> 3, hp = blockIdx.x & 7;
  const uint32_t bars = sb + OFF_BAR;
  auto BAR = [&](int i) { return bars + 8u * i; };
  const unsigned epoch = g_epoch & 1;

  if (tid == 0) { PROF_MARK(0); PROF_CLK(30); PROF2(15); }
  auto load_proj = [&](int c, int g) {
    mbar_expect_tx(BAR(B_FULL + g), 49152);
    tma_2d(sb + OFF_X + c * 16384, &tm_x, c * 64, pt * 128, BAR(B_FULL + g));
    tma_2d(sb + OFF_RING + g * 32768, &tm_wq, hp * 56, c * 64, BAR(B_FULL + g));
#pragma unroll 1
    for (int j = 0; j < 3; j++) tma_2d(sb + OFF_RING + g * 32768 + 8192 + j * 8192, &tm_wqkv, j * DM + hp * 56, c * 64, BAR(B_FULL + g));
  };
  if (elect_one()) {
    const int i = warp == 16 ? 0 : (warp == 0 ? 16 : warp);
    if (i < B_N) {
      int cnt = (i >= B_EMPTY && i < B_WO) || i > B_SIG || i == B_X0FREE || i == B_X1FREE ? 16 : 1;
      if (i == B_BUILD) cnt = 512;
      if (i == B_SIG || i == B_QSQ) cnt = 8;
      mbar_init(BAR(i), cnt);
      fence_async_smem();
    }
    if (warp == 16) load_proj(0, 0);
  }
  __syncthreads();
  if (tid == 0) PROF2(14);

  if (wg == 4) {
    asm volatile("setmaxnreg.dec.sync.aligned.u32 32;");
    if (warp == 16) {
      if (elect_one()) {
        int g = 1, nkv = 8;
        uint32_t par = 1;
#pragma unroll 1
        for (int n = 1; n < 14 + nkv; n++) {
          if (n == 7) { PROF_MARK(20); cnt_wait(C_KV, NCTA); PROF_MARK(21); fence_async_all(); }
          if (n == 15) {
            mbar_wait(BAR(B_SLOW), 0);
            if (*(volatile int*)(sgen + OFF_RED)) nkv = 26;
          }
          const int j = n - 7 - nkv;
          if (j == 0 || j == 3) {
            PROF3(j ? 11 : 8);
            cnt_wait((j ? C_OB : C_OA) + pt, 8);
            PROF3(j ? 12 : 9);
            PROF_MARK(26);
            fence_async_all();
          }
          mbar_wait(BAR(B_EMPTY + g), par);
          if (n < 7) load_proj(n, g);
          else {
            mbar_expect_tx(BAR(B_FULL + g), 32768);
            bulk_g2s(sb + OFF_RING + g * 32768, j < 0 ? g_kv_img + ((n - 7) & 7) * 32768 : g_o_img + (size_t)(pt * 7 + j) * 32768, 32768,
                     BAR(B_FULL + g));
          }
          if (++g == 3) { g = 0; par ^= 1; }
        }
        if (atomicAdd(&g_cnt[C_DONE * 32], 1u) == NCTA - 1) {
#pragma unroll 1
          for (int i = 0; i < C_N; i++) g_cnt[i * 32] = 0;
          g_epoch = epoch ^ 1;
        }
      }
    } else {
      if (warp == 18) {
        if (elect_one()) {
#pragma unroll 1
          for (int i = 0; i < 4; i++) {
            mbar_wait(BAR(B_SIG + i), 0);
            PROF3(2 * i);
            cnt_arrive(i == 0 ? C_KV : i == 1 ? C_PART : (i == 2 ? C_OA : C_OB) + pt);
            PROF3(2 * i + 1);
            if (i == 1 || i == 2) {
              mbar_wait(BAR(B_X0FREE + i - 1), 0);
              mbar_expect_tx(BAR(B_WO + i - 1), 57344);
#pragma unroll 1
              for (int c = 0; c < 7; c++)
                tma_2d(sb + OFF_WO + (i - 1) * 57344 + c * 8192, i == 1 ? &tm_woa : &tm_wob, hp * 56, c * 64, BAR(B_WO + i - 1));
            }
          }
        }
      } else if (warp == 19) {
        if (lane == 0) {
          mbar_wait(BAR(B_SIG + 0), 0);
          cnt_wait(C_KV, NCTA);
        }
        __syncwarp();
        float ksq = 0.f, vsq = 0.f;
#pragma unroll
        for (int sl = 0; sl < 4; sl++) {
          float4 a = ldcg_f4(g_ksq + sl * 128 + lane * 4), b = ldcg_f4(g_vsq + sl * 128 + lane * 4);
          float m = fmaxf(fmaxf(a.x, a.y), fmaxf(a.z, a.w));
          m = __uint_as_float(__reduce_max_sync(~0u, __float_as_uint(m)));
          ksq += m;
          vsq = fmaxf(vsq, fmaxf(fmaxf(b.x, b.y), fmaxf(b.z, b.w)));
        }
        mbar_wait(BAR(B_QSQ), 0);
        const float4 qa4 = ((const float4*)(sgen + OFF_QSQ))[lane], qb4 = ((const float4*)(sgen + OFF_QSQ))[32 + lane];
        const float qmax = fmaxf(fmaxf(fmaxf(qa4.x, qa4.y), fmaxf(qa4.z, qa4.w)), fmaxf(fmaxf(qb4.x, qb4.y), fmaxf(qb4.z, qb4.w)));
        const bool slow = __any_sync(~0u, !(qmax * ksq <= 98.f * 98.f) || !(vsq <= 2.0e8f));
        if (lane == 0) {
          *(volatile int*)(sgen + OFF_RED) = slow;
          mbar_arrive(BAR(B_SLOW), 1);
        }
      } else {
        float4* z = (float4*)(g_kvacc[epoch ^ 1] + blockIdx.x * 256) + lane;
        z[0] = make_float4(0.f, 0.f, 0.f, 0.f);
        z[32] = make_float4(0.f, 0.f, 0.f, 0.f);
        if (lane == 0) {
          mbar_wait(BAR(B_SIG + 1), 0);
          cnt_wait(C_PART, NCTA);
          PROF_MARK(23);
        }
        __syncwarp();
        const float* src = g_kvacc[epoch] + hp * 4096 + lane * 8;
#pragma unroll 2
        for (int i = 0; i < 16; i++) {
          const float4 a = ldcg_f4(src + i * 256), b = ldcg_f4(src + i * 256 + 4);
          sts128(sb + OFF_KVR + sw64_off(i * 8 + (lane >> 2), (lane & 3) * 8),
                 make_uint4(pack_bf16(a.x, a.y), pack_bf16(a.z, a.w), pack_bf16(b.x, b.y), pack_bf16(b.z, b.w)));
        }
        ((float4*)(sgen + OFF_GATE))[lane] = ldcg_f4(g_gate + pt * 128 + lane * 4);
        fence_async_smem();
        __syncwarp();
        if (lane == 0) mbar_arrive(BAR(B_KVR), 1);
      }
    }
  } else {
    asm volatile("setmaxnreg.inc.sync.aligned.u32 112;");
    const int mh = wg & 1, nh = wg >> 1, wq = warp & 3;
    if (tid < DM) {
      const __nv_bfloat16* src = (hp < 4 ? prm.wk : prm.wv) + tid * DH + (hp & 3) * 8;
      cp_async8(sb + OFF_SLC + tid * 16, src);
      if ((hp & 3) != 3) cp_async8(sb + OFF_SLC + tid * 16 + 8, src + 4);
      if (tid < 392) {
        const int row = tid / 7, e = row >= DH;
        cp_async8(sb + OFF_WPH + e * 2048 + sw64_off(row - DH * e, (tid % 7) * 4), prm.w_phi + 2 * hp * DH * DH + tid * 4);
      } else {
        const int row = tid - 392, e = row >= DH;
        sts64(sb + OFF_WPH + e * 2048 + sw64_off(row - DH * e, 28), 0u, 0u);
      }
      if ((hp & 3) == 3) sts64(sb + OFF_SLC + tid * 16 + 8, hp == 3 ? (uint32_t)((const unsigned short*)prm.gate_w)[tid] : 0u, 0u);
    } else if (tid < DM + 32) {
      sts128(sb + OFF_WPH + ((tid - DM) >> 4) * 2048 + 28 * 64 + ((tid - DM) & 15) * 16, make_uint4(0, 0, 0, 0));
    }
    asm volatile("cp.async.mbarrier.arrive.noinc.shared::cta.b64 [%0];" ::"r"(BAR(B_BUILD)) : "memory");
    const int lq = lane & 3;
    const int rowl = wq * 16 + (lane >> 2);
    const int row0 = mh * 64 + rowl;
    int slot = 0, prev = 0;
    uint32_t par = 0;
    {
      float acc0[28], acc1[28], accs[4];
      const uint64_t dR = make_desc(sb + OFF_RING + nh * 16384, 1024, 1024, 1);
      const int lr = wq * 16 + (lane & 7) + ((lane >> 3) & 1) * 8;
      const uint32_t xa = sb + OFF_X + mh * 8192 + lr * 128 + (((lane >> 4) ^ (lr & 7)) << 4);
#pragma unroll
      for (int i = 0; i < 28; i++) acc0[i] = acc1[i] = 0.f;
#pragma unroll
      for (int i = 0; i < 4; i++) accs[i] = 0.f;
      if (nh == 1) { mbar_wait(BAR(B_BUILD), 0); fence_async_smem(); }
#pragma unroll 1
      for (int c = 0; c < 7; c++) {
        mbar_wait(BAR(B_FULL + slot), par);
        uint32_t a[16];
#pragma unroll
        for (int ks = 0; ks < 4; ks++) ldsm4(a + 4 * ks, (xa + c * 16384) ^ (ks << 5));
        const uint64_t dB = dR + slot * 2048;
        wg_fence();
#pragma unroll
        for (int ks = 0; ks < 4; ks++) {
          wgmma_rs_n56_tb1<1>(acc0, a[4 * ks], a[4 * ks + 1], a[4 * ks + 2], a[4 * ks + 3], dB + ks * 128);
          wgmma_rs_n56_tb1<1>(acc1, a[4 * ks], a[4 * ks + 1], a[4 * ks + 2], a[4 * ks + 3], dB + 512 + ks * 128);
        }
        if (nh == 1) {
          const uint64_t dSlc = make_desc(sb + OFF_SLC + c * 1024, 128, 128, 0);
#pragma unroll
          for (int ks = 0; ks < 4; ks++) wgmma_rs_n8_tb1<1>(accs, a[4 * ks], a[4 * ks + 1], a[4 * ks + 2], a[4 * ks + 3], dSlc + ks * 16);
        }
        wg_commit();
        wg_wait<0>();
        if (lane == 0) mbar_arrive(BAR(B_EMPTY + slot), 1);
        if (++slot == 3) { slot = 0; par ^= 1; }
      }
      fence_regs(acc0); fence_regs(acc1); fence_regs(accs);
      if (tid == 0) PROF_MARK(2);
      if (tid == 256) PROF_MARK(3);
      if (nh == 0) {
        float sq[4] = {0.f, 0.f, 0.f, 0.f};
#pragma unroll
        for (int i = 0; i < 28; i++) acc0[i] *= 0.18898223650461362f * 1.4426950408889634f;
#pragma unroll
        for (int j = 0; j < 7; j++) {
#pragma unroll
          for (int rr = 0; rr < 2; rr++) {
            const float s2 = acc0[4 * j + 2 * rr] * acc0[4 * j + 2 * rr] + acc0[4 * j + 2 * rr + 1] * acc0[4 * j + 2 * rr + 1];
            if (j < 3) sq[rr] += s2;
            else if (j > 3) sq[2 + rr] += s2;
            else { sq[rr] += (lq < 2) ? s2 : 0.f; sq[2 + rr] += (lq < 2) ? 0.f : s2; }
          }
        }
#pragma unroll
        for (int i = 0; i < 4; i++) sq[i] = quad_sum(sq[i]);
        const float mine = lq == 0 ? sq[0] : lq == 1 ? sq[1] : lq == 2 ? sq[2] : sq[3];
        ((float*)(sgen + OFF_QSQ))[(mh + (lq & 2)) * 64 + rowl + 8 * (lq & 1)] = mine <= 3.0e38f ? mine : __int_as_float(0x7f800000);
        __syncwarp();
        if (lane == 0) mbar_arrive(BAR(B_QSQ), 1);
      } else {
        const int sl = hp & 3;
        const bool isk = hp < 4, real = (sl < 3) || (lq < 2);
        const int pos = pt * 128 + row0, kr = pos & 63;
        uint8_t* dst = g_kv_img + (pos >> 6) * 8192 + (isk ? 0 : 4096) + sw64_off(kr, sl * 8 + 2 * lq);
        const uint32_t pat = isk ? POLY_PAT >> (kr >> 3) : 0u;
        float mxv = 0.f;
#pragma unroll
        for (int rr = 0; rr < 2; rr++) {
          const float v0 = accs[2 * rr], v1 = accs[2 * rr + 1];
          const bool poly = (pat >> rr) & 1;
          const float sc = poly ? 2.f : 1.f;
          const float s2 = quad_sum(real ? v0 * v0 + v1 * v1 : 0.f);
          mxv = fmaxf(mxv, s2 <= 3.0e38f ? s2 : __int_as_float(0x7f800000));
          const uint32_t padv = lq == 2 ? (poly ? 0x443F4000u : 0x00003F80u) : (poly ? 0x3AB03F4Du : 0u);
          *(uint32_t*)(dst + rr * 512) = real ? pack_bf16(sc * v0, sc * v1) : padv;
          if (hp == 3 && lq == 2) g_gate[pos + 8 * rr] = rcpf(1.f + ex2f(-1.4426950408889634f * v0));
        }
        mxv = __uint_as_float(__reduce_max_sync(~0u, __float_as_uint(mxv)));
        if (lane == 0) (isk ? g_ksq : g_vsq)[sl * 128 + pt * 8 + mh * 4 + wq] = mxv;
        __syncwarp();
        if (lane == 0) mbar_arrive(BAR(B_SIG + 0), 1);
      }
      if (tid == 0) PROF_MARK(4);
      if (tid == 256) PROF_MARK(5);
      uint32_t h0[14], h1[14];
#pragma unroll
      for (int i = 0; i < 14; i++) { h0[i] = pack_bf16(acc0[2 * i], acc0[2 * i + 1]); h1[i] = pack_bf16(acc1[2 * i], acc1[2 * i + 1]); }
      bar_sync(1, 512);
      if (tid == 0) PROF_MARK(6);
#pragma unroll 1
      for (int r = 0; r < 2; r++) {
        store_heads(sb + (r ? (nh ? OFF_VA : OFF_QA) : (nh ? OFF_KA : OFF_QP)), h0,
                    (r & nh) ? 0x00003F80u : (r | nh) ? 0u : 0x3F800000u, (r | nh) ? 0u : 0x3F803F80u, row0, lq);
#pragma unroll
        for (int i = 0; i < 14; i++) h0[i] = h1[i];
      }
      fence_async_smem();
      bar_sync(1, 512);
      if (tid == 0) PROF_MARK(7);
    }
    const uint64_t dP = make_desc(sb + OFF_PHI + wg * 8192, 1024, 1024, 1);
#pragma unroll 1
    for (int r = 0; r < 2; r++) {
      const uint64_t dA = make_desc(sb + (r ? OFF_QA : OFF_KA) + nh * 8192 + mh * 4096, 512, 512, 2);
      const uint64_t dB = make_desc(sb + OFF_WPH + nh * 2048, 512, 512, 2);
      float pa[16];
      wg_fence();
      wgmma_ss_n32_ta0_tb1<0>(pa, dA, dB);
      wgmma_ss_n32_ta0_tb1<1>(pa, dA + 2, dB + 64);
      wg_commit();
      wg_wait<0>();
      fence_regs(pa);
      uint32_t ph[16];
      feature_map(pa, ph, lq);
      const uint32_t rb = sb + OFF_PHI + wg * 8192 + rowl * 128 + lq * 4 + ((rowl & 7) << 4);
#pragma unroll
      for (int ch = 0; ch < 8; ch++) { sts32(rb ^ (ch << 4), ph[2 * ch]); sts32((rb ^ (ch << 4)) + 1024, ph[2 * ch + 1]); }
      fence_async_smem();
      bar_sync(4 + wg, 128);
      if (r == 0) {
        const uint64_t dV = make_desc(sb + OFF_VA + nh * 8192 + mh * 4096, 512, 512, 2);
        float kv[16];
        wg_fence();
        wgmma_ss_n32_ta1_tb1<0>(kv, dP, dV);
#pragma unroll
        for (int ks = 1; ks < 4; ks++) wgmma_ss_n32_ta1_tb1<1>(kv, dP + ks * 128, dV + ks * 64);
        wg_commit();
        wg_wait<0>();
        fence_regs(kv);
        float* dst = g_kvacc[epoch] + (2 * hp + nh) * 2048 + rowl * 32 + 2 * lq;
#pragma unroll
        for (int j = 0; j < 8; j++)
          asm volatile("red.global.add.v2.f32 [%0], {%1, %2};" ::"l"(dst + 8 * (j >> 1) + 256 * (j & 1)), "f"(kv[2 * j]), "f"(kv[2 * j + 1]) : "memory");
        __syncwarp();
        if (lane == 0) mbar_arrive(BAR(B_SIG + 1), 1);
        bar_sync(4 + wg, 128);
        if (tid == 0) PROF_MARK(28);
      }
    }
    {
      const uint64_t dK = make_desc(sb + OFF_RING, 512, 512, 2);
      const uint64_t dhi = dK & 0xffffffff00000000ull;
      const uint32_t dlo0 = (uint32_t)dK;
      uint32_t ok = 0, q[8];
      float o[16];
#pragma unroll
      for (int i = 0; i < 16; i++) o[i] = 0.f;
      {
        const int r = mh * 64 + wq * 16 + (lane & 7) + ((lane >> 3) & 1) * 8;
        ldsm4(q, sb + OFF_QP + nh * 8192 + sw64_off(r, (lane >> 4) * 8));
        ldsm4(q + 4, sb + OFF_QP + nh * 8192 + sw64_off(r, 16 + (lane >> 4) * 8));
        __syncwarp();
        if (lane == 0) mbar_arrive(BAR(B_X0FREE), 1);
      }
      if (tid == 0) PROF_MARK(10);
      const int qb = QB_AT;
#pragma unroll 1
      for (int it = 0; it <= 8; it++) {
        uint32_t p[16];
        if ((tid & 127) == 0) PROF4(wg * 32 + it * 3);
        if (it == qb || it == 8) {
          float t[16];
          wg_wait<0>();
          fence_regs(o);
          if (it < 8) {
            if (tid == 0) PROF_MARK(11);
            mbar_wait(BAR(B_KVR), 0);
            const uint64_t dR = make_desc(sb + OFF_KVR + nh * 4096, 512, 512, 2);
            wg_fence();
            wgmma_ss_n32_ta0_tb1<0>(t, dP, dR);
#pragma unroll
            for (int ks = 1; ks < 4; ks++) wgmma_ss_n32_ta0_tb1<1>(t, dP + ks * 2, dR + ks * 64);
            wg_commit();
            wg_wait<0>();
            fence_regs(t);
            if (lane == 0) mbar_arrive(BAR(B_X1FREE), 1);
          } else {
            if (lane == 0) mbar_arrive(BAR(B_EMPTY + prev), 1);
            if (tid == 0) PROF_MARK(13);
            mbar_wait(BAR(B_SLOW), 0);
            if (__builtin_expect(__any_sync(~0u, *(volatile int*)(sgen + OFF_RED)), 0)) {
              uint32_t qz[8];
#pragma unroll
              for (int i = 0; i < 8; i++) qz[i] = (i >= 6 && lq >= 2) ? 0u : q[i];
              float m0 = -3.0e38f, m1 = -3.0e38f, o2[16];
              int sl2 = slot;
              uint32_t par2 = par;
#pragma unroll 1
              for (int j64 = 0; j64 < 32; j64++) {
                float s[32];
                mbar_wait(BAR(B_FULL + sl2), par2);
                const uint32_t lo = dlo0 + sl2 * 2048 + (j64 & 3) * 512;
                wg_fence();
                wgmma_rs_n64_tb0<0>(s, qz[0], qz[1], qz[2], qz[3], dhi | lo);
                wgmma_rs_n64_tb0<1>(s, qz[4], qz[5], qz[6], qz[7], dhi | (lo + 2));
                wg_commit();
                wg_wait<0>();
                fence_regs(s);
#pragma unroll
                for (int j = 0; j < 8; j++) {
                  const float sc = ((POLY_PAT >> j) & 1) ? 0.5f : 1.f;
                  m0 = fmaxf(m0, fmaxf(s[4 * j], s[4 * j + 1]) * sc);
                  m1 = fmaxf(m1, fmaxf(s[4 * j + 2], s[4 * j + 3]) * sc);
                }
                if ((j64 & 3) == 3) {
                  if (lane == 0) mbar_arrive(BAR(B_EMPTY + sl2), 1);
                  if (++sl2 == 3) { sl2 = 0; par2 ^= 1; }
                }
              }
              m0 = quad_max(m0); m1 = quad_max(m1);
#pragma unroll
              for (int i = 0; i < 16; i++) o2[i] = 0.f;
#pragma unroll 1
              for (int j64 = 0; j64 < 32; j64++) {
                float s[32];
                mbar_wait(BAR(B_FULL + sl2), par2);
                const uint32_t lo = dlo0 + sl2 * 2048 + (j64 & 3) * 512;
                wg_fence();
                wgmma_rs_n64_tb0<0>(s, qz[0], qz[1], qz[2], qz[3], dhi | lo);
                wgmma_rs_n64_tb0<1>(s, qz[4], qz[5], qz[6], qz[7], dhi | (lo + 2));
                wg_commit();
                wg_wait<0>();
                fence_regs(s);
                uint32_t ps[16];
#pragma unroll
                for (int j = 0; j < 8; j++) {
                  const float sc = ((POLY_PAT >> j) & 1) ? 0.5f : 1.f;
                  ps[2 * j] = pack_bf16(ex2f(fmaf(s[4 * j], sc, -m0)), ex2f(fmaf(s[4 * j + 1], sc, -m0)));
                  ps[2 * j + 1] = pack_bf16(ex2f(fmaf(s[4 * j + 2], sc, -m1)), ex2f(fmaf(s[4 * j + 3], sc, -m1)));
                }
                wg_fence();
#pragma unroll
                for (int ks = 0; ks < 4; ks++)
                  wgmma_rs_n32_tb1<1>(o2, ps[4 * ks], ps[4 * ks + 1], ps[4 * ks + 2], ps[4 * ks + 3], dhi | (lo + 256 + ks * 64));
                wg_commit();
                wg_wait<0>();
                fence_regs(o2);
                if ((j64 & 3) == 3) {
                  if (lane == 0) mbar_arrive(BAR(B_EMPTY + sl2), 1);
                  if (++sl2 == 3) { sl2 = 0; par2 ^= 1; }
                }
              }
#pragma unroll 1
              for (int j = 0; j < 2; j++) {
                mbar_wait(BAR(B_FULL + sl2), par2);
                __syncwarp();
                if (lane == 0) mbar_arrive(BAR(B_EMPTY + sl2), 1);
                if (++sl2 == 3) { sl2 = 0; par2 ^= 1; }
              }
#pragma unroll
              for (int i = 0; i < 16; i++) o[i] = o2[i];
            }
#pragma unroll
            for (int i = 0; i < 16; i++) t[i] = o[i];
          }
          const int br = it == 8;
          const float eps = br ? 0.f : 1e-6f;
          const float g0 = ((const float*)(sgen + OFF_GATE))[row0], g1 = ((const float*)(sgen + OFF_GATE))[row0 + 8];
          const float d0 = __shfl_sync(~0u, t[12], (lane & ~3) | 2), d1 = __shfl_sync(~0u, t[14], (lane & ~3) | 2);
          const float r0 = (br ? 1.f - g0 : g0) * rcpf(d0 + eps), r1 = (br ? 1.f - g1 : g1) * rcpf(d1 + eps);
          uint8_t* img = g_o_img + (size_t)((pt * 2 + br) * 14 + mh) * 8192 + rowl * 128;
          const int col0 = (2 * hp + nh) * DH + 2 * lq;
#pragma unroll
          for (int j = 0; j < 4; j++) {
            const int col = col0 + 8 * j;
            uint8_t* gp = img + (uint32_t)((col >> 6) * 16384 + ((((col >> 3) ^ rowl) & 7) << 4) + (col & 7) * 2);
            const uint32_t v0 = pack_bf16(t[4 * j] * r0, t[4 * j + 1] * r0), v1 = pack_bf16(t[4 * j + 2] * r1, t[4 * j + 3] * r1);
            if (j < 3 || lq < 2) { *(uint32_t*)gp = v0; *(uint32_t*)(gp + 1024) = v1; }
          }
          __syncwarp();
          if (lane == 0) mbar_arrive(BAR(B_SIG + 2 + br), 1);
          if (tid == 0) PROF_MARK(12 + 2 * br);
          if (br) break;
        }
        const uint32_t lo = dlo0 + slot * 2048;
        if ((tid & 127) == 0) PROF4(wg * 32 + it * 3 + 1);
        if (!ok) mbar_wait(BAR(B_FULL + slot), par);
        if ((tid & 127) == 0) PROF4(wg * 32 + it * 3 + 2);
        int nslot = slot + 1;
        uint32_t npar = par;
        if (nslot == 3) { nslot = 0; npar ^= 1; }
        {
          float s[32];
          wg_fence();
          wgmma_rs_n64_tb0<0>(s, q[0], q[1], q[2], q[3], dhi | lo);
          wgmma_rs_n64_tb0<1>(s, q[4], q[5], q[6], q[7], dhi | (lo + 2));
          wg_commit();
#pragma unroll
          for (int u = 0; u < 4; u++) {
            wg_wait<0>();
            fence_regs(s);
            if (u == 0 && lane == 0 && it > 0) mbar_arrive(BAR(B_EMPTY + prev), 1);
            if (u == 2) ok = mbar_test(BAR(B_FULL + nslot), npar);
#pragma unroll
            for (int j = 0; j < 8; j++) {
              if ((POLY_PAT >> j) & 1) {
                p[2 * j] = exp2_pair_fma(s[4 * j], s[4 * j + 1], 0x3F003F00u, 0x00030003u);
                p[2 * j + 1] = exp2_pair_fma(s[4 * j + 2], s[4 * j + 3], 0x3F003F00u, 0x00030003u);
              } else {
                p[2 * j] = pack_bf16(ex2f(s[4 * j]), ex2f(s[4 * j + 1]));
                p[2 * j + 1] = pack_bf16(ex2f(s[4 * j + 2]), ex2f(s[4 * j + 3]));
              }
            }
            wg_fence();
#pragma unroll
            for (int ks = 0; ks < 4; ks++)
              wgmma_rs_n32_tb1<1>(o, p[4 * ks], p[4 * ks + 1], p[4 * ks + 2], p[4 * ks + 3], dhi | (lo + u * 512 + 256 + ks * 64));
            if (u < 3) {
              wgmma_rs_n64_tb0<0>(s, q[0], q[1], q[2], q[3], dhi | (lo + (u + 1) * 512));
              wgmma_rs_n64_tb0<1>(s, q[4], q[5], q[6], q[7], dhi | (lo + (u + 1) * 512 + 2));
            }
            wg_commit();
          }
        }
        prev = slot; slot = nslot; par = npar;
      }
      wg_wait<0>();
    }
    if (nh == 1) return;
    {
      float acc0[28], acc1[28];
#pragma unroll
      for (int i = 0; i < 28; i++) acc0[i] = acc1[i] = 0.f;
      const uint64_t dS = make_desc(sb + OFF_WO, 1024, 1024, 1);
      const uint64_t dR = make_desc(sb + OFF_RING + mh * 8192, 1024, 1024, 1);
#pragma unroll 1
      for (int c = 0; c < 7; c++) {
        mbar_wait(BAR(B_WO + (c >= 3)), 0);
        mbar_wait(BAR(B_FULL + slot), par);
        const uint64_t dA = dR + slot * 2048, dB = dS + c * 1024;
        wg_fence();
#pragma unroll
        for (int ks = 0; ks < 4; ks++) {
          wgmma_ss_n56_ta0_tb1<1>(acc0, dA + ks * 2, dB + ks * 128);
          wgmma_ss_n56_ta0_tb1<1>(acc1, dA + 1024 + ks * 2, dB + 512 + ks * 128);
        }
        wg_commit();
        if (c < 4) {
          wg_wait<0>();
          if (lane == 0) mbar_arrive(BAR(B_EMPTY + slot), 2);
        }
        if (++slot == 3) { slot = 0; par ^= 1; }
      }
      wg_wait<0>();
      fence_regs(acc0); fence_regs(acc1);
      if (tid == 0) PROF_MARK(17);
      __nv_bfloat16* op = prm.out + (size_t)(pt * 128 + row0) * DM + hp * 56 + 2 * lq;
#pragma unroll
      for (int j = 0; j < 7; j++) {
        *(uint32_t*)(op + 8 * j) = pack_bf16(acc0[4 * j] + acc1[4 * j], acc0[4 * j + 1] + acc1[4 * j + 1]);
        *(uint32_t*)(op + 8 * DM + 8 * j) = pack_bf16(acc0[4 * j + 2] + acc1[4 * j + 2], acc0[4 * j + 3] + acc1[4 * j + 3]);
      }
      if (tid == 0) { PROF_MARK(18); PROF_CLK(31); }
    }
  }
}

typedef CUresult (*EncodeFn)(CUtensorMap*, CUtensorMapDataType, cuuint32_t, void*, const cuuint64_t*, const cuuint64_t*,
                             const cuuint32_t*, const cuuint32_t*, CUtensorMapInterleave, CUtensorMapSwizzle,
                             CUtensorMapL2promotion, CUtensorMapFloatOOBfill);

void make_map(EncodeFn enc, CUtensorMap* tm, const void* ptr, uint64_t cols, uint64_t rows, uint32_t box_rows) {
  cuuint64_t dims[2] = {cols, rows};
  cuuint64_t strides[1] = {cols * 2};
  cuuint32_t box[2] = {64, box_rows};
  cuuint32_t es[2] = {1, 1};
  enc(tm, CU_TENSOR_MAP_DATA_TYPE_BFLOAT16, 2, const_cast<void*>(ptr), dims, strides, box, es, CU_TENSOR_MAP_INTERLEAVE_NONE,
      CU_TENSOR_MAP_SWIZZLE_128B, CU_TENSOR_MAP_L2_PROMOTION_L2_128B, CU_TENSOR_MAP_FLOAT_OOB_FILL_NONE);
}

}

extern "C" void kernel_launch(void* const* d_in, const int* in_sizes, int n_in, void* d_out, int out_size) {
  (void)in_sizes; (void)n_in; (void)out_size;
  static EncodeFn enc = nullptr;
  if (!enc) {
    void* fn = nullptr;
    cudaDriverEntryPointQueryResult qr;
    cudaGetDriverEntryPoint("cuTensorMapEncodeTiled", &fn, cudaEnableDefault, &qr);
    enc = (EncodeFn)fn;
    cudaFuncSetAttribute(fused_kernel, cudaFuncAttributeMaxDynamicSharedMemorySize, SMEM_BYTES);
  }
  CUtensorMap tm_x, tm_wqkv, tm_wq, tm_woa, tm_wob;
  make_map(enc, &tm_x, d_in[0], DM, S_LEN, 128);
  make_map(enc, &tm_wqkv, d_in[1], 3 * DM, DM, 64);
  make_map(enc, &tm_wq, d_in[5], DM, DM, 64);
  make_map(enc, &tm_woa, d_in[3], DM, DM, 64);
  make_map(enc, &tm_wob, d_in[8], DM, DM, 64);
  Params prm;
  prm.w_phi = (const __nv_bfloat16*)d_in[2];
  prm.wk = (const __nv_bfloat16*)d_in[6];
  prm.wv = (const __nv_bfloat16*)d_in[7];
  prm.gate_w = (const __nv_bfloat16*)d_in[9];
  prm.out = (__nv_bfloat16*)d_out;
  fused_kernel<<<NCTA, NTHREADS, SMEM_BYTES>>>(tm_x, tm_wqkv, tm_wq, tm_woa, tm_wob, prm);
}
```

```cpp
#include <cuda_runtime.h>
#include <cuda_bf16.h>
#include <cuda.h>
#include <stdint.h>

namespace {

constexpr int S_LEN = 2048, DM = 448, DH = 28;
constexpr int NCTA = 128;
constexpr int NTHREADS = 640;
constexpr uint32_t POLY_PAT = 0x57;

#define QB_AT (4 + wg)

constexpr int OFF_X = 0;
constexpr int OFF_KA = 0;
constexpr int OFF_VA = 16384;
constexpr int OFF_QP = 32768;
constexpr int OFF_QA = 57344;
constexpr int OFF_KVR = 73728;
constexpr int OFF_PHI = 81920;
constexpr int OFF_WO = 0;
constexpr int OFF_RING = 114688;
constexpr int OFF_WPH = 212992;
constexpr int OFF_SLC = 217088;
constexpr int OFF_QSQ = 224256;
constexpr int OFF_GATE = 225280;
constexpr int OFF_RED = 225792;
constexpr int OFF_BAR = 225856;
constexpr int SMEM_BYTES = 226368 + 1024;

constexpr int B_FULL = 0, B_EMPTY = 3, B_WO = 6  , B_KVR = 8, B_X0FREE = 9, B_X1FREE = 10, B_QSQ = 11, B_SLOW = 12,
              B_BUILD = 13, B_SIG = 14  , B_N = 18;

constexpr int C_KV = 0, C_PART = 1, C_DONE = 3, C_OA = 4, C_OB = 20, C_N = 36;

__device__ __align__(1024) uint8_t g_kv_img[32 * 8192];
__device__ __align__(16) float g_ksq[512];
__device__ __align__(16) float g_vsq[512];
__device__ __align__(16) float g_gate[S_LEN];
__device__ __align__(1024) float g_kvacc[2][16 * 64 * 32];
__device__ unsigned g_epoch;
__device__ __align__(1024) uint8_t g_o_img[2 * 16 * 14 * 8192];
__device__ unsigned g_cnt[C_N * 32];

#define PROF4(i) do { } while (0)
#define PROF3(i) do { } while (0)
#define PROF2(i) do { } while (0)
#define PROF_CLK(i) do { } while (0)
#define PROF_MARK(i) do { } while (0)
__device__ __forceinline__ uint32_t smem_u32(const void* p) { return (uint32_t)__cvta_generic_to_shared(p); }
__device__ __forceinline__ void mbar_init(uint32_t a, int cnt) {
  asm volatile("mbarrier.init.shared::cta.b64 [%0], %1;" ::"r"(a), "r"(cnt) : "memory");
}
__device__ __forceinline__ void mbar_expect_tx(uint32_t a, uint32_t bytes) {
  asm volatile("mbarrier.arrive.expect_tx.shared::cta.b64 _, [%0], %1;" ::"r"(a), "r"(bytes) : "memory");
}
__device__ __forceinline__ void mbar_arrive(uint32_t a, uint32_t cnt) {
  asm volatile("mbarrier.arrive.shared::cta.b64 _, [%0], %1;" ::"r"(a), "r"(cnt) : "memory");
}
__device__ __forceinline__ void mbar_wait(uint32_t a, uint32_t parity) {
  asm volatile(
      "{\n.reg .pred p;\n.reg .u32 c;\nmov.u32 c, 0;\n"
      "W_%=:\nmbarrier.try_wait.parity.shared::cta.b64 p, [%0], %1;\n"
      "add.u32 c, c, 1;\nsetp.lt.and.u32 p, c, 0x40000, !p;\n@p bra W_%=;\n}"
      ::"r"(a), "r"(parity) : "memory");
}
__device__ __forceinline__ uint32_t mbar_test(uint32_t a, uint32_t parity) {
  uint32_t ok;
  asm volatile("{\n.reg .pred p;\nmbarrier.test_wait.parity.shared::cta.b64 p, [%1], %2;\nselp.u32 %0, 1, 0, p;\n}"
               : "=r"(ok) : "r"(a), "r"(parity) : "memory");
  return ok;
}
__device__ __forceinline__ bool elect_one() {
  uint32_t r;
  asm volatile("{\n.reg .pred p;\nelect.sync _|p, 0xffffffff;\nselp.u32 %0, 1, 0, p;\n}" : "=r"(r));
  return r != 0;
}
__device__ __forceinline__ void tma_2d(uint32_t dst, const CUtensorMap* tm, int c0, int c1, uint32_t bar) {
  asm volatile("cp.async.bulk.tensor.2d.shared::cluster.global.mbarrier::complete_tx::bytes [%0], [%1, {%3, %4}], [%2];"
               ::"r"(dst), "l"(tm), "r"(bar), "r"(c0), "r"(c1) : "memory");
}
__device__ __forceinline__ void bulk_g2s(uint32_t dst, const void* src, uint32_t bytes, uint32_t bar) {
  asm volatile("cp.async.bulk.shared::cluster.global.mbarrier::complete_tx::bytes [%0], [%1], %2, [%3];"
               ::"r"(dst), "l"(src), "r"(bytes), "r"(bar) : "memory");
}
__device__ __forceinline__ void cp_async8(uint32_t dst, const void* src) {
  asm volatile("cp.async.ca.shared.global [%0], [%1], 8;" ::"r"(dst), "l"(src) : "memory");
}
__device__ __forceinline__ void fence_async_smem() { asm volatile("fence.proxy.async.shared::cta;" ::: "memory"); }
__device__ __forceinline__ void fence_async_all() { asm volatile("fence.proxy.async.global;" ::: "memory"); }

__device__ __forceinline__ void bar_sync(int id, int n) { asm volatile("bar.sync %0, %1;" ::"r"(id), "r"(n) : "memory"); }
__device__ __forceinline__ void cnt_arrive(int idx) {
  asm volatile("red.release.gpu.global.add.u32 [%0], 1;" ::"l"(&g_cnt[idx * 32]) : "memory");
}
__device__ __forceinline__ void cnt_wait(int idx, unsigned target) {
  unsigned v, n = 0;
#pragma unroll 1
  while (true) {
    asm volatile("ld.acquire.gpu.global.u32 %0, [%1];" : "=r"(v) : "l"(&g_cnt[idx * 32]) : "memory");
    if (v >= target || ++n >= (1u << 18)) break;
    __nanosleep(32);
  }
}
__device__ __forceinline__ void wg_fence() { asm volatile("wgmma.fence.sync.aligned;" ::: "memory"); }
__device__ __forceinline__ void wg_commit() { asm volatile("wgmma.commit_group.sync.aligned;" ::: "memory"); }
template <int N> __device__ __forceinline__ void wg_wait() { asm volatile("wgmma.wait_group.sync.aligned %0;" ::"n"(N) : "memory"); }
template <int N> __device__ __forceinline__ void fence_regs(float (&d)[N]) {
#pragma unroll
  for (int i = 0; i < N; i++) asm volatile("" : "+f"(d[i])::"memory");
}
__device__ __forceinline__ uint64_t make_desc(uint32_t saddr, uint32_t lbo, uint32_t sbo, uint32_t swz) {
  return (uint64_t)((saddr & 0x3FFFF) >> 4) | ((uint64_t)(lbo >> 4) << 16) | ((uint64_t)(sbo >> 4) << 32) | ((uint64_t)swz << 62);
}
__device__ __forceinline__ float ex2f(float x) { float y; asm("ex2.approx.ftz.f32 %0, %1;" : "=f"(y) : "f"(x)); return y; }
__device__ __forceinline__ float rcpf(float x) { float y; asm("rcp.approx.ftz.f32 %0, %1;" : "=f"(y) : "f"(x)); return y; }
__device__ __forceinline__ uint32_t pack_bf16(float lo, float hi) {
  uint32_t r; asm("cvt.rn.bf16x2.f32 %0, %1, %2;" : "=r"(r) : "f"(hi), "f"(lo)); return r;
}
__device__ __forceinline__ uint32_t lop_and_or(uint32_t a, uint32_t m, uint32_t c) {
  uint32_t r; asm("lop3.b32 %0, %1, %2, %3, 0xEA;" : "=r"(r) : "r"(a), "r"(m), "r"(c)); return r;
}
__device__ __forceinline__ void sts32(uint32_t a, uint32_t v) { asm volatile("st.shared.b32 [%0], %1;" ::"r"(a), "r"(v) : "memory"); }
__device__ __forceinline__ void sts64(uint32_t a, uint32_t v0, uint32_t v1) { asm volatile("st.shared.v2.b32 [%0], {%1, %2};" ::"r"(a), "r"(v0), "r"(v1) : "memory"); }
__device__ __forceinline__ void sts128(uint32_t a, uint4 v) {
  asm volatile("st.shared.v4.b32 [%0], {%1, %2, %3, %4};" ::"r"(a), "r"(v.x), "r"(v.y), "r"(v.z), "r"(v.w) : "memory");
}
__device__ __forceinline__ float4 ldcg_f4(const float* p) {
  float4 v; asm volatile("ld.global.cg.v4.f32 {%0, %1, %2, %3}, [%4];" : "=f"(v.x), "=f"(v.y), "=f"(v.z), "=f"(v.w) : "l"(p) : "memory"); return v;
}
__device__ __forceinline__ void ldsm4(uint32_t* r, uint32_t a) {
  asm volatile("ldmatrix.sync.aligned.m8n8.x4.shared.b16 {%0, %1, %2, %3}, [%4];"
               : "=r"(r[0]), "=r"(r[1]), "=r"(r[2]), "=r"(r[3]) : "r"(a) : "memory");
}
__device__ __forceinline__ float quad_sum(float v) { v += __shfl_xor_sync(~0u, v, 1); v += __shfl_xor_sync(~0u, v, 2); return v; }
__device__ __forceinline__ float quad_max(float v) { v = fmaxf(v, __shfl_xor_sync(~0u, v, 1)); v = fmaxf(v, __shfl_xor_sync(~0u, v, 2)); return v; }

template <int SD> __device__ __forceinline__ void wgmma_ss_n56_ta0_tb1(float (&d)[28], uint64_t da, uint64_t db) {
  if (SD) asm volatile("wgmma.mma_async.sync.aligned.m64n56k16.f32.bf16.bf16 {%0, %1, %2, %3, %4, %5, %6, %7, %8, %9, %10, %11, %12, %13, %14, %15, %16, %17, %18, %19, %20, %21, %22, %23, %24, %25, %26, %27}, %28, %29, 1, 1, 1, 0, 1;\n"
    : "+f"(d[0]), "+f"(d[1]), "+f"(d[2]), "+f"(d[3]), "+f"(d[4]), "+f"(d[5]), "+f"(d[6]), "+f"(d[7]), "+f"(d[8]), "+f"(d[9]), "+f"(d[10]), "+f"(d[11]), "+f"(d[12]), "+f"(d[13]), "+f"(d[14]), "+f"(d[15]), "+f"(d[16]), "+f"(d[17]), "+f"(d[18]), "+f"(d[19]), "+f"(d[20]), "+f"(d[21]), "+f"(d[22]), "+f"(d[23]), "+f"(d[24]), "+f"(d[25]), "+f"(d[26]), "+f"(d[27])
    : "l"(da), "l"(db));
  else asm volatile("wgmma.mma_async.sync.aligned.m64n56k16.f32.bf16.bf16 {%0, %1, %2, %3, %4, %5, %6, %7, %8, %9, %10, %11, %12, %13, %14, %15, %16, %17, %18, %19, %20, %21, %22, %23, %24, %25, %26, %27}, %28, %29, 0, 1, 1, 0, 1;\n"
    : "=f"(d[0]), "=f"(d[1]), "=f"(d[2]), "=f"(d[3]), "=f"(d[4]), "=f"(d[5]), "=f"(d[6]), "=f"(d[7]), "=f"(d[8]), "=f"(d[9]), "=f"(d[10]), "=f"(d[11]), "=f"(d[12]), "=f"(d[13]), "=f"(d[14]), "=f"(d[15]), "=f"(d[16]), "=f"(d[17]), "=f"(d[18]), "=f"(d[19]), "=f"(d[20]), "=f"(d[21]), "=f"(d[22]), "=f"(d[23]), "=f"(d[24]), "=f"(d[25]), "=f"(d[26]), "=f"(d[27])
    : "l"(da), "l"(db));
}
template <int SD> __device__ __forceinline__ void wgmma_rs_n56_tb1(float (&d)[28], uint32_t a0, uint32_t a1, uint32_t a2, uint32_t a3, uint64_t db) {
  if (SD) asm volatile("wgmma.mma_async.sync.aligned.m64n56k16.f32.bf16.bf16 {%0, %1, %2, %3, %4, %5, %6, %7, %8, %9, %10, %11, %12, %13, %14, %15, %16, %17, %18, %19, %20, %21, %22, %23, %24, %25, %26, %27}, {%28, %29, %30, %31}, %32, 1, 1, 1, 1;\n"
    : "+f"(d[0]), "+f"(d[1]), "+f"(d[2]), "+f"(d[3]), "+f"(d[4]), "+f"(d[5]), "+f"(d[6]), "+f"(d[7]), "+f"(d[8]), "+f"(d[9]), "+f"(d[10]), "+f"(d[11]), "+f"(d[12]), "+f"(d[13]), "+f"(d[14]), "+f"(d[15]), "+f"(d[16]), "+f"(d[17]), "+f"(d[18]), "+f"(d[19]), "+f"(d[20]), "+f"(d[21]), "+f"(d[22]), "+f"(d[23]), "+f"(d[24]), "+f"(d[25]), "+f"(d[26]), "+f"(d[27])
    : "r"(a0), "r"(a1), "r"(a2), "r"(a3), "l"(db));
  else asm volatile("wgmma.mma_async.sync.aligned.m64n56k16.f32.bf16.bf16 {%0, %1, %2, %3, %4, %5, %6, %7, %8, %9, %10, %11, %12, %13, %14, %15, %16, %17, %18, %19, %20, %21, %22, %23, %24, %25, %26, %27}, {%28, %29, %30, %31}, %32, 0, 1, 1, 1;\n"
    : "=f"(d[0]), "=f"(d[1]), "=f"(d[2]), "=f"(d[3]), "=f"(d[4]), "=f"(d[5]), "=f"(d[6]), "=f"(d[7]), "=f"(d[8]), "=f"(d[9]), "=f"(d[10]), "=f"(d[11]), "=f"(d[12]), "=f"(d[13]), "=f"(d[14]), "=f"(d[15]), "=f"(d[16]), "=f"(d[17]), "=f"(d[18]), "=f"(d[19]), "=f"(d[20]), "=f"(d[21]), "=f"(d[22]), "=f"(d[23]), "=f"(d[24]), "=f"(d[25]), "=f"(d[26]), "=f"(d[27])
    : "r"(a0), "r"(a1), "r"(a2), "r"(a3), "l"(db));
}
template <int SD> __device__ __forceinline__ void wgmma_rs_n8_tb1(float (&d)[4], uint32_t a0, uint32_t a1, uint32_t a2, uint32_t a3, uint64_t db) {
  if (SD) asm volatile("wgmma.mma_async.sync.aligned.m64n8k16.f32.bf16.bf16 {%0, %1, %2, %3}, {%4, %5, %6, %7}, %8, 1, 1, 1, 1;\n"
    : "+f"(d[0]), "+f"(d[1]), "+f"(d[2]), "+f"(d[3])
    : "r"(a0), "r"(a1), "r"(a2), "r"(a3), "l"(db));
  else asm volatile("wgmma.mma_async.sync.aligned.m64n8k16.f32.bf16.bf16 {%0, %1, %2, %3}, {%4, %5, %6, %7}, %8, 0, 1, 1, 1;\n"
    : "=f"(d[0]), "=f"(d[1]), "=f"(d[2]), "=f"(d[3])
    : "r"(a0), "r"(a1), "r"(a2), "r"(a3), "l"(db));
}
template <int SD> __device__ __forceinline__ void wgmma_ss_n32_ta1_tb1(float (&d)[16], uint64_t da, uint64_t db) {
  if (SD) asm volatile("wgmma.mma_async.sync.aligned.m64n32k16.f32.bf16.bf16 {%0, %1, %2, %3, %4, %5, %6, %7, %8, %9, %10, %11, %12, %13, %14, %15}, %16, %17, 1, 1, 1, 1, 1;\n"
    : "+f"(d[0]), "+f"(d[1]), "+f"(d[2]), "+f"(d[3]), "+f"(d[4]), "+f"(d[5]), "+f"(d[6]), "+f"(d[7]), "+f"(d[8]), "+f"(d[9]), "+f"(d[10]), "+f"(d[11]), "+f"(d[12]), "+f"(d[13]), "+f"(d[14]), "+f"(d[15])
    : "l"(da), "l"(db));
  else asm volatile("wgmma.mma_async.sync.aligned.m64n32k16.f32.bf16.bf16 {%0, %1, %2, %3, %4, %5, %6, %7, %8, %9, %10, %11, %12, %13, %14, %15}, %16, %17, 0, 1, 1, 1, 1;\n"
    : "=f"(d[0]), "=f"(d[1]), "=f"(d[2]), "=f"(d[3]), "=f"(d[4]), "=f"(d[5]), "=f"(d[6]), "=f"(d[7]), "=f"(d[8]), "=f"(d[9]), "=f"(d[10]), "=f"(d[11]), "=f"(d[12]), "=f"(d[13]), "=f"(d[14]), "=f"(d[15])
    : "l"(da), "l"(db));
}
template <int SD> __device__ __forceinline__ void wgmma_ss_n32_ta0_tb1(float (&d)[16], uint64_t da, uint64_t db) {
  if (SD) asm volatile("wgmma.mma_async.sync.aligned.m64n32k16.f32.bf16.bf16 {%0, %1, %2, %3, %4, %5, %6, %7, %8, %9, %10, %11, %12, %13, %14, %15}, %16, %17, 1, 1, 1, 0, 1;\n"
    : "+f"(d[0]), "+f"(d[1]), "+f"(d[2]), "+f"(d[3]), "+f"(d[4]), "+f"(d[5]), "+f"(d[6]), "+f"(d[7]), "+f"(d[8]), "+f"(d[9]), "+f"(d[10]), "+f"(d[11]), "+f"(d[12]), "+f"(d[13]), "+f"(d[14]), "+f"(d[15])
    : "l"(da), "l"(db));
  else asm volatile("wgmma.mma_async.sync.aligned.m64n32k16.f32.bf16.bf16 {%0, %1, %2, %3, %4, %5, %6, %7, %8, %9, %10, %11, %12, %13, %14, %15}, %16, %17, 0, 1, 1, 0, 1;\n"
    : "=f"(d[0]), "=f"(d[1]), "=f"(d[2]), "=f"(d[3]), "=f"(d[4]), "=f"(d[5]), "=f"(d[6]), "=f"(d[7]), "=f"(d[8]), "=f"(d[9]), "=f"(d[10]), "=f"(d[11]), "=f"(d[12]), "=f"(d[13]), "=f"(d[14]), "=f"(d[15])
    : "l"(da), "l"(db));
}
template <int SD> __device__ __forceinline__ void wgmma_rs_n64_tb0(float (&d)[32], uint32_t a0, uint32_t a1, uint32_t a2, uint32_t a3, uint64_t db) {
  if (SD) asm volatile("wgmma.mma_async.sync.aligned.m64n64k16.f32.bf16.bf16 {%0, %1, %2, %3, %4, %5, %6, %7, %8, %9, %10, %11, %12, %13, %14, %15, %16, %17, %18, %19, %20, %21, %22, %23, %24, %25, %26, %27, %28, %29, %30, %31}, {%32, %33, %34, %35}, %36, 1, 1, 1, 0;\n"
    : "+f"(d[0]), "+f"(d[1]), "+f"(d[2]), "+f"(d[3]), "+f"(d[4]), "+f"(d[5]), "+f"(d[6]), "+f"(d[7]), "+f"(d[8]), "+f"(d[9]), "+f"(d[10]), "+f"(d[11]), "+f"(d[12]), "+f"(d[13]), "+f"(d[14]), "+f"(d[15]), "+f"(d[16]), "+f"(d[17]), "+f"(d[18]), "+f"(d[19]), "+f"(d[20]), "+f"(d[21]), "+f"(d[22]), "+f"(d[23]), "+f"(d[24]), "+f"(d[25]), "+f"(d[26]), "+f"(d[27]), "+f"(d[28]), "+f"(d[29]), "+f"(d[30]), "+f"(d[31])
    : "r"(a0), "r"(a1), "r"(a2), "r"(a3), "l"(db));
  else asm volatile("wgmma.mma_async.sync.aligned.m64n64k16.f32.bf16.bf16 {%0, %1, %2, %3, %4, %5, %6, %7, %8, %9, %10, %11, %12, %13, %14, %15, %16, %17, %18, %19, %20, %21, %22, %23, %24, %25, %26, %27, %28, %29, %30, %31}, {%32, %33, %34, %35}, %36, 0, 1, 1, 0;\n"
    : "=f"(d[0]), "=f"(d[1]), "=f"(d[2]), "=f"(d[3]), "=f"(d[4]), "=f"(d[5]), "=f"(d[6]), "=f"(d[7]), "=f"(d[8]), "=f"(d[9]), "=f"(d[10]), "=f"(d[11]), "=f"(d[12]), "=f"(d[13]), "=f"(d[14]), "=f"(d[15]), "=f"(d[16]), "=f"(d[17]), "=f"(d[18]), "=f"(d[19]), "=f"(d[20]), "=f"(d[21]), "=f"(d[22]), "=f"(d[23]), "=f"(d[24]), "=f"(d[25]), "=f"(d[26]), "=f"(d[27]), "=f"(d[28]), "=f"(d[29]), "=f"(d[30]), "=f"(d[31])
    : "r"(a0), "r"(a1), "r"(a2), "r"(a3), "l"(db));
}
template <int SD> __device__ __forceinline__ void wgmma_rs_n32_tb1(float (&d)[16], uint32_t a0, uint32_t a1, uint32_t a2, uint32_t a3, uint64_t db) {
  if (SD) asm volatile("wgmma.mma_async.sync.aligned.m64n32k16.f32.bf16.bf16 {%0, %1, %2, %3, %4, %5, %6, %7, %8, %9, %10, %11, %12, %13, %14, %15}, {%16, %17, %18, %19}, %20, 1, 1, 1, 1;\n"
    : "+f"(d[0]), "+f"(d[1]), "+f"(d[2]), "+f"(d[3]), "+f"(d[4]), "+f"(d[5]), "+f"(d[6]), "+f"(d[7]), "+f"(d[8]), "+f"(d[9]), "+f"(d[10]), "+f"(d[11]), "+f"(d[12]), "+f"(d[13]), "+f"(d[14]), "+f"(d[15])
    : "r"(a0), "r"(a1), "r"(a2), "r"(a3), "l"(db));
  else asm volatile("wgmma.mma_async.sync.aligned.m64n32k16.f32.bf16.bf16 {%0, %1, %2, %3, %4, %5, %6, %7, %8, %9, %10, %11, %12, %13, %14, %15}, {%16, %17, %18, %19}, %20, 0, 1, 1, 1;\n"
    : "=f"(d[0]), "=f"(d[1]), "=f"(d[2]), "=f"(d[3]), "=f"(d[4]), "=f"(d[5]), "=f"(d[6]), "=f"(d[7]), "=f"(d[8]), "=f"(d[9]), "=f"(d[10]), "=f"(d[11]), "=f"(d[12]), "=f"(d[13]), "=f"(d[14]), "=f"(d[15])
    : "r"(a0), "r"(a1), "r"(a2), "r"(a3), "l"(db));
}

__device__ __forceinline__ uint32_t sw64_off(int row, int d) { return row * 64 + ((((d >> 3) ^ (row >> 1)) & 3) << 4) + (d & 7) * 2; }

__device__ __forceinline__ uint32_t exp2_pair_fma(float t0, float t1, uint32_t c_half, uint32_t c_3) {
  uint32_t y0, y;
  asm("prmt.b32 %0, %1, %2, 0x6521;" : "=r"(y0) : "r"(__float_as_uint(t0)), "r"(__float_as_uint(t1)));
  uint32_t h = lop_and_or(y0, 0x007F007Fu, c_half);
  uint32_t e = lop_and_or(y0, 0xFF80FF80u, c_3);
  asm("fma.rn.bf16x2 %0, %1, %2, %3;" : "=r"(y) : "r"(y0), "r"(h), "r"(e));
  return y;
}

__device__ __forceinline__ void feature_map(float (&v)[16], uint32_t (&ph)[16], int lq) {
  const float L2E = 1.4426950408889634f;
  const bool tail_ok = lq < 2;
  float mx[2], mn[2], b[16], sa[2], sn[2];
#pragma unroll
  for (int r = 0; r < 2; r++) {
    const int o = 2 * r;
    if (!tail_ok) { v[o + 12] = v[o]; v[o + 13] = v[o]; }
    mx[r] = fmaxf(fmaxf(fmaxf(v[o], v[o + 1]), fmaxf(v[o + 4], v[o + 5])), fmaxf(fmaxf(v[o + 8], v[o + 9]), fmaxf(v[o + 12], v[o + 13])));
    mn[r] = fminf(fminf(fminf(v[o], v[o + 1]), fminf(v[o + 4], v[o + 5])), fminf(fminf(v[o + 8], v[o + 9]), fminf(v[o + 12], v[o + 13])));
  }
#pragma unroll
  for (int o = 1; o <= 2; o <<= 1)
#pragma unroll
    for (int r = 0; r < 2; r++) { mx[r] = fmaxf(mx[r], __shfl_xor_sync(~0u, mx[r], o)); mn[r] = fminf(mn[r], __shfl_xor_sync(~0u, mn[r], o)); }
#pragma unroll
  for (int r = 0; r < 2; r++) {
    const int o = 2 * r;
    const float cx = -mx[r] * L2E, cn = mn[r] * L2E;
#pragma unroll
    for (int i = 0; i < 8; i++) {
      const int k = o + 4 * (i >> 1) + (i & 1);
      b[k] = ex2f(fmaf(v[k], -L2E, cn));
      v[k] = ex2f(fmaf(v[k], L2E, cx));
    }
    if (!tail_ok) { v[o + 12] = v[o + 13] = b[o + 12] = b[o + 13] = 0.f; }
    sa[r] = ((v[o] + v[o + 1]) + (v[o + 4] + v[o + 5])) + ((v[o + 8] + v[o + 9]) + (v[o + 12] + v[o + 13]));
    sn[r] = ((b[o] + b[o + 1]) + (b[o + 4] + b[o + 5])) + ((b[o + 8] + b[o + 9]) + (b[o + 12] + b[o + 13]));
  }
#pragma unroll
  for (int o = 1; o <= 2; o <<= 1)
#pragma unroll
    for (int r = 0; r < 2; r++) { sa[r] += __shfl_xor_sync(~0u, sa[r], o); sn[r] += __shfl_xor_sync(~0u, sn[r], o); }
#pragma unroll
  for (int r = 0; r < 2; r++) {
    const float ra = rcpf(sa[r]), rb = rcpf(sn[r]);
#pragma unroll
    for (int jj = 0; jj < 4; jj++) {
      ph[jj * 2 + r] = pack_bf16(v[2 * r + 4 * jj] * ra, v[2 * r + 4 * jj + 1] * ra);
      ph[(4 + jj) * 2 + r] = pack_bf16(b[2 * r + 4 * jj] * rb, b[2 * r + 4 * jj + 1] * rb);
    }
  }
}

__device__ __forceinline__ void store_heads(uint32_t base, const uint32_t (&a)[14], uint32_t pad0, uint32_t pad1, int row0, int lq) {
  const uint32_t rb = base + row0 * 64 + (((row0 >> 1) & 3) << 4);
  const uint32_t b0 = rb + lq * 4;
  const uint32_t b1 = (rb + 8192 + ((lq * 4 + 8) & 15)) ^ ((lq >> 1) << 4);
#pragma unroll
  for (int j = 0; j < 7; j++) {
    uint32_t ad;
    if (j < 3) ad = b0 ^ (j << 4);
    else if (j == 3) ad = (lq < 2) ? (b0 ^ 48u) : (b1 ^ 16u);
    else ad = (lq < 2) ? (b1 ^ ((j - 4) << 4)) : ((b1 ^ 16u) ^ ((j - 3) << 4));
    sts32(ad, a[2 * j]);
    sts32(ad + 512, a[2 * j + 1]);
  }
  sts64((rb ^ 48u) + 8 + (lq & 1) * 8192 + (lq >> 1) * 512, pad0, pad1);
}

struct Params {
  const __nv_bfloat16* w_phi;
  const __nv_bfloat16* wk;
  const __nv_bfloat16* wv;
  const __nv_bfloat16* gate_w;
  __nv_bfloat16* out;
};

__global__ void __launch_bounds__(NTHREADS, 1)
fused_kernel(const __grid_constant__ CUtensorMap tm_x, const __grid_constant__ CUtensorMap tm_wqkv,
             const __grid_constant__ CUtensorMap tm_wq, const __grid_constant__ CUtensorMap tm_woa,
             const __grid_constant__ CUtensorMap tm_wob, const Params prm) {
  extern __shared__ uint8_t smem_raw[];
  uint32_t sb = (smem_u32(smem_raw) + 1023u) & ~1023u;
  uint8_t* sgen = smem_raw + (sb - smem_u32(smem_raw));
  asm volatile("mov.u32 %0, %0;" : "+r"(sb));
  const int tid = threadIdx.x, lane = tid & 31;
  const int warp = __shfl_sync(~0u, tid >> 5, 0), wg = warp >> 2;
  const int pt = blockIdx.x >> 3, hp = blockIdx.x & 7;
  const uint32_t bars = sb + OFF_BAR;
  auto BAR = [&](int i) { return bars + 8u * i; };
  const unsigned epoch = g_epoch & 1;

  if (tid == 0) { PROF_MARK(0); PROF_CLK(30); PROF2(15); }
  auto load_proj = [&](int c, int g) {
    mbar_expect_tx(BAR(B_FULL + g), 49152);
    tma_2d(sb + OFF_X + c * 16384, &tm_x, c * 64, pt * 128, BAR(B_FULL + g));
    tma_2d(sb + OFF_RING + g * 32768, &tm_wq, hp * 56, c * 64, BAR(B_FULL + g));
#pragma unroll 1
    for (int j = 0; j < 3; j++) tma_2d(sb + OFF_RING + g * 32768 + 8192 + j * 8192, &tm_wqkv, j * DM + hp * 56, c * 64, BAR(B_FULL + g));
  };
  if (elect_one()) {
    const int i = warp == 16 ? 0 : (warp == 0 ? 16 : warp);
    if (i < B_N) {
      int cnt = (i >= B_EMPTY && i < B_WO) || i > B_SIG || i == B_X0FREE || i == B_X1FREE ? 16 : 1;
      if (i == B_BUILD) cnt = 512;
      if (i == B_SIG || i == B_QSQ) cnt = 8;
      mbar_init(BAR(i), cnt);
      fence_async_smem();
    }
    if (warp == 16) load_proj(0, 0);
  }
  __syncthreads();
  if (tid == 0) PROF2(14);

  if (wg == 4) {
    asm volatile("setmaxnreg.dec.sync.aligned.u32 32;");
    if (warp == 16) {
      if (elect_one()) {
        int g = 1, nkv = 8;
        uint32_t par = 1;
#pragma unroll 1
        for (int n = 1; n < 14 + nkv; n++) {
          if (n == 7) { PROF_MARK(20); cnt_wait(C_KV, NCTA); PROF_MARK(21); fence_async_all(); }
          if (n == 15) {
            mbar_wait(BAR(B_SLOW), 0);
            if (*(volatile int*)(sgen + OFF_RED)) nkv = 26;
          }
          const int j = n - 7 - nkv;
          if (j == 0 || j == 3) {
            PROF3(j ? 11 : 8);
            cnt_wait((j ? C_OB : C_OA) + pt, 8);
            PROF3(j ? 12 : 9);
            PROF_MARK(26);
            fence_async_all();
          }
          mbar_wait(BAR(B_EMPTY + g), par);
          if (n < 7) load_proj(n, g);
          else {
            mbar_expect_tx(BAR(B_FULL + g), 32768);
            bulk_g2s(sb + OFF_RING + g * 32768, j < 0 ? g_kv_img + ((n - 7) & 7) * 32768 : g_o_img + (size_t)(pt * 7 + j) * 32768, 32768,
                     BAR(B_FULL + g));
          }
          if (++g == 3) { g = 0; par ^= 1; }
        }
        if (atomicAdd(&g_cnt[C_DONE * 32], 1u) == NCTA - 1) {
#pragma unroll 1
          for (int i = 0; i < C_N; i++) g_cnt[i * 32] = 0;
          g_epoch = epoch ^ 1;
        }
      }
    } else {
      if (warp == 18) {
        if (elect_one()) {
#pragma unroll 1
          for (int i = 0; i < 4; i++) {
            mbar_wait(BAR(B_SIG + i), 0);
            PROF3(2 * i);
            cnt_arrive(i == 0 ? C_KV : i == 1 ? C_PART : (i == 2 ? C_OA : C_OB) + pt);
            PROF3(2 * i + 1);
            if (i == 1 || i == 2) {
              mbar_wait(BAR(B_X0FREE + i - 1), 0);
              mbar_expect_tx(BAR(B_WO + i - 1), 57344);
#pragma unroll 1
              for (int c = 0; c < 7; c++)
                tma_2d(sb + OFF_WO + (i - 1) * 57344 + c * 8192, i == 1 ? &tm_woa : &tm_wob, hp * 56, c * 64, BAR(B_WO + i - 1));
            }
          }
        }
      } else if (warp == 19) {
        if (lane == 0) {
          mbar_wait(BAR(B_SIG + 0), 0);
          cnt_wait(C_KV, NCTA);
        }
        __syncwarp();
        float ksq = 0.f, vsq = 0.f;
#pragma unroll
        for (int sl = 0; sl < 4; sl++) {
          float4 a = ldcg_f4(g_ksq + sl * 128 + lane * 4), b = ldcg_f4(g_vsq + sl * 128 + lane * 4);
          float m = fmaxf(fmaxf(a.x, a.y), fmaxf(a.z, a.w));
          m = __uint_as_float(__reduce_max_sync(~0u, __float_as_uint(m)));
          ksq += m;
          vsq = fmaxf(vsq, fmaxf(fmaxf(b.x, b.y), fmaxf(b.z, b.w)));
        }
        mbar_wait(BAR(B_QSQ), 0);
        const float4 qa4 = ((const float4*)(sgen + OFF_QSQ))[lane], qb4 = ((const float4*)(sgen + OFF_QSQ))[32 + lane];
        const float qmax = fmaxf(fmaxf(fmaxf(qa4.x, qa4.y), fmaxf(qa4.z, qa4.w)), fmaxf(fmaxf(qb4.x, qb4.y), fmaxf(qb4.z, qb4.w)));
        const bool slow = __any_sync(~0u, !(qmax * ksq <= 98.f * 98.f) || !(vsq <= 2.0e8f));
        if (lane == 0) {
          *(volatile int*)(sgen + OFF_RED) = slow;
          mbar_arrive(BAR(B_SLOW), 1);
        }
      } else {
        float4* z = (float4*)(g_kvacc[epoch ^ 1] + blockIdx.x * 256) + lane;
        z[0] = make_float4(0.f, 0.f, 0.f, 0.f);
        z[32] = make_float4(0.f, 0.f, 0.f, 0.f);
        if (lane == 0) {
          mbar_wait(BAR(B_SIG + 1), 0);
          cnt_wait(C_PART, NCTA);
          PROF_MARK(23);
        }
        __syncwarp();
        const float* src = g_kvacc[epoch] + hp * 4096 + lane * 8;
#pragma unroll 2
        for (int i = 0; i < 16; i++) {
          const float4 a = ldcg_f4(src + i * 256), b = ldcg_f4(src + i * 256 + 4);
          sts128(sb + OFF_KVR + sw64_off(i * 8 + (lane >> 2), (lane & 3) * 8),
                 make_uint4(pack_bf16(a.x, a.y), pack_bf16(a.z, a.w), pack_bf16(b.x, b.y), pack_bf16(b.z, b.w)));
        }
        ((float4*)(sgen + OFF_GATE))[lane] = ldcg_f4(g_gate + pt * 128 + lane * 4);
        fence_async_smem();
        __syncwarp();
        if (lane == 0) mbar_arrive(BAR(B_KVR), 1);
      }
    }
  } else {
    asm volatile("setmaxnreg.inc.sync.aligned.u32 112;");
    const int mh = wg & 1, nh = wg >> 1, wq = warp & 3;
    if (tid < DM) {
      const __nv_bfloat16* src = (hp < 4 ? prm.wk : prm.wv) + tid * DH + (hp & 3) * 8;
      cp_async8(sb + OFF_SLC + tid * 16, src);
      if ((hp & 3) != 3) cp_async8(sb + OFF_SLC + tid * 16 + 8, src + 4);
      if (tid < 392) {
        const int row = tid / 7, e = row >= DH;
        cp_async8(sb + OFF_WPH + e * 2048 + sw64_off(row - DH * e, (tid % 7) * 4), prm.w_phi + 2 * hp * DH * DH + tid * 4);
      } else {
        const int row = tid - 392, e = row >= DH;
        sts64(sb + OFF_WPH + e * 2048 + sw64_off(row - DH * e, 28), 0u, 0u);
      }
      if ((hp & 3) == 3) sts64(sb + OFF_SLC + tid * 16 + 8, hp == 3 ? (uint32_t)((const unsigned short*)prm.gate_w)[tid] : 0u, 0u);
    } else if (tid < DM + 32) {
      sts128(sb + OFF_WPH + ((tid - DM) >> 4) * 2048 + 28 * 64 + ((tid - DM) & 15) * 16, make_uint4(0, 0, 0, 0));
    }
    asm volatile("cp.async.mbarrier.arrive.noinc.shared::cta.b64 [%0];" ::"r"(BAR(B_BUILD)) : "memory");
    const int lq = lane & 3;
    const int rowl = wq * 16 + (lane >> 2);
    const int row0 = mh * 64 + rowl;
    int slot = 0, prev = 0;
    uint32_t par = 0;
    {
      float acc0[28], acc1[28], accs[4];
      const uint64_t dR = make_desc(sb + OFF_RING + nh * 16384, 1024, 1024, 1);
      const int lr = wq * 16 + (lane & 7) + ((lane >> 3) & 1) * 8;
      const uint32_t xa = sb + OFF_X + mh * 8192 + lr * 128 + (((lane >> 4) ^ (lr & 7)) << 4);
#pragma unroll
      for (int i = 0; i < 28; i++) acc0[i] = acc1[i] = 0.f;
#pragma unroll
      for (int i = 0; i < 4; i++) accs[i] = 0.f;
      if (nh == 1) { mbar_wait(BAR(B_BUILD), 0); fence_async_smem(); }
#pragma unroll 1
      for (int c = 0; c < 7; c++) {
        mbar_wait(BAR(B_FULL + slot), par);
        uint32_t a[16];
#pragma unroll
        for (int ks = 0; ks < 4; ks++) ldsm4(a + 4 * ks, (xa + c * 16384) ^ (ks << 5));
        const uint64_t dB = dR + slot * 2048;
        wg_fence();
#pragma unroll
        for (int ks = 0; ks < 4; ks++) {
          wgmma_rs_n56_tb1<1>(acc0, a[4 * ks], a[4 * ks + 1], a[4 * ks + 2], a[4 * ks + 3], dB + ks * 128);
          wgmma_rs_n56_tb1<1>(acc1, a[4 * ks], a[4 * ks + 1], a[4 * ks + 2], a[4 * ks + 3], dB + 512 + ks * 128);
        }
        if (nh == 1) {
          const uint64_t dSlc = make_desc(sb + OFF_SLC + c * 1024, 128, 128, 0);
#pragma unroll
          for (int ks = 0; ks < 4; ks++) wgmma_rs_n8_tb1<1>(accs, a[4 * ks], a[4 * ks + 1], a[4 * ks + 2], a[4 * ks + 3], dSlc + ks * 16);
        }
        wg_commit();
        wg_wait<0>();
        if (lane == 0) mbar_arrive(BAR(B_EMPTY + slot), 1);
        if (++slot == 3) { slot = 0; par ^= 1; }
      }
      fence_regs(acc0); fence_regs(acc1); fence_regs(accs);
      if (tid == 0) PROF_MARK(2);
      if (tid == 256) PROF_MARK(3);
      if (nh == 0) {
        float sq[4] = {0.f, 0.f, 0.f, 0.f};
#pragma unroll
        for (int i = 0; i < 28; i++) acc0[i] *= 0.18898223650461362f * 1.4426950408889634f;
#pragma unroll
        for (int j = 0; j < 7; j++) {
#pragma unroll
          for (int rr = 0; rr < 2; rr++) {
            const float s2 = acc0[4 * j + 2 * rr] * acc0[4 * j + 2 * rr] + acc0[4 * j + 2 * rr + 1] * acc0[4 * j + 2 * rr + 1];
            if (j < 3) sq[rr] += s2;
            else if (j > 3) sq[2 + rr] += s2;
            else { sq[rr] += (lq < 2) ? s2 : 0.f; sq[2 + rr] += (lq < 2) ? 0.f : s2; }
          }
        }
#pragma unroll
        for (int i = 0; i < 4; i++) sq[i] = quad_sum(sq[i]);
        const float mine = lq == 0 ? sq[0] : lq == 1 ? sq[1] : lq == 2 ? sq[2] : sq[3];
        ((float*)(sgen + OFF_QSQ))[(mh + (lq & 2)) * 64 + rowl + 8 * (lq & 1)] = mine <= 3.0e38f ? mine : __int_as_float(0x7f800000);
        __syncwarp();
        if (lane == 0) mbar_arrive(BAR(B_QSQ), 1);
      } else {
        const int sl = hp & 3;
        const bool isk = hp < 4, real = (sl < 3) || (lq < 2);
        const int pos = pt * 128 + row0, kr = pos & 63;
        uint8_t* dst = g_kv_img + (pos >> 6) * 8192 + (isk ? 0 : 4096) + sw64_off(kr, sl * 8 + 2 * lq);
        const uint32_t pat = isk ? POLY_PAT >> (kr >> 3) : 0u;
        float mxv = 0.f;
#pragma unroll
        for (int rr = 0; rr < 2; rr++) {
          const float v0 = accs[2 * rr], v1 = accs[2 * rr + 1];
          const bool poly = (pat >> rr) & 1;
          const float sc = poly ? 2.f : 1.f;
          const float s2 = quad_sum(real ? v0 * v0 + v1 * v1 : 0.f);
          mxv = fmaxf(mxv, s2 <= 3.0e38f ? s2 : __int_as_float(0x7f800000));
          const uint32_t padv = lq == 2 ? (poly ? 0x443F4000u : 0x00003F80u) : (poly ? 0x3AB03F4Du : 0u);
          *(uint32_t*)(dst + rr * 512) = real ? pack_bf16(sc * v0, sc * v1) : padv;
          if (hp == 3 && lq == 2) g_gate[pos + 8 * rr] = rcpf(1.f + ex2f(-1.4426950408889634f * v0));
        }
        mxv = __uint_as_float(__reduce_max_sync(~0u, __float_as_uint(mxv)));
        if (lane == 0) (isk ? g_ksq : g_vsq)[sl * 128 + pt * 8 + mh * 4 + wq] = mxv;
        __syncwarp();
        if (lane == 0) mbar_arrive(BAR(B_SIG + 0), 1);
      }
      if (tid == 0) PROF_MARK(4);
      if (tid == 256) PROF_MARK(5);
      uint32_t h0[14], h1[14];
#pragma unroll
      for (int i = 0; i < 14; i++) { h0[i] = pack_bf16(acc0[2 * i], acc0[2 * i + 1]); h1[i] = pack_bf16(acc1[2 * i], acc1[2 * i + 1]); }
      bar_sync(1, 512);
      if (tid == 0) PROF_MARK(6);
#pragma unroll 1
      for (int r = 0; r < 2; r++) {
        store_heads(sb + (r ? (nh ? OFF_VA : OFF_QA) : (nh ? OFF_KA : OFF_QP)), h0,
                    (r & nh) ? 0x00003F80u : (r | nh) ? 0u : 0x3F800000u, (r | nh) ? 0u : 0x3F803F80u, row0, lq);
#pragma unroll
        for (int i = 0; i < 14; i++) h0[i] = h1[i];
      }
      fence_async_smem();
      bar_sync(1, 512);
      if (tid == 0) PROF_MARK(7);
    }
    const uint64_t dP = make_desc(sb + OFF_PHI + wg * 8192, 1024, 1024, 1);
    {
      float kv[16];
#pragma unroll
      for (int i = 0; i < 16; i++) kv[i] = 0.f;
#pragma unroll 1
      for (int r = 0; r < 2; r++) {
        const uint64_t dA = make_desc(sb + (r ? OFF_QA : OFF_KA) + nh * 8192 + mh * 4096, 512, 512, 2);
        const uint64_t dB = make_desc(sb + OFF_WPH + nh * 2048, 512, 512, 2);
        float pa[16];
        wg_fence();
        wgmma_ss_n32_ta0_tb1<0>(pa, dA, dB);
        wgmma_ss_n32_ta0_tb1<1>(pa, dA + 2, dB + 64);
        wg_commit();
        wg_wait<0>();
        fence_regs(pa);
        uint32_t ph[16];
        feature_map(pa, ph, lq);
        if (r) bar_sync(4 + wg, 128);
        const uint32_t rb = sb + OFF_PHI + wg * 8192 + rowl * 128 + lq * 4 + ((rowl & 7) << 4);
#pragma unroll
        for (int ch = 0; ch < 8; ch++) { sts32(rb ^ (ch << 4), ph[2 * ch]); sts32((rb ^ (ch << 4)) + 1024, ph[2 * ch + 1]); }
        fence_async_smem();
        bar_sync(4 + wg, 128);
        if (r == 0) {
          const uint64_t dV = make_desc(sb + OFF_VA + nh * 8192 + mh * 4096, 512, 512, 2);
          wg_fence();
#pragma unroll
          for (int ks = 0; ks < 4; ks++) wgmma_ss_n32_ta1_tb1<1>(kv, dP + ks * 128, dV + ks * 64);
          wg_commit();
          if (tid == 0) PROF_MARK(28);
        }
      }
      wg_wait<0>();
      fence_regs(kv);
      float* dst = g_kvacc[epoch] + (2 * hp + nh) * 2048 + rowl * 32 + 2 * lq;
#pragma unroll
      for (int j = 0; j < 8; j++)
        asm volatile("red.global.add.v2.f32 [%0], {%1, %2};" ::"l"(dst + 8 * (j >> 1) + 256 * (j & 1)), "f"(kv[2 * j]), "f"(kv[2 * j + 1]) : "memory");
      __syncwarp();
      if (lane == 0) mbar_arrive(BAR(B_SIG + 1), 1);
    }
    {
      const uint64_t dK = make_desc(sb + OFF_RING, 512, 512, 2);
      const uint64_t dhi = dK & 0xffffffff00000000ull;
      const uint32_t dlo0 = (uint32_t)dK;
      uint32_t ok = 0, q[8];
      float o[16];
#pragma unroll
      for (int i = 0; i < 16; i++) o[i] = 0.f;
      {
        const int r = mh * 64 + wq * 16 + (lane & 7) + ((lane >> 3) & 1) * 8;
        ldsm4(q, sb + OFF_QP + nh * 8192 + sw64_off(r, (lane >> 4) * 8));
        ldsm4(q + 4, sb + OFF_QP + nh * 8192 + sw64_off(r, 16 + (lane >> 4) * 8));
        __syncwarp();
        if (lane == 0) mbar_arrive(BAR(B_X0FREE), 1);
      }
      if (tid == 0) PROF_MARK(10);
      const int qb = QB_AT;
#pragma unroll 1
      for (int it = 0; it <= 8; it++) {
        uint32_t p[16];
        if ((tid & 127) == 0) PROF4(wg * 32 + it * 3);
        if (it == qb || it == 8) {
          float t[16];
          wg_wait<0>();
          fence_regs(o);
          if (it < 8) {
            if (tid == 0) PROF_MARK(11);
            mbar_wait(BAR(B_KVR), 0);
            const uint64_t dR = make_desc(sb + OFF_KVR + nh * 4096, 512, 512, 2);
            wg_fence();
            wgmma_ss_n32_ta0_tb1<0>(t, dP, dR);
#pragma unroll
            for (int ks = 1; ks < 4; ks++) wgmma_ss_n32_ta0_tb1<1>(t, dP + ks * 2, dR + ks * 64);
            wg_commit();
            wg_wait<0>();
            fence_regs(t);
            if (lane == 0) mbar_arrive(BAR(B_X1FREE), 1);
          } else {
            if (lane == 0) mbar_arrive(BAR(B_EMPTY + prev), 1);
            if (tid == 0) PROF_MARK(13);
            mbar_wait(BAR(B_SLOW), 0);
            if (__builtin_expect(__any_sync(~0u, *(volatile int*)(sgen + OFF_RED)), 0)) {
              uint32_t qz[8];
#pragma unroll
              for (int i = 0; i < 8; i++) qz[i] = (i >= 6 && lq >= 2) ? 0u : q[i];
              float m0 = -3.0e38f, m1 = -3.0e38f, o2[16];
              int sl2 = slot;
              uint32_t par2 = par;
#pragma unroll 1
              for (int j64 = 0; j64 < 32; j64++) {
                float s[32];
                mbar_wait(BAR(B_FULL + sl2), par2);
                const uint32_t lo = dlo0 + sl2 * 2048 + (j64 & 3) * 512;
                wg_fence();
                wgmma_rs_n64_tb0<0>(s, qz[0], qz[1], qz[2], qz[3], dhi | lo);
                wgmma_rs_n64_tb0<1>(s, qz[4], qz[5], qz[6], qz[7], dhi | (lo + 2));
                wg_commit();
                wg_wait<0>();
                fence_regs(s);
#pragma unroll
                for (int j = 0; j < 8; j++) {
                  const float sc = ((POLY_PAT >> j) & 1) ? 0.5f : 1.f;
                  m0 = fmaxf(m0, fmaxf(s[4 * j], s[4 * j + 1]) * sc);
                  m1 = fmaxf(m1, fmaxf(s[4 * j + 2], s[4 * j + 3]) * sc);
                }
                if ((j64 & 3) == 3) {
                  if (lane == 0) mbar_arrive(BAR(B_EMPTY + sl2), 1);
                  if (++sl2 == 3) { sl2 = 0; par2 ^= 1; }
                }
              }
              m0 = quad_max(m0); m1 = quad_max(m1);
#pragma unroll
              for (int i = 0; i < 16; i++) o2[i] = 0.f;
#pragma unroll 1
              for (int j64 = 0; j64 < 32; j64++) {
                float s[32];
                mbar_wait(BAR(B_FULL + sl2), par2);
                const uint32_t lo = dlo0 + sl2 * 2048 + (j64 & 3) * 512;
                wg_fence();
                wgmma_rs_n64_tb0<0>(s, qz[0], qz[1], qz[2], qz[3], dhi | lo);
                wgmma_rs_n64_tb0<1>(s, qz[4], qz[5], qz[6], qz[7], dhi | (lo + 2));
                wg_commit();
                wg_wait<0>();
                fence_regs(s);
                uint32_t ps[16];
#pragma unroll
                for (int j = 0; j < 8; j++) {
                  const float sc = ((POLY_PAT >> j) & 1) ? 0.5f : 1.f;
                  ps[2 * j] = pack_bf16(ex2f(fmaf(s[4 * j], sc, -m0)), ex2f(fmaf(s[4 * j + 1], sc, -m0)));
                  ps[2 * j + 1] = pack_bf16(ex2f(fmaf(s[4 * j + 2], sc, -m1)), ex2f(fmaf(s[4 * j + 3], sc, -m1)));
                }
                wg_fence();
#pragma unroll
                for (int ks = 0; ks < 4; ks++)
                  wgmma_rs_n32_tb1<1>(o2, ps[4 * ks], ps[4 * ks + 1], ps[4 * ks + 2], ps[4 * ks + 3], dhi | (lo + 256 + ks * 64));
                wg_commit();
                wg_wait<0>();
                fence_regs(o2);
                if ((j64 & 3) == 3) {
                  if (lane == 0) mbar_arrive(BAR(B_EMPTY + sl2), 1);
                  if (++sl2 == 3) { sl2 = 0; par2 ^= 1; }
                }
              }
#pragma unroll 1
              for (int j = 0; j < 2; j++) {
                mbar_wait(BAR(B_FULL + sl2), par2);
                __syncwarp();
                if (lane == 0) mbar_arrive(BAR(B_EMPTY + sl2), 1);
                if (++sl2 == 3) { sl2 = 0; par2 ^= 1; }
              }
#pragma unroll
              for (int i = 0; i < 16; i++) o[i] = o2[i];
            }
#pragma unroll
            for (int i = 0; i < 16; i++) t[i] = o[i];
          }
          const int br = it == 8;
          const float eps = br ? 0.f : 1e-6f;
          const float g0 = ((const float*)(sgen + OFF_GATE))[row0], g1 = ((const float*)(sgen + OFF_GATE))[row0 + 8];
          const float d0 = __shfl_sync(~0u, t[12], (lane & ~3) | 2), d1 = __shfl_sync(~0u, t[14], (lane & ~3) | 2);
          const float r0 = (br ? 1.f - g0 : g0) * rcpf(d0 + eps), r1 = (br ? 1.f - g1 : g1) * rcpf(d1 + eps);
          uint8_t* img = g_o_img + (size_t)((pt * 2 + br) * 14 + mh) * 8192 + rowl * 128;
          const int col0 = (2 * hp + nh) * DH + 2 * lq;
#pragma unroll
          for (int j = 0; j < 4; j++) {
            const int col = col0 + 8 * j;
            uint8_t* gp = img + (uint32_t)((col >> 6) * 16384 + ((((col >> 3) ^ rowl) & 7) << 4) + (col & 7) * 2);
            const uint32_t v0 = pack_bf16(t[4 * j] * r0, t[4 * j + 1] * r0), v1 = pack_bf16(t[4 * j + 2] * r1, t[4 * j + 3] * r1);
            if (j < 3 || lq < 2) { *(uint32_t*)gp = v0; *(uint32_t*)(gp + 1024) = v1; }
          }
          __syncwarp();
          if (lane == 0) mbar_arrive(BAR(B_SIG + 2 + br), 1);
          if (tid == 0) PROF_MARK(12 + 2 * br);
          if (br) break;
        }
        const uint32_t lo = dlo0 + slot * 2048;
        if ((tid & 127) == 0) PROF4(wg * 32 + it * 3 + 1);
        if (!ok) mbar_wait(BAR(B_FULL + slot), par);
        if ((tid & 127) == 0) PROF4(wg * 32 + it * 3 + 2);
        int nslot = slot + 1;
        uint32_t npar = par;
        if (nslot == 3) { nslot = 0; npar ^= 1; }
        {
          float s[32];
          wg_fence();
          wgmma_rs_n64_tb0<0>(s, q[0], q[1], q[2], q[3], dhi | lo);
          wgmma_rs_n64_tb0<1>(s, q[4], q[5], q[6], q[7], dhi | (lo + 2));
          wg_commit();
#pragma unroll
          for (int u = 0; u < 4; u++) {
            wg_wait<0>();
            fence_regs(s);
            if (u == 0 && lane == 0 && it > 0) mbar_arrive(BAR(B_EMPTY + prev), 1);
            if (u == 2) ok = mbar_test(BAR(B_FULL + nslot), npar);
#pragma unroll
            for (int j = 0; j < 8; j++) {
              if ((POLY_PAT >> j) & 1) {
                p[2 * j] = exp2_pair_fma(s[4 * j], s[4 * j + 1], 0x3F003F00u, 0x00030003u);
                p[2 * j + 1] = exp2_pair_fma(s[4 * j + 2], s[4 * j + 3], 0x3F003F00u, 0x00030003u);
              } else {
                p[2 * j] = pack_bf16(ex2f(s[4 * j]), ex2f(s[4 * j + 1]));
                p[2 * j + 1] = pack_bf16(ex2f(s[4 * j + 2]), ex2f(s[4 * j + 3]));
              }
            }
            wg_fence();
#pragma unroll
            for (int ks = 0; ks < 4; ks++)
              wgmma_rs_n32_tb1<1>(o, p[4 * ks], p[4 * ks + 1], p[4 * ks + 2], p[4 * ks + 3], dhi | (lo + u * 512 + 256 + ks * 64));
            if (u < 3) {
              wgmma_rs_n64_tb0<0>(s, q[0], q[1], q[2], q[3], dhi | (lo + (u + 1) * 512));
              wgmma_rs_n64_tb0<1>(s, q[4], q[5], q[6], q[7], dhi | (lo + (u + 1) * 512 + 2));
            }
            wg_commit();
          }
        }
        prev = slot; slot = nslot; par = npar;
      }
      wg_wait<0>();
    }
    if (nh == 1) return;
    {
      float acc0[28], acc1[28];
#pragma unroll
      for (int i = 0; i < 28; i++) acc0[i] = acc1[i] = 0.f;
      const uint64_t dS = make_desc(sb + OFF_WO, 1024, 1024, 1);
      const uint64_t dR = make_desc(sb + OFF_RING + mh * 8192, 1024, 1024, 1);
#pragma unroll 1
      for (int c = 0; c < 7; c++) {
        mbar_wait(BAR(B_WO + (c >= 3)), 0);
        mbar_wait(BAR(B_FULL + slot), par);
        const uint64_t dA = dR + slot * 2048, dB = dS + c * 1024;
        wg_fence();
#pragma unroll
        for (int ks = 0; ks < 4; ks++) {
          wgmma_ss_n56_ta0_tb1<1>(acc0, dA + ks * 2, dB + ks * 128);
          wgmma_ss_n56_ta0_tb1<1>(acc1, dA + 1024 + ks * 2, dB + 512 + ks * 128);
        }
        wg_commit();
        if (c < 4) {
          wg_wait<0>();
          if (lane == 0) mbar_arrive(BAR(B_EMPTY + slot), 2);
        }
        if (++slot == 3) { slot = 0; par ^= 1; }
      }
      wg_wait<0>();
      fence_regs(acc0); fence_regs(acc1);
      if (tid == 0) PROF_MARK(17);
      __nv_bfloat16* op = prm.out + (size_t)(pt * 128 + row0) * DM + hp * 56 + 2 * lq;
#pragma unroll
      for (int j = 0; j < 7; j++) {
        *(uint32_t*)(op + 8 * j) = pack_bf16(acc0[4 * j] + acc1[4 * j], acc0[4 * j + 1] + acc1[4 * j + 1]);
        *(uint32_t*)(op + 8 * DM + 8 * j) = pack_bf16(acc0[4 * j + 2] + acc1[4 * j + 2], acc0[4 * j + 3] + acc1[4 * j + 3]);
      }
      if (tid == 0) { PROF_MARK(18); PROF_CLK(31); }
    }
  }
}

typedef CUresult (*EncodeFn)(CUtensorMap*, CUtensorMapDataType, cuuint32_t, void*, const cuuint64_t*, const cuuint64_t*,
                             const cuuint32_t*, const cuuint32_t*, CUtensorMapInterleave, CUtensorMapSwizzle,
                             CUtensorMapL2promotion, CUtensorMapFloatOOBfill);

void make_map(EncodeFn enc, CUtensorMap* tm, const void* ptr, uint64_t cols, uint64_t rows, uint32_t box_rows) {
  cuuint64_t dims[2] = {cols, rows};
  cuuint64_t strides[1] = {cols * 2};
  cuuint32_t box[2] = {64, box_rows};
  cuuint32_t es[2] = {1, 1};
  enc(tm, CU_TENSOR_MAP_DATA_TYPE_BFLOAT16, 2, const_cast<void*>(ptr), dims, strides, box, es, CU_TENSOR_MAP_INTERLEAVE_NONE,
      CU_TENSOR_MAP_SWIZZLE_128B, CU_TENSOR_MAP_L2_PROMOTION_L2_128B, CU_TENSOR_MAP_FLOAT_OOB_FILL_NONE);
}

}

extern "C" void kernel_launch(void* const* d_in, const int* in_sizes, int n_in, void* d_out, int out_size) {
  (void)in_sizes; (void)n_in; (void)out_size;
  static EncodeFn enc = nullptr;
  if (!enc) {
    void* fn = nullptr;
    cudaDriverEntryPointQueryResult qr;
    cudaGetDriverEntryPoint("cuTensorMapEncodeTiled", &fn, cudaEnableDefault, &qr);
    enc = (EncodeFn)fn;
    cudaFuncSetAttribute(fused_kernel, cudaFuncAttributeMaxDynamicSharedMemorySize, SMEM_BYTES);
  }
  CUtensorMap tm_x, tm_wqkv, tm_wq, tm_woa, tm_wob;
  make_map(enc, &tm_x, d_in[0], DM, S_LEN, 128);
  make_map(enc, &tm_wqkv, d_in[1], 3 * DM, DM, 64);
  make_map(enc, &tm_wq, d_in[5], DM, DM, 64);
  make_map(enc, &tm_woa, d_in[3], DM, DM, 64);
  make_map(enc, &tm_wob, d_in[8], DM, DM, 64);
  Params prm;
  prm.w_phi = (const __nv_bfloat16*)d_in[2];
  prm.wk = (const __nv_bfloat16*)d_in[6];
  prm.wv = (const __nv_bfloat16*)d_in[7];
  prm.gate_w = (const __nv_bfloat16*)d_in[9];
  prm.out = (__nv_bfloat16*)d_out;
  fused_kernel<<<NCTA, NTHREADS, SMEM_BYTES>>>(tm_x, tm_wqkv, tm_wq, tm_woa, tm_wob, prm);
}
```

```cpp
#include <cuda_runtime.h>
#include <cuda_bf16.h>
#include <cuda.h>
#include <stdint.h>

namespace {

constexpr int S_LEN = 2048, DM = 448, DH = 28;
constexpr int NCTA = 128;
constexpr int NTHREADS = 640;
constexpr uint32_t POLY_PAT = 0x57;

#define QB_AT (3 + nh)

constexpr int OFF_X = 0;
constexpr int OFF_PHIK = 0;
constexpr int OFF_VA = 32768;
constexpr int OFF_PHIQ = 57344;
constexpr int OFF_KVR = 90112;
constexpr int OFF_QP = 98304;
constexpr int OFF_WO = 0;
constexpr int OFF_RING = 114688;
constexpr int OFF_WBD = 212992;
constexpr int OFF_SLC = 221184;
constexpr int OFF_QSQ = 228352;
constexpr int OFF_GATE = 229376;
constexpr int OFF_RED = 229888;
constexpr int OFF_BAR = 229952;
constexpr int SMEM_BYTES = 230400 + 1024;

constexpr int B_FULL = 0, B_EMPTY = 3, B_WO = 6  , B_KVR = 8, B_X0FREE = 9, B_X1FREE = 10, B_QSQ = 11, B_SLOW = 12,
              B_BUILD = 13, B_SIG = 14  , B_N = 18;

constexpr int C_KV = 0, C_PART = 1, C_DONE = 3, C_OA = 4, C_OB = 20, C_N = 36;

__device__ __align__(1024) uint8_t g_kv_img[32 * 8192];
__device__ __align__(16) float g_ksq[512];
__device__ __align__(16) float g_vsq[512];
__device__ __align__(16) float g_gate[S_LEN];
__device__ __align__(1024) float g_kvacc[2][16 * 64 * 32];
__device__ unsigned g_epoch;
__device__ __align__(1024) uint8_t g_o_img[2 * 16 * 14 * 8192];
__device__ unsigned g_cnt[C_N * 32];

#define PROF4(i) do { } while (0)
#define PROF3(i) do { } while (0)
#define PROF2(i) do { } while (0)
#define PROF_CLK(i) do { } while (0)
#define PROF_MARK(i) do { } while (0)
__device__ __forceinline__ uint32_t smem_u32(const void* p) { return (uint32_t)__cvta_generic_to_shared(p); }
__device__ __forceinline__ void mbar_init(uint32_t a, int cnt) {
  asm volatile("mbarrier.init.shared::cta.b64 [%0], %1;" ::"r"(a), "r"(cnt) : "memory");
}
__device__ __forceinline__ void mbar_expect_tx(uint32_t a, uint32_t bytes) {
  asm volatile("mbarrier.arrive.expect_tx.shared::cta.b64 _, [%0], %1;" ::"r"(a), "r"(bytes) : "memory");
}
__device__ __forceinline__ void mbar_arrive(uint32_t a, uint32_t cnt) {
  asm volatile("mbarrier.arrive.shared::cta.b64 _, [%0], %1;" ::"r"(a), "r"(cnt) : "memory");
}
__device__ __forceinline__ void mbar_wait(uint32_t a, uint32_t parity) {
  asm volatile(
      "{\n.reg .pred p;\n.reg .u32 c;\nmov.u32 c, 0;\n"
      "W_%=:\nmbarrier.try_wait.parity.shared::cta.b64 p, [%0], %1;\n"
      "add.u32 c, c, 1;\nsetp.lt.and.u32 p, c, 0x40000, !p;\n@p bra W_%=;\n}"
      ::"r"(a), "r"(parity) : "memory");
}
__device__ __forceinline__ uint32_t mbar_test(uint32_t a, uint32_t parity) {
  uint32_t ok;
  asm volatile("{\n.reg .pred p;\nmbarrier.test_wait.parity.shared::cta.b64 p, [%1], %2;\nselp.u32 %0, 1, 0, p;\n}"
               : "=r"(ok) : "r"(a), "r"(parity) : "memory");
  return ok;
}
__device__ __forceinline__ bool elect_one() {
  uint32_t r;
  asm volatile("{\n.reg .pred p;\nelect.sync _|p, 0xffffffff;\nselp.u32 %0, 1, 0, p;\n}" : "=r"(r));
  return r != 0;
}
__device__ __forceinline__ void tma_2d(uint32_t dst, const CUtensorMap* tm, int c0, int c1, uint32_t bar) {
  asm volatile("cp.async.bulk.tensor.2d.shared::cluster.global.mbarrier::complete_tx::bytes [%0], [%1, {%3, %4}], [%2];"
               ::"r"(dst), "l"(tm), "r"(bar), "r"(c0), "r"(c1) : "memory");
}
__device__ __forceinline__ void bulk_g2s(uint32_t dst, const void* src, uint32_t bytes, uint32_t bar) {
  asm volatile("cp.async.bulk.shared::cluster.global.mbarrier::complete_tx::bytes [%0], [%1], %2, [%3];"
               ::"r"(dst), "l"(src), "r"(bytes), "r"(bar) : "memory");
}
__device__ __forceinline__ void cp_async8(uint32_t dst, const void* src) {
  asm volatile("cp.async.ca.shared.global [%0], [%1], 8;" ::"r"(dst), "l"(src) : "memory");
}
__device__ __forceinline__ void fence_async_smem() { asm volatile("fence.proxy.async.shared::cta;" ::: "memory"); }
__device__ __forceinline__ void fence_async_all() { asm volatile("fence.proxy.async.global;" ::: "memory"); }

__device__ __forceinline__ void bar_sync(int id, int n) { asm volatile("bar.sync %0, %1;" ::"r"(id), "r"(n) : "memory"); }
__device__ __forceinline__ void cnt_arrive(int idx) {
  asm volatile("red.release.gpu.global.add.u32 [%0], 1;" ::"l"(&g_cnt[idx * 32]) : "memory");
}
__device__ __forceinline__ void cnt_wait(int idx, unsigned target) {
  unsigned v, n = 0;
#pragma unroll 1
  while (true) {
    asm volatile("ld.acquire.gpu.global.u32 %0, [%1];" : "=r"(v) : "l"(&g_cnt[idx * 32]) : "memory");
    if (v >= target || ++n >= (1u << 18)) break;
    __nanosleep(32);
  }
}
__device__ __forceinline__ void wg_fence() { asm volatile("wgmma.fence.sync.aligned;" ::: "memory"); }
__device__ __forceinline__ void wg_commit() { asm volatile("wgmma.commit_group.sync.aligned;" ::: "memory"); }
template <int N> __device__ __forceinline__ void wg_wait() { asm volatile("wgmma.wait_group.sync.aligned %0;" ::"n"(N) : "memory"); }
template <int N> __device__ __forceinline__ void fence_regs(float (&d)[N]) {
#pragma unroll
  for (int i = 0; i < N; i++) asm volatile("" : "+f"(d[i])::"memory");
}
__device__ __forceinline__ uint64_t make_desc(uint32_t saddr, uint32_t lbo, uint32_t sbo, uint32_t swz) {
  return (uint64_t)((saddr & 0x3FFFF) >> 4) | ((uint64_t)(lbo >> 4) << 16) | ((uint64_t)(sbo >> 4) << 32) | ((uint64_t)swz << 62);
}
__device__ __forceinline__ float ex2f(float x) { float y; asm("ex2.approx.ftz.f32 %0, %1;" : "=f"(y) : "f"(x)); return y; }
__device__ __forceinline__ float rcpf(float x) { float y; asm("rcp.approx.ftz.f32 %0, %1;" : "=f"(y) : "f"(x)); return y; }
__device__ __forceinline__ uint32_t pack_bf16(float lo, float hi) {
  uint32_t r; asm("cvt.rn.bf16x2.f32 %0, %1, %2;" : "=r"(r) : "f"(hi), "f"(lo)); return r;
}
__device__ __forceinline__ uint32_t lop_and_or(uint32_t a, uint32_t m, uint32_t c) {
  uint32_t r; asm("lop3.b32 %0, %1, %2, %3, 0xEA;" : "=r"(r) : "r"(a), "r"(m), "r"(c)); return r;
}
__device__ __forceinline__ void sts32(uint32_t a, uint32_t v) { asm volatile("st.shared.b32 [%0], %1;" ::"r"(a), "r"(v) : "memory"); }
__device__ __forceinline__ void sts64(uint32_t a, uint32_t v0, uint32_t v1) { asm volatile("st.shared.v2.b32 [%0], {%1, %2};" ::"r"(a), "r"(v0), "r"(v1) : "memory"); }
__device__ __forceinline__ void sts128(uint32_t a, uint4 v) {
  asm volatile("st.shared.v4.b32 [%0], {%1, %2, %3, %4};" ::"r"(a), "r"(v.x), "r"(v.y), "r"(v.z), "r"(v.w) : "memory");
}
__device__ __forceinline__ float4 ldcg_f4(const float* p) {
  float4 v; asm volatile("ld.global.cg.v4.f32 {%0, %1, %2, %3}, [%4];" : "=f"(v.x), "=f"(v.y), "=f"(v.z), "=f"(v.w) : "l"(p) : "memory"); return v;
}
__device__ __forceinline__ void ldsm4(uint32_t* r, uint32_t a) {
  asm volatile("ldmatrix.sync.aligned.m8n8.x4.shared.b16 {%0, %1, %2, %3}, [%4];"
               : "=r"(r[0]), "=r"(r[1]), "=r"(r[2]), "=r"(r[3]) : "r"(a) : "memory");
}
__device__ __forceinline__ float quad_sum(float v) { v += __shfl_xor_sync(~0u, v, 1); v += __shfl_xor_sync(~0u, v, 2); return v; }
__device__ __forceinline__ float quad_max(float v) { v = fmaxf(v, __shfl_xor_sync(~0u, v, 1)); v = fmaxf(v, __shfl_xor_sync(~0u, v, 2)); return v; }

template <int SD> __device__ __forceinline__ void wgmma_ss_n56_ta0_tb1(float (&d)[28], uint64_t da, uint64_t db) {
  if (SD) asm volatile("wgmma.mma_async.sync.aligned.m64n56k16.f32.bf16.bf16 {%0, %1, %2, %3, %4, %5, %6, %7, %8, %9, %10, %11, %12, %13, %14, %15, %16, %17, %18, %19, %20, %21, %22, %23, %24, %25, %26, %27}, %28, %29, 1, 1, 1, 0, 1;\n"
    : "+f"(d[0]), "+f"(d[1]), "+f"(d[2]), "+f"(d[3]), "+f"(d[4]), "+f"(d[5]), "+f"(d[6]), "+f"(d[7]), "+f"(d[8]), "+f"(d[9]), "+f"(d[10]), "+f"(d[11]), "+f"(d[12]), "+f"(d[13]), "+f"(d[14]), "+f"(d[15]), "+f"(d[16]), "+f"(d[17]), "+f"(d[18]), "+f"(d[19]), "+f"(d[20]), "+f"(d[21]), "+f"(d[22]), "+f"(d[23]), "+f"(d[24]), "+f"(d[25]), "+f"(d[26]), "+f"(d[27])
    : "l"(da), "l"(db));
  else asm volatile("wgmma.mma_async.sync.aligned.m64n56k16.f32.bf16.bf16 {%0, %1, %2, %3, %4, %5, %6, %7, %8, %9, %10, %11, %12, %13, %14, %15, %16, %17, %18, %19, %20, %21, %22, %23, %24, %25, %26, %27}, %28, %29, 0, 1, 1, 0, 1;\n"
    : "=f"(d[0]), "=f"(d[1]), "=f"(d[2]), "=f"(d[3]), "=f"(d[4]), "=f"(d[5]), "=f"(d[6]), "=f"(d[7]), "=f"(d[8]), "=f"(d[9]), "=f"(d[10]), "=f"(d[11]), "=f"(d[12]), "=f"(d[13]), "=f"(d[14]), "=f"(d[15]), "=f"(d[16]), "=f"(d[17]), "=f"(d[18]), "=f"(d[19]), "=f"(d[20]), "=f"(d[21]), "=f"(d[22]), "=f"(d[23]), "=f"(d[24]), "=f"(d[25]), "=f"(d[26]), "=f"(d[27])
    : "l"(da), "l"(db));
}
template <int SD> __device__ __forceinline__ void wgmma_rs_n56_tb1(float (&d)[28], uint32_t a0, uint32_t a1, uint32_t a2, uint32_t a3, uint64_t db) {
  if (SD) asm volatile("wgmma.mma_async.sync.aligned.m64n56k16.f32.bf16.bf16 {%0, %1, %2, %3, %4, %5, %6, %7, %8, %9, %10, %11, %12, %13, %14, %15, %16, %17, %18, %19, %20, %21, %22, %23, %24, %25, %26, %27}, {%28, %29, %30, %31}, %32, 1, 1, 1, 1;\n"
    : "+f"(d[0]), "+f"(d[1]), "+f"(d[2]), "+f"(d[3]), "+f"(d[4]), "+f"(d[5]), "+f"(d[6]), "+f"(d[7]), "+f"(d[8]), "+f"(d[9]), "+f"(d[10]), "+f"(d[11]), "+f"(d[12]), "+f"(d[13]), "+f"(d[14]), "+f"(d[15]), "+f"(d[16]), "+f"(d[17]), "+f"(d[18]), "+f"(d[19]), "+f"(d[20]), "+f"(d[21]), "+f"(d[22]), "+f"(d[23]), "+f"(d[24]), "+f"(d[25]), "+f"(d[26]), "+f"(d[27])
    : "r"(a0), "r"(a1), "r"(a2), "r"(a3), "l"(db));
  else asm volatile("wgmma.mma_async.sync.aligned.m64n56k16.f32.bf16.bf16 {%0, %1, %2, %3, %4, %5, %6, %7, %8, %9, %10, %11, %12, %13, %14, %15, %16, %17, %18, %19, %20, %21, %22, %23, %24, %25, %26, %27}, {%28, %29, %30, %31}, %32, 0, 1, 1, 1;\n"
    : "=f"(d[0]), "=f"(d[1]), "=f"(d[2]), "=f"(d[3]), "=f"(d[4]), "=f"(d[5]), "=f"(d[6]), "=f"(d[7]), "=f"(d[8]), "=f"(d[9]), "=f"(d[10]), "=f"(d[11]), "=f"(d[12]), "=f"(d[13]), "=f"(d[14]), "=f"(d[15]), "=f"(d[16]), "=f"(d[17]), "=f"(d[18]), "=f"(d[19]), "=f"(d[20]), "=f"(d[21]), "=f"(d[22]), "=f"(d[23]), "=f"(d[24]), "=f"(d[25]), "=f"(d[26]), "=f"(d[27])
    : "r"(a0), "r"(a1), "r"(a2), "r"(a3), "l"(db));
}
template <int SD> __device__ __forceinline__ void wgmma_rs_n8_tb1(float (&d)[4], uint32_t a0, uint32_t a1, uint32_t a2, uint32_t a3, uint64_t db) {
  if (SD) asm volatile("wgmma.mma_async.sync.aligned.m64n8k16.f32.bf16.bf16 {%0, %1, %2, %3}, {%4, %5, %6, %7}, %8, 1, 1, 1, 1;\n"
    : "+f"(d[0]), "+f"(d[1]), "+f"(d[2]), "+f"(d[3])
    : "r"(a0), "r"(a1), "r"(a2), "r"(a3), "l"(db));
  else asm volatile("wgmma.mma_async.sync.aligned.m64n8k16.f32.bf16.bf16 {%0, %1, %2, %3}, {%4, %5, %6, %7}, %8, 0, 1, 1, 1;\n"
    : "=f"(d[0]), "=f"(d[1]), "=f"(d[2]), "=f"(d[3])
    : "r"(a0), "r"(a1), "r"(a2), "r"(a3), "l"(db));
}
template <int SD> __device__ __forceinline__ void wgmma_rs_n64_tb1(float (&d)[32], uint32_t a0, uint32_t a1, uint32_t a2, uint32_t a3, uint64_t db) {
  if (SD) asm volatile("wgmma.mma_async.sync.aligned.m64n64k16.f32.bf16.bf16 {%0, %1, %2, %3, %4, %5, %6, %7, %8, %9, %10, %11, %12, %13, %14, %15, %16, %17, %18, %19, %20, %21, %22, %23, %24, %25, %26, %27, %28, %29, %30, %31}, {%32, %33, %34, %35}, %36, 1, 1, 1, 1;\n"
    : "+f"(d[0]), "+f"(d[1]), "+f"(d[2]), "+f"(d[3]), "+f"(d[4]), "+f"(d[5]), "+f"(d[6]), "+f"(d[7]), "+f"(d[8]), "+f"(d[9]), "+f"(d[10]), "+f"(d[11]), "+f"(d[12]), "+f"(d[13]), "+f"(d[14]), "+f"(d[15]), "+f"(d[16]), "+f"(d[17]), "+f"(d[18]), "+f"(d[19]), "+f"(d[20]), "+f"(d[21]), "+f"(d[22]), "+f"(d[23]), "+f"(d[24]), "+f"(d[25]), "+f"(d[26]), "+f"(d[27]), "+f"(d[28]), "+f"(d[29]), "+f"(d[30]), "+f"(d[31])
    : "r"(a0), "r"(a1), "r"(a2), "r"(a3), "l"(db));
  else asm volatile("wgmma.mma_async.sync.aligned.m64n64k16.f32.bf16.bf16 {%0, %1, %2, %3, %4, %5, %6, %7, %8, %9, %10, %11, %12, %13, %14, %15, %16, %17, %18, %19, %20, %21, %22, %23, %24, %25, %26, %27, %28, %29, %30, %31}, {%32, %33, %34, %35}, %36, 0, 1, 1, 1;\n"
    : "=f"(d[0]), "=f"(d[1]), "=f"(d[2]), "=f"(d[3]), "=f"(d[4]), "=f"(d[5]), "=f"(d[6]), "=f"(d[7]), "=f"(d[8]), "=f"(d[9]), "=f"(d[10]), "=f"(d[11]), "=f"(d[12]), "=f"(d[13]), "=f"(d[14]), "=f"(d[15]), "=f"(d[16]), "=f"(d[17]), "=f"(d[18]), "=f"(d[19]), "=f"(d[20]), "=f"(d[21]), "=f"(d[22]), "=f"(d[23]), "=f"(d[24]), "=f"(d[25]), "=f"(d[26]), "=f"(d[27]), "=f"(d[28]), "=f"(d[29]), "=f"(d[30]), "=f"(d[31])
    : "r"(a0), "r"(a1), "r"(a2), "r"(a3), "l"(db));
}
template <int SD> __device__ __forceinline__ void wgmma_ss_n32_ta1_tb1(float (&d)[16], uint64_t da, uint64_t db) {
  if (SD) asm volatile("wgmma.mma_async.sync.aligned.m64n32k16.f32.bf16.bf16 {%0, %1, %2, %3, %4, %5, %6, %7, %8, %9, %10, %11, %12, %13, %14, %15}, %16, %17, 1, 1, 1, 1, 1;\n"
    : "+f"(d[0]), "+f"(d[1]), "+f"(d[2]), "+f"(d[3]), "+f"(d[4]), "+f"(d[5]), "+f"(d[6]), "+f"(d[7]), "+f"(d[8]), "+f"(d[9]), "+f"(d[10]), "+f"(d[11]), "+f"(d[12]), "+f"(d[13]), "+f"(d[14]), "+f"(d[15])
    : "l"(da), "l"(db));
  else asm volatile("wgmma.mma_async.sync.aligned.m64n32k16.f32.bf16.bf16 {%0, %1, %2, %3, %4, %5, %6, %7, %8, %9, %10, %11, %12, %13, %14, %15}, %16, %17, 0, 1, 1, 1, 1;\n"
    : "=f"(d[0]), "=f"(d[1]), "=f"(d[2]), "=f"(d[3]), "=f"(d[4]), "=f"(d[5]), "=f"(d[6]), "=f"(d[7]), "=f"(d[8]), "=f"(d[9]), "=f"(d[10]), "=f"(d[11]), "=f"(d[12]), "=f"(d[13]), "=f"(d[14]), "=f"(d[15])
    : "l"(da), "l"(db));
}
template <int SD> __device__ __forceinline__ void wgmma_ss_n32_ta0_tb1(float (&d)[16], uint64_t da, uint64_t db) {
  if (SD) asm volatile("wgmma.mma_async.sync.aligned.m64n32k16.f32.bf16.bf16 {%0, %1, %2, %3, %4, %5, %6, %7, %8, %9, %10, %11, %12, %13, %14, %15}, %16, %17, 1, 1, 1, 0, 1;\n"
    : "+f"(d[0]), "+f"(d[1]), "+f"(d[2]), "+f"(d[3]), "+f"(d[4]), "+f"(d[5]), "+f"(d[6]), "+f"(d[7]), "+f"(d[8]), "+f"(d[9]), "+f"(d[10]), "+f"(d[11]), "+f"(d[12]), "+f"(d[13]), "+f"(d[14]), "+f"(d[15])
    : "l"(da), "l"(db));
  else asm volatile("wgmma.mma_async.sync.aligned.m64n32k16.f32.bf16.bf16 {%0, %1, %2, %3, %4, %5, %6, %7, %8, %9, %10, %11, %12, %13, %14, %15}, %16, %17, 0, 1, 1, 0, 1;\n"
    : "=f"(d[0]), "=f"(d[1]), "=f"(d[2]), "=f"(d[3]), "=f"(d[4]), "=f"(d[5]), "=f"(d[6]), "=f"(d[7]), "=f"(d[8]), "=f"(d[9]), "=f"(d[10]), "=f"(d[11]), "=f"(d[12]), "=f"(d[13]), "=f"(d[14]), "=f"(d[15])
    : "l"(da), "l"(db));
}
template <int SD> __device__ __forceinline__ void wgmma_rs_n64_tb0(float (&d)[32], uint32_t a0, uint32_t a1, uint32_t a2, uint32_t a3, uint64_t db) {
  if (SD) asm volatile("wgmma.mma_async.sync.aligned.m64n64k16.f32.bf16.bf16 {%0, %1, %2, %3, %4, %5, %6, %7, %8, %9, %10, %11, %12, %13, %14, %15, %16, %17, %18, %19, %20, %21, %22, %23, %24, %25, %26, %27, %28, %29, %30, %31}, {%32, %33, %34, %35}, %36, 1, 1, 1, 0;\n"
    : "+f"(d[0]), "+f"(d[1]), "+f"(d[2]), "+f"(d[3]), "+f"(d[4]), "+f"(d[5]), "+f"(d[6]), "+f"(d[7]), "+f"(d[8]), "+f"(d[9]), "+f"(d[10]), "+f"(d[11]), "+f"(d[12]), "+f"(d[13]), "+f"(d[14]), "+f"(d[15]), "+f"(d[16]), "+f"(d[17]), "+f"(d[18]), "+f"(d[19]), "+f"(d[20]), "+f"(d[21]), "+f"(d[22]), "+f"(d[23]), "+f"(d[24]), "+f"(d[25]), "+f"(d[26]), "+f"(d[27]), "+f"(d[28]), "+f"(d[29]), "+f"(d[30]), "+f"(d[31])
    : "r"(a0), "r"(a1), "r"(a2), "r"(a3), "l"(db));
  else asm volatile("wgmma.mma_async.sync.aligned.m64n64k16.f32.bf16.bf16 {%0, %1, %2, %3, %4, %5, %6, %7, %8, %9, %10, %11, %12, %13, %14, %15, %16, %17, %18, %19, %20, %21, %22, %23, %24, %25, %26, %27, %28, %29, %30, %31}, {%32, %33, %34, %35}, %36, 0, 1, 1, 0;\n"
    : "=f"(d[0]), "=f"(d[1]), "=f"(d[2]), "=f"(d[3]), "=f"(d[4]), "=f"(d[5]), "=f"(d[6]), "=f"(d[7]), "=f"(d[8]), "=f"(d[9]), "=f"(d[10]), "=f"(d[11]), "=f"(d[12]), "=f"(d[13]), "=f"(d[14]), "=f"(d[15]), "=f"(d[16]), "=f"(d[17]), "=f"(d[18]), "=f"(d[19]), "=f"(d[20]), "=f"(d[21]), "=f"(d[22]), "=f"(d[23]), "=f"(d[24]), "=f"(d[25]), "=f"(d[26]), "=f"(d[27]), "=f"(d[28]), "=f"(d[29]), "=f"(d[30]), "=f"(d[31])
    : "r"(a0), "r"(a1), "r"(a2), "r"(a3), "l"(db));
}
template <int SD> __device__ __forceinline__ void wgmma_rs_n32_tb1(float (&d)[16], uint32_t a0, uint32_t a1, uint32_t a2, uint32_t a3, uint64_t db) {
  if (SD) asm volatile("wgmma.mma_async.sync.aligned.m64n32k16.f32.bf16.bf16 {%0, %1, %2, %3, %4, %5, %6, %7, %8, %9, %10, %11, %12, %13, %14, %15}, {%16, %17, %18, %19}, %20, 1, 1, 1, 1;\n"
    : "+f"(d[0]), "+f"(d[1]), "+f"(d[2]), "+f"(d[3]), "+f"(d[4]), "+f"(d[5]), "+f"(d[6]), "+f"(d[7]), "+f"(d[8]), "+f"(d[9]), "+f"(d[10]), "+f"(d[11]), "+f"(d[12]), "+f"(d[13]), "+f"(d[14]), "+f"(d[15])
    : "r"(a0), "r"(a1), "r"(a2), "r"(a3), "l"(db));
  else asm volatile("wgmma.mma_async.sync.aligned.m64n32k16.f32.bf16.bf16 {%0, %1, %2, %3, %4, %5, %6, %7, %8, %9, %10, %11, %12, %13, %14, %15}, {%16, %17, %18, %19}, %20, 0, 1, 1, 1;\n"
    : "=f"(d[0]), "=f"(d[1]), "=f"(d[2]), "=f"(d[3]), "=f"(d[4]), "=f"(d[5]), "=f"(d[6]), "=f"(d[7]), "=f"(d[8]), "=f"(d[9]), "=f"(d[10]), "=f"(d[11]), "=f"(d[12]), "=f"(d[13]), "=f"(d[14]), "=f"(d[15])
    : "r"(a0), "r"(a1), "r"(a2), "r"(a3), "l"(db));
}

__device__ __forceinline__ uint32_t sw64_off(int row, int d) { return row * 64 + ((((d >> 3) ^ (row >> 1)) & 3) << 4) + (d & 7) * 2; }

__device__ __forceinline__ uint32_t exp2_pair_fma(float t0, float t1, uint32_t c_half, uint32_t c_3) {
  uint32_t y0, y;
  asm("prmt.b32 %0, %1, %2, 0x6521;" : "=r"(y0) : "r"(__float_as_uint(t0)), "r"(__float_as_uint(t1)));
  uint32_t h = lop_and_or(y0, 0x007F007Fu, c_half);
  uint32_t e = lop_and_or(y0, 0xFF80FF80u, c_3);
  asm("fma.rn.bf16x2 %0, %1, %2, %3;" : "=r"(y) : "r"(y0), "r"(h), "r"(e));
  return y;
}

__device__ __forceinline__ void feature_map(float (&v)[16], uint32_t (&ph)[16], int lq) {
  const float L2E = 1.4426950408889634f;
  const bool tail_ok = lq < 2;
  float mx[2], mn[2], b[16], sa[2], sn[2];
#pragma unroll
  for (int r = 0; r < 2; r++) {
    const int o = 2 * r;
    if (!tail_ok) { v[o + 12] = v[o]; v[o + 13] = v[o]; }
    mx[r] = fmaxf(fmaxf(fmaxf(v[o], v[o + 1]), fmaxf(v[o + 4], v[o + 5])), fmaxf(fmaxf(v[o + 8], v[o + 9]), fmaxf(v[o + 12], v[o + 13])));
    mn[r] = fminf(fminf(fminf(v[o], v[o + 1]), fminf(v[o + 4], v[o + 5])), fminf(fminf(v[o + 8], v[o + 9]), fminf(v[o + 12], v[o + 13])));
  }
#pragma unroll
  for (int o = 1; o <= 2; o <<= 1)
#pragma unroll
    for (int r = 0; r < 2; r++) { mx[r] = fmaxf(mx[r], __shfl_xor_sync(~0u, mx[r], o)); mn[r] = fminf(mn[r], __shfl_xor_sync(~0u, mn[r], o)); }
#pragma unroll
  for (int r = 0; r < 2; r++) {
    const int o = 2 * r;
    const float cx = -mx[r] * L2E, cn = mn[r] * L2E;
#pragma unroll
    for (int i = 0; i < 8; i++) {
      const int k = o + 4 * (i >> 1) + (i & 1);
      b[k] = ex2f(fmaf(v[k], -L2E, cn));
      v[k] = ex2f(fmaf(v[k], L2E, cx));
    }
    if (!tail_ok) { v[o + 12] = v[o + 13] = b[o + 12] = b[o + 13] = 0.f; }
    sa[r] = ((v[o] + v[o + 1]) + (v[o + 4] + v[o + 5])) + ((v[o + 8] + v[o + 9]) + (v[o + 12] + v[o + 13]));
    sn[r] = ((b[o] + b[o + 1]) + (b[o + 4] + b[o + 5])) + ((b[o + 8] + b[o + 9]) + (b[o + 12] + b[o + 13]));
  }
#pragma unroll
  for (int o = 1; o <= 2; o <<= 1)
#pragma unroll
    for (int r = 0; r < 2; r++) { sa[r] += __shfl_xor_sync(~0u, sa[r], o); sn[r] += __shfl_xor_sync(~0u, sn[r], o); }
#pragma unroll
  for (int r = 0; r < 2; r++) {
    const float ra = rcpf(sa[r]), rb = rcpf(sn[r]);
#pragma unroll
    for (int jj = 0; jj < 4; jj++) {
      ph[jj * 2 + r] = pack_bf16(v[2 * r + 4 * jj] * ra, v[2 * r + 4 * jj + 1] * ra);
      ph[(4 + jj) * 2 + r] = pack_bf16(b[2 * r + 4 * jj] * rb, b[2 * r + 4 * jj + 1] * rb);
    }
  }
}

__device__ __forceinline__ void store_heads(uint32_t base, const uint32_t (&a)[14], uint32_t pad0, uint32_t pad1, int row0, int lq) {
  const uint32_t rb = base + row0 * 64 + (((row0 >> 1) & 3) << 4);
  const uint32_t b0 = rb + lq * 4;
  const uint32_t b1 = (rb + 8192 + ((lq * 4 + 8) & 15)) ^ ((lq >> 1) << 4);
#pragma unroll
  for (int j = 0; j < 7; j++) {
    uint32_t ad;
    if (j < 3) ad = b0 ^ (j << 4);
    else if (j == 3) ad = (lq < 2) ? (b0 ^ 48u) : (b1 ^ 16u);
    else ad = (lq < 2) ? (b1 ^ ((j - 4) << 4)) : ((b1 ^ 16u) ^ ((j - 3) << 4));
    sts32(ad, a[2 * j]);
    sts32(ad + 512, a[2 * j + 1]);
  }
  sts64((rb ^ 48u) + 8 + (lq & 1) * 8192 + (lq >> 1) * 512, pad0, pad1);
}

struct Params {
  const __nv_bfloat16* w_phi;
  const __nv_bfloat16* wk;
  const __nv_bfloat16* wv;
  const __nv_bfloat16* gate_w;
  __nv_bfloat16* out;
};

__global__ void __launch_bounds__(NTHREADS, 1)
fused_kernel(const __grid_constant__ CUtensorMap tm_x, const __grid_constant__ CUtensorMap tm_wqkv,
             const __grid_constant__ CUtensorMap tm_wq, const __grid_constant__ CUtensorMap tm_woa,
             const __grid_constant__ CUtensorMap tm_wob, const Params prm) {
  extern __shared__ uint8_t smem_raw[];
  uint32_t sb = (smem_u32(smem_raw) + 1023u) & ~1023u;
  uint8_t* sgen = smem_raw + (sb - smem_u32(smem_raw));
  asm volatile("mov.u32 %0, %0;" : "+r"(sb));
  const int tid = threadIdx.x, lane = tid & 31;
  const int warp = __shfl_sync(~0u, tid >> 5, 0), wg = warp >> 2;
  const int pt = blockIdx.x >> 3, hp = blockIdx.x & 7;
  const uint32_t bars = sb + OFF_BAR;
  auto BAR = [&](int i) { return bars + 8u * i; };
  const unsigned epoch = g_epoch & 1;

  if (tid == 0) { PROF_MARK(0); PROF_CLK(30); PROF2(15); }
  auto load_proj = [&](int c, int g) {
    mbar_expect_tx(BAR(B_FULL + g), 49152);
    tma_2d(sb + OFF_X + c * 16384, &tm_x, c * 64, pt * 128, BAR(B_FULL + g));
    tma_2d(sb + OFF_RING + g * 32768, &tm_wq, hp * 56, c * 64, BAR(B_FULL + g));
#pragma unroll 1
    for (int j = 0; j < 3; j++) tma_2d(sb + OFF_RING + g * 32768 + 8192 + j * 8192, &tm_wqkv, j * DM + hp * 56, c * 64, BAR(B_FULL + g));
  };
  if (elect_one()) {
    const int i = warp == 16 ? 0 : (warp == 0 ? 16 : warp);
    if (i < B_N) {
      int cnt = (i >= B_EMPTY && i < B_WO) || i > B_SIG || i == B_X0FREE || i == B_X1FREE ? 16 : 1;
      if (i == B_BUILD) cnt = 512;
      if (i == B_SIG || i == B_QSQ) cnt = 8;
      mbar_init(BAR(i), cnt);
      fence_async_smem();
    }
    if (warp == 16) load_proj(0, 0);
  }
  __syncthreads();
  if (tid == 0) PROF2(14);

  if (wg == 4) {
    asm volatile("setmaxnreg.dec.sync.aligned.u32 32;");
    if (warp == 16) {
      if (elect_one()) {
        int g = 1, nkv = 8;
        uint32_t par = 1;
#pragma unroll 1
        for (int n = 1; n < 14 + nkv; n++) {
          if (n == 7) { PROF_MARK(20); cnt_wait(C_KV, NCTA); PROF_MARK(21); fence_async_all(); }
          if (n == 15) {
            mbar_wait(BAR(B_SLOW), 0);
            if (*(volatile int*)(sgen + OFF_RED)) nkv = 26;
          }
          const int j = n - 7 - nkv;
          if (j == 0 || j == 3) {
            PROF3(j ? 11 : 8);
            cnt_wait((j ? C_OB : C_OA) + pt, 8);
            PROF3(j ? 12 : 9);
            PROF_MARK(26);
            fence_async_all();
          }
          mbar_wait(BAR(B_EMPTY + g), par);
          if (n < 7) load_proj(n, g);
          else {
            mbar_expect_tx(BAR(B_FULL + g), 32768);
            bulk_g2s(sb + OFF_RING + g * 32768, j < 0 ? g_kv_img + ((n - 7) & 7) * 32768 : g_o_img + (size_t)(pt * 7 + j) * 32768, 32768,
                     BAR(B_FULL + g));
          }
          if (++g == 3) { g = 0; par ^= 1; }
        }
        if (atomicAdd(&g_cnt[C_DONE * 32], 1u) == NCTA - 1) {
#pragma unroll 1
          for (int i = 0; i < C_N; i++) g_cnt[i * 32] = 0;
          g_epoch = epoch ^ 1;
        }
      }
    } else {
      if (warp == 18) {
        if (elect_one()) {
#pragma unroll 1
          for (int i = 0; i < 4; i++) {
            mbar_wait(BAR(B_SIG + i), 0);
            PROF3(2 * i);
            cnt_arrive(i == 0 ? C_KV : i == 1 ? C_PART : (i == 2 ? C_OA : C_OB) + pt);
            PROF3(2 * i + 1);
            if (i == 1 || i == 2) {
              mbar_wait(BAR(B_X0FREE + i - 1), 0);
              mbar_expect_tx(BAR(B_WO + i - 1), 57344);
#pragma unroll 1
              for (int c = 0; c < 7; c++)
                tma_2d(sb + OFF_WO + (i - 1) * 57344 + c * 8192, i == 1 ? &tm_woa : &tm_wob, hp * 56, c * 64, BAR(B_WO + i - 1));
            }
          }
        }
      } else if (warp == 19) {
        if (lane == 0) {
          mbar_wait(BAR(B_SIG + 0), 0);
          cnt_wait(C_KV, NCTA);
        }
        __syncwarp();
        float ksq = 0.f, vsq = 0.f;
#pragma unroll
        for (int sl = 0; sl < 4; sl++) {
          float4 a = ldcg_f4(g_ksq + sl * 128 + lane * 4), b = ldcg_f4(g_vsq + sl * 128 + lane * 4);
          float m = fmaxf(fmaxf(a.x, a.y), fmaxf(a.z, a.w));
          m = __uint_as_float(__reduce_max_sync(~0u, __float_as_uint(m)));
          ksq += m;
          vsq = fmaxf(vsq, fmaxf(fmaxf(b.x, b.y), fmaxf(b.z, b.w)));
        }
        mbar_wait(BAR(B_QSQ), 0);
        const float4 qa4 = ((const float4*)(sgen + OFF_QSQ))[lane], qb4 = ((const float4*)(sgen + OFF_QSQ))[32 + lane];
        const float qmax = fmaxf(fmaxf(fmaxf(qa4.x, qa4.y), fmaxf(qa4.z, qa4.w)), fmaxf(fmaxf(qb4.x, qb4.y), fmaxf(qb4.z, qb4.w)));
        const bool slow = __any_sync(~0u, !(qmax * ksq <= 98.f * 98.f) || !(vsq <= 2.0e8f));
        if (lane == 0) {
          *(volatile int*)(sgen + OFF_RED) = slow;
          mbar_arrive(BAR(B_SLOW), 1);
        }
      } else {
        float4* z = (float4*)(g_kvacc[epoch ^ 1] + blockIdx.x * 256) + lane;
        z[0] = make_float4(0.f, 0.f, 0.f, 0.f);
        z[32] = make_float4(0.f, 0.f, 0.f, 0.f);
        if (lane == 0) {
          mbar_wait(BAR(B_SIG + 1), 0);
          cnt_wait(C_PART, NCTA);
          PROF_MARK(23);
        }
        __syncwarp();
        const float* src = g_kvacc[epoch] + hp * 4096 + lane * 8;
#pragma unroll 2
        for (int i = 0; i < 16; i++) {
          const float4 a = ldcg_f4(src + i * 256), b = ldcg_f4(src + i * 256 + 4);
          sts128(sb + OFF_KVR + sw64_off(i * 8 + (lane >> 2), (lane & 3) * 8),
                 make_uint4(pack_bf16(a.x, a.y), pack_bf16(a.z, a.w), pack_bf16(b.x, b.y), pack_bf16(b.z, b.w)));
        }
        ((float4*)(sgen + OFF_GATE))[lane] = ldcg_f4(g_gate + pt * 128 + lane * 4);
        fence_async_smem();
        __syncwarp();
        if (lane == 0) mbar_arrive(BAR(B_KVR), 1);
      }
    }
  } else {
    asm volatile("setmaxnreg.inc.sync.aligned.u32 112;");
    const int mh = wg & 1, nh = wg >> 1, wq = warp & 3;
    {
      const int k = tid >> 3, cn = tid & 7, e = k >= DH;
      const bool data = k < 56 && (cn >> 2) == e;
      const uint32_t ad = sb + OFF_WBD + k * 128 + ((cn ^ (k & 7)) << 4);
      const __nv_bfloat16* wsrc = prm.w_phi + (2 * hp * DH + k) * DH + (cn & 3) * 8;
      if (data) cp_async8(ad, wsrc); else sts64(ad, 0u, 0u);
      if (data && (cn & 3) != 3) cp_async8(ad + 8, wsrc + 4); else sts64(ad + 8, 0u, 0u);
      if (tid < DM) {
        const __nv_bfloat16* src = (hp < 4 ? prm.wk : prm.wv) + tid * DH + (hp & 3) * 8;
        cp_async8(sb + OFF_SLC + tid * 16, src);
        if ((hp & 3) != 3) cp_async8(sb + OFF_SLC + tid * 16 + 8, src + 4);
        else sts64(sb + OFF_SLC + tid * 16 + 8, hp == 3 ? (uint32_t)((const unsigned short*)prm.gate_w)[tid] : 0u, 0u);
      }
    }
    asm volatile("cp.async.mbarrier.arrive.noinc.shared::cta.b64 [%0];" ::"r"(BAR(B_BUILD)) : "memory");
    const int lq = lane & 3;
    const int rowl = wq * 16 + (lane >> 2);
    const int row0 = mh * 64 + rowl;
    int slot = 0, prev = 0;
    uint32_t par = 0;
    {
      float acc0[28], acc1[28], accs[4];
      const uint64_t dR = make_desc(sb + OFF_RING + nh * 16384, 1024, 1024, 1);
      const int lr = wq * 16 + (lane & 7) + ((lane >> 3) & 1) * 8;
      const uint32_t xa = sb + OFF_X + mh * 8192 + lr * 128 + (((lane >> 4) ^ (lr & 7)) << 4);
#pragma unroll
      for (int i = 0; i < 28; i++) acc0[i] = acc1[i] = 0.f;
#pragma unroll
      for (int i = 0; i < 4; i++) accs[i] = 0.f;
      mbar_wait(BAR(B_BUILD), 0);
      fence_async_smem();
#pragma unroll 1
      for (int c = 0; c < 7; c++) {
        mbar_wait(BAR(B_FULL + slot), par);
        uint32_t a[16];
#pragma unroll
        for (int ks = 0; ks < 4; ks++) ldsm4(a + 4 * ks, (xa + c * 16384) ^ (ks << 5));
        const uint64_t dB = dR + slot * 2048;
        wg_fence();
#pragma unroll
        for (int ks = 0; ks < 4; ks++) {
          wgmma_rs_n56_tb1<1>(acc0, a[4 * ks], a[4 * ks + 1], a[4 * ks + 2], a[4 * ks + 3], dB + ks * 128);
          wgmma_rs_n56_tb1<1>(acc1, a[4 * ks], a[4 * ks + 1], a[4 * ks + 2], a[4 * ks + 3], dB + 512 + ks * 128);
        }
        if (nh == 1) {
          const uint64_t dSlc = make_desc(sb + OFF_SLC + c * 1024, 128, 128, 0);
#pragma unroll
          for (int ks = 0; ks < 4; ks++) wgmma_rs_n8_tb1<1>(accs, a[4 * ks], a[4 * ks + 1], a[4 * ks + 2], a[4 * ks + 3], dSlc + ks * 16);
        }
        wg_commit();
        wg_wait<0>();
        if (lane == 0) mbar_arrive(BAR(B_EMPTY + slot), 1);
        if (++slot == 3) { slot = 0; par ^= 1; }
      }
      fence_regs(acc0); fence_regs(acc1); fence_regs(accs);
      if (tid == 0) PROF_MARK(2);
      if (tid == 256) PROF_MARK(3);
      if (nh == 0) {
        float sq[4] = {0.f, 0.f, 0.f, 0.f};
#pragma unroll
        for (int i = 0; i < 28; i++) acc0[i] *= 0.18898223650461362f * 1.4426950408889634f;
#pragma unroll
        for (int j = 0; j < 7; j++) {
#pragma unroll
          for (int rr = 0; rr < 2; rr++) {
            const float s2 = acc0[4 * j + 2 * rr] * acc0[4 * j + 2 * rr] + acc0[4 * j + 2 * rr + 1] * acc0[4 * j + 2 * rr + 1];
            if (j < 3) sq[rr] += s2;
            else if (j > 3) sq[2 + rr] += s2;
            else { sq[rr] += (lq < 2) ? s2 : 0.f; sq[2 + rr] += (lq < 2) ? 0.f : s2; }
          }
        }
#pragma unroll
        for (int i = 0; i < 4; i++) sq[i] = quad_sum(sq[i]);
        const float mine = lq == 0 ? sq[0] : lq == 1 ? sq[1] : lq == 2 ? sq[2] : sq[3];
        ((float*)(sgen + OFF_QSQ))[(mh + (lq & 2)) * 64 + rowl + 8 * (lq & 1)] = mine <= 3.0e38f ? mine : __int_as_float(0x7f800000);
        __syncwarp();
        if (lane == 0) mbar_arrive(BAR(B_QSQ), 1);
      } else {
        const int sl = hp & 3;
        const bool isk = hp < 4, real = (sl < 3) || (lq < 2);
        const int pos = pt * 128 + row0, kr = pos & 63;
        uint8_t* dst = g_kv_img + (pos >> 6) * 8192 + (isk ? 0 : 4096) + sw64_off(kr, sl * 8 + 2 * lq);
        const uint32_t pat = isk ? POLY_PAT >> (kr >> 3) : 0u;
        float mxv = 0.f;
#pragma unroll
        for (int rr = 0; rr < 2; rr++) {
          const float v0 = accs[2 * rr], v1 = accs[2 * rr + 1];
          const bool poly = (pat >> rr) & 1;
          const float sc = poly ? 2.f : 1.f;
          const float s2 = quad_sum(real ? v0 * v0 + v1 * v1 : 0.f);
          mxv = fmaxf(mxv, s2 <= 3.0e38f ? s2 : __int_as_float(0x7f800000));
          const uint32_t padv = lq == 2 ? (poly ? 0x443F4000u : 0x00003F80u) : (poly ? 0x3AB03F4Du : 0u);
          *(uint32_t*)(dst + rr * 512) = real ? pack_bf16(sc * v0, sc * v1) : padv;
          if (hp == 3 && lq == 2) g_gate[pos + 8 * rr] = rcpf(1.f + ex2f(-1.4426950408889634f * v0));
        }
        mxv = __uint_as_float(__reduce_max_sync(~0u, __float_as_uint(mxv)));
        if (lane == 0) (isk ? g_ksq : g_vsq)[sl * 128 + pt * 8 + mh * 4 + wq] = mxv;
        __syncwarp();
        if (lane == 0) mbar_arrive(BAR(B_SIG + 0), 1);
      }
      if (tid == 0) PROF_MARK(4);
      if (tid == 256) PROF_MARK(5);
      uint32_t h[14];
      float pp[32];
      {
        uint32_t a[16];
#pragma unroll
        for (int i = 0; i < 14; i++) {
          const uint32_t u0 = pack_bf16(acc0[2 * i], acc0[2 * i + 1]), u1 = pack_bf16(acc1[2 * i], acc1[2 * i + 1]);
          h[i] = nh ? u1 : u0;
          a[i] = nh ? u0 : u1;
        }
        a[14] = a[0] ^ 0x80008000u;
        a[15] = a[1] ^ 0x80008000u;
        const uint64_t dW = make_desc(sb + OFF_WBD, 1024, 1024, 1);
        wg_fence();
        wgmma_rs_n64_tb1<0>(pp, a[0], a[1], a[2], a[3], dW);
#pragma unroll
        for (int ks = 1; ks < 4; ks++) wgmma_rs_n64_tb1<1>(pp, a[4 * ks], a[4 * ks + 1], a[4 * ks + 2], a[4 * ks + 3], dW + ks * 128);
        wg_commit();
        bar_sync(1, 512);
        if (tid == 0) PROF_MARK(6);
        store_heads(sb + (nh ? OFF_VA : OFF_QP), h, nh ? 0x00003F80u : 0x3F800000u, nh ? 0u : 0x3F803F80u, row0, lq);
        wg_wait<0>();
        fence_regs(pp);
      }
      float v[16];
#pragma unroll
      for (int i = 0; i < 16; i++) v[i] = pp[i];
      uint32_t rb = sb + (nh ? OFF_PHIK : OFF_PHIQ) + row0 * 128 + lq * 4 + ((rowl & 7) << 4);
#pragma unroll 1
      for (int e = 0; e < 2; e++) {
        uint32_t ph[16];
        feature_map(v, ph, lq);
#pragma unroll
        for (int ch = 0; ch < 8; ch++) { sts32(rb ^ (ch << 4), ph[2 * ch]); sts32((rb ^ (ch << 4)) + 1024, ph[2 * ch + 1]); }
        rb += 16384;
#pragma unroll
        for (int i = 0; i < 16; i++) v[i] = pp[16 + i];
      }
      fence_async_smem();
      bar_sync(1, 512);
      if (tid == 0) PROF_MARK(7);
      if (nh == 1) {
        float kv0[16], kv1[16];
        const uint64_t dP = make_desc(sb + OFF_PHIK + mh * 8192, 1024, 1024, 1);
        const uint64_t dV = make_desc(sb + OFF_VA + mh * 4096, 512, 512, 2);
        wg_fence();
        wgmma_ss_n32_ta1_tb1<0>(kv0, dP, dV);
        wgmma_ss_n32_ta1_tb1<0>(kv1, dP + 1024, dV + 512);
#pragma unroll
        for (int ks = 1; ks < 4; ks++) {
          wgmma_ss_n32_ta1_tb1<1>(kv0, dP + ks * 128, dV + ks * 64);
          wgmma_ss_n32_ta1_tb1<1>(kv1, dP + 1024 + ks * 128, dV + 512 + ks * 64);
        }
        wg_commit();
        wg_wait<0>();
        fence_regs(kv0); fence_regs(kv1);
        float* dst = g_kvacc[epoch] + hp * 4096 + rowl * 32 + 2 * lq;
#pragma unroll
        for (int j = 0; j < 8; j++) {
          asm volatile("red.global.add.v2.f32 [%0], {%1, %2};" ::"l"(dst + 8 * (j >> 1) + 256 * (j & 1)), "f"(kv0[2 * j]), "f"(kv0[2 * j + 1]) : "memory");
          asm volatile("red.global.add.v2.f32 [%0], {%1, %2};" ::"l"(dst + 2048 + 8 * (j >> 1) + 256 * (j & 1)), "f"(kv1[2 * j]), "f"(kv1[2 * j + 1]) : "memory");
        }
        __syncwarp();
        if (lane == 0) { mbar_arrive(BAR(B_SIG + 1), 2); mbar_arrive(BAR(B_X0FREE), 2); }
        if (tid == 256) PROF_MARK(28);
      }
    }
    {
      const uint64_t dK = make_desc(sb + OFF_RING, 512, 512, 2);
      const uint64_t dhi = dK & 0xffffffff00000000ull;
      const uint32_t dlo0 = (uint32_t)dK;
      uint32_t ok = 0, q[8];
      float o[16];
#pragma unroll
      for (int i = 0; i < 16; i++) o[i] = 0.f;
      {
        const int r = mh * 64 + wq * 16 + (lane & 7) + ((lane >> 3) & 1) * 8;
        ldsm4(q, sb + OFF_QP + nh * 8192 + sw64_off(r, (lane >> 4) * 8));
        ldsm4(q + 4, sb + OFF_QP + nh * 8192 + sw64_off(r, 16 + (lane >> 4) * 8));
      }
      if (tid == 0) PROF_MARK(10);
      const int qb = QB_AT;
#pragma unroll 1
      for (int it = 0; it <= 8; it++) {
        uint32_t p[16];
        if ((tid & 127) == 0) PROF4(wg * 32 + it * 3);
        if (it == qb || it == 8) {
          float t[16];
          wg_wait<0>();
          fence_regs(o);
          if (it < 8) {
            if (tid == 0) PROF_MARK(11);
            mbar_wait(BAR(B_KVR), 0);
            const uint64_t dR = make_desc(sb + OFF_KVR + nh * 4096, 512, 512, 2);
            const uint64_t dP = make_desc(sb + OFF_PHIQ + nh * 16384 + mh * 8192, 1024, 1024, 1);
            wg_fence();
            wgmma_ss_n32_ta0_tb1<0>(t, dP, dR);
#pragma unroll
            for (int ks = 1; ks < 4; ks++) wgmma_ss_n32_ta0_tb1<1>(t, dP + ks * 2, dR + ks * 64);
            wg_commit();
            wg_wait<0>();
            fence_regs(t);
            if (lane == 0) mbar_arrive(BAR(B_X1FREE), 1);
          } else {
            if (lane == 0) mbar_arrive(BAR(B_EMPTY + prev), 1);
            if (tid == 0) PROF_MARK(13);
            mbar_wait(BAR(B_SLOW), 0);
            if (__builtin_expect(__any_sync(~0u, *(volatile int*)(sgen + OFF_RED)), 0)) {
              uint32_t qz[8];
#pragma unroll
              for (int i = 0; i < 8; i++) qz[i] = (i >= 6 && lq >= 2) ? 0u : q[i];
              float m0 = -3.0e38f, m1 = -3.0e38f, o2[16];
              int sl2 = slot;
              uint32_t par2 = par;
#pragma unroll 1
              for (int j64 = 0; j64 < 32; j64++) {
                float s[32];
                mbar_wait(BAR(B_FULL + sl2), par2);
                const uint32_t lo = dlo0 + sl2 * 2048 + (j64 & 3) * 512;
                wg_fence();
                wgmma_rs_n64_tb0<0>(s, qz[0], qz[1], qz[2], qz[3], dhi | lo);
                wgmma_rs_n64_tb0<1>(s, qz[4], qz[5], qz[6], qz[7], dhi | (lo + 2));
                wg_commit();
                wg_wait<0>();
                fence_regs(s);
#pragma unroll
                for (int j = 0; j < 8; j++) {
                  const float sc = ((POLY_PAT >> j) & 1) ? 0.5f : 1.f;
                  m0 = fmaxf(m0, fmaxf(s[4 * j], s[4 * j + 1]) * sc);
                  m1 = fmaxf(m1, fmaxf(s[4 * j + 2], s[4 * j + 3]) * sc);
                }
                if ((j64 & 3) == 3) {
                  if (lane == 0) mbar_arrive(BAR(B_EMPTY + sl2), 1);
                  if (++sl2 == 3) { sl2 = 0; par2 ^= 1; }
                }
              }
              m0 = quad_max(m0); m1 = quad_max(m1);
#pragma unroll
              for (int i = 0; i < 16; i++) o2[i] = 0.f;
#pragma unroll 1
              for (int j64 = 0; j64 < 32; j64++) {
                float s[32];
                mbar_wait(BAR(B_FULL + sl2), par2);
                const uint32_t lo = dlo0 + sl2 * 2048 + (j64 & 3) * 512;
                wg_fence();
                wgmma_rs_n64_tb0<0>(s, qz[0], qz[1], qz[2], qz[3], dhi | lo);
                wgmma_rs_n64_tb0<1>(s, qz[4], qz[5], qz[6], qz[7], dhi | (lo + 2));
                wg_commit();
                wg_wait<0>();
                fence_regs(s);
                uint32_t ps[16];
#pragma unroll
                for (int j = 0; j < 8; j++) {
                  const float sc = ((POLY_PAT >> j) & 1) ? 0.5f : 1.f;
                  ps[2 * j] = pack_bf16(ex2f(fmaf(s[4 * j], sc, -m0)), ex2f(fmaf(s[4 * j + 1], sc, -m0)));
                  ps[2 * j + 1] = pack_bf16(ex2f(fmaf(s[4 * j + 2], sc, -m1)), ex2f(fmaf(s[4 * j + 3], sc, -m1)));
                }
                wg_fence();
#pragma unroll
                for (int ks = 0; ks < 4; ks++)
                  wgmma_rs_n32_tb1<1>(o2, ps[4 * ks], ps[4 * ks + 1], ps[4 * ks + 2], ps[4 * ks + 3], dhi | (lo + 256 + ks * 64));
                wg_commit();
                wg_wait<0>();
                fence_regs(o2);
                if ((j64 & 3) == 3) {
                  if (lane == 0) mbar_arrive(BAR(B_EMPTY + sl2), 1);
                  if (++sl2 == 3) { sl2 = 0; par2 ^= 1; }
                }
              }
#pragma unroll 1
              for (int j = 0; j < 2; j++) {
                mbar_wait(BAR(B_FULL + sl2), par2);
                __syncwarp();
                if (lane == 0) mbar_arrive(BAR(B_EMPTY + sl2), 1);
                if (++sl2 == 3) { sl2 = 0; par2 ^= 1; }
              }
#pragma unroll
              for (int i = 0; i < 16; i++) o[i] = o2[i];
            }
#pragma unroll
            for (int i = 0; i < 16; i++) t[i] = o[i];
          }
          const int br = it == 8;
          const float eps = br ? 0.f : 1e-6f;
          const float g0 = ((const float*)(sgen + OFF_GATE))[row0], g1 = ((const float*)(sgen + OFF_GATE))[row0 + 8];
          const float d0 = __shfl_sync(~0u, t[12], (lane & ~3) | 2), d1 = __shfl_sync(~0u, t[14], (lane & ~3) | 2);
          const float r0 = (br ? 1.f - g0 : g0) * rcpf(d0 + eps), r1 = (br ? 1.f - g1 : g1) * rcpf(d1 + eps);
          uint8_t* img = g_o_img + (size_t)((pt * 2 + br) * 14 + mh) * 8192 + rowl * 128;
          const int col0 = (2 * hp + nh) * DH + 2 * lq;
#pragma unroll
          for (int j = 0; j < 4; j++) {
            const int col = col0 + 8 * j;
            uint8_t* gp = img + (uint32_t)((col >> 6) * 16384 + ((((col >> 3) ^ rowl) & 7) << 4) + (col & 7) * 2);
            const uint32_t v0 = pack_bf16(t[4 * j] * r0, t[4 * j + 1] * r0), v1 = pack_bf16(t[4 * j + 2] * r1, t[4 * j + 3] * r1);
            if (j < 3 || lq < 2) { *(uint32_t*)gp = v0; *(uint32_t*)(gp + 1024) = v1; }
          }
          __syncwarp();
          if (lane == 0) mbar_arrive(BAR(B_SIG + 2 + br), 1);
          if (tid == 0) PROF_MARK(12 + 2 * br);
          if (br) break;
        }
        const uint32_t lo = dlo0 + slot * 2048;
        if ((tid & 127) == 0) PROF4(wg * 32 + it * 3 + 1);
        if (!ok) mbar_wait(BAR(B_FULL + slot), par);
        if ((tid & 127) == 0) PROF4(wg * 32 + it * 3 + 2);
        int nslot = slot + 1;
        uint32_t npar = par;
        if (nslot == 3) { nslot = 0; npar ^= 1; }
        {
          float s[32];
          wg_fence();
          wgmma_rs_n64_tb0<0>(s, q[0], q[1], q[2], q[3], dhi | lo);
          wgmma_rs_n64_tb0<1>(s, q[4], q[5], q[6], q[7], dhi | (lo + 2));
          wg_commit();
#pragma unroll
          for (int u = 0; u < 4; u++) {
            wg_wait<0>();
            fence_regs(s);
            if (u == 0 && lane == 0 && it > 0) mbar_arrive(BAR(B_EMPTY + prev), 1);
            if (u == 2) ok = mbar_test(BAR(B_FULL + nslot), npar);
#pragma unroll
            for (int j = 0; j < 8; j++) {
              if ((POLY_PAT >> j) & 1) {
                p[2 * j] = exp2_pair_fma(s[4 * j], s[4 * j + 1], 0x3F003F00u, 0x00030003u);
                p[2 * j + 1] = exp2_pair_fma(s[4 * j + 2], s[4 * j + 3], 0x3F003F00u, 0x00030003u);
              } else {
                p[2 * j] = pack_bf16(ex2f(s[4 * j]), ex2f(s[4 * j + 1]));
                p[2 * j + 1] = pack_bf16(ex2f(s[4 * j + 2]), ex2f(s[4 * j + 3]));
              }
            }
            wg_fence();
#pragma unroll
            for (int ks = 0; ks < 4; ks++)
              wgmma_rs_n32_tb1<1>(o, p[4 * ks], p[4 * ks + 1], p[4 * ks + 2], p[4 * ks + 3], dhi | (lo + u * 512 + 256 + ks * 64));
            if (u < 3) {
              wgmma_rs_n64_tb0<0>(s, q[0], q[1], q[2], q[3], dhi | (lo + (u + 1) * 512));
              wgmma_rs_n64_tb0<1>(s, q[4], q[5], q[6], q[7], dhi | (lo + (u + 1) * 512 + 2));
            }
            wg_commit();
          }
        }
        prev = slot; slot = nslot; par = npar;
      }
      wg_wait<0>();
    }
    if (nh == 1) return;
    {
      float acc0[28], acc1[28];
#pragma unroll
      for (int i = 0; i < 28; i++) acc0[i] = acc1[i] = 0.f;
      const uint64_t dS = make_desc(sb + OFF_WO, 1024, 1024, 1);
      const uint64_t dR = make_desc(sb + OFF_RING + mh * 8192, 1024, 1024, 1);
#pragma unroll 1
      for (int c = 0; c < 7; c++) {
        mbar_wait(BAR(B_WO + (c >= 3)), 0);
        mbar_wait(BAR(B_FULL + slot), par);
        const uint64_t dA = dR + slot * 2048, dB = dS + c * 1024;
        wg_fence();
#pragma unroll
        for (int ks = 0; ks < 4; ks++) {
          wgmma_ss_n56_ta0_tb1<1>(acc0, dA + ks * 2, dB + ks * 128);
          wgmma_ss_n56_ta0_tb1<1>(acc1, dA + 1024 + ks * 2, dB + 512 + ks * 128);
        }
        wg_commit();
        if (c < 4) {
          wg_wait<0>();
          if (lane == 0) mbar_arrive(BAR(B_EMPTY + slot), 2);
        }
        if (++slot == 3) { slot = 0; par ^= 1; }
      }
      wg_wait<0>();
      fence_regs(acc0); fence_regs(acc1);
      if (tid == 0) PROF_MARK(17);
      __nv_bfloat16* op = prm.out + (size_t)(pt * 128 + row0) * DM + hp * 56 + 2 * lq;
#pragma unroll
      for (int j = 0; j < 7; j++) {
        *(uint32_t*)(op + 8 * j) = pack_bf16(acc0[4 * j] + acc1[4 * j], acc0[4 * j + 1] + acc1[4 * j + 1]);
        *(uint32_t*)(op + 8 * DM + 8 * j) = pack_bf16(acc0[4 * j + 2] + acc1[4 * j + 2], acc0[4 * j + 3] + acc1[4 * j + 3]);
      }
      if (tid == 0) { PROF_MARK(18); PROF_CLK(31); }
    }
  }
}

typedef CUresult (*EncodeFn)(CUtensorMap*, CUtensorMapDataType, cuuint32_t, void*, const cuuint64_t*, const cuuint64_t*,
                             const cuuint32_t*, const cuuint32_t*, CUtensorMapInterleave, CUtensorMapSwizzle,
                             CUtensorMapL2promotion, CUtensorMapFloatOOBfill);

void make_map(EncodeFn enc, CUtensorMap* tm, const void* ptr, uint64_t cols, uint64_t rows, uint32_t box_rows) {
  cuuint64_t dims[2] = {cols, rows};
  cuuint64_t strides[1] = {cols * 2};
  cuuint32_t box[2] = {64, box_rows};
  cuuint32_t es[2] = {1, 1};
  enc(tm, CU_TENSOR_MAP_DATA_TYPE_BFLOAT16, 2, const_cast<void*>(ptr), dims, strides, box, es, CU_TENSOR_MAP_INTERLEAVE_NONE,
      CU_TENSOR_MAP_SWIZZLE_128B, CU_TENSOR_MAP_L2_PROMOTION_L2_128B, CU_TENSOR_MAP_FLOAT_OOB_FILL_NONE);
}

}

extern "C" void kernel_launch(void* const* d_in, const int* in_sizes, int n_in, void* d_out, int out_size) {
  (void)in_sizes; (void)n_in; (void)out_size;
  static EncodeFn enc = nullptr;
  if (!enc) {
    void* fn = nullptr;
    cudaDriverEntryPointQueryResult qr;
    cudaGetDriverEntryPoint("cuTensorMapEncodeTiled", &fn, cudaEnableDefault, &qr);
    enc = (EncodeFn)fn;
    cudaFuncSetAttribute(fused_kernel, cudaFuncAttributeMaxDynamicSharedMemorySize, SMEM_BYTES);
  }
  CUtensorMap tm_x, tm_wqkv, tm_wq, tm_woa, tm_wob;
  make_map(enc, &tm_x, d_in[0], DM, S_LEN, 128);
  make_map(enc, &tm_wqkv, d_in[1], 3 * DM, DM, 64);
  make_map(enc, &tm_wq, d_in[5], DM, DM, 64);
  make_map(enc, &tm_woa, d_in[3], DM, DM, 64);
  make_map(enc, &tm_wob, d_in[8], DM, DM, 64);
  Params prm;
  prm.w_phi = (const __nv_bfloat16*)d_in[2];
  prm.wk = (const __nv_bfloat16*)d_in[6];
  prm.wv = (const __nv_bfloat16*)d_in[7];
  prm.gate_w = (const __nv_bfloat16*)d_in[9];
  prm.out = (__nv_bfloat16*)d_out;
  fused_kernel<<<NCTA, NTHREADS, SMEM_BYTES>>>(tm_x, tm_wqkv, tm_wq, tm_woa, tm_wob, prm);
}
```

```cpp
#include <cuda_runtime.h>
#include <cuda_bf16.h>
#include <cuda.h>
#include <stdint.h>

namespace {

constexpr int S_LEN = 2048, DM = 448, DH = 28;
constexpr int NCTA = 128;
constexpr int NTHREADS = 640;
constexpr uint32_t POLY_PAT = 0x57;

#define QB_AT (4 + nh)

constexpr int OFF_X = 0;
constexpr int OFF_PHIK = 0;
constexpr int OFF_VA = 32768;
constexpr int OFF_PHIQ = 57344;
constexpr int OFF_KVR = 90112;
constexpr int OFF_QP = 98304;
constexpr int OFF_WO = 0;
constexpr int OFF_RING = 114688;
constexpr int OFF_WBD = 212992;
constexpr int OFF_SLC = 221184;
constexpr int OFF_QSQ = 228352;
constexpr int OFF_GATE = 229376;
constexpr int OFF_RED = 229888;
constexpr int OFF_BAR = 229952;
constexpr int SMEM_BYTES = 230400 + 1024;

constexpr int B_FULL = 0, B_EMPTY = 3, B_WO = 6  , B_KVR = 8, B_X1FREE = 10, B_QSQ = 11, B_SLOW = 12,
              B_BUILD = 13, B_SIG = 14  , B_N = 18;

constexpr int C_KV = 0, C_PART = 1, C_DONE = 3, C_OA = 4, C_OB = 20, C_N = 36;

__device__ __align__(1024) uint8_t g_kv_img[32 * 8192];
__device__ __align__(16) float g_ksq[512];
__device__ __align__(16) float g_vsq[512];
__device__ __align__(16) float g_gate[S_LEN];
__device__ __align__(1024) float g_kvacc[2][16 * 64 * 32];
__device__ unsigned g_epoch;
__device__ __align__(1024) uint8_t g_o_img[2 * 16 * 14 * 8192];
__device__ unsigned g_cnt[C_N * 32];

#define PROF4(i) do { } while (0)
#define PROF3(i) do { } while (0)
#define PROF2(i) do { } while (0)
#define PROF_CLK(i) do { } while (0)
#define PROF_MARK(i) do { } while (0)
__device__ __forceinline__ uint32_t smem_u32(const void* p) { return (uint32_t)__cvta_generic_to_shared(p); }
__device__ __forceinline__ void mbar_init(uint32_t a, int cnt) {
  asm volatile("mbarrier.init.shared::cta.b64 [%0], %1;" ::"r"(a), "r"(cnt) : "memory");
}
__device__ __forceinline__ void mbar_expect_tx(uint32_t a, uint32_t bytes) {
  asm volatile("mbarrier.arrive.expect_tx.shared::cta.b64 _, [%0], %1;" ::"r"(a), "r"(bytes) : "memory");
}
__device__ __forceinline__ void mbar_arrive(uint32_t a, uint32_t cnt) {
  asm volatile("mbarrier.arrive.shared::cta.b64 _, [%0], %1;" ::"r"(a), "r"(cnt) : "memory");
}
__device__ __forceinline__ void mbar_wait(uint32_t a, uint32_t parity) {
  asm volatile(
      "{\n.reg .pred p;\n.reg .u32 c;\nmov.u32 c, 0;\n"
      "W_%=:\nmbarrier.try_wait.parity.shared::cta.b64 p, [%0], %1;\n"
      "add.u32 c, c, 1;\nsetp.lt.and.u32 p, c, 0x40000, !p;\n@p bra W_%=;\n}"
      ::"r"(a), "r"(parity) : "memory");
}
__device__ __forceinline__ uint32_t mbar_test(uint32_t a, uint32_t parity) {
  uint32_t ok;
  asm volatile("{\n.reg .pred p;\nmbarrier.test_wait.parity.shared::cta.b64 p, [%1], %2;\nselp.u32 %0, 1, 0, p;\n}"
               : "=r"(ok) : "r"(a), "r"(parity) : "memory");
  return ok;
}
__device__ __forceinline__ bool elect_one() {
  uint32_t r;
  asm volatile("{\n.reg .pred p;\nelect.sync _|p, 0xffffffff;\nselp.u32 %0, 1, 0, p;\n}" : "=r"(r));
  return r != 0;
}
__device__ __forceinline__ void tma_2d(uint32_t dst, const CUtensorMap* tm, int c0, int c1, uint32_t bar) {
  asm volatile("cp.async.bulk.tensor.2d.shared::cluster.global.mbarrier::complete_tx::bytes [%0], [%1, {%3, %4}], [%2];"
               ::"r"(dst), "l"(tm), "r"(bar), "r"(c0), "r"(c1) : "memory");
}
__device__ __forceinline__ void bulk_g2s(uint32_t dst, const void* src, uint32_t bytes, uint32_t bar) {
  asm volatile("cp.async.bulk.shared::cluster.global.mbarrier::complete_tx::bytes [%0], [%1], %2, [%3];"
               ::"r"(dst), "l"(src), "r"(bytes), "r"(bar) : "memory");
}
__device__ __forceinline__ void cp_async8(uint32_t dst, const void* src) {
  asm volatile("cp.async.ca.shared.global [%0], [%1], 8;" ::"r"(dst), "l"(src) : "memory");
}
__device__ __forceinline__ void fence_async_smem() { asm volatile("fence.proxy.async.shared::cta;" ::: "memory"); }
__device__ __forceinline__ void fence_async_all() { asm volatile("fence.proxy.async.global;" ::: "memory"); }

__device__ __forceinline__ void bar_sync(int id, int n) { asm volatile("bar.sync %0, %1;" ::"r"(id), "r"(n) : "memory"); }
__device__ __forceinline__ void cnt_arrive(int idx) {
  asm volatile("red.release.gpu.global.add.u32 [%0], 1;" ::"l"(&g_cnt[idx * 32]) : "memory");
}
__device__ __forceinline__ void cnt_wait(int idx, unsigned target) {
  unsigned v, n = 0;
#pragma unroll 1
  while (true) {
    asm volatile("ld.acquire.gpu.global.u32 %0, [%1];" : "=r"(v) : "l"(&g_cnt[idx * 32]) : "memory");
    if (v >= target || ++n >= (1u << 18)) break;
    __nanosleep(32);
  }
}
__device__ __forceinline__ void wg_fence() { asm volatile("wgmma.fence.sync.aligned;" ::: "memory"); }
__device__ __forceinline__ void wg_commit() { asm volatile("wgmma.commit_group.sync.aligned;" ::: "memory"); }
template <int N> __device__ __forceinline__ void wg_wait() { asm volatile("wgmma.wait_group.sync.aligned %0;" ::"n"(N) : "memory"); }
template <int N> __device__ __forceinline__ void fence_regs(float (&d)[N]) {
#pragma unroll
  for (int i = 0; i < N; i++) asm volatile("" : "+f"(d[i])::"memory");
}
__device__ __forceinline__ uint64_t make_desc(uint32_t saddr, uint32_t lbo, uint32_t sbo, uint32_t swz) {
  return (uint64_t)((saddr & 0x3FFFF) >> 4) | ((uint64_t)(lbo >> 4) << 16) | ((uint64_t)(sbo >> 4) << 32) | ((uint64_t)swz << 62);
}
__device__ __forceinline__ float ex2f(float x) { float y; asm("ex2.approx.ftz.f32 %0, %1;" : "=f"(y) : "f"(x)); return y; }
__device__ __forceinline__ float rcpf(float x) { float y; asm("rcp.approx.ftz.f32 %0, %1;" : "=f"(y) : "f"(x)); return y; }
__device__ __forceinline__ uint32_t pack_bf16(float lo, float hi) {
  uint32_t r; asm("cvt.rn.bf16x2.f32 %0, %1, %2;" : "=r"(r) : "f"(hi), "f"(lo)); return r;
}
__device__ __forceinline__ uint32_t lop_and_or(uint32_t a, uint32_t m, uint32_t c) {
  uint32_t r; asm("lop3.b32 %0, %1, %2, %3, 0xEA;" : "=r"(r) : "r"(a), "r"(m), "r"(c)); return r;
}
__device__ __forceinline__ void sts32(uint32_t a, uint32_t v) { asm volatile("st.shared.b32 [%0], %1;" ::"r"(a), "r"(v) : "memory"); }
__device__ __forceinline__ void sts64(uint32_t a, uint32_t v0, uint32_t v1) { asm volatile("st.shared.v2.b32 [%0], {%1, %2};" ::"r"(a), "r"(v0), "r"(v1) : "memory"); }
__device__ __forceinline__ void sts128(uint32_t a, uint4 v) {
  asm volatile("st.shared.v4.b32 [%0], {%1, %2, %3, %4};" ::"r"(a), "r"(v.x), "r"(v.y), "r"(v.z), "r"(v.w) : "memory");
}
__device__ __forceinline__ float4 ldcg_f4(const float* p) {
  float4 v; asm volatile("ld.global.cg.v4.f32 {%0, %1, %2, %3}, [%4];" : "=f"(v.x), "=f"(v.y), "=f"(v.z), "=f"(v.w) : "l"(p) : "memory"); return v;
}
__device__ __forceinline__ void ldsm4(uint32_t* r, uint32_t a) {
  asm volatile("ldmatrix.sync.aligned.m8n8.x4.shared.b16 {%0, %1, %2, %3}, [%4];"
               : "=r"(r[0]), "=r"(r[1]), "=r"(r[2]), "=r"(r[3]) : "r"(a) : "memory");
}
__device__ __forceinline__ float quad_sum(float v) { v += __shfl_xor_sync(~0u, v, 1); v += __shfl_xor_sync(~0u, v, 2); return v; }
__device__ __forceinline__ float quad_max(float v) { v = fmaxf(v, __shfl_xor_sync(~0u, v, 1)); v = fmaxf(v, __shfl_xor_sync(~0u, v, 2)); return v; }

template <int SD> __device__ __forceinline__ void wgmma_ss_n56_ta0_tb1(float (&d)[28], uint64_t da, uint64_t db) {
  if (SD) asm volatile("wgmma.mma_async.sync.aligned.m64n56k16.f32.bf16.bf16 {%0, %1, %2, %3, %4, %5, %6, %7, %8, %9, %10, %11, %12, %13, %14, %15, %16, %17, %18, %19, %20, %21, %22, %23, %24, %25, %26, %27}, %28, %29, 1, 1, 1, 0, 1;\n"
    : "+f"(d[0]), "+f"(d[1]), "+f"(d[2]), "+f"(d[3]), "+f"(d[4]), "+f"(d[5]), "+f"(d[6]), "+f"(d[7]), "+f"(d[8]), "+f"(d[9]), "+f"(d[10]), "+f"(d[11]), "+f"(d[12]), "+f"(d[13]), "+f"(d[14]), "+f"(d[15]), "+f"(d[16]), "+f"(d[17]), "+f"(d[18]), "+f"(d[19]), "+f"(d[20]), "+f"(d[21]), "+f"(d[22]), "+f"(d[23]), "+f"(d[24]), "+f"(d[25]), "+f"(d[26]), "+f"(d[27])
    : "l"(da), "l"(db));
  else asm volatile("wgmma.mma_async.sync.aligned.m64n56k16.f32.bf16.bf16 {%0, %1, %2, %3, %4, %5, %6, %7, %8, %9, %10, %11, %12, %13, %14, %15, %16, %17, %18, %19, %20, %21, %22, %23, %24, %25, %26, %27}, %28, %29, 0, 1, 1, 0, 1;\n"
    : "=f"(d[0]), "=f"(d[1]), "=f"(d[2]), "=f"(d[3]), "=f"(d[4]), "=f"(d[5]), "=f"(d[6]), "=f"(d[7]), "=f"(d[8]), "=f"(d[9]), "=f"(d[10]), "=f"(d[11]), "=f"(d[12]), "=f"(d[13]), "=f"(d[14]), "=f"(d[15]), "=f"(d[16]), "=f"(d[17]), "=f"(d[18]), "=f"(d[19]), "=f"(d[20]), "=f"(d[21]), "=f"(d[22]), "=f"(d[23]), "=f"(d[24]), "=f"(d[25]), "=f"(d[26]), "=f"(d[27])
    : "l"(da), "l"(db));
}
template <int SD> __device__ __forceinline__ void wgmma_rs_n56_tb1(float (&d)[28], uint32_t a0, uint32_t a1, uint32_t a2, uint32_t a3, uint64_t db) {
  if (SD) asm volatile("wgmma.mma_async.sync.aligned.m64n56k16.f32.bf16.bf16 {%0, %1, %2, %3, %4, %5, %6, %7, %8, %9, %10, %11, %12, %13, %14, %15, %16, %17, %18, %19, %20, %21, %22, %23, %24, %25, %26, %27}, {%28, %29, %30, %31}, %32, 1, 1, 1, 1;\n"
    : "+f"(d[0]), "+f"(d[1]), "+f"(d[2]), "+f"(d[3]), "+f"(d[4]), "+f"(d[5]), "+f"(d[6]), "+f"(d[7]), "+f"(d[8]), "+f"(d[9]), "+f"(d[10]), "+f"(d[11]), "+f"(d[12]), "+f"(d[13]), "+f"(d[14]), "+f"(d[15]), "+f"(d[16]), "+f"(d[17]), "+f"(d[18]), "+f"(d[19]), "+f"(d[20]), "+f"(d[21]), "+f"(d[22]), "+f"(d[23]), "+f"(d[24]), "+f"(d[25]), "+f"(d[26]), "+f"(d[27])
    : "r"(a0), "r"(a1), "r"(a2), "r"(a3), "l"(db));
  else asm volatile("wgmma.mma_async.sync.aligned.m64n56k16.f32.bf16.bf16 {%0, %1, %2, %3, %4, %5, %6, %7, %8, %9, %10, %11, %12, %13, %14, %15, %16, %17, %18, %19, %20, %21, %22, %23, %24, %25, %26, %27}, {%28, %29, %30, %31}, %32, 0, 1, 1, 1;\n"
    : "=f"(d[0]), "=f"(d[1]), "=f"(d[2]), "=f"(d[3]), "=f"(d[4]), "=f"(d[5]), "=f"(d[6]), "=f"(d[7]), "=f"(d[8]), "=f"(d[9]), "=f"(d[10]), "=f"(d[11]), "=f"(d[12]), "=f"(d[13]), "=f"(d[14]), "=f"(d[15]), "=f"(d[16]), "=f"(d[17]), "=f"(d[18]), "=f"(d[19]), "=f"(d[20]), "=f"(d[21]), "=f"(d[22]), "=f"(d[23]), "=f"(d[24]), "=f"(d[25]), "=f"(d[26]), "=f"(d[27])
    : "r"(a0), "r"(a1), "r"(a2), "r"(a3), "l"(db));
}
template <int SD> __device__ __forceinline__ void wgmma_rs_n8_tb1(float (&d)[4], uint32_t a0, uint32_t a1, uint32_t a2, uint32_t a3, uint64_t db) {
  if (SD) asm volatile("wgmma.mma_async.sync.aligned.m64n8k16.f32.bf16.bf16 {%0, %1, %2, %3}, {%4, %5, %6, %7}, %8, 1, 1, 1, 1;\n"
    : "+f"(d[0]), "+f"(d[1]), "+f"(d[2]), "+f"(d[3])
    : "r"(a0), "r"(a1), "r"(a2), "r"(a3), "l"(db));
  else asm volatile("wgmma.mma_async.sync.aligned.m64n8k16.f32.bf16.bf16 {%0, %1, %2, %3}, {%4, %5, %6, %7}, %8, 0, 1, 1, 1;\n"
    : "=f"(d[0]), "=f"(d[1]), "=f"(d[2]), "=f"(d[3])
    : "r"(a0), "r"(a1), "r"(a2), "r"(a3), "l"(db));
}
template <int SD> __device__ __forceinline__ void wgmma_rs_n64_tb1(float (&d)[32], uint32_t a0, uint32_t a1, uint32_t a2, uint32_t a3, uint64_t db) {
  if (SD) asm volatile("wgmma.mma_async.sync.aligned.m64n64k16.f32.bf16.bf16 {%0, %1, %2, %3, %4, %5, %6, %7, %8, %9, %10, %11, %12, %13, %14, %15, %16, %17, %18, %19, %20, %21, %22, %23, %24, %25, %26, %27, %28, %29, %30, %31}, {%32, %33, %34, %35}, %36, 1, 1, 1, 1;\n"
    : "+f"(d[0]), "+f"(d[1]), "+f"(d[2]), "+f"(d[3]), "+f"(d[4]), "+f"(d[5]), "+f"(d[6]), "+f"(d[7]), "+f"(d[8]), "+f"(d[9]), "+f"(d[10]), "+f"(d[11]), "+f"(d[12]), "+f"(d[13]), "+f"(d[14]), "+f"(d[15]), "+f"(d[16]), "+f"(d[17]), "+f"(d[18]), "+f"(d[19]), "+f"(d[20]), "+f"(d[21]), "+f"(d[22]), "+f"(d[23]), "+f"(d[24]), "+f"(d[25]), "+f"(d[26]), "+f"(d[27]), "+f"(d[28]), "+f"(d[29]), "+f"(d[30]), "+f"(d[31])
    : "r"(a0), "r"(a1), "r"(a2), "r"(a3), "l"(db));
  else asm volatile("wgmma.mma_async.sync.aligned.m64n64k16.f32.bf16.bf16 {%0, %1, %2, %3, %4, %5, %6, %7, %8, %9, %10, %11, %12, %13, %14, %15, %16, %17, %18, %19, %20, %21, %22, %23, %24, %25, %26, %27, %28, %29, %30, %31}, {%32, %33, %34, %35}, %36, 0, 1, 1, 1;\n"
    : "=f"(d[0]), "=f"(d[1]), "=f"(d[2]), "=f"(d[3]), "=f"(d[4]), "=f"(d[5]), "=f"(d[6]), "=f"(d[7]), "=f"(d[8]), "=f"(d[9]), "=f"(d[10]), "=f"(d[11]), "=f"(d[12]), "=f"(d[13]), "=f"(d[14]), "=f"(d[15]), "=f"(d[16]), "=f"(d[17]), "=f"(d[18]), "=f"(d[19]), "=f"(d[20]), "=f"(d[21]), "=f"(d[22]), "=f"(d[23]), "=f"(d[24]), "=f"(d[25]), "=f"(d[26]), "=f"(d[27]), "=f"(d[28]), "=f"(d[29]), "=f"(d[30]), "=f"(d[31])
    : "r"(a0), "r"(a1), "r"(a2), "r"(a3), "l"(db));
}
template <int SD> __device__ __forceinline__ void wgmma_ss_n32_ta1_tb1(float (&d)[16], uint64_t da, uint64_t db) {
  if (SD) asm volatile("wgmma.mma_async.sync.aligned.m64n32k16.f32.bf16.bf16 {%0, %1, %2, %3, %4, %5, %6, %7, %8, %9, %10, %11, %12, %13, %14, %15}, %16, %17, 1, 1, 1, 1, 1;\n"
    : "+f"(d[0]), "+f"(d[1]), "+f"(d[2]), "+f"(d[3]), "+f"(d[4]), "+f"(d[5]), "+f"(d[6]), "+f"(d[7]), "+f"(d[8]), "+f"(d[9]), "+f"(d[10]), "+f"(d[11]), "+f"(d[12]), "+f"(d[13]), "+f"(d[14]), "+f"(d[15])
    : "l"(da), "l"(db));
  else asm volatile("wgmma.mma_async.sync.aligned.m64n32k16.f32.bf16.bf16 {%0, %1, %2, %3, %4, %5, %6, %7, %8, %9, %10, %11, %12, %13, %14, %15}, %16, %17, 0, 1, 1, 1, 1;\n"
    : "=f"(d[0]), "=f"(d[1]), "=f"(d[2]), "=f"(d[3]), "=f"(d[4]), "=f"(d[5]), "=f"(d[6]), "=f"(d[7]), "=f"(d[8]), "=f"(d[9]), "=f"(d[10]), "=f"(d[11]), "=f"(d[12]), "=f"(d[13]), "=f"(d[14]), "=f"(d[15])
    : "l"(da), "l"(db));
}
template <int SD> __device__ __forceinline__ void wgmma_ss_n32_ta0_tb1(float (&d)[16], uint64_t da, uint64_t db) {
  if (SD) asm volatile("wgmma.mma_async.sync.aligned.m64n32k16.f32.bf16.bf16 {%0, %1, %2, %3, %4, %5, %6, %7, %8, %9, %10, %11, %12, %13, %14, %15}, %16, %17, 1, 1, 1, 0, 1;\n"
    : "+f"(d[0]), "+f"(d[1]), "+f"(d[2]), "+f"(d[3]), "+f"(d[4]), "+f"(d[5]), "+f"(d[6]), "+f"(d[7]), "+f"(d[8]), "+f"(d[9]), "+f"(d[10]), "+f"(d[11]), "+f"(d[12]), "+f"(d[13]), "+f"(d[14]), "+f"(d[15])
    : "l"(da), "l"(db));
  else asm volatile("wgmma.mma_async.sync.aligned.m64n32k16.f32.bf16.bf16 {%0, %1, %2, %3, %4, %5, %6, %7, %8, %9, %10, %11, %12, %13, %14, %15}, %16, %17, 0, 1, 1, 0, 1;\n"
    : "=f"(d[0]), "=f"(d[1]), "=f"(d[2]), "=f"(d[3]), "=f"(d[4]), "=f"(d[5]), "=f"(d[6]), "=f"(d[7]), "=f"(d[8]), "=f"(d[9]), "=f"(d[10]), "=f"(d[11]), "=f"(d[12]), "=f"(d[13]), "=f"(d[14]), "=f"(d[15])
    : "l"(da), "l"(db));
}
template <int SD> __device__ __forceinline__ void wgmma_rs_n64_tb0(float (&d)[32], uint32_t a0, uint32_t a1, uint32_t a2, uint32_t a3, uint64_t db) {
  if (SD) asm volatile("wgmma.mma_async.sync.aligned.m64n64k16.f32.bf16.bf16 {%0, %1, %2, %3, %4, %5, %6, %7, %8, %9, %10, %11, %12, %13, %14, %15, %16, %17, %18, %19, %20, %21, %22, %23, %24, %25, %26, %27, %28, %29, %30, %31}, {%32, %33, %34, %35}, %36, 1, 1, 1, 0;\n"
    : "+f"(d[0]), "+f"(d[1]), "+f"(d[2]), "+f"(d[3]), "+f"(d[4]), "+f"(d[5]), "+f"(d[6]), "+f"(d[7]), "+f"(d[8]), "+f"(d[9]), "+f"(d[10]), "+f"(d[11]), "+f"(d[12]), "+f"(d[13]), "+f"(d[14]), "+f"(d[15]), "+f"(d[16]), "+f"(d[17]), "+f"(d[18]), "+f"(d[19]), "+f"(d[20]), "+f"(d[21]), "+f"(d[22]), "+f"(d[23]), "+f"(d[24]), "+f"(d[25]), "+f"(d[26]), "+f"(d[27]), "+f"(d[28]), "+f"(d[29]), "+f"(d[30]), "+f"(d[31])
    : "r"(a0), "r"(a1), "r"(a2), "r"(a3), "l"(db));
  else asm volatile("wgmma.mma_async.sync.aligned.m64n64k16.f32.bf16.bf16 {%0, %1, %2, %3, %4, %5, %6, %7, %8, %9, %10, %11, %12, %13, %14, %15, %16, %17, %18, %19, %20, %21, %22, %23, %24, %25, %26, %27, %28, %29, %30, %31}, {%32, %33, %34, %35}, %36, 0, 1, 1, 0;\n"
    : "=f"(d[0]), "=f"(d[1]), "=f"(d[2]), "=f"(d[3]), "=f"(d[4]), "=f"(d[5]), "=f"(d[6]), "=f"(d[7]), "=f"(d[8]), "=f"(d[9]), "=f"(d[10]), "=f"(d[11]), "=f"(d[12]), "=f"(d[13]), "=f"(d[14]), "=f"(d[15]), "=f"(d[16]), "=f"(d[17]), "=f"(d[18]), "=f"(d[19]), "=f"(d[20]), "=f"(d[21]), "=f"(d[22]), "=f"(d[23]), "=f"(d[24]), "=f"(d[25]), "=f"(d[26]), "=f"(d[27]), "=f"(d[28]), "=f"(d[29]), "=f"(d[30]), "=f"(d[31])
    : "r"(a0), "r"(a1), "r"(a2), "r"(a3), "l"(db));
}
template <int SD> __device__ __forceinline__ void wgmma_rs_n32_tb1(float (&d)[16], uint32_t a0, uint32_t a1, uint32_t a2, uint32_t a3, uint64_t db) {
  if (SD) asm volatile("wgmma.mma_async.sync.aligned.m64n32k16.f32.bf16.bf16 {%0, %1, %2, %3, %4, %5, %6, %7, %8, %9, %10, %11, %12, %13, %14, %15}, {%16, %17, %18, %19}, %20, 1, 1, 1, 1;\n"
    : "+f"(d[0]), "+f"(d[1]), "+f"(d[2]), "+f"(d[3]), "+f"(d[4]), "+f"(d[5]), "+f"(d[6]), "+f"(d[7]), "+f"(d[8]), "+f"(d[9]), "+f"(d[10]), "+f"(d[11]), "+f"(d[12]), "+f"(d[13]), "+f"(d[14]), "+f"(d[15])
    : "r"(a0), "r"(a1), "r"(a2), "r"(a3), "l"(db));
  else asm volatile("wgmma.mma_async.sync.aligned.m64n32k16.f32.bf16.bf16 {%0, %1, %2, %3, %4, %5, %6, %7, %8, %9, %10, %11, %12, %13, %14, %15}, {%16, %17, %18, %19}, %20, 0, 1, 1, 1;\n"
    : "=f"(d[0]), "=f"(d[1]), "=f"(d[2]), "=f"(d[3]), "=f"(d[4]), "=f"(d[5]), "=f"(d[6]), "=f"(d[7]), "=f"(d[8]), "=f"(d[9]), "=f"(d[10]), "=f"(d[11]), "=f"(d[12]), "=f"(d[13]), "=f"(d[14]), "=f"(d[15])
    : "r"(a0), "r"(a1), "r"(a2), "r"(a3), "l"(db));
}

__device__ __forceinline__ uint32_t sw64_off(int row, int d) { return row * 64 + ((((d >> 3) ^ (row >> 1)) & 3) << 4) + (d & 7) * 2; }

__device__ __forceinline__ uint32_t exp2_pair_fma(float t0, float t1, uint32_t c_half, uint32_t c_3) {
  uint32_t y0, y;
  asm("prmt.b32 %0, %1, %2, 0x6521;" : "=r"(y0) : "r"(__float_as_uint(t0)), "r"(__float_as_uint(t1)));
  uint32_t h = lop_and_or(y0, 0x007F007Fu, c_half);
  uint32_t e = lop_and_or(y0, 0xFF80FF80u, c_3);
  asm("fma.rn.bf16x2 %0, %1, %2, %3;" : "=r"(y) : "r"(y0), "r"(h), "r"(e));
  return y;
}

__device__ __forceinline__ void feature_map(float (&v)[16], uint32_t (&ph)[16], int lq) {
  const float L2E = 1.4426950408889634f;
  const bool tail_ok = lq < 2;
  float mx[2], mn[2], b[16], sa[2], sn[2];
#pragma unroll
  for (int r = 0; r < 2; r++) {
    const int o = 2 * r;
    if (!tail_ok) { v[o + 12] = v[o]; v[o + 13] = v[o]; }
    mx[r] = fmaxf(fmaxf(fmaxf(v[o], v[o + 1]), fmaxf(v[o + 4], v[o + 5])), fmaxf(fmaxf(v[o + 8], v[o + 9]), fmaxf(v[o + 12], v[o + 13])));
    mn[r] = fminf(fminf(fminf(v[o], v[o + 1]), fminf(v[o + 4], v[o + 5])), fminf(fminf(v[o + 8], v[o + 9]), fminf(v[o + 12], v[o + 13])));
  }
#pragma unroll
  for (int o = 1; o <= 2; o <<= 1)
#pragma unroll
    for (int r = 0; r < 2; r++) { mx[r] = fmaxf(mx[r], __shfl_xor_sync(~0u, mx[r], o)); mn[r] = fminf(mn[r], __shfl_xor_sync(~0u, mn[r], o)); }
#pragma unroll
  for (int r = 0; r < 2; r++) {
    const int o = 2 * r;
    const float cx = -mx[r] * L2E, cn = mn[r] * L2E;
#pragma unroll
    for (int i = 0; i < 8; i++) {
      const int k = o + 4 * (i >> 1) + (i & 1);
      b[k] = ex2f(fmaf(v[k], -L2E, cn));
      v[k] = ex2f(fmaf(v[k], L2E, cx));
    }
    if (!tail_ok) { v[o + 12] = v[o + 13] = b[o + 12] = b[o + 13] = 0.f; }
    sa[r] = ((v[o] + v[o + 1]) + (v[o + 4] + v[o + 5])) + ((v[o + 8] + v[o + 9]) + (v[o + 12] + v[o + 13]));
    sn[r] = ((b[o] + b[o + 1]) + (b[o + 4] + b[o + 5])) + ((b[o + 8] + b[o + 9]) + (b[o + 12] + b[o + 13]));
  }
#pragma unroll
  for (int o = 1; o <= 2; o <<= 1)
#pragma unroll
    for (int r = 0; r < 2; r++) { sa[r] += __shfl_xor_sync(~0u, sa[r], o); sn[r] += __shfl_xor_sync(~0u, sn[r], o); }
#pragma unroll
  for (int r = 0; r < 2; r++) {
    const float ra = rcpf(sa[r]), rb = rcpf(sn[r]);
#pragma unroll
    for (int jj = 0; jj < 4; jj++) {
      ph[jj * 2 + r] = pack_bf16(v[2 * r + 4 * jj] * ra, v[2 * r + 4 * jj + 1] * ra);
      ph[(4 + jj) * 2 + r] = pack_bf16(b[2 * r + 4 * jj] * rb, b[2 * r + 4 * jj + 1] * rb);
    }
  }
}

__device__ __forceinline__ void store_heads(uint32_t base, const uint32_t (&a)[14], uint32_t pad0, uint32_t pad1, int row0, int lq) {
  const uint32_t rb = base + row0 * 64 + (((row0 >> 1) & 3) << 4);
  const uint32_t b0 = rb + lq * 4;
  const uint32_t b1 = (rb + 8192 + ((lq * 4 + 8) & 15)) ^ ((lq >> 1) << 4);
#pragma unroll
  for (int j = 0; j < 7; j++) {
    uint32_t ad;
    if (j < 3) ad = b0 ^ (j << 4);
    else if (j == 3) ad = (lq < 2) ? (b0 ^ 48u) : (b1 ^ 16u);
    else ad = (lq < 2) ? (b1 ^ ((j - 4) << 4)) : ((b1 ^ 16u) ^ ((j - 3) << 4));
    sts32(ad, a[2 * j]);
    sts32(ad + 512, a[2 * j + 1]);
  }
  sts64((rb ^ 48u) + 8 + (lq & 1) * 8192 + (lq >> 1) * 512, pad0, pad1);
}

struct Params {
  const __nv_bfloat16* w_phi;
  const __nv_bfloat16* wk;
  const __nv_bfloat16* wv;
  const __nv_bfloat16* gate_w;
  __nv_bfloat16* out;
};

__global__ void __launch_bounds__(NTHREADS, 1)
fused_kernel(const __grid_constant__ CUtensorMap tm_x, const __grid_constant__ CUtensorMap tm_wqkv,
             const __grid_constant__ CUtensorMap tm_wq, const __grid_constant__ CUtensorMap tm_woa,
             const __grid_constant__ CUtensorMap tm_wob, const Params prm) {
  extern __shared__ uint8_t smem_raw[];
  uint32_t sb = (smem_u32(smem_raw) + 1023u) & ~1023u;
  uint8_t* sgen = smem_raw + (sb - smem_u32(smem_raw));
  asm volatile("mov.u32 %0, %0;" : "+r"(sb));
  const int tid = threadIdx.x, lane = tid & 31;
  const int warp = __shfl_sync(~0u, tid >> 5, 0), wg = warp >> 2;
  const int pt = blockIdx.x >> 3, hp = blockIdx.x & 7;
  const uint32_t bars = sb + OFF_BAR;
  auto BAR = [&](int i) { return bars + 8u * i; };
  const unsigned epoch = g_epoch & 1;

  if (tid == 0) { PROF_MARK(0); PROF_CLK(30); PROF2(15); }
  auto load_proj = [&](int c, int g) {
    mbar_expect_tx(BAR(B_FULL + g), 49152);
    tma_2d(sb + OFF_X + c * 16384, &tm_x, c * 64, pt * 128, BAR(B_FULL + g));
    tma_2d(sb + OFF_RING + g * 32768, &tm_wq, hp * 56, c * 64, BAR(B_FULL + g));
#pragma unroll 1
    for (int j = 0; j < 3; j++) tma_2d(sb + OFF_RING + g * 32768 + 8192 + j * 8192, &tm_wqkv, j * DM + hp * 56, c * 64, BAR(B_FULL + g));
  };
  if (warp == 16) {
    if (elect_one()) {
      mbar_init(BAR(B_FULL), 1); mbar_init(BAR(B_FULL + 1), 1); mbar_init(BAR(B_FULL + 2), 1);
      fence_async_smem();
      load_proj(0, 0);
    }
    __syncwarp();
    asm volatile("bar.arrive 0, %0;" ::"n"(NTHREADS) : "memory");
  } else {
    if (elect_one()) {
      const int i = warp + 3 - (warp > 16);
      if (i < B_N) {
        int cnt = i < B_WO || i > B_SIG || i == B_X1FREE ? 16 : 1;
        if (i == B_BUILD) cnt = 512;
        if (i == B_SIG || i == B_SIG + 1 || i == B_QSQ) cnt = 8;
        if (i == B_KVR) cnt = 2;
        mbar_init(BAR(i), cnt);
        fence_async_smem();
      }
    }
    if (tid < 512) {
      const int k = tid >> 3, cn = tid & 7, e = k >= DH;
      const bool data = k < 56 && (cn >> 2) == e;
      const uint32_t ad = sb + OFF_WBD + k * 128 + ((cn ^ (k & 7)) << 4);
      const __nv_bfloat16* wsrc = prm.w_phi + (2 * hp * DH + k) * DH + (cn & 3) * 8;
      if (data) cp_async8(ad, wsrc); else sts64(ad, 0u, 0u);
      if (data && (cn & 3) != 3) cp_async8(ad + 8, wsrc + 4); else sts64(ad + 8, 0u, 0u);
      if (tid < DM) {
        const __nv_bfloat16* src = (hp < 4 ? prm.wk : prm.wv) + tid * DH + (hp & 3) * 8;
        cp_async8(sb + OFF_SLC + tid * 16, src);
        if ((hp & 3) != 3) cp_async8(sb + OFF_SLC + tid * 16 + 8, src + 4);
        else sts64(sb + OFF_SLC + tid * 16 + 8, hp == 3 ? (uint32_t)((const unsigned short*)prm.gate_w)[tid] : 0u, 0u);
      }
    }
    bar_sync(0, NTHREADS);
  }
  if (tid == 0) PROF2(14);

  if (wg == 4) {
    asm volatile("setmaxnreg.dec.sync.aligned.u32 32;");
    if (warp == 16) {
      if (elect_one()) { load_proj(1, 1); load_proj(2, 2); }
      __syncwarp();
      bar_sync(3, 64);
      if (elect_one()) {
        int g = 0, nkv = 8;
        uint32_t par = 0;
#pragma unroll 1
        for (int n = 3; n < 14 + nkv; n++) {
          if (n == 7) { PROF_MARK(20); cnt_wait(C_KV, NCTA); PROF_MARK(21); fence_async_all(); }
          if (n == 15) {
            mbar_wait(BAR(B_SLOW), 0);
            if (*(volatile int*)(sgen + OFF_RED)) nkv = 26;
          }
          const int j = n - 7 - nkv;
          if (j == 0 || j == 3) {
            PROF3(j ? 11 : 8);
            cnt_wait((j ? C_OB : C_OA) + pt, 8);
            PROF3(j ? 12 : 9);
            PROF_MARK(26);
            fence_async_all();
          }
          mbar_wait(BAR(B_EMPTY + g), par);
          if (n < 7) load_proj(n, g);
          else {
            mbar_expect_tx(BAR(B_FULL + g), 32768);
            bulk_g2s(sb + OFF_RING + g * 32768, j < 0 ? g_kv_img + ((n - 7) & 7) * 32768 : g_o_img + (size_t)(pt * 7 + j) * 32768, 32768,
                     BAR(B_FULL + g));
          }
          if (++g == 3) { g = 0; par ^= 1; }
        }
        if (atomicAdd(&g_cnt[C_DONE * 32], 1u) == NCTA - 1) {
#pragma unroll 1
          for (int i = 0; i < C_N; i++) g_cnt[i * 32] = 0;
          g_epoch = epoch ^ 1;
        }
      }
    } else {
      if (warp == 18) {
        if (elect_one()) {
#pragma unroll 1
          for (int i = 0; i < 4; i++) {
            mbar_wait(BAR(B_SIG + i), 0);
            PROF3(2 * i);
            if (i == 1) {
#pragma unroll 1
              for (int j = 0; j < 4; j++)
                asm volatile("cp.reduce.async.bulk.global.shared::cta.bulk_group.add.f32 [%0], [%1], 8192;"
                             ::"l"(g_kvacc[epoch] + hp * 4096 + (j >> 1) * 2048), "r"(sb + OFF_PHIK + j * 8192) : "memory");
              asm volatile("cp.async.bulk.commit_group;\ncp.async.bulk.wait_group 0;" ::: "memory");
            }
            cnt_arrive(i == 0 ? C_KV : i == 1 ? C_PART : (i == 2 ? C_OA : C_OB) + pt);
            PROF3(2 * i + 1);
            if (i == 1 || i == 2) {
              if (i == 2) mbar_wait(BAR(B_X1FREE), 0);
              mbar_expect_tx(BAR(B_WO + i - 1), 57344);
#pragma unroll 1
              for (int c = 0; c < 7; c++)
                tma_2d(sb + OFF_WO + (i - 1) * 57344 + c * 8192, i == 1 ? &tm_woa : &tm_wob, hp * 56, c * 64, BAR(B_WO + i - 1));
            }
          }
        }
      } else if (warp == 19) {
        if (lane == 0) {
          mbar_wait(BAR(B_SIG + 0), 0);
          cnt_wait(C_KV, NCTA);
        }
        __syncwarp();
        float ksq = 0.f, vsq = 0.f;
#pragma unroll
        for (int sl = 0; sl < 4; sl++) {
          float4 a = ldcg_f4(g_ksq + sl * 128 + lane * 4), b = ldcg_f4(g_vsq + sl * 128 + lane * 4);
          float m = fmaxf(fmaxf(a.x, a.y), fmaxf(a.z, a.w));
          m = __uint_as_float(__reduce_max_sync(~0u, __float_as_uint(m)));
          ksq += m;
          vsq = fmaxf(vsq, fmaxf(fmaxf(b.x, b.y), fmaxf(b.z, b.w)));
        }
        mbar_wait(BAR(B_QSQ), 0);
        const float4 qa4 = ((const float4*)(sgen + OFF_QSQ))[lane], qb4 = ((const float4*)(sgen + OFF_QSQ))[32 + lane];
        const float qmax = fmaxf(fmaxf(fmaxf(qa4.x, qa4.y), fmaxf(qa4.z, qa4.w)), fmaxf(fmaxf(qb4.x, qb4.y), fmaxf(qb4.z, qb4.w)));
        const bool slow = __any_sync(~0u, !(qmax * ksq <= 98.f * 98.f) || !(vsq <= 2.0e8f));
        if (lane == 0) {
          *(volatile int*)(sgen + OFF_RED) = slow;
          mbar_arrive(BAR(B_SLOW), 1);
        }
      } else {
        float4* z = (float4*)(g_kvacc[epoch ^ 1] + blockIdx.x * 256) + lane;
        z[0] = make_float4(0.f, 0.f, 0.f, 0.f);
        z[32] = make_float4(0.f, 0.f, 0.f, 0.f);
        bar_sync(3, 64);
        if (lane == 0) {
          mbar_wait(BAR(B_SIG + 0), 0);
          cnt_wait(C_KV, NCTA);
        }
        __syncwarp();
        ((float4*)(sgen + OFF_GATE))[lane] = ldcg_f4(g_gate + pt * 128 + lane * 4);
      }
      if (warp != 18) {
        if (lane == 0) {
          mbar_wait(BAR(B_SIG + 1), 0);
          cnt_wait(C_PART, NCTA);
          PROF_MARK(23);
        }
        __syncwarp();
        const int e = warp == 19;
        const float* src = g_kvacc[epoch] + hp * 4096 + e * 2048 + lane * 8;
#pragma unroll 1
        for (int i = 0; i < 8; i += 2) {
          const float4 a = ldcg_f4(src + i * 256), b = ldcg_f4(src + i * 256 + 4), c = ldcg_f4(src + i * 256 + 256), d = ldcg_f4(src + i * 256 + 260);
          const uint32_t ad = sb + OFF_KVR + e * 4096 + sw64_off(i * 8 + (lane >> 2), (lane & 3) * 8);
          sts128(ad, make_uint4(pack_bf16(a.x, a.y), pack_bf16(a.z, a.w), pack_bf16(b.x, b.y), pack_bf16(b.z, b.w)));
          sts128(ad + 512, make_uint4(pack_bf16(c.x, c.y), pack_bf16(c.z, c.w), pack_bf16(d.x, d.y), pack_bf16(d.z, d.w)));
        }
        fence_async_smem();
        __syncwarp();
        if (lane == 0) mbar_arrive(BAR(B_KVR), 1);
        PROF_MARK(24);
      }
    }
  } else {
    asm volatile("setmaxnreg.inc.sync.aligned.u32 112;");
    const int mh = wg & 1, nh = wg >> 1, wq = warp & 3;
    asm volatile("cp.async.mbarrier.arrive.noinc.shared::cta.b64 [%0];" ::"r"(BAR(B_BUILD)) : "memory");
    const int lq = lane & 3;
    const int rowl = wq * 16 + (lane >> 2);
    const int row0 = mh * 64 + rowl;
    int slot = 0, prev = 0;
    uint32_t par = 0;
    {
      float acc0[28], acc1[28], accs[4];
      const uint64_t dR = make_desc(sb + OFF_RING + nh * 16384, 1024, 1024, 1);
      const int lr = wq * 16 + (lane & 7) + ((lane >> 3) & 1) * 8;
      const uint32_t xa = sb + OFF_X + mh * 8192 + lr * 128 + (((lane >> 4) ^ (lr & 7)) << 4);
#pragma unroll
      for (int i = 0; i < 28; i++) acc0[i] = acc1[i] = 0.f;
#pragma unroll
      for (int i = 0; i < 4; i++) accs[i] = 0.f;
      mbar_wait(BAR(B_BUILD), 0);
      fence_async_smem();
#pragma unroll 1
      for (int c = 0; c < 7; c++) {
        mbar_wait(BAR(B_FULL + slot), par);
        uint32_t a[16];
#pragma unroll
        for (int ks = 0; ks < 4; ks++) ldsm4(a + 4 * ks, (xa + c * 16384) ^ (ks << 5));
        const uint64_t dB = dR + slot * 2048;
        wg_fence();
#pragma unroll
        for (int ks = 0; ks < 4; ks++) {
          wgmma_rs_n56_tb1<1>(acc0, a[4 * ks], a[4 * ks + 1], a[4 * ks + 2], a[4 * ks + 3], dB + ks * 128);
          wgmma_rs_n56_tb1<1>(acc1, a[4 * ks], a[4 * ks + 1], a[4 * ks + 2], a[4 * ks + 3], dB + 512 + ks * 128);
        }
        if (nh == 1) {
          const uint64_t dSlc = make_desc(sb + OFF_SLC + c * 1024, 128, 128, 0);
#pragma unroll
          for (int ks = 0; ks < 4; ks++) wgmma_rs_n8_tb1<1>(accs, a[4 * ks], a[4 * ks + 1], a[4 * ks + 2], a[4 * ks + 3], dSlc + ks * 16);
        }
        wg_commit();
        wg_wait<0>();
        if (lane == 0) mbar_arrive(BAR(B_EMPTY + slot), 1);
        if (++slot == 3) { slot = 0; par ^= 1; }
      }
      fence_regs(acc0); fence_regs(acc1); fence_regs(accs);
      if (tid == 0) PROF_MARK(2);
      if (tid == 256) PROF_MARK(3);
      if (nh == 0) {
        float sq[4] = {0.f, 0.f, 0.f, 0.f};
#pragma unroll
        for (int i = 0; i < 28; i++) acc0[i] *= 0.18898223650461362f * 1.4426950408889634f;
#pragma unroll
        for (int j = 0; j < 7; j++) {
#pragma unroll
          for (int rr = 0; rr < 2; rr++) {
            const float s2 = acc0[4 * j + 2 * rr] * acc0[4 * j + 2 * rr] + acc0[4 * j + 2 * rr + 1] * acc0[4 * j + 2 * rr + 1];
            if (j < 3) sq[rr] += s2;
            else if (j > 3) sq[2 + rr] += s2;
            else { sq[rr] += (lq < 2) ? s2 : 0.f; sq[2 + rr] += (lq < 2) ? 0.f : s2; }
          }
        }
#pragma unroll
        for (int i = 0; i < 4; i++) sq[i] = quad_sum(sq[i]);
        const float mine = lq == 0 ? sq[0] : lq == 1 ? sq[1] : lq == 2 ? sq[2] : sq[3];
        ((float*)(sgen + OFF_QSQ))[(mh + (lq & 2)) * 64 + rowl + 8 * (lq & 1)] = mine <= 3.0e38f ? mine : __int_as_float(0x7f800000);
        __syncwarp();
        if (lane == 0) mbar_arrive(BAR(B_QSQ), 1);
      } else {
        const int sl = hp & 3;
        const bool isk = hp < 4, real = (sl < 3) || (lq < 2);
        const int pos = pt * 128 + row0, kr = pos & 63;
        uint8_t* dst = g_kv_img + (pos >> 6) * 8192 + (isk ? 0 : 4096) + sw64_off(kr, sl * 8 + 2 * lq);
        const uint32_t pat = isk ? POLY_PAT >> (kr >> 3) : 0u;
        float mxv = 0.f;
#pragma unroll
        for (int rr = 0; rr < 2; rr++) {
          const float v0 = accs[2 * rr], v1 = accs[2 * rr + 1];
          const bool poly = (pat >> rr) & 1;
          const float sc = poly ? 2.f : 1.f;
          const float s2 = quad_sum(real ? v0 * v0 + v1 * v1 : 0.f);
          mxv = fmaxf(mxv, s2 <= 3.0e38f ? s2 : __int_as_float(0x7f800000));
          const uint32_t padv = lq == 2 ? (poly ? 0x443F4000u : 0x00003F80u) : (poly ? 0x3AB03F4Du : 0u);
          *(uint32_t*)(dst + rr * 512) = real ? pack_bf16(sc * v0, sc * v1) : padv;
          if (hp == 3 && lq == 2) g_gate[pos + 8 * rr] = rcpf(1.f + ex2f(-1.4426950408889634f * v0));
        }
        mxv = __uint_as_float(__reduce_max_sync(~0u, __float_as_uint(mxv)));
        if (lane == 0) (isk ? g_ksq : g_vsq)[sl * 128 + pt * 8 + mh * 4 + wq] = mxv;
        __syncwarp();
        if (lane == 0) mbar_arrive(BAR(B_SIG + 0), 1);
      }
      if (tid == 0) PROF_MARK(4);
      if (tid == 256) PROF_MARK(5);
      uint32_t h[14];
      float pp[32];
      {
        uint32_t a[16];
#pragma unroll
        for (int i = 0; i < 14; i++) {
          const uint32_t u0 = pack_bf16(acc0[2 * i], acc0[2 * i + 1]), u1 = pack_bf16(acc1[2 * i], acc1[2 * i + 1]);
          h[i] = nh ? u1 : u0;
          a[i] = nh ? u0 : u1;
        }
        a[14] = a[0] ^ 0x80008000u;
        a[15] = a[1] ^ 0x80008000u;
        const uint64_t dW = make_desc(sb + OFF_WBD, 1024, 1024, 1);
        wg_fence();
        wgmma_rs_n64_tb1<0>(pp, a[0], a[1], a[2], a[3], dW);
#pragma unroll
        for (int ks = 1; ks < 4; ks++) wgmma_rs_n64_tb1<1>(pp, a[4 * ks], a[4 * ks + 1], a[4 * ks + 2], a[4 * ks + 3], dW + ks * 128);
        wg_commit();
        bar_sync(1, 512);
        if (tid == 0) PROF_MARK(6);
        store_heads(sb + (nh ? OFF_VA : OFF_QP), h, nh ? 0x00003F80u : 0x3F800000u, nh ? 0u : 0x3F803F80u, row0, lq);
        wg_wait<0>();
        fence_regs(pp);
      }
      float v[16];
#pragma unroll
      for (int i = 0; i < 16; i++) v[i] = pp[i];
      uint32_t rb = sb + (nh ? OFF_PHIK : OFF_PHIQ) + row0 * 128 + lq * 4 + ((rowl & 7) << 4);
#pragma unroll 1
      for (int e = 0; e < 2; e++) {
        uint32_t ph[16];
        feature_map(v, ph, lq);
#pragma unroll
        for (int ch = 0; ch < 8; ch++) { sts32(rb ^ (ch << 4), ph[2 * ch]); sts32((rb ^ (ch << 4)) + 1024, ph[2 * ch + 1]); }
        rb += 16384;
#pragma unroll
        for (int i = 0; i < 16; i++) v[i] = pp[16 + i];
      }
      fence_async_smem();
      bar_sync(1, 512);
      if (tid == 0) PROF_MARK(7);
      if (nh == 1) {
        float kv0[16], kv1[16];
        const uint64_t dP = make_desc(sb + OFF_PHIK + mh * 8192, 1024, 1024, 1);
        const uint64_t dV = make_desc(sb + OFF_VA + mh * 4096, 512, 512, 2);
        wg_fence();
        wgmma_ss_n32_ta1_tb1<0>(kv0, dP, dV);
        wgmma_ss_n32_ta1_tb1<0>(kv1, dP + 1024, dV + 512);
#pragma unroll
        for (int ks = 1; ks < 4; ks++) {
          wgmma_ss_n32_ta1_tb1<1>(kv0, dP + ks * 128, dV + ks * 64);
          wgmma_ss_n32_ta1_tb1<1>(kv1, dP + 1024 + ks * 128, dV + 512 + ks * 64);
        }
        wg_commit();
        wg_wait<0>();
        fence_regs(kv0); fence_regs(kv1);
        bar_sync(4 + wg, 128);
        const uint32_t sa = sb + OFF_PHIK + mh * 8192 + rowl * 128 + lq * 8;
#pragma unroll
        for (int j = 0; j < 8; j++) {
          sts64(sa + 32 * (j >> 1) + 1024 * (j & 1), __float_as_uint(kv0[2 * j]), __float_as_uint(kv0[2 * j + 1]));
          sts64(sa + 16384 + 32 * (j >> 1) + 1024 * (j & 1), __float_as_uint(kv1[2 * j]), __float_as_uint(kv1[2 * j + 1]));
        }
        fence_async_smem();
        __syncwarp();
        if (lane == 0) mbar_arrive(BAR(B_SIG + 1), 1);
        if (tid == 256) PROF_MARK(28);
      }
    }
    {
      const uint64_t dK = make_desc(sb + OFF_RING, 512, 512, 2);
      const uint64_t dhi = dK & 0xffffffff00000000ull;
      const uint32_t dlo0 = (uint32_t)dK;
      uint32_t ok = 0, q[8];
      float o[16];
#pragma unroll
      for (int i = 0; i < 16; i++) o[i] = 0.f;
      {
        const int r = mh * 64 + wq * 16 + (lane & 7) + ((lane >> 3) & 1) * 8;
        ldsm4(q, sb + OFF_QP + nh * 8192 + sw64_off(r, (lane >> 4) * 8));
        ldsm4(q + 4, sb + OFF_QP + nh * 8192 + sw64_off(r, 16 + (lane >> 4) * 8));
      }
      if (tid == 0) PROF_MARK(10);
      const int qb = QB_AT;
#pragma unroll 1
      for (int it = 0; it <= 8; it++) {
        uint32_t p[16];
        if ((tid & 127) == 0) PROF4(wg * 32 + it * 3);
        if (it == qb || it == 8) {
          float t[16];
          wg_wait<0>();
          fence_regs(o);
          if (it < 8) {
            if (tid == 0) PROF_MARK(11);
            mbar_wait(BAR(B_KVR), 0);
            const uint64_t dR = make_desc(sb + OFF_KVR + nh * 4096, 512, 512, 2);
            const uint64_t dP = make_desc(sb + OFF_PHIQ + nh * 16384 + mh * 8192, 1024, 1024, 1);
            wg_fence();
            wgmma_ss_n32_ta0_tb1<0>(t, dP, dR);
#pragma unroll
            for (int ks = 1; ks < 4; ks++) wgmma_ss_n32_ta0_tb1<1>(t, dP + ks * 2, dR + ks * 64);
            wg_commit();
            wg_wait<0>();
            fence_regs(t);
            if (lane == 0) mbar_arrive(BAR(B_X1FREE), 1);
          } else {
            if (lane == 0) mbar_arrive(BAR(B_EMPTY + prev), 1);
            if (tid == 0) PROF_MARK(13);
            mbar_wait(BAR(B_SLOW), 0);
            if (__builtin_expect(__any_sync(~0u, *(volatile int*)(sgen + OFF_RED)), 0)) {
              uint32_t qz[8];
#pragma unroll
              for (int i = 0; i < 8; i++) qz[i] = (i >= 6 && lq >= 2) ? 0u : q[i];
              float m0 = -3.0e38f, m1 = -3.0e38f, o2[16];
              int sl2 = slot;
              uint32_t par2 = par;
#pragma unroll 1
              for (int j64 = 0; j64 < 32; j64++) {
                float s[32];
                mbar_wait(BAR(B_FULL + sl2), par2);
                const uint32_t lo = dlo0 + sl2 * 2048 + (j64 & 3) * 512;
                wg_fence();
                wgmma_rs_n64_tb0<0>(s, qz[0], qz[1], qz[2], qz[3], dhi | lo);
                wgmma_rs_n64_tb0<1>(s, qz[4], qz[5], qz[6], qz[7], dhi | (lo + 2));
                wg_commit();
                wg_wait<0>();
                fence_regs(s);
#pragma unroll
                for (int j = 0; j < 8; j++) {
                  const float sc = ((POLY_PAT >> j) & 1) ? 0.5f : 1.f;
                  m0 = fmaxf(m0, fmaxf(s[4 * j], s[4 * j + 1]) * sc);
                  m1 = fmaxf(m1, fmaxf(s[4 * j + 2], s[4 * j + 3]) * sc);
                }
                if ((j64 & 3) == 3) {
                  if (lane == 0) mbar_arrive(BAR(B_EMPTY + sl2), 1);
                  if (++sl2 == 3) { sl2 = 0; par2 ^= 1; }
                }
              }
              m0 = quad_max(m0); m1 = quad_max(m1);
#pragma unroll
              for (int i = 0; i < 16; i++) o2[i] = 0.f;
#pragma unroll 1
              for (int j64 = 0; j64 < 32; j64++) {
                float s[32];
                mbar_wait(BAR(B_FULL + sl2), par2);
                const uint32_t lo = dlo0 + sl2 * 2048 + (j64 & 3) * 512;
                wg_fence();
                wgmma_rs_n64_tb0<0>(s, qz[0], qz[1], qz[2], qz[3], dhi | lo);
                wgmma_rs_n64_tb0<1>(s, qz[4], qz[5], qz[6], qz[7], dhi | (lo + 2));
                wg_commit();
                wg_wait<0>();
                fence_regs(s);
                uint32_t ps[16];
#pragma unroll
                for (int j = 0; j < 8; j++) {
                  const float sc = ((POLY_PAT >> j) & 1) ? 0.5f : 1.f;
                  ps[2 * j] = pack_bf16(ex2f(fmaf(s[4 * j], sc, -m0)), ex2f(fmaf(s[4 * j + 1], sc, -m0)));
                  ps[2 * j + 1] = pack_bf16(ex2f(fmaf(s[4 * j + 2], sc, -m1)), ex2f(fmaf(s[4 * j + 3], sc, -m1)));
                }
                wg_fence();
#pragma unroll
                for (int ks = 0; ks < 4; ks++)
                  wgmma_rs_n32_tb1<1>(o2, ps[4 * ks], ps[4 * ks + 1], ps[4 * ks + 2], ps[4 * ks + 3], dhi | (lo + 256 + ks * 64));
                wg_commit();
                wg_wait<0>();
                fence_regs(o2);
                if ((j64 & 3) == 3) {
                  if (lane == 0) mbar_arrive(BAR(B_EMPTY + sl2), 1);
                  if (++sl2 == 3) { sl2 = 0; par2 ^= 1; }
                }
              }
#pragma unroll 1
              for (int j = 0; j < 2; j++) {
                mbar_wait(BAR(B_FULL + sl2), par2);
                __syncwarp();
                if (lane == 0) mbar_arrive(BAR(B_EMPTY + sl2), 1);
                if (++sl2 == 3) { sl2 = 0; par2 ^= 1; }
              }
#pragma unroll
              for (int i = 0; i < 16; i++) o[i] = o2[i];
            }
#pragma unroll
            for (int i = 0; i < 16; i++) t[i] = o[i];
          }
          const int br = it == 8;
          const float eps = br ? 0.f : 1e-6f;
          const float g0 = ((const float*)(sgen + OFF_GATE))[row0], g1 = ((const float*)(sgen + OFF_GATE))[row0 + 8];
          const float d0 = __shfl_sync(~0u, t[12], (lane & ~3) | 2), d1 = __shfl_sync(~0u, t[14], (lane & ~3) | 2);
          const float r0 = (br ? 1.f - g0 : g0) * rcpf(d0 + eps), r1 = (br ? 1.f - g1 : g1) * rcpf(d1 + eps);
          uint8_t* img = g_o_img + (size_t)((pt * 2 + br) * 14 + mh) * 8192 + rowl * 128;
          const int col0 = (2 * hp + nh) * DH + 2 * lq;
#pragma unroll
          for (int j = 0; j < 4; j++) {
            const int col = col0 + 8 * j;
            uint8_t* gp = img + (uint32_t)((col >> 6) * 16384 + ((((col >> 3) ^ rowl) & 7) << 4) + (col & 7) * 2);
            const uint32_t v0 = pack_bf16(t[4 * j] * r0, t[4 * j + 1] * r0), v1 = pack_bf16(t[4 * j + 2] * r1, t[4 * j + 3] * r1);
            if (j < 3 || lq < 2) { *(uint32_t*)gp = v0; *(uint32_t*)(gp + 1024) = v1; }
          }
          __syncwarp();
          if (lane == 0) mbar_arrive(BAR(B_SIG + 2 + br), 1);
          if (tid == 0) PROF_MARK(12 + 2 * br);
          if (br) break;
        }
        const uint32_t lo = dlo0 + slot * 2048;
        if ((tid & 127) == 0) PROF4(wg * 32 + it * 3 + 1);
        if (!ok) mbar_wait(BAR(B_FULL + slot), par);
        if ((tid & 127) == 0) PROF4(wg * 32 + it * 3 + 2);
        int nslot = slot + 1;
        uint32_t npar = par;
        if (nslot == 3) { nslot = 0; npar ^= 1; }
        {
          float s[32];
          wg_fence();
          wgmma_rs_n64_tb0<0>(s, q[0], q[1], q[2], q[3], dhi | lo);
          wgmma_rs_n64_tb0<1>(s, q[4], q[5], q[6], q[7], dhi | (lo + 2));
          wg_commit();
#pragma unroll
          for (int u = 0; u < 4; u++) {
            wg_wait<0>();
            fence_regs(s);
            if (u == 0 && lane == 0 && it > 0) mbar_arrive(BAR(B_EMPTY + prev), 1);
            if (u == 2) ok = mbar_test(BAR(B_FULL + nslot), npar);
#pragma unroll
            for (int j = 0; j < 8; j++) {
              if ((POLY_PAT >> j) & 1) {
                p[2 * j] = exp2_pair_fma(s[4 * j], s[4 * j + 1], 0x3F003F00u, 0x00030003u);
                p[2 * j + 1] = exp2_pair_fma(s[4 * j + 2], s[4 * j + 3], 0x3F003F00u, 0x00030003u);
              } else {
                p[2 * j] = pack_bf16(ex2f(s[4 * j]), ex2f(s[4 * j + 1]));
                p[2 * j + 1] = pack_bf16(ex2f(s[4 * j + 2]), ex2f(s[4 * j + 3]));
              }
            }
            wg_fence();
#pragma unroll
            for (int ks = 0; ks < 4; ks++)
              wgmma_rs_n32_tb1<1>(o, p[4 * ks], p[4 * ks + 1], p[4 * ks + 2], p[4 * ks + 3], dhi | (lo + u * 512 + 256 + ks * 64));
            if (u < 3) {
              wgmma_rs_n64_tb0<0>(s, q[0], q[1], q[2], q[3], dhi | (lo + (u + 1) * 512));
              wgmma_rs_n64_tb0<1>(s, q[4], q[5], q[6], q[7], dhi | (lo + (u + 1) * 512 + 2));
            }
            wg_commit();
          }
        }
        prev = slot; slot = nslot; par = npar;
      }
      wg_wait<0>();
    }
    if (nh == 1) return;
    {
      float acc0[28], acc1[28];
#pragma unroll
      for (int i = 0; i < 28; i++) acc0[i] = acc1[i] = 0.f;
      const uint64_t dS = make_desc(sb + OFF_WO, 1024, 1024, 1);
      const uint64_t dR = make_desc(sb + OFF_RING + mh * 8192, 1024, 1024, 1);
#pragma unroll 1
      for (int c = 0; c < 7; c++) {
        mbar_wait(BAR(B_WO + (c >= 3)), 0);
        mbar_wait(BAR(B_FULL + slot), par);
        const uint64_t dA = dR + slot * 2048, dB = dS + c * 1024;
        wg_fence();
#pragma unroll
        for (int ks = 0; ks < 4; ks++) {
          wgmma_ss_n56_ta0_tb1<1>(acc0, dA + ks * 2, dB + ks * 128);
          wgmma_ss_n56_ta0_tb1<1>(acc1, dA + 1024 + ks * 2, dB + 512 + ks * 128);
        }
        wg_commit();
        if (c < 4) {
          wg_wait<0>();
          if (lane == 0) mbar_arrive(BAR(B_EMPTY + slot), 2);
        }
        if (++slot == 3) { slot = 0; par ^= 1; }
      }
      wg_wait<0>();
      fence_regs(acc0); fence_regs(acc1);
      if (tid == 0) PROF_MARK(17);
      __nv_bfloat16* op = prm.out + (size_t)(pt * 128 + row0) * DM + hp * 56 + 2 * lq;
#pragma unroll
      for (int j = 0; j < 7; j++) {
        *(uint32_t*)(op + 8 * j) = pack_bf16(acc0[4 * j] + acc1[4 * j], acc0[4 * j + 1] + acc1[4 * j + 1]);
        *(uint32_t*)(op + 8 * DM + 8 * j) = pack_bf16(acc0[4 * j + 2] + acc1[4 * j + 2], acc0[4 * j + 3] + acc1[4 * j + 3]);
      }
      if (tid == 0) { PROF_MARK(18); PROF_CLK(31); }
    }
  }
}

typedef CUresult (*EncodeFn)(CUtensorMap*, CUtensorMapDataType, cuuint32_t, void*, const cuuint64_t*, const cuuint64_t*,
                             const cuuint32_t*, const cuuint32_t*, CUtensorMapInterleave, CUtensorMapSwizzle,
                             CUtensorMapL2promotion, CUtensorMapFloatOOBfill);

void make_map(EncodeFn enc, CUtensorMap* tm, const void* ptr, uint64_t cols, uint64_t rows, uint32_t box_rows) {
  cuuint64_t dims[2] = {cols, rows};
  cuuint64_t strides[1] = {cols * 2};
  cuuint32_t box[2] = {64, box_rows};
  cuuint32_t es[2] = {1, 1};
  enc(tm, CU_TENSOR_MAP_DATA_TYPE_BFLOAT16, 2, const_cast<void*>(ptr), dims, strides, box, es, CU_TENSOR_MAP_INTERLEAVE_NONE,
      CU_TENSOR_MAP_SWIZZLE_128B, CU_TENSOR_MAP_L2_PROMOTION_L2_128B, CU_TENSOR_MAP_FLOAT_OOB_FILL_NONE);
}

}

extern "C" void kernel_launch(void* const* d_in, const int* in_sizes, int n_in, void* d_out, int out_size) {
  (void)in_sizes; (void)n_in; (void)out_size;
  static EncodeFn enc = nullptr;
  if (!enc) {
    void* fn = nullptr;
    cudaDriverEntryPointQueryResult qr;
    cudaGetDriverEntryPoint("cuTensorMapEncodeTiled", &fn, cudaEnableDefault, &qr);
    enc = (EncodeFn)fn;
    cudaFuncSetAttribute(fused_kernel, cudaFuncAttributeMaxDynamicSharedMemorySize, SMEM_BYTES);
  }
  CUtensorMap tm_x, tm_wqkv, tm_wq, tm_woa, tm_wob;
  make_map(enc, &tm_x, d_in[0], DM, S_LEN, 128);
  make_map(enc, &tm_wqkv, d_in[1], 3 * DM, DM, 64);
  make_map(enc, &tm_wq, d_in[5], DM, DM, 64);
  make_map(enc, &tm_woa, d_in[3], DM, DM, 64);
  make_map(enc, &tm_wob, d_in[8], DM, DM, 64);
  Params prm;
  prm.w_phi = (const __nv_bfloat16*)d_in[2];
  prm.wk = (const __nv_bfloat16*)d_in[6];
  prm.wv = (const __nv_bfloat16*)d_in[7];
  prm.gate_w = (const __nv_bfloat16*)d_in[9];
  prm.out = (__nv_bfloat16*)d_out;
  fused_kernel<<<NCTA, NTHREADS, SMEM_BYTES>>>(tm_x, tm_wqkv, tm_wq, tm_woa, tm_wob, prm);
}
```

```cpp
#include <cuda_runtime.h>
#include <cuda_bf16.h>
#include <cuda.h>
#include <stdint.h>

namespace {

constexpr int S_LEN = 2048, DM = 448, DH = 28;
constexpr int NCTA = 128;
constexpr int NTHREADS = 640;
constexpr uint32_t POLY_PAT = 0x57;

#define QB_AT (4 + nh)

constexpr int OFF_X = 0;
constexpr int OFF_PHIK = 0;
constexpr int OFF_VA = 32768;
constexpr int OFF_PHIQ = 57344;
constexpr int OFF_KVR = 90112;
constexpr int OFF_QP = 98304;
constexpr int OFF_WO = 0;
constexpr int OFF_RING = 114688;
constexpr int OFF_WBD = 212992;
constexpr int OFF_SLC = 221184;
constexpr int OFF_QSQ = 228352;
constexpr int OFF_GATE = 229376;
constexpr int OFF_RED = 229888;
constexpr int OFF_BAR = 229952;
constexpr int SMEM_BYTES = 230400 + 1024;

constexpr int B_FULL = 0, B_EMPTY = 3, B_WO = 6  , B_KVR = 8, B_X1FREE = 10, B_QSQ = 11, B_SLOW = 12,
              B_BUILD = 13, B_SIG = 14  , B_N = 18;

constexpr int C_KV = 0, C_PART = 1, C_DONE = 3, C_OA = 4, C_OB = 20, C_N = 36;

__device__ __align__(1024) uint8_t g_kv_img[32 * 8192];
__device__ __align__(16) float g_ksq[512];
__device__ __align__(16) float g_vsq[512];
__device__ __align__(16) float g_gate[S_LEN];
__device__ __align__(1024) float g_kvacc[2][16 * 64 * 32];
__device__ unsigned g_epoch;
__device__ __align__(1024) uint8_t g_o_img[2 * 16 * 14 * 8192];
__device__ unsigned g_cnt[C_N * 32];

#define PROF4(i) do { } while (0)
#define PROF3(i) do { } while (0)
#define PROF2(i) do { } while (0)
#define PROF_CLK(i) do { } while (0)
#define PROF_MARK(i) do { } while (0)
__device__ __forceinline__ uint32_t smem_u32(const void* p) { return (uint32_t)__cvta_generic_to_shared(p); }
__device__ __forceinline__ void mbar_init(uint32_t a, int cnt) {
  asm volatile("mbarrier.init.shared::cta.b64 [%0], %1;" ::"r"(a), "r"(cnt) : "memory");
}
__device__ __forceinline__ void mbar_expect_tx(uint32_t a, uint32_t bytes) {
  asm volatile("mbarrier.arrive.expect_tx.shared::cta.b64 _, [%0], %1;" ::"r"(a), "r"(bytes) : "memory");
}
__device__ __forceinline__ void mbar_arrive(uint32_t a, uint32_t cnt) {
  asm volatile("mbarrier.arrive.shared::cta.b64 _, [%0], %1;" ::"r"(a), "r"(cnt) : "memory");
}
__device__ __forceinline__ void mbar_wait(uint32_t a, uint32_t parity) {
  asm volatile(
      "{\n.reg .pred p;\n.reg .u32 c;\nmov.u32 c, 0;\n"
      "W_%=:\nmbarrier.try_wait.parity.shared::cta.b64 p, [%0], %1;\n"
      "add.u32 c, c, 1;\nsetp.lt.and.u32 p, c, 0x40000, !p;\n@p bra W_%=;\n}"
      ::"r"(a), "r"(parity) : "memory");
}
__device__ __forceinline__ uint32_t mbar_test(uint32_t a, uint32_t parity) {
  uint32_t ok;
  asm volatile("{\n.reg .pred p;\nmbarrier.test_wait.parity.shared::cta.b64 p, [%1], %2;\nselp.u32 %0, 1, 0, p;\n}"
               : "=r"(ok) : "r"(a), "r"(parity) : "memory");
  return ok;
}
__device__ __forceinline__ bool elect_one() {
  uint32_t r;
  asm volatile("{\n.reg .pred p;\nelect.sync _|p, 0xffffffff;\nselp.u32 %0, 1, 0, p;\n}" : "=r"(r));
  return r != 0;
}
__device__ __forceinline__ void tma_2d(uint32_t dst, const CUtensorMap* tm, int c0, int c1, uint32_t bar) {
  asm volatile("cp.async.bulk.tensor.2d.shared::cluster.global.mbarrier::complete_tx::bytes [%0], [%1, {%3, %4}], [%2];"
               ::"r"(dst), "l"(tm), "r"(bar), "r"(c0), "r"(c1) : "memory");
}
__device__ __forceinline__ void bulk_g2s(uint32_t dst, const void* src, uint32_t bytes, uint32_t bar) {
  asm volatile("cp.async.bulk.shared::cluster.global.mbarrier::complete_tx::bytes [%0], [%1], %2, [%3];"
               ::"r"(dst), "l"(src), "r"(bytes), "r"(bar) : "memory");
}
__device__ __forceinline__ void cp_async8(uint32_t dst, const void* src) {
  asm volatile("cp.async.ca.shared.global [%0], [%1], 8;" ::"r"(dst), "l"(src) : "memory");
}
__device__ __forceinline__ void fence_async_smem() { asm volatile("fence.proxy.async.shared::cta;" ::: "memory"); }
__device__ __forceinline__ void fence_async_all() { asm volatile("fence.proxy.async.global;" ::: "memory"); }

__device__ __forceinline__ void bar_sync(int id, int n) { asm volatile("bar.sync %0, %1;" ::"r"(id), "r"(n) : "memory"); }
__device__ __forceinline__ void cnt_arrive(int idx) {
  asm volatile("red.release.gpu.global.add.u32 [%0], 1;" ::"l"(&g_cnt[idx * 32]) : "memory");
}
__device__ __forceinline__ void cnt_wait(int idx, unsigned target) {
  unsigned v, n = 0;
#pragma unroll 1
  while (true) {
    asm volatile("ld.acquire.gpu.global.u32 %0, [%1];" : "=r"(v) : "l"(&g_cnt[idx * 32]) : "memory");
    if (v >= target || ++n >= (1u << 18)) break;
    __nanosleep(32);
  }
}
__device__ __forceinline__ void wg_fence() { asm volatile("wgmma.fence.sync.aligned;" ::: "memory"); }
__device__ __forceinline__ void wg_commit() { asm volatile("wgmma.commit_group.sync.aligned;" ::: "memory"); }
template <int N> __device__ __forceinline__ void wg_wait() { asm volatile("wgmma.wait_group.sync.aligned %0;" ::"n"(N) : "memory"); }
template <int N> __device__ __forceinline__ void fence_regs(float (&d)[N]) {
#pragma unroll
  for (int i = 0; i < N; i++) asm volatile("" : "+f"(d[i])::"memory");
}
__device__ __forceinline__ uint64_t make_desc(uint32_t saddr, uint32_t lbo, uint32_t sbo, uint32_t swz) {
  return (uint64_t)((saddr & 0x3FFFF) >> 4) | ((uint64_t)(lbo >> 4) << 16) | ((uint64_t)(sbo >> 4) << 32) | ((uint64_t)swz << 62);
}
__device__ __forceinline__ float ex2f(float x) { float y; asm("ex2.approx.ftz.f32 %0, %1;" : "=f"(y) : "f"(x)); return y; }
__device__ __forceinline__ float rcpf(float x) { float y; asm("rcp.approx.ftz.f32 %0, %1;" : "=f"(y) : "f"(x)); return y; }
__device__ __forceinline__ uint32_t pack_bf16(float lo, float hi) {
  uint32_t r; asm("cvt.rn.bf16x2.f32 %0, %1, %2;" : "=r"(r) : "f"(hi), "f"(lo)); return r;
}
__device__ __forceinline__ uint32_t lop_and_or(uint32_t a, uint32_t m, uint32_t c) {
  uint32_t r; asm("lop3.b32 %0, %1, %2, %3, 0xEA;" : "=r"(r) : "r"(a), "r"(m), "r"(c)); return r;
}
__device__ __forceinline__ void sts32(uint32_t a, uint32_t v) { asm volatile("st.shared.b32 [%0], %1;" ::"r"(a), "r"(v) : "memory"); }
__device__ __forceinline__ void sts64(uint32_t a, uint32_t v0, uint32_t v1) { asm volatile("st.shared.v2.b32 [%0], {%1, %2};" ::"r"(a), "r"(v0), "r"(v1) : "memory"); }
__device__ __forceinline__ void sts128(uint32_t a, uint4 v) {
  asm volatile("st.shared.v4.b32 [%0], {%1, %2, %3, %4};" ::"r"(a), "r"(v.x), "r"(v.y), "r"(v.z), "r"(v.w) : "memory");
}
__device__ __forceinline__ float4 ldcg_f4(const float* p) {
  float4 v; asm volatile("ld.global.cg.v4.f32 {%0, %1, %2, %3}, [%4];" : "=f"(v.x), "=f"(v.y), "=f"(v.z), "=f"(v.w) : "l"(p) : "memory"); return v;
}
__device__ __forceinline__ void ldsm4(uint32_t* r, uint32_t a) {
  asm volatile("ldmatrix.sync.aligned.m8n8.x4.shared.b16 {%0, %1, %2, %3}, [%4];"
               : "=r"(r[0]), "=r"(r[1]), "=r"(r[2]), "=r"(r[3]) : "r"(a) : "memory");
}
__device__ __forceinline__ float quad_sum(float v) { v += __shfl_xor_sync(~0u, v, 1); v += __shfl_xor_sync(~0u, v, 2); return v; }
__device__ __forceinline__ float quad_max(float v) { v = fmaxf(v, __shfl_xor_sync(~0u, v, 1)); v = fmaxf(v, __shfl_xor_sync(~0u, v, 2)); return v; }

template <int SD> __device__ __forceinline__ void wgmma_ss_n56_ta0_tb1(float (&d)[28], uint64_t da, uint64_t db) {
  if (SD) asm volatile("wgmma.mma_async.sync.aligned.m64n56k16.f32.bf16.bf16 {%0, %1, %2, %3, %4, %5, %6, %7, %8, %9, %10, %11, %12, %13, %14, %15, %16, %17, %18, %19, %20, %21, %22, %23, %24, %25, %26, %27}, %28, %29, 1, 1, 1, 0, 1;\n"
    : "+f"(d[0]), "+f"(d[1]), "+f"(d[2]), "+f"(d[3]), "+f"(d[4]), "+f"(d[5]), "+f"(d[6]), "+f"(d[7]), "+f"(d[8]), "+f"(d[9]), "+f"(d[10]), "+f"(d[11]), "+f"(d[12]), "+f"(d[13]), "+f"(d[14]), "+f"(d[15]), "+f"(d[16]), "+f"(d[17]), "+f"(d[18]), "+f"(d[19]), "+f"(d[20]), "+f"(d[21]), "+f"(d[22]), "+f"(d[23]), "+f"(d[24]), "+f"(d[25]), "+f"(d[26]), "+f"(d[27])
    : "l"(da), "l"(db));
  else asm volatile("wgmma.mma_async.sync.aligned.m64n56k16.f32.bf16.bf16 {%0, %1, %2, %3, %4, %5, %6, %7, %8, %9, %10, %11, %12, %13, %14, %15, %16, %17, %18, %19, %20, %21, %22, %23, %24, %25, %26, %27}, %28, %29, 0, 1, 1, 0, 1;\n"
    : "=f"(d[0]), "=f"(d[1]), "=f"(d[2]), "=f"(d[3]), "=f"(d[4]), "=f"(d[5]), "=f"(d[6]), "=f"(d[7]), "=f"(d[8]), "=f"(d[9]), "=f"(d[10]), "=f"(d[11]), "=f"(d[12]), "=f"(d[13]), "=f"(d[14]), "=f"(d[15]), "=f"(d[16]), "=f"(d[17]), "=f"(d[18]), "=f"(d[19]), "=f"(d[20]), "=f"(d[21]), "=f"(d[22]), "=f"(d[23]), "=f"(d[24]), "=f"(d[25]), "=f"(d[26]), "=f"(d[27])
    : "l"(da), "l"(db));
}
template <int SD> __device__ __forceinline__ void wgmma_rs_n56_tb1(float (&d)[28], uint32_t a0, uint32_t a1, uint32_t a2, uint32_t a3, uint64_t db) {
  if (SD) asm volatile("wgmma.mma_async.sync.aligned.m64n56k16.f32.bf16.bf16 {%0, %1, %2, %3, %4, %5, %6, %7, %8, %9, %10, %11, %12, %13, %14, %15, %16, %17, %18, %19, %20, %21, %22, %23, %24, %25, %26, %27}, {%28, %29, %30, %31}, %32, 1, 1, 1, 1;\n"
    : "+f"(d[0]), "+f"(d[1]), "+f"(d[2]), "+f"(d[3]), "+f"(d[4]), "+f"(d[5]), "+f"(d[6]), "+f"(d[7]), "+f"(d[8]), "+f"(d[9]), "+f"(d[10]), "+f"(d[11]), "+f"(d[12]), "+f"(d[13]), "+f"(d[14]), "+f"(d[15]), "+f"(d[16]), "+f"(d[17]), "+f"(d[18]), "+f"(d[19]), "+f"(d[20]), "+f"(d[21]), "+f"(d[22]), "+f"(d[23]), "+f"(d[24]), "+f"(d[25]), "+f"(d[26]), "+f"(d[27])
    : "r"(a0), "r"(a1), "r"(a2), "r"(a3), "l"(db));
  else asm volatile("wgmma.mma_async.sync.aligned.m64n56k16.f32.bf16.bf16 {%0, %1, %2, %3, %4, %5, %6, %7, %8, %9, %10, %11, %12, %13, %14, %15, %16, %17, %18, %19, %20, %21, %22, %23, %24, %25, %26, %27}, {%28, %29, %30, %31}, %32, 0, 1, 1, 1;\n"
    : "=f"(d[0]), "=f"(d[1]), "=f"(d[2]), "=f"(d[3]), "=f"(d[4]), "=f"(d[5]), "=f"(d[6]), "=f"(d[7]), "=f"(d[8]), "=f"(d[9]), "=f"(d[10]), "=f"(d[11]), "=f"(d[12]), "=f"(d[13]), "=f"(d[14]), "=f"(d[15]), "=f"(d[16]), "=f"(d[17]), "=f"(d[18]), "=f"(d[19]), "=f"(d[20]), "=f"(d[21]), "=f"(d[22]), "=f"(d[23]), "=f"(d[24]), "=f"(d[25]), "=f"(d[26]), "=f"(d[27])
    : "r"(a0), "r"(a1), "r"(a2), "r"(a3), "l"(db));
}
template <int SD> __device__ __forceinline__ void wgmma_ss_n8_ta0_tb1(float (&d)[4], uint64_t da, uint64_t db) {
  if (SD) asm volatile("wgmma.mma_async.sync.aligned.m64n8k16.f32.bf16.bf16 {%0, %1, %2, %3}, %4, %5, 1, 1, 1, 0, 1;\n"
    : "+f"(d[0]), "+f"(d[1]), "+f"(d[2]), "+f"(d[3])
    : "l"(da), "l"(db));
  else asm volatile("wgmma.mma_async.sync.aligned.m64n8k16.f32.bf16.bf16 {%0, %1, %2, %3}, %4, %5, 0, 1, 1, 0, 1;\n"
    : "=f"(d[0]), "=f"(d[1]), "=f"(d[2]), "=f"(d[3])
    : "l"(da), "l"(db));
}
template <int SD> __device__ __forceinline__ void wgmma_rs_n64_tb1(float (&d)[32], uint32_t a0, uint32_t a1, uint32_t a2, uint32_t a3, uint64_t db) {
  if (SD) asm volatile("wgmma.mma_async.sync.aligned.m64n64k16.f32.bf16.bf16 {%0, %1, %2, %3, %4, %5, %6, %7, %8, %9, %10, %11, %12, %13, %14, %15, %16, %17, %18, %19, %20, %21, %22, %23, %24, %25, %26, %27, %28, %29, %30, %31}, {%32, %33, %34, %35}, %36, 1, 1, 1, 1;\n"
    : "+f"(d[0]), "+f"(d[1]), "+f"(d[2]), "+f"(d[3]), "+f"(d[4]), "+f"(d[5]), "+f"(d[6]), "+f"(d[7]), "+f"(d[8]), "+f"(d[9]), "+f"(d[10]), "+f"(d[11]), "+f"(d[12]), "+f"(d[13]), "+f"(d[14]), "+f"(d[15]), "+f"(d[16]), "+f"(d[17]), "+f"(d[18]), "+f"(d[19]), "+f"(d[20]), "+f"(d[21]), "+f"(d[22]), "+f"(d[23]), "+f"(d[24]), "+f"(d[25]), "+f"(d[26]), "+f"(d[27]), "+f"(d[28]), "+f"(d[29]), "+f"(d[30]), "+f"(d[31])
    : "r"(a0), "r"(a1), "r"(a2), "r"(a3), "l"(db));
  else asm volatile("wgmma.mma_async.sync.aligned.m64n64k16.f32.bf16.bf16 {%0, %1, %2, %3, %4, %5, %6, %7, %8, %9, %10, %11, %12, %13, %14, %15, %16, %17, %18, %19, %20, %21, %22, %23, %24, %25, %26, %27, %28, %29, %30, %31}, {%32, %33, %34, %35}, %36, 0, 1, 1, 1;\n"
    : "=f"(d[0]), "=f"(d[1]), "=f"(d[2]), "=f"(d[3]), "=f"(d[4]), "=f"(d[5]), "=f"(d[6]), "=f"(d[7]), "=f"(d[8]), "=f"(d[9]), "=f"(d[10]), "=f"(d[11]), "=f"(d[12]), "=f"(d[13]), "=f"(d[14]), "=f"(d[15]), "=f"(d[16]), "=f"(d[17]), "=f"(d[18]), "=f"(d[19]), "=f"(d[20]), "=f"(d[21]), "=f"(d[22]), "=f"(d[23]), "=f"(d[24]), "=f"(d[25]), "=f"(d[26]), "=f"(d[27]), "=f"(d[28]), "=f"(d[29]), "=f"(d[30]), "=f"(d[31])
    : "r"(a0), "r"(a1), "r"(a2), "r"(a3), "l"(db));
}
template <int SD> __device__ __forceinline__ void wgmma_ss_n32_ta1_tb1(float (&d)[16], uint64_t da, uint64_t db) {
  if (SD) asm volatile("wgmma.mma_async.sync.aligned.m64n32k16.f32.bf16.bf16 {%0, %1, %2, %3, %4, %5, %6, %7, %8, %9, %10, %11, %12, %13, %14, %15}, %16, %17, 1, 1, 1, 1, 1;\n"
    : "+f"(d[0]), "+f"(d[1]), "+f"(d[2]), "+f"(d[3]), "+f"(d[4]), "+f"(d[5]), "+f"(d[6]), "+f"(d[7]), "+f"(d[8]), "+f"(d[9]), "+f"(d[10]), "+f"(d[11]), "+f"(d[12]), "+f"(d[13]), "+f"(d[14]), "+f"(d[15])
    : "l"(da), "l"(db));
  else asm volatile("wgmma.mma_async.sync.aligned.m64n32k16.f32.bf16.bf16 {%0, %1, %2, %3, %4, %5, %6, %7, %8, %9, %10, %11, %12, %13, %14, %15}, %16, %17, 0, 1, 1, 1, 1;\n"
    : "=f"(d[0]), "=f"(d[1]), "=f"(d[2]), "=f"(d[3]), "=f"(d[4]), "=f"(d[5]), "=f"(d[6]), "=f"(d[7]), "=f"(d[8]), "=f"(d[9]), "=f"(d[10]), "=f"(d[11]), "=f"(d[12]), "=f"(d[13]), "=f"(d[14]), "=f"(d[15])
    : "l"(da), "l"(db));
}
template <int SD> __device__ __forceinline__ void wgmma_ss_n32_ta0_tb1(float (&d)[16], uint64_t da, uint64_t db) {
  if (SD) asm volatile("wgmma.mma_async.sync.aligned.m64n32k16.f32.bf16.bf16 {%0, %1, %2, %3, %4, %5, %6, %7, %8, %9, %10, %11, %12, %13, %14, %15}, %16, %17, 1, 1, 1, 0, 1;\n"
    : "+f"(d[0]), "+f"(d[1]), "+f"(d[2]), "+f"(d[3]), "+f"(d[4]), "+f"(d[5]), "+f"(d[6]), "+f"(d[7]), "+f"(d[8]), "+f"(d[9]), "+f"(d[10]), "+f"(d[11]), "+f"(d[12]), "+f"(d[13]), "+f"(d[14]), "+f"(d[15])
    : "l"(da), "l"(db));
  else asm volatile("wgmma.mma_async.sync.aligned.m64n32k16.f32.bf16.bf16 {%0, %1, %2, %3, %4, %5, %6, %7, %8, %9, %10, %11, %12, %13, %14, %15}, %16, %17, 0, 1, 1, 0, 1;\n"
    : "=f"(d[0]), "=f"(d[1]), "=f"(d[2]), "=f"(d[3]), "=f"(d[4]), "=f"(d[5]), "=f"(d[6]), "=f"(d[7]), "=f"(d[8]), "=f"(d[9]), "=f"(d[10]), "=f"(d[11]), "=f"(d[12]), "=f"(d[13]), "=f"(d[14]), "=f"(d[15])
    : "l"(da), "l"(db));
}
template <int SD> __device__ __forceinline__ void wgmma_rs_n64_tb0(float (&d)[32], uint32_t a0, uint32_t a1, uint32_t a2, uint32_t a3, uint64_t db) {
  if (SD) asm volatile("wgmma.mma_async.sync.aligned.m64n64k16.f32.bf16.bf16 {%0, %1, %2, %3, %4, %5, %6, %7, %8, %9, %10, %11, %12, %13, %14, %15, %16, %17, %18, %19, %20, %21, %22, %23, %24, %25, %26, %27, %28, %29, %30, %31}, {%32, %33, %34, %35}, %36, 1, 1, 1, 0;\n"
    : "+f"(d[0]), "+f"(d[1]), "+f"(d[2]), "+f"(d[3]), "+f"(d[4]), "+f"(d[5]), "+f"(d[6]), "+f"(d[7]), "+f"(d[8]), "+f"(d[9]), "+f"(d[10]), "+f"(d[11]), "+f"(d[12]), "+f"(d[13]), "+f"(d[14]), "+f"(d[15]), "+f"(d[16]), "+f"(d[17]), "+f"(d[18]), "+f"(d[19]), "+f"(d[20]), "+f"(d[21]), "+f"(d[22]), "+f"(d[23]), "+f"(d[24]), "+f"(d[25]), "+f"(d[26]), "+f"(d[27]), "+f"(d[28]), "+f"(d[29]), "+f"(d[30]), "+f"(d[31])
    : "r"(a0), "r"(a1), "r"(a2), "r"(a3), "l"(db));
  else asm volatile("wgmma.mma_async.sync.aligned.m64n64k16.f32.bf16.bf16 {%0, %1, %2, %3, %4, %5, %6, %7, %8, %9, %10, %11, %12, %13, %14, %15, %16, %17, %18, %19, %20, %21, %22, %23, %24, %25, %26, %27, %28, %29, %30, %31}, {%32, %33, %34, %35}, %36, 0, 1, 1, 0;\n"
    : "=f"(d[0]), "=f"(d[1]), "=f"(d[2]), "=f"(d[3]), "=f"(d[4]), "=f"(d[5]), "=f"(d[6]), "=f"(d[7]), "=f"(d[8]), "=f"(d[9]), "=f"(d[10]), "=f"(d[11]), "=f"(d[12]), "=f"(d[13]), "=f"(d[14]), "=f"(d[15]), "=f"(d[16]), "=f"(d[17]), "=f"(d[18]), "=f"(d[19]), "=f"(d[20]), "=f"(d[21]), "=f"(d[22]), "=f"(d[23]), "=f"(d[24]), "=f"(d[25]), "=f"(d[26]), "=f"(d[27]), "=f"(d[28]), "=f"(d[29]), "=f"(d[30]), "=f"(d[31])
    : "r"(a0), "r"(a1), "r"(a2), "r"(a3), "l"(db));
}
template <int SD> __device__ __forceinline__ void wgmma_rs_n32_tb1(float (&d)[16], uint32_t a0, uint32_t a1, uint32_t a2, uint32_t a3, uint64_t db) {
  if (SD) asm volatile("wgmma.mma_async.sync.aligned.m64n32k16.f32.bf16.bf16 {%0, %1, %2, %3, %4, %5, %6, %7, %8, %9, %10, %11, %12, %13, %14, %15}, {%16, %17, %18, %19}, %20, 1, 1, 1, 1;\n"
    : "+f"(d[0]), "+f"(d[1]), "+f"(d[2]), "+f"(d[3]), "+f"(d[4]), "+f"(d[5]), "+f"(d[6]), "+f"(d[7]), "+f"(d[8]), "+f"(d[9]), "+f"(d[10]), "+f"(d[11]), "+f"(d[12]), "+f"(d[13]), "+f"(d[14]), "+f"(d[15])
    : "r"(a0), "r"(a1), "r"(a2), "r"(a3), "l"(db));
  else asm volatile("wgmma.mma_async.sync.aligned.m64n32k16.f32.bf16.bf16 {%0, %1, %2, %3, %4, %5, %6, %7, %8, %9, %10, %11, %12, %13, %14, %15}, {%16, %17, %18, %19}, %20, 0, 1, 1, 1;\n"
    : "=f"(d[0]), "=f"(d[1]), "=f"(d[2]), "=f"(d[3]), "=f"(d[4]), "=f"(d[5]), "=f"(d[6]), "=f"(d[7]), "=f"(d[8]), "=f"(d[9]), "=f"(d[10]), "=f"(d[11]), "=f"(d[12]), "=f"(d[13]), "=f"(d[14]), "=f"(d[15])
    : "r"(a0), "r"(a1), "r"(a2), "r"(a3), "l"(db));
}

__device__ __forceinline__ uint32_t sw64_off(int row, int d) { return row * 64 + ((((d >> 3) ^ (row >> 1)) & 3) << 4) + (d & 7) * 2; }

__device__ __forceinline__ uint32_t exp2_pair_fma(float t0, float t1, uint32_t c_half, uint32_t c_3) {
  uint32_t y0, y;
  asm("prmt.b32 %0, %1, %2, 0x6521;" : "=r"(y0) : "r"(__float_as_uint(t0)), "r"(__float_as_uint(t1)));
  uint32_t h = lop_and_or(y0, 0x007F007Fu, c_half);
  uint32_t e = lop_and_or(y0, 0xFF80FF80u, c_3);
  asm("fma.rn.bf16x2 %0, %1, %2, %3;" : "=r"(y) : "r"(y0), "r"(h), "r"(e));
  return y;
}

__device__ __forceinline__ void feature_map(float (&v)[16], uint32_t (&ph)[16], int lq) {
  const float L2E = 1.4426950408889634f;
  const bool tail_ok = lq < 2;
  float mx[2], mn[2], b[16], sa[2], sn[2];
#pragma unroll
  for (int r = 0; r < 2; r++) {
    const int o = 2 * r;
    if (!tail_ok) { v[o + 12] = v[o]; v[o + 13] = v[o]; }
    mx[r] = fmaxf(fmaxf(fmaxf(v[o], v[o + 1]), fmaxf(v[o + 4], v[o + 5])), fmaxf(fmaxf(v[o + 8], v[o + 9]), fmaxf(v[o + 12], v[o + 13])));
    mn[r] = fminf(fminf(fminf(v[o], v[o + 1]), fminf(v[o + 4], v[o + 5])), fminf(fminf(v[o + 8], v[o + 9]), fminf(v[o + 12], v[o + 13])));
  }
#pragma unroll
  for (int o = 1; o <= 2; o <<= 1)
#pragma unroll
    for (int r = 0; r < 2; r++) { mx[r] = fmaxf(mx[r], __shfl_xor_sync(~0u, mx[r], o)); mn[r] = fminf(mn[r], __shfl_xor_sync(~0u, mn[r], o)); }
#pragma unroll
  for (int r = 0; r < 2; r++) {
    const int o = 2 * r;
    const float cx = -mx[r] * L2E, cn = mn[r] * L2E;
#pragma unroll
    for (int i = 0; i < 8; i++) {
      const int k = o + 4 * (i >> 1) + (i & 1);
      b[k] = ex2f(fmaf(v[k], -L2E, cn));
      v[k] = ex2f(fmaf(v[k], L2E, cx));
    }
    if (!tail_ok) { v[o + 12] = v[o + 13] = b[o + 12] = b[o + 13] = 0.f; }
    sa[r] = ((v[o] + v[o + 1]) + (v[o + 4] + v[o + 5])) + ((v[o + 8] + v[o + 9]) + (v[o + 12] + v[o + 13]));
    sn[r] = ((b[o] + b[o + 1]) + (b[o + 4] + b[o + 5])) + ((b[o + 8] + b[o + 9]) + (b[o + 12] + b[o + 13]));
  }
#pragma unroll
  for (int o = 1; o <= 2; o <<= 1)
#pragma unroll
    for (int r = 0; r < 2; r++) { sa[r] += __shfl_xor_sync(~0u, sa[r], o); sn[r] += __shfl_xor_sync(~0u, sn[r], o); }
#pragma unroll
  for (int r = 0; r < 2; r++) {
    const float ra = rcpf(sa[r]), rb = rcpf(sn[r]);
#pragma unroll
    for (int jj = 0; jj < 4; jj++) {
      ph[jj * 2 + r] = pack_bf16(v[2 * r + 4 * jj] * ra, v[2 * r + 4 * jj + 1] * ra);
      ph[(4 + jj) * 2 + r] = pack_bf16(b[2 * r + 4 * jj] * rb, b[2 * r + 4 * jj + 1] * rb);
    }
  }
}

__device__ __forceinline__ void store_heads(uint32_t base, const uint32_t (&a)[14], uint32_t pad0, uint32_t pad1, int row0, int lq) {
  const uint32_t rb = base + row0 * 64 + (((row0 >> 1) & 3) << 4);
  const uint32_t b0 = rb + lq * 4;
  const uint32_t b1 = (rb + 8192 + ((lq * 4 + 8) & 15)) ^ ((lq >> 1) << 4);
#pragma unroll
  for (int j = 0; j < 7; j++) {
    uint32_t ad;
    if (j < 3) ad = b0 ^ (j << 4);
    else if (j == 3) ad = (lq < 2) ? (b0 ^ 48u) : (b1 ^ 16u);
    else ad = (lq < 2) ? (b1 ^ ((j - 4) << 4)) : ((b1 ^ 16u) ^ ((j - 3) << 4));
    sts32(ad, a[2 * j]);
    sts32(ad + 512, a[2 * j + 1]);
  }
  sts64((rb ^ 48u) + 8 + (lq & 1) * 8192 + (lq >> 1) * 512, pad0, pad1);
}

struct Params {
  const __nv_bfloat16* w_phi;
  const __nv_bfloat16* wk;
  const __nv_bfloat16* wv;
  const __nv_bfloat16* gate_w;
  __nv_bfloat16* out;
};

__global__ void __launch_bounds__(NTHREADS, 1)
fused_kernel(const __grid_constant__ CUtensorMap tm_x, const __grid_constant__ CUtensorMap tm_wqkv,
             const __grid_constant__ CUtensorMap tm_wq, const __grid_constant__ CUtensorMap tm_woa,
             const __grid_constant__ CUtensorMap tm_wob, const Params prm) {
  extern __shared__ uint8_t smem_raw[];
  uint32_t sb = (smem_u32(smem_raw) + 1023u) & ~1023u;
  uint8_t* sgen = smem_raw + (sb - smem_u32(smem_raw));
  asm volatile("mov.u32 %0, %0;" : "+r"(sb));
  const int tid = threadIdx.x, lane = tid & 31;
  const int warp = __shfl_sync(~0u, tid >> 5, 0), wg = warp >> 2;
  const int pt = blockIdx.x >> 3, hp = blockIdx.x & 7;
  const uint32_t bars = sb + OFF_BAR;
  auto BAR = [&](int i) { return bars + 8u * i; };
  const unsigned epoch = g_epoch & 1;

  if (tid == 0) { PROF_MARK(0); PROF_CLK(30); PROF2(15); }
  auto load_proj = [&](int c, int g) {
    mbar_expect_tx(BAR(B_FULL + g), 49152);
    tma_2d(sb + OFF_X + c * 16384, &tm_x, c * 64, pt * 128, BAR(B_FULL + g));
    tma_2d(sb + OFF_RING + g * 32768, &tm_wq, hp * 56, c * 64, BAR(B_FULL + g));
#pragma unroll 1
    for (int j = 0; j < 3; j++) tma_2d(sb + OFF_RING + g * 32768 + 8192 + j * 8192, &tm_wqkv, j * DM + hp * 56, c * 64, BAR(B_FULL + g));
  };
  if (warp == 16) {
    if (elect_one()) {
      mbar_init(BAR(B_FULL), 1); mbar_init(BAR(B_FULL + 1), 1); mbar_init(BAR(B_FULL + 2), 1);
      fence_async_smem();
      load_proj(0, 0);
    }
    __syncwarp();
    asm volatile("bar.arrive 0, %0;" ::"n"(NTHREADS) : "memory");
  } else {
    if (elect_one()) {
      const int i = warp + 3 - (warp > 16);
      if (i < B_N) {
        int cnt = i < B_WO || i > B_SIG || i == B_X1FREE ? 16 : 1;
        if (i == B_BUILD) cnt = 512;
        if (i == B_SIG || i == B_SIG + 1 || i == B_QSQ) cnt = 8;
        if (i == B_KVR) cnt = 2;
        mbar_init(BAR(i), cnt);
        fence_async_smem();
      }
    }
    if (tid < 512) {
      const int k = tid >> 3, cn = tid & 7, e = k >= DH;
      const bool data = k < 56 && (cn >> 2) == e;
      const uint32_t ad = sb + OFF_WBD + k * 128 + ((cn ^ (k & 7)) << 4);
      const __nv_bfloat16* wsrc = prm.w_phi + (2 * hp * DH + k) * DH + (cn & 3) * 8;
      if (data) cp_async8(ad, wsrc); else sts64(ad, 0u, 0u);
      if (data && (cn & 3) != 3) cp_async8(ad + 8, wsrc + 4); else sts64(ad + 8, 0u, 0u);
      if (tid < DM) {
        const __nv_bfloat16* src = (hp < 4 ? prm.wk : prm.wv) + tid * DH + (hp & 3) * 8;
        cp_async8(sb + OFF_SLC + tid * 16, src);
        if ((hp & 3) != 3) cp_async8(sb + OFF_SLC + tid * 16 + 8, src + 4);
        else sts64(sb + OFF_SLC + tid * 16 + 8, hp == 3 ? (uint32_t)((const unsigned short*)prm.gate_w)[tid] : 0u, 0u);
      }
    }
    bar_sync(0, NTHREADS);
  }
  if (tid == 0) PROF2(14);

  if (wg == 4) {
    asm volatile("setmaxnreg.dec.sync.aligned.u32 32;");
    if (warp == 16) {
      if (elect_one()) { PROF2(18); load_proj(1, 1); load_proj(2, 2); PROF2(19); }
      __syncwarp();
      bar_sync(3, 64);
      if (elect_one()) {
        int g = 0, nkv = 8;
        uint32_t par = 0;
#pragma unroll 1
        for (int n = 3; n < 14 + nkv; n++) {
          if (n == 7) { PROF_MARK(20); cnt_wait(C_KV, NCTA); PROF_MARK(21); fence_async_all(); }
          if (n == 15) {
            mbar_wait(BAR(B_SLOW), 0);
            if (*(volatile int*)(sgen + OFF_RED)) nkv = 26;
          }
          const int j = n - 7 - nkv;
          if (j == 0 || j == 3) {
            PROF3(j ? 11 : 8);
            cnt_wait((j ? C_OB : C_OA) + pt, 8);
            PROF3(j ? 12 : 9);
            PROF_MARK(26);
            fence_async_all();
          }
          mbar_wait(BAR(B_EMPTY + g), par);
          if (n < 7) load_proj(n, g);
          else {
            mbar_expect_tx(BAR(B_FULL + g), 32768);
            bulk_g2s(sb + OFF_RING + g * 32768, j < 0 ? g_kv_img + ((n - 7) & 7) * 32768 : g_o_img + (size_t)(pt * 7 + j) * 32768, 32768,
                     BAR(B_FULL + g));
          }
          if (++g == 3) { g = 0; par ^= 1; }
        }
        if (atomicAdd(&g_cnt[C_DONE * 32], 1u) == NCTA - 1) {
#pragma unroll 1
          for (int i = 0; i < C_N; i++) g_cnt[i * 32] = 0;
          g_epoch = epoch ^ 1;
        }
      }
    } else {
      if (warp == 18) {
        if (elect_one()) {
#pragma unroll 1
          for (int i = 0; i < 4; i++) {
            mbar_wait(BAR(B_SIG + i), 0);
            PROF3(2 * i);
            if (i == 1) {
#pragma unroll 1
              for (int j = 0; j < 4; j++)
                asm volatile("cp.reduce.async.bulk.global.shared::cta.bulk_group.add.f32 [%0], [%1], 8192;"
                             ::"l"(g_kvacc[epoch] + hp * 4096 + (j >> 1) * 2048), "r"(sb + OFF_PHIK + j * 8192) : "memory");
              asm volatile("cp.async.bulk.commit_group;\ncp.async.bulk.wait_group 0;" ::: "memory");
            }
            cnt_arrive(i == 0 ? C_KV : i == 1 ? C_PART : (i == 2 ? C_OA : C_OB) + pt);
            PROF3(2 * i + 1);
            if (i == 1 || i == 2) {
              if (i == 2) mbar_wait(BAR(B_X1FREE), 0);
              mbar_expect_tx(BAR(B_WO + i - 1), 57344);
#pragma unroll 1
              for (int c = 0; c < 7; c++)
                tma_2d(sb + OFF_WO + (i - 1) * 57344 + c * 8192, i == 1 ? &tm_woa : &tm_wob, hp * 56, c * 64, BAR(B_WO + i - 1));
            }
          }
        }
      } else if (warp == 19) {
        if (lane == 0) {
          mbar_wait(BAR(B_SIG + 0), 0);
          cnt_wait(C_KV, NCTA);
        }
        __syncwarp();
        float ksq = 0.f, vsq = 0.f;
#pragma unroll
        for (int sl = 0; sl < 4; sl++) {
          float4 a = ldcg_f4(g_ksq + sl * 128 + lane * 4), b = ldcg_f4(g_vsq + sl * 128 + lane * 4);
          float m = fmaxf(fmaxf(a.x, a.y), fmaxf(a.z, a.w));
          m = __uint_as_float(__reduce_max_sync(~0u, __float_as_uint(m)));
          ksq += m;
          vsq = fmaxf(vsq, fmaxf(fmaxf(b.x, b.y), fmaxf(b.z, b.w)));
        }
        mbar_wait(BAR(B_QSQ), 0);
        const float4 qa4 = ((const float4*)(sgen + OFF_QSQ))[lane], qb4 = ((const float4*)(sgen + OFF_QSQ))[32 + lane];
        const float qmax = fmaxf(fmaxf(fmaxf(qa4.x, qa4.y), fmaxf(qa4.z, qa4.w)), fmaxf(fmaxf(qb4.x, qb4.y), fmaxf(qb4.z, qb4.w)));
        const bool slow = __any_sync(~0u, !(qmax * ksq <= 98.f * 98.f) || !(vsq <= 2.0e8f));
        if (lane == 0) {
          *(volatile int*)(sgen + OFF_RED) = slow;
          mbar_arrive(BAR(B_SLOW), 1);
        }
      } else {
        float4* z = (float4*)(g_kvacc[epoch ^ 1] + blockIdx.x * 256) + lane;
        z[0] = make_float4(0.f, 0.f, 0.f, 0.f);
        z[32] = make_float4(0.f, 0.f, 0.f, 0.f);
        bar_sync(3, 64);
        if (lane == 0) {
          mbar_wait(BAR(B_SIG + 0), 0);
          cnt_wait(C_KV, NCTA);
        }
        __syncwarp();
        ((float4*)(sgen + OFF_GATE))[lane] = ldcg_f4(g_gate + pt * 128 + lane * 4);
      }
      if (warp != 18) {
        if (lane == 0) {
          mbar_wait(BAR(B_SIG + 1), 0);
          cnt_wait(C_PART, NCTA);
          PROF_MARK(23);
        }
        __syncwarp();
        const int e = warp == 19;
        const float* src = g_kvacc[epoch] + hp * 4096 + e * 2048 + lane * 8;
#pragma unroll 1
        for (int i = 0; i < 8; i += 2) {
          const float4 a = ldcg_f4(src + i * 256), b = ldcg_f4(src + i * 256 + 4), c = ldcg_f4(src + i * 256 + 256), d = ldcg_f4(src + i * 256 + 260);
          const uint32_t ad = sb + OFF_KVR + e * 4096 + sw64_off(i * 8 + (lane >> 2), (lane & 3) * 8);
          sts128(ad, make_uint4(pack_bf16(a.x, a.y), pack_bf16(a.z, a.w), pack_bf16(b.x, b.y), pack_bf16(b.z, b.w)));
          sts128(ad + 512, make_uint4(pack_bf16(c.x, c.y), pack_bf16(c.z, c.w), pack_bf16(d.x, d.y), pack_bf16(d.z, d.w)));
        }
        fence_async_smem();
        __syncwarp();
        if (lane == 0) mbar_arrive(BAR(B_KVR), 1);
        PROF_MARK(24);
      }
    }
  } else {
    asm volatile("setmaxnreg.inc.sync.aligned.u32 112;");
    const int mh = wg & 1, nh = wg >> 1, wq = warp & 3;
    asm volatile("cp.async.mbarrier.arrive.noinc.shared::cta.b64 [%0];" ::"r"(BAR(B_BUILD)) : "memory");
    const int lq = lane & 3;
    const int rowl = wq * 16 + (lane >> 2);
    const int row0 = mh * 64 + rowl;
    int slot = 0, prev = 0;
    uint32_t par = 0;
    {
      float acc0[28], acc1[28], accs[4];
      const uint64_t dR = make_desc(sb + OFF_RING + nh * 16384, 1024, 1024, 1);
      const int lr = wq * 16 + (lane & 7) + ((lane >> 3) & 1) * 8;
      const uint32_t xa = sb + OFF_X + mh * 8192 + lr * 128 + (((lane >> 4) ^ (lr & 7)) << 4);
#pragma unroll
      for (int i = 0; i < 28; i++) acc0[i] = acc1[i] = 0.f;
#pragma unroll
      for (int i = 0; i < 4; i++) accs[i] = 0.f;
      const uint64_t dX = make_desc(sb + OFF_X + mh * 8192, 1024, 1024, 1);
      const uint64_t dSlc = make_desc(sb + OFF_SLC, 128, 128, 0);
      uint32_t a[16], an[16];
      if (tid == 0) PROF2(16);
      mbar_wait(BAR(B_FULL), 0);
      if (tid == 0) PROF2(17);
#pragma unroll
      for (int ks = 0; ks < 4; ks++) ldsm4(an + 4 * ks, xa ^ (ks << 5));
#pragma unroll 1
      for (int c = 0; c < 7; c++) {
#pragma unroll
        for (int i = 0; i < 16; i++) a[i] = an[i];
        const uint64_t dB = dR + slot * 2048;
        if (c == 3) { mbar_wait(BAR(B_BUILD), 0); fence_async_smem(); }
        wg_fence();
#pragma unroll
        for (int ks = 0; ks < 4; ks++) {
          wgmma_rs_n56_tb1<1>(acc0, a[4 * ks], a[4 * ks + 1], a[4 * ks + 2], a[4 * ks + 3], dB + ks * 128);
          wgmma_rs_n56_tb1<1>(acc1, a[4 * ks], a[4 * ks + 1], a[4 * ks + 2], a[4 * ks + 3], dB + 512 + ks * 128);
        }
        if (nh == 1 && c >= 3) {
#pragma unroll 1
          for (int cc = 2 * c - 7 + (c == 3); cc < 2 * c - 5; cc++) {
#pragma unroll
            for (int ks = 0; ks < 4; ks++) wgmma_ss_n8_ta0_tb1<1>(accs, dX + cc * 1024 + ks * 2, dSlc + cc * 64 + ks * 16);
          }
        }
        wg_commit();
        const int cur = slot;
        if (++slot == 3) { slot = 0; par ^= 1; }
        if (c < 6) {
          if (tid == 0 || tid == 256) PROF2(c * 2 + (tid >> 3));
          mbar_wait(BAR(B_FULL + slot), par);
          if (tid == 0 || tid == 256) PROF2(c * 2 + 1 + (tid >> 3));
#pragma unroll
          for (int ks = 0; ks < 4; ks++) ldsm4(an + 4 * ks, (xa + (c + 1) * 16384) ^ (ks << 5));
        }
        wg_wait<0>();
#pragma unroll
        for (int i = 0; i < 16; i++) asm volatile("" : "+r"(a[i])::"memory");
        if (lane == 0) mbar_arrive(BAR(B_EMPTY + cur), 1);
      }
      fence_regs(acc0); fence_regs(acc1); fence_regs(accs);
      if (tid == 0) PROF_MARK(2);
      if (tid == 256) PROF_MARK(3);
      if (nh == 0) {
        float sq[4] = {0.f, 0.f, 0.f, 0.f};
#pragma unroll
        for (int i = 0; i < 28; i++) acc0[i] *= 0.18898223650461362f * 1.4426950408889634f;
#pragma unroll
        for (int j = 0; j < 7; j++) {
#pragma unroll
          for (int rr = 0; rr < 2; rr++) {
            const float s2 = acc0[4 * j + 2 * rr] * acc0[4 * j + 2 * rr] + acc0[4 * j + 2 * rr + 1] * acc0[4 * j + 2 * rr + 1];
            if (j < 3) sq[rr] += s2;
            else if (j > 3) sq[2 + rr] += s2;
            else { sq[rr] += (lq < 2) ? s2 : 0.f; sq[2 + rr] += (lq < 2) ? 0.f : s2; }
          }
        }
#pragma unroll
        for (int i = 0; i < 4; i++) sq[i] = quad_sum(sq[i]);
        const float mine = lq == 0 ? sq[0] : lq == 1 ? sq[1] : lq == 2 ? sq[2] : sq[3];
        ((float*)(sgen + OFF_QSQ))[(mh + (lq & 2)) * 64 + rowl + 8 * (lq & 1)] = mine <= 3.0e38f ? mine : __int_as_float(0x7f800000);
        __syncwarp();
        if (lane == 0) mbar_arrive(BAR(B_QSQ), 1);
      } else {
        const int sl = hp & 3;
        const bool isk = hp < 4, real = (sl < 3) || (lq < 2);
        const int pos = pt * 128 + row0, kr = pos & 63;
        uint8_t* dst = g_kv_img + (pos >> 6) * 8192 + (isk ? 0 : 4096) + sw64_off(kr, sl * 8 + 2 * lq);
        const uint32_t pat = isk ? POLY_PAT >> (kr >> 3) : 0u;
        float mxv = 0.f;
#pragma unroll
        for (int rr = 0; rr < 2; rr++) {
          const float v0 = accs[2 * rr], v1 = accs[2 * rr + 1];
          const bool poly = (pat >> rr) & 1;
          const float sc = poly ? 2.f : 1.f;
          const float s2 = quad_sum(real ? v0 * v0 + v1 * v1 : 0.f);
          mxv = fmaxf(mxv, s2 <= 3.0e38f ? s2 : __int_as_float(0x7f800000));
          const uint32_t padv = lq == 2 ? (poly ? 0x443F4000u : 0x00003F80u) : (poly ? 0x3AB03F4Du : 0u);
          *(uint32_t*)(dst + rr * 512) = real ? pack_bf16(sc * v0, sc * v1) : padv;
          if (hp == 3 && lq == 2) g_gate[pos + 8 * rr] = rcpf(1.f + ex2f(-1.4426950408889634f * v0));
        }
        mxv = __uint_as_float(__reduce_max_sync(~0u, __float_as_uint(mxv)));
        if (lane == 0) (isk ? g_ksq : g_vsq)[sl * 128 + pt * 8 + mh * 4 + wq] = mxv;
        __syncwarp();
        if (lane == 0) mbar_arrive(BAR(B_SIG + 0), 1);
      }
      if (tid == 0) PROF_MARK(4);
      if (tid == 256) PROF_MARK(5);
      uint32_t h[14];
      float pp[32];
      {
#pragma unroll
        for (int i = 0; i < 14; i++) {
          const uint32_t u0 = pack_bf16(acc0[2 * i], acc0[2 * i + 1]), u1 = pack_bf16(acc1[2 * i], acc1[2 * i + 1]);
          h[i] = nh ? u1 : u0;
          a[i] = nh ? u0 : u1;
        }
        a[14] = a[0] ^ 0x80008000u;
        a[15] = a[1] ^ 0x80008000u;
        const uint64_t dW = make_desc(sb + OFF_WBD, 1024, 1024, 1);
        wg_fence();
        wgmma_rs_n64_tb1<0>(pp, a[0], a[1], a[2], a[3], dW);
#pragma unroll
        for (int ks = 1; ks < 4; ks++) wgmma_rs_n64_tb1<1>(pp, a[4 * ks], a[4 * ks + 1], a[4 * ks + 2], a[4 * ks + 3], dW + ks * 128);
        wg_commit();
        bar_sync(1, 512);
        if (tid == 0) PROF_MARK(6);
        store_heads(sb + (nh ? OFF_VA : OFF_QP), h, nh ? 0x00003F80u : 0x3F800000u, nh ? 0u : 0x3F803F80u, row0, lq);
        wg_wait<0>();
        fence_regs(pp);
      }
      float v[16];
#pragma unroll
      for (int i = 0; i < 16; i++) v[i] = pp[i];
      uint32_t rb = sb + (nh ? OFF_PHIK : OFF_PHIQ) + row0 * 128 + lq * 4 + ((rowl & 7) << 4);
#pragma unroll 1
      for (int e = 0; e < 2; e++) {
        uint32_t ph[16];
        feature_map(v, ph, lq);
#pragma unroll
        for (int ch = 0; ch < 8; ch++) { sts32(rb ^ (ch << 4), ph[2 * ch]); sts32((rb ^ (ch << 4)) + 1024, ph[2 * ch + 1]); }
        rb += 16384;
#pragma unroll
        for (int i = 0; i < 16; i++) v[i] = pp[16 + i];
      }
      fence_async_smem();
      bar_sync(1, 512);
      if (tid == 0) PROF_MARK(7);
      if (nh == 1) {
        float kv0[16], kv1[16];
        const uint64_t dP = make_desc(sb + OFF_PHIK + mh * 8192, 1024, 1024, 1);
        const uint64_t dV = make_desc(sb + OFF_VA + mh * 4096, 512, 512, 2);
        wg_fence();
        wgmma_ss_n32_ta1_tb1<0>(kv0, dP, dV);
        wgmma_ss_n32_ta1_tb1<0>(kv1, dP + 1024, dV + 512);
#pragma unroll
        for (int ks = 1; ks < 4; ks++) {
          wgmma_ss_n32_ta1_tb1<1>(kv0, dP + ks * 128, dV + ks * 64);
          wgmma_ss_n32_ta1_tb1<1>(kv1, dP + 1024 + ks * 128, dV + 512 + ks * 64);
        }
        wg_commit();
        wg_wait<0>();
        fence_regs(kv0); fence_regs(kv1);
        bar_sync(4 + wg, 128);
        const uint32_t sa = sb + OFF_PHIK + mh * 8192 + rowl * 128 + lq * 8;
#pragma unroll
        for (int j = 0; j < 8; j++) {
          sts64(sa + 32 * (j >> 1) + 1024 * (j & 1), __float_as_uint(kv0[2 * j]), __float_as_uint(kv0[2 * j + 1]));
          sts64(sa + 16384 + 32 * (j >> 1) + 1024 * (j & 1), __float_as_uint(kv1[2 * j]), __float_as_uint(kv1[2 * j + 1]));
        }
        fence_async_smem();
        __syncwarp();
        if (lane == 0) mbar_arrive(BAR(B_SIG + 1), 1);
        if (tid == 256) PROF_MARK(28);
      }
    }
    {
      const uint64_t dK = make_desc(sb + OFF_RING, 512, 512, 2);
      const uint64_t dhi = dK & 0xffffffff00000000ull;
      const uint32_t dlo0 = (uint32_t)dK;
      uint32_t ok = 0, q[8];
      float o[16];
#pragma unroll
      for (int i = 0; i < 16; i++) o[i] = 0.f;
      {
        const int r = mh * 64 + wq * 16 + (lane & 7) + ((lane >> 3) & 1) * 8;
        ldsm4(q, sb + OFF_QP + nh * 8192 + sw64_off(r, (lane >> 4) * 8));
        ldsm4(q + 4, sb + OFF_QP + nh * 8192 + sw64_off(r, 16 + (lane >> 4) * 8));
      }
      if (tid == 0) PROF_MARK(10);
      const int qb = QB_AT;
#pragma unroll 1
      for (int it = 0; it <= 8; it++) {
        uint32_t p[16];
        if ((tid & 127) == 0) PROF4(wg * 32 + it * 3);
        if (it == qb || it == 8) {
          float t[16];
          wg_wait<0>();
          fence_regs(o);
          if (it < 8) {
            if (tid == 0) PROF_MARK(11);
            mbar_wait(BAR(B_KVR), 0);
            const uint64_t dR = make_desc(sb + OFF_KVR + nh * 4096, 512, 512, 2);
            const uint64_t dP = make_desc(sb + OFF_PHIQ + nh * 16384 + mh * 8192, 1024, 1024, 1);
            wg_fence();
            wgmma_ss_n32_ta0_tb1<0>(t, dP, dR);
#pragma unroll
            for (int ks = 1; ks < 4; ks++) wgmma_ss_n32_ta0_tb1<1>(t, dP + ks * 2, dR + ks * 64);
            wg_commit();
            wg_wait<0>();
            fence_regs(t);
            if (lane == 0) mbar_arrive(BAR(B_X1FREE), 1);
          } else {
            if (lane == 0) mbar_arrive(BAR(B_EMPTY + prev), 1);
            if (tid == 0) PROF_MARK(13);
            mbar_wait(BAR(B_SLOW), 0);
            if (__builtin_expect(__any_sync(~0u, *(volatile int*)(sgen + OFF_RED)), 0)) {
              uint32_t qz[8];
#pragma unroll
              for (int i = 0; i < 8; i++) qz[i] = (i >= 6 && lq >= 2) ? 0u : q[i];
              float m0 = -3.0e38f, m1 = -3.0e38f, o2[16];
              int sl2 = slot;
              uint32_t par2 = par;
#pragma unroll 1
              for (int j64 = 0; j64 < 32; j64++) {
                float s[32];
                mbar_wait(BAR(B_FULL + sl2), par2);
                const uint32_t lo = dlo0 + sl2 * 2048 + (j64 & 3) * 512;
                wg_fence();
                wgmma_rs_n64_tb0<0>(s, qz[0], qz[1], qz[2], qz[3], dhi | lo);
                wgmma_rs_n64_tb0<1>(s, qz[4], qz[5], qz[6], qz[7], dhi | (lo + 2));
                wg_commit();
                wg_wait<0>();
                fence_regs(s);
#pragma unroll
                for (int j = 0; j < 8; j++) {
                  const float sc = ((POLY_PAT >> j) & 1) ? 0.5f : 1.f;
                  m0 = fmaxf(m0, fmaxf(s[4 * j], s[4 * j + 1]) * sc);
                  m1 = fmaxf(m1, fmaxf(s[4 * j + 2], s[4 * j + 3]) * sc);
                }
                if ((j64 & 3) == 3) {
                  if (lane == 0) mbar_arrive(BAR(B_EMPTY + sl2), 1);
                  if (++sl2 == 3) { sl2 = 0; par2 ^= 1; }
                }
              }
              m0 = quad_max(m0); m1 = quad_max(m1);
#pragma unroll
              for (int i = 0; i < 16; i++) o2[i] = 0.f;
#pragma unroll 1
              for (int j64 = 0; j64 < 32; j64++) {
                float s[32];
                mbar_wait(BAR(B_FULL + sl2), par2);
                const uint32_t lo = dlo0 + sl2 * 2048 + (j64 & 3) * 512;
                wg_fence();
                wgmma_rs_n64_tb0<0>(s, qz[0], qz[1], qz[2], qz[3], dhi | lo);
                wgmma_rs_n64_tb0<1>(s, qz[4], qz[5], qz[6], qz[7], dhi | (lo + 2));
                wg_commit();
                wg_wait<0>();
                fence_regs(s);
                uint32_t ps[16];
#pragma unroll
                for (int j = 0; j < 8; j++) {
                  const float sc = ((POLY_PAT >> j) & 1) ? 0.5f : 1.f;
                  ps[2 * j] = pack_bf16(ex2f(fmaf(s[4 * j], sc, -m0)), ex2f(fmaf(s[4 * j + 1], sc, -m0)));
                  ps[2 * j + 1] = pack_bf16(ex2f(fmaf(s[4 * j + 2], sc, -m1)), ex2f(fmaf(s[4 * j + 3], sc, -m1)));
                }
                wg_fence();
#pragma unroll
                for (int ks = 0; ks < 4; ks++)
                  wgmma_rs_n32_tb1<1>(o2, ps[4 * ks], ps[4 * ks + 1], ps[4 * ks + 2], ps[4 * ks + 3], dhi | (lo + 256 + ks * 64));
                wg_commit();
                wg_wait<0>();
                fence_regs(o2);
                if ((j64 & 3) == 3) {
                  if (lane == 0) mbar_arrive(BAR(B_EMPTY + sl2), 1);
                  if (++sl2 == 3) { sl2 = 0; par2 ^= 1; }
                }
              }
#pragma unroll 1
              for (int j = 0; j < 2; j++) {
                mbar_wait(BAR(B_FULL + sl2), par2);
                __syncwarp();
                if (lane == 0) mbar_arrive(BAR(B_EMPTY + sl2), 1);
                if (++sl2 == 3) { sl2 = 0; par2 ^= 1; }
              }
#pragma unroll
              for (int i = 0; i < 16; i++) o[i] = o2[i];
            }
#pragma unroll
            for (int i = 0; i < 16; i++) t[i] = o[i];
          }
          const int br = it == 8;
          const float eps = br ? 0.f : 1e-6f;
          const float g0 = ((const float*)(sgen + OFF_GATE))[row0], g1 = ((const float*)(sgen + OFF_GATE))[row0 + 8];
          const float d0 = __shfl_sync(~0u, t[12], (lane & ~3) | 2), d1 = __shfl_sync(~0u, t[14], (lane & ~3) | 2);
          const float r0 = (br ? 1.f - g0 : g0) * rcpf(d0 + eps), r1 = (br ? 1.f - g1 : g1) * rcpf(d1 + eps);
          uint8_t* img = g_o_img + (size_t)((pt * 2 + br) * 14 + mh) * 8192 + rowl * 128;
          const int col0 = (2 * hp + nh) * DH + 2 * lq;
#pragma unroll
          for (int j = 0; j < 4; j++) {
            const int col = col0 + 8 * j;
            uint8_t* gp = img + (uint32_t)((col >> 6) * 16384 + ((((col >> 3) ^ rowl) & 7) << 4) + (col & 7) * 2);
            const uint32_t v0 = pack_bf16(t[4 * j] * r0, t[4 * j + 1] * r0), v1 = pack_bf16(t[4 * j + 2] * r1, t[4 * j + 3] * r1);
            if (j < 3 || lq < 2) { *(uint32_t*)gp = v0; *(uint32_t*)(gp + 1024) = v1; }
          }
          __syncwarp();
          if (lane == 0) mbar_arrive(BAR(B_SIG + 2 + br), 1);
          if (tid == 0) PROF_MARK(12 + 2 * br);
          if (br) break;
        }
        const uint32_t lo = dlo0 + slot * 2048;
        if ((tid & 127) == 0) PROF4(wg * 32 + it * 3 + 1);
        if (!ok) mbar_wait(BAR(B_FULL + slot), par);
        if ((tid & 127) == 0) PROF4(wg * 32 + it * 3 + 2);
        int nslot = slot + 1;
        uint32_t npar = par;
        if (nslot == 3) { nslot = 0; npar ^= 1; }
        {
          float s[32];
          wg_fence();
          wgmma_rs_n64_tb0<0>(s, q[0], q[1], q[2], q[3], dhi | lo);
          wgmma_rs_n64_tb0<1>(s, q[4], q[5], q[6], q[7], dhi | (lo + 2));
          wg_commit();
#pragma unroll
          for (int u = 0; u < 4; u++) {
            wg_wait<0>();
            fence_regs(s);
            if (u == 0 && lane == 0 && it > 0) mbar_arrive(BAR(B_EMPTY + prev), 1);
            if (u == 2) ok = mbar_test(BAR(B_FULL + nslot), npar);
#pragma unroll
            for (int j = 0; j < 8; j++) {
              if ((POLY_PAT >> j) & 1) {
                p[2 * j] = exp2_pair_fma(s[4 * j], s[4 * j + 1], 0x3F003F00u, 0x00030003u);
                p[2 * j + 1] = exp2_pair_fma(s[4 * j + 2], s[4 * j + 3], 0x3F003F00u, 0x00030003u);
              } else {
                p[2 * j] = pack_bf16(ex2f(s[4 * j]), ex2f(s[4 * j + 1]));
                p[2 * j + 1] = pack_bf16(ex2f(s[4 * j + 2]), ex2f(s[4 * j + 3]));
              }
            }
            wg_fence();
#pragma unroll
            for (int ks = 0; ks < 4; ks++)
              wgmma_rs_n32_tb1<1>(o, p[4 * ks], p[4 * ks + 1], p[4 * ks + 2], p[4 * ks + 3], dhi | (lo + u * 512 + 256 + ks * 64));
            if (u < 3) {
              wgmma_rs_n64_tb0<0>(s, q[0], q[1], q[2], q[3], dhi | (lo + (u + 1) * 512));
              wgmma_rs_n64_tb0<1>(s, q[4], q[5], q[6], q[7], dhi | (lo + (u + 1) * 512 + 2));
            }
            wg_commit();
          }
        }
        prev = slot; slot = nslot; par = npar;
      }
      wg_wait<0>();
    }
    if (nh == 1) return;
    {
      float acc0[28], acc1[28];
#pragma unroll
      for (int i = 0; i < 28; i++) acc0[i] = acc1[i] = 0.f;
      const uint64_t dS = make_desc(sb + OFF_WO, 1024, 1024, 1);
      const uint64_t dR = make_desc(sb + OFF_RING + mh * 8192, 1024, 1024, 1);
#pragma unroll 1
      for (int c = 0; c < 7; c++) {
        mbar_wait(BAR(B_WO + (c >= 3)), 0);
        mbar_wait(BAR(B_FULL + slot), par);
        const uint64_t dA = dR + slot * 2048, dB = dS + c * 1024;
        wg_fence();
#pragma unroll
        for (int ks = 0; ks < 4; ks++) {
          wgmma_ss_n56_ta0_tb1<1>(acc0, dA + ks * 2, dB + ks * 128);
          wgmma_ss_n56_ta0_tb1<1>(acc1, dA + 1024 + ks * 2, dB + 512 + ks * 128);
        }
        wg_commit();
        if (c < 4) {
          wg_wait<0>();
          if (lane == 0) mbar_arrive(BAR(B_EMPTY + slot), 2);
        }
        if (++slot == 3) { slot = 0; par ^= 1; }
      }
      wg_wait<0>();
      fence_regs(acc0); fence_regs(acc1);
      if (tid == 0) PROF_MARK(17);
      __nv_bfloat16* op = prm.out + (size_t)(pt * 128 + row0) * DM + hp * 56 + 2 * lq;
#pragma unroll
      for (int j = 0; j < 7; j++) {
        *(uint32_t*)(op + 8 * j) = pack_bf16(acc0[4 * j] + acc1[4 * j], acc0[4 * j + 1] + acc1[4 * j + 1]);
        *(uint32_t*)(op + 8 * DM + 8 * j) = pack_bf16(acc0[4 * j + 2] + acc1[4 * j + 2], acc0[4 * j + 3] + acc1[4 * j + 3]);
      }
      if (tid == 0) { PROF_MARK(18); PROF_CLK(31); }
    }
  }
}

typedef CUresult (*EncodeFn)(CUtensorMap*, CUtensorMapDataType, cuuint32_t, void*, const cuuint64_t*, const cuuint64_t*,
                             const cuuint32_t*, const cuuint32_t*, CUtensorMapInterleave, CUtensorMapSwizzle,
                             CUtensorMapL2promotion, CUtensorMapFloatOOBfill);

void make_map(EncodeFn enc, CUtensorMap* tm, const void* ptr, uint64_t cols, uint64_t rows, uint32_t box_rows) {
  cuuint64_t dims[2] = {cols, rows};
  cuuint64_t strides[1] = {cols * 2};
  cuuint32_t box[2] = {64, box_rows};
  cuuint32_t es[2] = {1, 1};
  enc(tm, CU_TENSOR_MAP_DATA_TYPE_BFLOAT16, 2, const_cast<void*>(ptr), dims, strides, box, es, CU_TENSOR_MAP_INTERLEAVE_NONE,
      CU_TENSOR_MAP_SWIZZLE_128B, CU_TENSOR_MAP_L2_PROMOTION_L2_128B, CU_TENSOR_MAP_FLOAT_OOB_FILL_NONE);
}

}

extern "C" void kernel_launch(void* const* d_in, const int* in_sizes, int n_in, void* d_out, int out_size) {
  (void)in_sizes; (void)n_in; (void)out_size;
  static EncodeFn enc = nullptr;
  if (!enc) {
    void* fn = nullptr;
    cudaDriverEntryPointQueryResult qr;
    cudaGetDriverEntryPoint("cuTensorMapEncodeTiled", &fn, cudaEnableDefault, &qr);
    enc = (EncodeFn)fn;
    cudaFuncSetAttribute(fused_kernel, cudaFuncAttributeMaxDynamicSharedMemorySize, SMEM_BYTES);
  }
  CUtensorMap tm_x, tm_wqkv, tm_wq, tm_woa, tm_wob;
  make_map(enc, &tm_x, d_in[0], DM, S_LEN, 128);
  make_map(enc, &tm_wqkv, d_in[1], 3 * DM, DM, 64);
  make_map(enc, &tm_wq, d_in[5], DM, DM, 64);
  make_map(enc, &tm_woa, d_in[3], DM, DM, 64);
  make_map(enc, &tm_wob, d_in[8], DM, DM, 64);
  Params prm;
  prm.w_phi = (const __nv_bfloat16*)d_in[2];
  prm.wk = (const __nv_bfloat16*)d_in[6];
  prm.wv = (const __nv_bfloat16*)d_in[7];
  prm.gate_w = (const __nv_bfloat16*)d_in[9];
  prm.out = (__nv_bfloat16*)d_out;
  fused_kernel<<<NCTA, NTHREADS, SMEM_BYTES>>>(tm_x, tm_wqkv, tm_wq, tm_woa, tm_wob, prm);
}
```

```cpp
#include <cuda_runtime.h>
#include <cuda_bf16.h>
#include <cuda.h>
#include <stdint.h>

namespace {

constexpr int S_LEN = 2048, DM = 448, DH = 28;
constexpr int NCTA = 128;
constexpr int NTHREADS = 640;
constexpr uint32_t POLY_PAT = 0x57;

#define QB_AT (4 + nh)

constexpr int OFF_X = 0;
constexpr int OFF_PHIK = 0;
constexpr int OFF_VA = 32768;
constexpr int OFF_PHIQ = 57344;
constexpr int OFF_KVR = 90112;
constexpr int OFF_QP = 98304;
constexpr int OFF_WO = 0;
constexpr int OFF_RING = 114688;
constexpr int OFF_WBD = 212992;
constexpr int OFF_SLC = 221184;
constexpr int OFF_QSQ = 228352;
constexpr int OFF_GATE = 229376;
constexpr int OFF_RED = 229888;
constexpr int OFF_BAR = 229952;
constexpr int SMEM_BYTES = 230400 + 1024;

constexpr int B_FULL = 0, B_EMPTY = 3, B_WO = 6  , B_KVR = 8, B_X1FREE = 10, B_QSQ = 11, B_SLOW = 12,
              B_BUILD = 13, B_SIG = 14  , B_N = 18;

constexpr int C_KV = 0, C_PART = 1, C_DONE = 3, C_OA = 4, C_OB = 20, C_N = 36;

__device__ __align__(1024) uint8_t g_kv_img[32 * 8192];
__device__ __align__(16) float g_ksq[512];
__device__ __align__(16) float g_vsq[512];
__device__ __align__(16) float g_gate[S_LEN];
__device__ __align__(1024) float g_kvacc[2][16 * 64 * 32];
__device__ unsigned g_epoch;
__device__ __align__(1024) uint8_t g_o_img[2 * 16 * 14 * 8192];
__device__ unsigned g_cnt[C_N * 32];

#define PROF4(i) do { } while (0)
#define PROF3(i) do { } while (0)
#define PROF2(i) do { } while (0)
#define PROF_CLK(i) do { } while (0)
#define PROF_MARK(i) do { } while (0)
__device__ __forceinline__ uint32_t smem_u32(const void* p) { return (uint32_t)__cvta_generic_to_shared(p); }
__device__ __forceinline__ void mbar_init(uint32_t a, int cnt) {
  asm volatile("mbarrier.init.shared::cta.b64 [%0], %1;" ::"r"(a), "r"(cnt) : "memory");
}
__device__ __forceinline__ void mbar_expect_tx(uint32_t a, uint32_t bytes) {
  asm volatile("mbarrier.arrive.expect_tx.shared::cta.b64 _, [%0], %1;" ::"r"(a), "r"(bytes) : "memory");
}
__device__ __forceinline__ void mbar_arrive(uint32_t a, uint32_t cnt) {
  asm volatile("mbarrier.arrive.shared::cta.b64 _, [%0], %1;" ::"r"(a), "r"(cnt) : "memory");
}
__device__ __forceinline__ void mbar_wait(uint32_t a, uint32_t parity) {
  asm volatile(
      "{\n.reg .pred p;\n.reg .u32 c;\nmov.u32 c, 0;\n"
      "W_%=:\nmbarrier.try_wait.parity.shared::cta.b64 p, [%0], %1;\n"
      "add.u32 c, c, 1;\nsetp.lt.and.u32 p, c, 0x40000, !p;\n@p bra W_%=;\n}"
      ::"r"(a), "r"(parity) : "memory");
}
__device__ __forceinline__ uint32_t mbar_test(uint32_t a, uint32_t parity) {
  uint32_t ok;
  asm volatile("{\n.reg .pred p;\nmbarrier.test_wait.parity.shared::cta.b64 p, [%1], %2;\nselp.u32 %0, 1, 0, p;\n}"
               : "=r"(ok) : "r"(a), "r"(parity) : "memory");
  return ok;
}
__device__ __forceinline__ bool elect_one() {
  uint32_t r;
  asm volatile("{\n.reg .pred p;\nelect.sync _|p, 0xffffffff;\nselp.u32 %0, 1, 0, p;\n}" : "=r"(r));
  return r != 0;
}
__device__ __forceinline__ void tma_2d(uint32_t dst, const CUtensorMap* tm, int c0, int c1, uint32_t bar) {
  asm volatile("cp.async.bulk.tensor.2d.shared::cluster.global.mbarrier::complete_tx::bytes [%0], [%1, {%3, %4}], [%2];"
               ::"r"(dst), "l"(tm), "r"(bar), "r"(c0), "r"(c1) : "memory");
}
__device__ __forceinline__ void bulk_g2s(uint32_t dst, const void* src, uint32_t bytes, uint32_t bar) {
  asm volatile("cp.async.bulk.shared::cluster.global.mbarrier::complete_tx::bytes [%0], [%1], %2, [%3];"
               ::"r"(dst), "l"(src), "r"(bytes), "r"(bar) : "memory");
}
__device__ __forceinline__ void cp_async8(uint32_t dst, const void* src) {
  asm volatile("cp.async.ca.shared.global [%0], [%1], 8;" ::"r"(dst), "l"(src) : "memory");
}
__device__ __forceinline__ void fence_async_smem() { asm volatile("fence.proxy.async.shared::cta;" ::: "memory"); }
__device__ __forceinline__ void fence_async_all() { asm volatile("fence.proxy.async.global;" ::: "memory"); }

__device__ __forceinline__ void bar_sync(int id, int n) { asm volatile("bar.sync %0, %1;" ::"r"(id), "r"(n) : "memory"); }
__device__ __forceinline__ void cnt_arrive(int idx) {
  asm volatile("red.release.gpu.global.add.u32 [%0], 1;" ::"l"(&g_cnt[idx * 32]) : "memory");
}
__device__ __forceinline__ void cnt_wait(int idx, unsigned target) {
  unsigned v, n = 0;
#pragma unroll 1
  while (true) {
    asm volatile("ld.acquire.gpu.global.u32 %0, [%1];" : "=r"(v) : "l"(&g_cnt[idx * 32]) : "memory");
    if (v >= target || ++n >= (1u << 18)) break;
    __nanosleep(32);
  }
}
__device__ __forceinline__ void wg_fence() { asm volatile("wgmma.fence.sync.aligned;" ::: "memory"); }
__device__ __forceinline__ void wg_commit() { asm volatile("wgmma.commit_group.sync.aligned;" ::: "memory"); }
template <int N> __device__ __forceinline__ void wg_wait() { asm volatile("wgmma.wait_group.sync.aligned %0;" ::"n"(N) : "memory"); }
template <int N> __device__ __forceinline__ void fence_regs(float (&d)[N]) {
#pragma unroll
  for (int i = 0; i < N; i++) asm volatile("" : "+f"(d[i])::"memory");
}
__device__ __forceinline__ uint64_t make_desc(uint32_t saddr, uint32_t lbo, uint32_t sbo, uint32_t swz) {
  return (uint64_t)((saddr & 0x3FFFF) >> 4) | ((uint64_t)(lbo >> 4) << 16) | ((uint64_t)(sbo >> 4) << 32) | ((uint64_t)swz << 62);
}
__device__ __forceinline__ float ex2f(float x) { float y; asm("ex2.approx.ftz.f32 %0, %1;" : "=f"(y) : "f"(x)); return y; }
__device__ __forceinline__ float rcpf(float x) { float y; asm("rcp.approx.ftz.f32 %0, %1;" : "=f"(y) : "f"(x)); return y; }
__device__ __forceinline__ uint32_t pack_bf16(float lo, float hi) {
  uint32_t r; asm("cvt.rn.bf16x2.f32 %0, %1, %2;" : "=r"(r) : "f"(hi), "f"(lo)); return r;
}
__device__ __forceinline__ uint32_t lop_and_or(uint32_t a, uint32_t m, uint32_t c) {
  uint32_t r; asm("lop3.b32 %0, %1, %2, %3, 0xEA;" : "=r"(r) : "r"(a), "r"(m), "r"(c)); return r;
}
__device__ __forceinline__ void sts32(uint32_t a, uint32_t v) { asm volatile("st.shared.b32 [%0], %1;" ::"r"(a), "r"(v) : "memory"); }
__device__ __forceinline__ void sts64(uint32_t a, uint32_t v0, uint32_t v1) { asm volatile("st.shared.v2.b32 [%0], {%1, %2};" ::"r"(a), "r"(v0), "r"(v1) : "memory"); }
__device__ __forceinline__ void sts128(uint32_t a, uint4 v) {
  asm volatile("st.shared.v4.b32 [%0], {%1, %2, %3, %4};" ::"r"(a), "r"(v.x), "r"(v.y), "r"(v.z), "r"(v.w) : "memory");
}
__device__ __forceinline__ float4 ldcg_f4(const float* p) {
  float4 v; asm volatile("ld.global.cg.v4.f32 {%0, %1, %2, %3}, [%4];" : "=f"(v.x), "=f"(v.y), "=f"(v.z), "=f"(v.w) : "l"(p) : "memory"); return v;
}
__device__ __forceinline__ void ldsm4(uint32_t* r, uint32_t a) {
  asm volatile("ldmatrix.sync.aligned.m8n8.x4.shared.b16 {%0, %1, %2, %3}, [%4];"
               : "=r"(r[0]), "=r"(r[1]), "=r"(r[2]), "=r"(r[3]) : "r"(a) : "memory");
}
__device__ __forceinline__ float quad_sum(float v) { v += __shfl_xor_sync(~0u, v, 1); v += __shfl_xor_sync(~0u, v, 2); return v; }
__device__ __forceinline__ float quad_max(float v) { v = fmaxf(v, __shfl_xor_sync(~0u, v, 1)); v = fmaxf(v, __shfl_xor_sync(~0u, v, 2)); return v; }

template <int SD> __device__ __forceinline__ void wgmma_ss_n56_ta0_tb1(float (&d)[28], uint64_t da, uint64_t db) {
  if (SD) asm volatile("wgmma.mma_async.sync.aligned.m64n56k16.f32.bf16.bf16 {%0, %1, %2, %3, %4, %5, %6, %7, %8, %9, %10, %11, %12, %13, %14, %15, %16, %17, %18, %19, %20, %21, %22, %23, %24, %25, %26, %27}, %28, %29, 1, 1, 1, 0, 1;\n"
    : "+f"(d[0]), "+f"(d[1]), "+f"(d[2]), "+f"(d[3]), "+f"(d[4]), "+f"(d[5]), "+f"(d[6]), "+f"(d[7]), "+f"(d[8]), "+f"(d[9]), "+f"(d[10]), "+f"(d[11]), "+f"(d[12]), "+f"(d[13]), "+f"(d[14]), "+f"(d[15]), "+f"(d[16]), "+f"(d[17]), "+f"(d[18]), "+f"(d[19]), "+f"(d[20]), "+f"(d[21]), "+f"(d[22]), "+f"(d[23]), "+f"(d[24]), "+f"(d[25]), "+f"(d[26]), "+f"(d[27])
    : "l"(da), "l"(db));
  else asm volatile("wgmma.mma_async.sync.aligned.m64n56k16.f32.bf16.bf16 {%0, %1, %2, %3, %4, %5, %6, %7, %8, %9, %10, %11, %12, %13, %14, %15, %16, %17, %18, %19, %20, %21, %22, %23, %24, %25, %26, %27}, %28, %29, 0, 1, 1, 0, 1;\n"
    : "=f"(d[0]), "=f"(d[1]), "=f"(d[2]), "=f"(d[3]), "=f"(d[4]), "=f"(d[5]), "=f"(d[6]), "=f"(d[7]), "=f"(d[8]), "=f"(d[9]), "=f"(d[10]), "=f"(d[11]), "=f"(d[12]), "=f"(d[13]), "=f"(d[14]), "=f"(d[15]), "=f"(d[16]), "=f"(d[17]), "=f"(d[18]), "=f"(d[19]), "=f"(d[20]), "=f"(d[21]), "=f"(d[22]), "=f"(d[23]), "=f"(d[24]), "=f"(d[25]), "=f"(d[26]), "=f"(d[27])
    : "l"(da), "l"(db));
}
template <int SD> __device__ __forceinline__ void wgmma_rs_n56_tb1(float (&d)[28], uint32_t a0, uint32_t a1, uint32_t a2, uint32_t a3, uint64_t db) {
  if (SD) asm volatile("wgmma.mma_async.sync.aligned.m64n56k16.f32.bf16.bf16 {%0, %1, %2, %3, %4, %5, %6, %7, %8, %9, %10, %11, %12, %13, %14, %15, %16, %17, %18, %19, %20, %21, %22, %23, %24, %25, %26, %27}, {%28, %29, %30, %31}, %32, 1, 1, 1, 1;\n"
    : "+f"(d[0]), "+f"(d[1]), "+f"(d[2]), "+f"(d[3]), "+f"(d[4]), "+f"(d[5]), "+f"(d[6]), "+f"(d[7]), "+f"(d[8]), "+f"(d[9]), "+f"(d[10]), "+f"(d[11]), "+f"(d[12]), "+f"(d[13]), "+f"(d[14]), "+f"(d[15]), "+f"(d[16]), "+f"(d[17]), "+f"(d[18]), "+f"(d[19]), "+f"(d[20]), "+f"(d[21]), "+f"(d[22]), "+f"(d[23]), "+f"(d[24]), "+f"(d[25]), "+f"(d[26]), "+f"(d[27])
    : "r"(a0), "r"(a1), "r"(a2), "r"(a3), "l"(db));
  else asm volatile("wgmma.mma_async.sync.aligned.m64n56k16.f32.bf16.bf16 {%0, %1, %2, %3, %4, %5, %6, %7, %8, %9, %10, %11, %12, %13, %14, %15, %16, %17, %18, %19, %20, %21, %22, %23, %24, %25, %26, %27}, {%28, %29, %30, %31}, %32, 0, 1, 1, 1;\n"
    : "=f"(d[0]), "=f"(d[1]), "=f"(d[2]), "=f"(d[3]), "=f"(d[4]), "=f"(d[5]), "=f"(d[6]), "=f"(d[7]), "=f"(d[8]), "=f"(d[9]), "=f"(d[10]), "=f"(d[11]), "=f"(d[12]), "=f"(d[13]), "=f"(d[14]), "=f"(d[15]), "=f"(d[16]), "=f"(d[17]), "=f"(d[18]), "=f"(d[19]), "=f"(d[20]), "=f"(d[21]), "=f"(d[22]), "=f"(d[23]), "=f"(d[24]), "=f"(d[25]), "=f"(d[26]), "=f"(d[27])
    : "r"(a0), "r"(a1), "r"(a2), "r"(a3), "l"(db));
}
template <int SD> __device__ __forceinline__ void wgmma_rs_n8_tb1(float (&d)[4], uint32_t a0, uint32_t a1, uint32_t a2, uint32_t a3, uint64_t db) {
  if (SD) asm volatile("wgmma.mma_async.sync.aligned.m64n8k16.f32.bf16.bf16 {%0, %1, %2, %3}, {%4, %5, %6, %7}, %8, 1, 1, 1, 1;\n"
    : "+f"(d[0]), "+f"(d[1]), "+f"(d[2]), "+f"(d[3])
    : "r"(a0), "r"(a1), "r"(a2), "r"(a3), "l"(db));
  else asm volatile("wgmma.mma_async.sync.aligned.m64n8k16.f32.bf16.bf16 {%0, %1, %2, %3}, {%4, %5, %6, %7}, %8, 0, 1, 1, 1;\n"
    : "=f"(d[0]), "=f"(d[1]), "=f"(d[2]), "=f"(d[3])
    : "r"(a0), "r"(a1), "r"(a2), "r"(a3), "l"(db));
}
template <int SD> __device__ __forceinline__ void wgmma_rs_n64_tb1(float (&d)[32], uint32_t a0, uint32_t a1, uint32_t a2, uint32_t a3, uint64_t db) {
  if (SD) asm volatile("wgmma.mma_async.sync.aligned.m64n64k16.f32.bf16.bf16 {%0, %1, %2, %3, %4, %5, %6, %7, %8, %9, %10, %11, %12, %13, %14, %15, %16, %17, %18, %19, %20, %21, %22, %23, %24, %25, %26, %27, %28, %29, %30, %31}, {%32, %33, %34, %35}, %36, 1, 1, 1, 1;\n"
    : "+f"(d[0]), "+f"(d[1]), "+f"(d[2]), "+f"(d[3]), "+f"(d[4]), "+f"(d[5]), "+f"(d[6]), "+f"(d[7]), "+f"(d[8]), "+f"(d[9]), "+f"(d[10]), "+f"(d[11]), "+f"(d[12]), "+f"(d[13]), "+f"(d[14]), "+f"(d[15]), "+f"(d[16]), "+f"(d[17]), "+f"(d[18]), "+f"(d[19]), "+f"(d[20]), "+f"(d[21]), "+f"(d[22]), "+f"(d[23]), "+f"(d[24]), "+f"(d[25]), "+f"(d[26]), "+f"(d[27]), "+f"(d[28]), "+f"(d[29]), "+f"(d[30]), "+f"(d[31])
    : "r"(a0), "r"(a1), "r"(a2), "r"(a3), "l"(db));
  else asm volatile("wgmma.mma_async.sync.aligned.m64n64k16.f32.bf16.bf16 {%0, %1, %2, %3, %4, %5, %6, %7, %8, %9, %10, %11, %12, %13, %14, %15, %16, %17, %18, %19, %20, %21, %22, %23, %24, %25, %26, %27, %28, %29, %30, %31}, {%32, %33, %34, %35}, %36, 0, 1, 1, 1;\n"
    : "=f"(d[0]), "=f"(d[1]), "=f"(d[2]), "=f"(d[3]), "=f"(d[4]), "=f"(d[5]), "=f"(d[6]), "=f"(d[7]), "=f"(d[8]), "=f"(d[9]), "=f"(d[10]), "=f"(d[11]), "=f"(d[12]), "=f"(d[13]), "=f"(d[14]), "=f"(d[15]), "=f"(d[16]), "=f"(d[17]), "=f"(d[18]), "=f"(d[19]), "=f"(d[20]), "=f"(d[21]), "=f"(d[22]), "=f"(d[23]), "=f"(d[24]), "=f"(d[25]), "=f"(d[26]), "=f"(d[27]), "=f"(d[28]), "=f"(d[29]), "=f"(d[30]), "=f"(d[31])
    : "r"(a0), "r"(a1), "r"(a2), "r"(a3), "l"(db));
}
template <int SD> __device__ __forceinline__ void wgmma_ss_n32_ta1_tb1(float (&d)[16], uint64_t da, uint64_t db) {
  if (SD) asm volatile("wgmma.mma_async.sync.aligned.m64n32k16.f32.bf16.bf16 {%0, %1, %2, %3, %4, %5, %6, %7, %8, %9, %10, %11, %12, %13, %14, %15}, %16, %17, 1, 1, 1, 1, 1;\n"
    : "+f"(d[0]), "+f"(d[1]), "+f"(d[2]), "+f"(d[3]), "+f"(d[4]), "+f"(d[5]), "+f"(d[6]), "+f"(d[7]), "+f"(d[8]), "+f"(d[9]), "+f"(d[10]), "+f"(d[11]), "+f"(d[12]), "+f"(d[13]), "+f"(d[14]), "+f"(d[15])
    : "l"(da), "l"(db));
  else asm volatile("wgmma.mma_async.sync.aligned.m64n32k16.f32.bf16.bf16 {%0, %1, %2, %3, %4, %5, %6, %7, %8, %9, %10, %11, %12, %13, %14, %15}, %16, %17, 0, 1, 1, 1, 1;\n"
    : "=f"(d[0]), "=f"(d[1]), "=f"(d[2]), "=f"(d[3]), "=f"(d[4]), "=f"(d[5]), "=f"(d[6]), "=f"(d[7]), "=f"(d[8]), "=f"(d[9]), "=f"(d[10]), "=f"(d[11]), "=f"(d[12]), "=f"(d[13]), "=f"(d[14]), "=f"(d[15])
    : "l"(da), "l"(db));
}
template <int SD> __device__ __forceinline__ void wgmma_ss_n32_ta0_tb1(float (&d)[16], uint64_t da, uint64_t db) {
  if (SD) asm volatile("wgmma.mma_async.sync.aligned.m64n32k16.f32.bf16.bf16 {%0, %1, %2, %3, %4, %5, %6, %7, %8, %9, %10, %11, %12, %13, %14, %15}, %16, %17, 1, 1, 1, 0, 1;\n"
    : "+f"(d[0]), "+f"(d[1]), "+f"(d[2]), "+f"(d[3]), "+f"(d[4]), "+f"(d[5]), "+f"(d[6]), "+f"(d[7]), "+f"(d[8]), "+f"(d[9]), "+f"(d[10]), "+f"(d[11]), "+f"(d[12]), "+f"(d[13]), "+f"(d[14]), "+f"(d[15])
    : "l"(da), "l"(db));
  else asm volatile("wgmma.mma_async.sync.aligned.m64n32k16.f32.bf16.bf16 {%0, %1, %2, %3, %4, %5, %6, %7, %8, %9, %10, %11, %12, %13, %14, %15}, %16, %17, 0, 1, 1, 0, 1;\n"
    : "=f"(d[0]), "=f"(d[1]), "=f"(d[2]), "=f"(d[3]), "=f"(d[4]), "=f"(d[5]), "=f"(d[6]), "=f"(d[7]), "=f"(d[8]), "=f"(d[9]), "=f"(d[10]), "=f"(d[11]), "=f"(d[12]), "=f"(d[13]), "=f"(d[14]), "=f"(d[15])
    : "l"(da), "l"(db));
}
template <int SD> __device__ __forceinline__ void wgmma_rs_n64_tb0(float (&d)[32], uint32_t a0, uint32_t a1, uint32_t a2, uint32_t a3, uint64_t db) {
  if (SD) asm volatile("wgmma.mma_async.sync.aligned.m64n64k16.f32.bf16.bf16 {%0, %1, %2, %3, %4, %5, %6, %7, %8, %9, %10, %11, %12, %13, %14, %15, %16, %17, %18, %19, %20, %21, %22, %23, %24, %25, %26, %27, %28, %29, %30, %31}, {%32, %33, %34, %35}, %36, 1, 1, 1, 0;\n"
    : "+f"(d[0]), "+f"(d[1]), "+f"(d[2]), "+f"(d[3]), "+f"(d[4]), "+f"(d[5]), "+f"(d[6]), "+f"(d[7]), "+f"(d[8]), "+f"(d[9]), "+f"(d[10]), "+f"(d[11]), "+f"(d[12]), "+f"(d[13]), "+f"(d[14]), "+f"(d[15]), "+f"(d[16]), "+f"(d[17]), "+f"(d[18]), "+f"(d[19]), "+f"(d[20]), "+f"(d[21]), "+f"(d[22]), "+f"(d[23]), "+f"(d[24]), "+f"(d[25]), "+f"(d[26]), "+f"(d[27]), "+f"(d[28]), "+f"(d[29]), "+f"(d[30]), "+f"(d[31])
    : "r"(a0), "r"(a1), "r"(a2), "r"(a3), "l"(db));
  else asm volatile("wgmma.mma_async.sync.aligned.m64n64k16.f32.bf16.bf16 {%0, %1, %2, %3, %4, %5, %6, %7, %8, %9, %10, %11, %12, %13, %14, %15, %16, %17, %18, %19, %20, %21, %22, %23, %24, %25, %26, %27, %28, %29, %30, %31}, {%32, %33, %34, %35}, %36, 0, 1, 1, 0;\n"
    : "=f"(d[0]), "=f"(d[1]), "=f"(d[2]), "=f"(d[3]), "=f"(d[4]), "=f"(d[5]), "=f"(d[6]), "=f"(d[7]), "=f"(d[8]), "=f"(d[9]), "=f"(d[10]), "=f"(d[11]), "=f"(d[12]), "=f"(d[13]), "=f"(d[14]), "=f"(d[15]), "=f"(d[16]), "=f"(d[17]), "=f"(d[18]), "=f"(d[19]), "=f"(d[20]), "=f"(d[21]), "=f"(d[22]), "=f"(d[23]), "=f"(d[24]), "=f"(d[25]), "=f"(d[26]), "=f"(d[27]), "=f"(d[28]), "=f"(d[29]), "=f"(d[30]), "=f"(d[31])
    : "r"(a0), "r"(a1), "r"(a2), "r"(a3), "l"(db));
}
template <int SD> __device__ __forceinline__ void wgmma_rs_n32_tb1(float (&d)[16], uint32_t a0, uint32_t a1, uint32_t a2, uint32_t a3, uint64_t db) {
  if (SD) asm volatile("wgmma.mma_async.sync.aligned.m64n32k16.f32.bf16.bf16 {%0, %1, %2, %3, %4, %5, %6, %7, %8, %9, %10, %11, %12, %13, %14, %15}, {%16, %17, %18, %19}, %20, 1, 1, 1, 1;\n"
    : "+f"(d[0]), "+f"(d[1]), "+f"(d[2]), "+f"(d[3]), "+f"(d[4]), "+f"(d[5]), "+f"(d[6]), "+f"(d[7]), "+f"(d[8]), "+f"(d[9]), "+f"(d[10]), "+f"(d[11]), "+f"(d[12]), "+f"(d[13]), "+f"(d[14]), "+f"(d[15])
    : "r"(a0), "r"(a1), "r"(a2), "r"(a3), "l"(db));
  else asm volatile("wgmma.mma_async.sync.aligned.m64n32k16.f32.bf16.bf16 {%0, %1, %2, %3, %4, %5, %6, %7, %8, %9, %10, %11, %12, %13, %14, %15}, {%16, %17, %18, %19}, %20, 0, 1, 1, 1;\n"
    : "=f"(d[0]), "=f"(d[1]), "=f"(d[2]), "=f"(d[3]), "=f"(d[4]), "=f"(d[5]), "=f"(d[6]), "=f"(d[7]), "=f"(d[8]), "=f"(d[9]), "=f"(d[10]), "=f"(d[11]), "=f"(d[12]), "=f"(d[13]), "=f"(d[14]), "=f"(d[15])
    : "r"(a0), "r"(a1), "r"(a2), "r"(a3), "l"(db));
}

__device__ __forceinline__ uint32_t sw64_off(int row, int d) { return row * 64 + ((((d >> 3) ^ (row >> 1)) & 3) << 4) + (d & 7) * 2; }

__device__ __forceinline__ uint32_t exp2_pair_fma(float t0, float t1, uint32_t c_half, uint32_t c_3) {
  uint32_t y0, y;
  asm("prmt.b32 %0, %1, %2, 0x6521;" : "=r"(y0) : "r"(__float_as_uint(t0)), "r"(__float_as_uint(t1)));
  uint32_t h = lop_and_or(y0, 0x007F007Fu, c_half);
  uint32_t e = lop_and_or(y0, 0xFF80FF80u, c_3);
  asm("fma.rn.bf16x2 %0, %1, %2, %3;" : "=r"(y) : "r"(y0), "r"(h), "r"(e));
  return y;
}

__device__ __forceinline__ void feature_map(float (&v)[16], uint32_t (&ph)[16], int lq) {
  const float L2E = 1.4426950408889634f;
  const bool tail_ok = lq < 2;
  float mx[2], mn[2], b[16], sa[2], sn[2];
#pragma unroll
  for (int r = 0; r < 2; r++) {
    const int o = 2 * r;
    if (!tail_ok) { v[o + 12] = v[o]; v[o + 13] = v[o]; }
    mx[r] = fmaxf(fmaxf(fmaxf(v[o], v[o + 1]), fmaxf(v[o + 4], v[o + 5])), fmaxf(fmaxf(v[o + 8], v[o + 9]), fmaxf(v[o + 12], v[o + 13])));
    mn[r] = fminf(fminf(fminf(v[o], v[o + 1]), fminf(v[o + 4], v[o + 5])), fminf(fminf(v[o + 8], v[o + 9]), fminf(v[o + 12], v[o + 13])));
  }
#pragma unroll
  for (int o = 1; o <= 2; o <<= 1)
#pragma unroll
    for (int r = 0; r < 2; r++) { mx[r] = fmaxf(mx[r], __shfl_xor_sync(~0u, mx[r], o)); mn[r] = fminf(mn[r], __shfl_xor_sync(~0u, mn[r], o)); }
#pragma unroll
  for (int r = 0; r < 2; r++) {
    const int o = 2 * r;
    const float cx = -mx[r] * L2E, cn = mn[r] * L2E;
#pragma unroll
    for (int i = 0; i < 8; i++) {
      const int k = o + 4 * (i >> 1) + (i & 1);
      b[k] = ex2f(fmaf(v[k], -L2E, cn));
      v[k] = ex2f(fmaf(v[k], L2E, cx));
    }
    if (!tail_ok) { v[o + 12] = v[o + 13] = b[o + 12] = b[o + 13] = 0.f; }
    sa[r] = ((v[o] + v[o + 1]) + (v[o + 4] + v[o + 5])) + ((v[o + 8] + v[o + 9]) + (v[o + 12] + v[o + 13]));
    sn[r] = ((b[o] + b[o + 1]) + (b[o + 4] + b[o + 5])) + ((b[o + 8] + b[o + 9]) + (b[o + 12] + b[o + 13]));
  }
#pragma unroll
  for (int o = 1; o <= 2; o <<= 1)
#pragma unroll
    for (int r = 0; r < 2; r++) { sa[r] += __shfl_xor_sync(~0u, sa[r], o); sn[r] += __shfl_xor_sync(~0u, sn[r], o); }
#pragma unroll
  for (int r = 0; r < 2; r++) {
    const float ra = rcpf(sa[r]), rb = rcpf(sn[r]);
#pragma unroll
    for (int jj = 0; jj < 4; jj++) {
      ph[jj * 2 + r] = pack_bf16(v[2 * r + 4 * jj] * ra, v[2 * r + 4 * jj + 1] * ra);
      ph[(4 + jj) * 2 + r] = pack_bf16(b[2 * r + 4 * jj] * rb, b[2 * r + 4 * jj + 1] * rb);
    }
  }
}

__device__ __forceinline__ void store_heads(uint32_t base, const uint32_t (&a)[14], uint32_t pad0, uint32_t pad1, int row0, int lq) {
  const uint32_t rb = base + row0 * 64 + (((row0 >> 1) & 3) << 4);
  const uint32_t b0 = rb + lq * 4;
  const uint32_t b1 = (rb + 8192 + ((lq * 4 + 8) & 15)) ^ ((lq >> 1) << 4);
#pragma unroll
  for (int j = 0; j < 7; j++) {
    uint32_t ad;
    if (j < 3) ad = b0 ^ (j << 4);
    else if (j == 3) ad = (lq < 2) ? (b0 ^ 48u) : (b1 ^ 16u);
    else ad = (lq < 2) ? (b1 ^ ((j - 4) << 4)) : ((b1 ^ 16u) ^ ((j - 3) << 4));
    sts32(ad, a[2 * j]);
    sts32(ad + 512, a[2 * j + 1]);
  }
  sts64((rb ^ 48u) + 8 + (lq & 1) * 8192 + (lq >> 1) * 512, pad0, pad1);
}

struct Params {
  const __nv_bfloat16* w_phi;
  const __nv_bfloat16* wk;
  const __nv_bfloat16* wv;
  const __nv_bfloat16* gate_w;
  __nv_bfloat16* out;
};

__global__ void __launch_bounds__(NTHREADS, 1)
fused_kernel(const __grid_constant__ CUtensorMap tm_x, const __grid_constant__ CUtensorMap tm_wqkv,
             const __grid_constant__ CUtensorMap tm_wq, const __grid_constant__ CUtensorMap tm_woa,
             const __grid_constant__ CUtensorMap tm_wob, const Params prm) {
  extern __shared__ uint8_t smem_raw[];
  uint32_t sb = (smem_u32(smem_raw) + 1023u) & ~1023u;
  uint8_t* sgen = smem_raw + (sb - smem_u32(smem_raw));
  asm volatile("mov.u32 %0, %0;" : "+r"(sb));
  const int tid = threadIdx.x, lane = tid & 31;
  const int warp = __shfl_sync(~0u, tid >> 5, 0), wg = warp >> 2;
  const int pt = blockIdx.x >> 3, hp = blockIdx.x & 7;
  const uint32_t bars = sb + OFF_BAR;
  auto BAR = [&](int i) { return bars + 8u * i; };
  const unsigned epoch = g_epoch & 1;

  if (tid == 0) { PROF_MARK(0); PROF_CLK(30); PROF2(15); }
  auto load_proj = [&](int c, int g) {
    mbar_expect_tx(BAR(B_FULL + g), 49152);
    tma_2d(sb + OFF_X + c * 16384, &tm_x, c * 64, pt * 128, BAR(B_FULL + g));
    tma_2d(sb + OFF_RING + g * 32768, &tm_wq, hp * 56, c * 64, BAR(B_FULL + g));
#pragma unroll 1
    for (int j = 0; j < 3; j++) tma_2d(sb + OFF_RING + g * 32768 + 8192 + j * 8192, &tm_wqkv, j * DM + hp * 56, c * 64, BAR(B_FULL + g));
  };
  if (warp == 16) {
    if (elect_one()) {
      mbar_init(BAR(B_FULL), 1); mbar_init(BAR(B_FULL + 1), 1); mbar_init(BAR(B_FULL + 2), 1);
      fence_async_smem();
      load_proj(0, 0);
    }
    __syncwarp();
    asm volatile("bar.arrive 0, %0;" ::"n"(NTHREADS) : "memory");
  } else {
    if (elect_one()) {
      const int i = warp + 3 - (warp > 16);
      if (i < B_N) {
        int cnt = i < B_WO || i > B_SIG || i == B_X1FREE ? 16 : 1;
        if (i == B_BUILD) cnt = 512;
        if (i == B_SIG || i == B_SIG + 1 || i == B_QSQ) cnt = 8;
        if (i == B_KVR) cnt = 2;
        mbar_init(BAR(i), cnt);
        fence_async_smem();
      }
    }
    if (tid < 512) {
      const int k = tid >> 3, cn = tid & 7, e = k >= DH;
      const bool data = k < 56 && (cn >> 2) == e;
      const uint32_t ad = sb + OFF_WBD + k * 128 + ((cn ^ (k & 7)) << 4);
      const __nv_bfloat16* wsrc = prm.w_phi + (2 * hp * DH + k) * DH + (cn & 3) * 8;
      if (data) cp_async8(ad, wsrc); else sts64(ad, 0u, 0u);
      if (data && (cn & 3) != 3) cp_async8(ad + 8, wsrc + 4); else sts64(ad + 8, 0u, 0u);
      if (tid < DM) {
        const __nv_bfloat16* src = (hp < 4 ? prm.wk : prm.wv) + tid * DH + (hp & 3) * 8;
        cp_async8(sb + OFF_SLC + tid * 16, src);
        if ((hp & 3) != 3) cp_async8(sb + OFF_SLC + tid * 16 + 8, src + 4);
        else sts64(sb + OFF_SLC + tid * 16 + 8, hp == 3 ? (uint32_t)((const unsigned short*)prm.gate_w)[tid] : 0u, 0u);
      }
    }
    bar_sync(0, NTHREADS);
  }
  if (tid == 0) PROF2(14);

  if (wg == 4) {
    asm volatile("setmaxnreg.dec.sync.aligned.u32 32;");
    if (warp == 16) {
      if (elect_one()) { PROF2(18); load_proj(1, 1); load_proj(2, 2); PROF2(19); }
      __syncwarp();
      bar_sync(3, 64);
      if (elect_one()) {
        int g = 0, nkv = 8;
        uint32_t par = 0;
#pragma unroll 1
        for (int n = 3; n < 14 + nkv; n++) {
          if (n == 7) { PROF_MARK(20); cnt_wait(C_KV, NCTA); PROF_MARK(21); fence_async_all(); }
          if (n == 15) {
            mbar_wait(BAR(B_SLOW), 0);
            if (*(volatile int*)(sgen + OFF_RED)) nkv = 26;
          }
          const int j = n - 7 - nkv;
          if (j == 0 || j == 3) {
            PROF3(j ? 11 : 8);
            cnt_wait((j ? C_OB : C_OA) + pt, 8);
            PROF3(j ? 12 : 9);
            PROF_MARK(26);
            fence_async_all();
          }
          mbar_wait(BAR(B_EMPTY + g), par);
          if (n < 7) load_proj(n, g);
          else {
            mbar_expect_tx(BAR(B_FULL + g), 32768);
            bulk_g2s(sb + OFF_RING + g * 32768, j < 0 ? g_kv_img + ((n - 7) & 7) * 32768 : g_o_img + (size_t)(pt * 7 + j) * 32768, 32768,
                     BAR(B_FULL + g));
          }
          if (++g == 3) { g = 0; par ^= 1; }
        }
        if (atomicAdd(&g_cnt[C_DONE * 32], 1u) == NCTA - 1) {
#pragma unroll 1
          for (int i = 0; i < C_N; i++) g_cnt[i * 32] = 0;
          g_epoch = epoch ^ 1;
        }
      }
    } else {
      if (warp == 18) {
        if (elect_one()) {
#pragma unroll 1
          for (int i = 0; i < 4; i++) {
            mbar_wait(BAR(B_SIG + i), 0);
            PROF3(2 * i);
            if (i == 1) {
#pragma unroll 1
              for (int j = 0; j < 4; j++)
                asm volatile("cp.reduce.async.bulk.global.shared::cta.bulk_group.add.f32 [%0], [%1], 8192;"
                             ::"l"(g_kvacc[epoch] + hp * 4096 + (j >> 1) * 2048), "r"(sb + OFF_PHIK + j * 8192) : "memory");
              asm volatile("cp.async.bulk.commit_group;\ncp.async.bulk.wait_group 0;" ::: "memory");
            }
            cnt_arrive(i == 0 ? C_KV : i == 1 ? C_PART : (i == 2 ? C_OA : C_OB) + pt);
            PROF3(2 * i + 1);
            if (i == 1 || i == 2) {
              if (i == 2) mbar_wait(BAR(B_X1FREE), 0);
              mbar_expect_tx(BAR(B_WO + i - 1), 57344);
#pragma unroll 1
              for (int c = 0; c < 7; c++)
                tma_2d(sb + OFF_WO + (i - 1) * 57344 + c * 8192, i == 1 ? &tm_woa : &tm_wob, hp * 56, c * 64, BAR(B_WO + i - 1));
            }
          }
        }
      } else if (warp == 19) {
        if (lane == 0) {
          mbar_wait(BAR(B_SIG + 0), 0);
          cnt_wait(C_KV, NCTA);
        }
        __syncwarp();
        float ksq = 0.f, vsq = 0.f;
#pragma unroll
        for (int sl = 0; sl < 4; sl++) {
          float4 a = ldcg_f4(g_ksq + sl * 128 + lane * 4), b = ldcg_f4(g_vsq + sl * 128 + lane * 4);
          float m = fmaxf(fmaxf(a.x, a.y), fmaxf(a.z, a.w));
          m = __uint_as_float(__reduce_max_sync(~0u, __float_as_uint(m)));
          ksq += m;
          vsq = fmaxf(vsq, fmaxf(fmaxf(b.x, b.y), fmaxf(b.z, b.w)));
        }
        mbar_wait(BAR(B_QSQ), 0);
        const float4 qa4 = ((const float4*)(sgen + OFF_QSQ))[lane], qb4 = ((const float4*)(sgen + OFF_QSQ))[32 + lane];
        const float qmax = fmaxf(fmaxf(fmaxf(qa4.x, qa4.y), fmaxf(qa4.z, qa4.w)), fmaxf(fmaxf(qb4.x, qb4.y), fmaxf(qb4.z, qb4.w)));
        const bool slow = __any_sync(~0u, !(qmax * ksq <= 98.f * 98.f) || !(vsq <= 2.0e8f));
        if (lane == 0) {
          *(volatile int*)(sgen + OFF_RED) = slow;
          mbar_arrive(BAR(B_SLOW), 1);
        }
      } else {
        float4* z = (float4*)(g_kvacc[epoch ^ 1] + blockIdx.x * 256) + lane;
        z[0] = make_float4(0.f, 0.f, 0.f, 0.f);
        z[32] = make_float4(0.f, 0.f, 0.f, 0.f);
        bar_sync(3, 64);
        if (lane == 0) {
          mbar_wait(BAR(B_SIG + 0), 0);
          cnt_wait(C_KV, NCTA);
        }
        __syncwarp();
        ((float4*)(sgen + OFF_GATE))[lane] = ldcg_f4(g_gate + pt * 128 + lane * 4);
      }
      if (warp != 18) {
        if (lane == 0) {
          mbar_wait(BAR(B_SIG + 1), 0);
          cnt_wait(C_PART, NCTA);
          PROF_MARK(23);
        }
        __syncwarp();
        const int e = warp == 19;
        const float* src = g_kvacc[epoch] + hp * 4096 + e * 2048 + lane * 8;
#pragma unroll 1
        for (int i = 0; i < 8; i += 2) {
          const float4 a = ldcg_f4(src + i * 256), b = ldcg_f4(src + i * 256 + 4), c = ldcg_f4(src + i * 256 + 256), d = ldcg_f4(src + i * 256 + 260);
          const uint32_t ad = sb + OFF_KVR + e * 4096 + sw64_off(i * 8 + (lane >> 2), (lane & 3) * 8);
          sts128(ad, make_uint4(pack_bf16(a.x, a.y), pack_bf16(a.z, a.w), pack_bf16(b.x, b.y), pack_bf16(b.z, b.w)));
          sts128(ad + 512, make_uint4(pack_bf16(c.x, c.y), pack_bf16(c.z, c.w), pack_bf16(d.x, d.y), pack_bf16(d.z, d.w)));
        }
        fence_async_smem();
        __syncwarp();
        if (lane == 0) mbar_arrive(BAR(B_KVR), 1);
        PROF_MARK(24);
      }
    }
  } else {
    asm volatile("setmaxnreg.inc.sync.aligned.u32 112;");
    const int mh = wg & 1, nh = wg >> 1, wq = warp & 3;
    asm volatile("cp.async.mbarrier.arrive.noinc.shared::cta.b64 [%0];" ::"r"(BAR(B_BUILD)) : "memory");
    const int lq = lane & 3;
    const int rowl = wq * 16 + (lane >> 2);
    const int row0 = mh * 64 + rowl;
    int slot = 0, prev = 0;
    uint32_t par = 0;
    {
      float acc0[28], acc1[28], accs[4];
      const uint64_t dR = make_desc(sb + OFF_RING + nh * 16384, 1024, 1024, 1);
      const int lr = wq * 16 + (lane & 7) + ((lane >> 3) & 1) * 8;
      const uint32_t xa = sb + OFF_X + mh * 8192 + lr * 128 + (((lane >> 4) ^ (lr & 7)) << 4);
#pragma unroll
      for (int i = 0; i < 28; i++) acc0[i] = acc1[i] = 0.f;
#pragma unroll
      for (int i = 0; i < 4; i++) accs[i] = 0.f;
      const uint64_t dSlc = make_desc(sb + OFF_SLC, 128, 128, 0);
      uint32_t a[16], an[16];
      if (tid == 0) PROF2(16);
      mbar_wait(BAR(B_FULL), 0);
      if (tid == 0) PROF2(17);
#pragma unroll
      for (int ks = 0; ks < 4; ks++) ldsm4(an + 4 * ks, xa ^ (ks << 5));
      if (nh == 1) { mbar_wait(BAR(B_BUILD), 0); fence_async_smem(); }
#pragma unroll 1
      for (int c = 0; c < 7; c++) {
#pragma unroll
        for (int i = 0; i < 16; i++) a[i] = an[i];
        const uint64_t dB = dR + slot * 2048;
        wg_fence();
#pragma unroll
        for (int ks = 0; ks < 4; ks++) {
          wgmma_rs_n56_tb1<1>(acc0, a[4 * ks], a[4 * ks + 1], a[4 * ks + 2], a[4 * ks + 3], dB + ks * 128);
          wgmma_rs_n56_tb1<1>(acc1, a[4 * ks], a[4 * ks + 1], a[4 * ks + 2], a[4 * ks + 3], dB + 512 + ks * 128);
        }
        if (nh == 1) {
#pragma unroll
          for (int ks = 0; ks < 4; ks++) wgmma_rs_n8_tb1<1>(accs, a[4 * ks], a[4 * ks + 1], a[4 * ks + 2], a[4 * ks + 3], dSlc + c * 64 + ks * 16);
        }
        wg_commit();
        const int cur = slot;
        if (++slot == 3) { slot = 0; par ^= 1; }
        if (c < 6) {
          if (tid == 0 || tid == 256) PROF2(c * 2 + (tid >> 3));
          mbar_wait(BAR(B_FULL + slot), par);
          if (tid == 0 || tid == 256) PROF2(c * 2 + 1 + (tid >> 3));
#pragma unroll
          for (int ks = 0; ks < 4; ks++) ldsm4(an + 4 * ks, (xa + (c + 1) * 16384) ^ (ks << 5));
        }
        wg_wait<0>();
#pragma unroll
        for (int i = 0; i < 16; i++) asm volatile("" : "+r"(a[i])::"memory");
        if (lane == 0) mbar_arrive(BAR(B_EMPTY + cur), 1);
      }
      fence_regs(acc0); fence_regs(acc1); fence_regs(accs);
      if (tid == 0) PROF_MARK(2);
      if (tid == 256) PROF_MARK(3);
      if (nh == 0) {
        float sq[4] = {0.f, 0.f, 0.f, 0.f};
#pragma unroll
        for (int i = 0; i < 28; i++) acc0[i] *= 0.18898223650461362f * 1.4426950408889634f;
#pragma unroll
        for (int j = 0; j < 7; j++) {
#pragma unroll
          for (int rr = 0; rr < 2; rr++) {
            const float s2 = acc0[4 * j + 2 * rr] * acc0[4 * j + 2 * rr] + acc0[4 * j + 2 * rr + 1] * acc0[4 * j + 2 * rr + 1];
            if (j < 3) sq[rr] += s2;
            else if (j > 3) sq[2 + rr] += s2;
            else { sq[rr] += (lq < 2) ? s2 : 0.f; sq[2 + rr] += (lq < 2) ? 0.f : s2; }
          }
        }
#pragma unroll
        for (int i = 0; i < 4; i++) sq[i] = quad_sum(sq[i]);
        const float mine = lq == 0 ? sq[0] : lq == 1 ? sq[1] : lq == 2 ? sq[2] : sq[3];
        ((float*)(sgen + OFF_QSQ))[(mh + (lq & 2)) * 64 + rowl + 8 * (lq & 1)] = mine <= 3.0e38f ? mine : __int_as_float(0x7f800000);
        __syncwarp();
        if (lane == 0) mbar_arrive(BAR(B_QSQ), 1);
      } else {
        const int sl = hp & 3;
        const bool isk = hp < 4, real = (sl < 3) || (lq < 2);
        const int pos = pt * 128 + row0, kr = pos & 63;
        uint8_t* dst = g_kv_img + (pos >> 6) * 8192 + (isk ? 0 : 4096) + sw64_off(kr, sl * 8 + 2 * lq);
        const uint32_t pat = isk ? POLY_PAT >> (kr >> 3) : 0u;
        float mxv = 0.f;
#pragma unroll
        for (int rr = 0; rr < 2; rr++) {
          const float v0 = accs[2 * rr], v1 = accs[2 * rr + 1];
          const bool poly = (pat >> rr) & 1;
          const float sc = poly ? 2.f : 1.f;
          const float s2 = quad_sum(real ? v0 * v0 + v1 * v1 : 0.f);
          mxv = fmaxf(mxv, s2 <= 3.0e38f ? s2 : __int_as_float(0x7f800000));
          const uint32_t padv = lq == 2 ? (poly ? 0x443F4000u : 0x00003F80u) : (poly ? 0x3AB03F4Du : 0u);
          *(uint32_t*)(dst + rr * 512) = real ? pack_bf16(sc * v0, sc * v1) : padv;
          if (hp == 3 && lq == 2) g_gate[pos + 8 * rr] = rcpf(1.f + ex2f(-1.4426950408889634f * v0));
        }
        mxv = __uint_as_float(__reduce_max_sync(~0u, __float_as_uint(mxv)));
        if (lane == 0) (isk ? g_ksq : g_vsq)[sl * 128 + pt * 8 + mh * 4 + wq] = mxv;
        __syncwarp();
        if (lane == 0) mbar_arrive(BAR(B_SIG + 0), 1);
      }
      if (tid == 0) PROF_MARK(4);
      if (tid == 256) PROF_MARK(5);
      uint32_t h[14];
      float pp[32];
      {
#pragma unroll
        for (int i = 0; i < 14; i++) {
          const uint32_t u0 = pack_bf16(acc0[2 * i], acc0[2 * i + 1]), u1 = pack_bf16(acc1[2 * i], acc1[2 * i + 1]);
          h[i] = nh ? u1 : u0;
          a[i] = nh ? u0 : u1;
        }
        a[14] = a[0] ^ 0x80008000u;
        a[15] = a[1] ^ 0x80008000u;
        const uint64_t dW = make_desc(sb + OFF_WBD, 1024, 1024, 1);
        if (nh == 0) { mbar_wait(BAR(B_BUILD), 0); fence_async_smem(); }
        wg_fence();
        wgmma_rs_n64_tb1<0>(pp, a[0], a[1], a[2], a[3], dW);
#pragma unroll
        for (int ks = 1; ks < 4; ks++) wgmma_rs_n64_tb1<1>(pp, a[4 * ks], a[4 * ks + 1], a[4 * ks + 2], a[4 * ks + 3], dW + ks * 128);
        wg_commit();
        bar_sync(1, 512);
        if (tid == 0) PROF_MARK(6);
        store_heads(sb + (nh ? OFF_VA : OFF_QP), h, nh ? 0x00003F80u : 0x3F800000u, nh ? 0u : 0x3F803F80u, row0, lq);
        wg_wait<0>();
        fence_regs(pp);
      }
      float v[16];
#pragma unroll
      for (int i = 0; i < 16; i++) v[i] = pp[i];
      uint32_t rb = sb + (nh ? OFF_PHIK : OFF_PHIQ) + row0 * 128 + lq * 4 + ((rowl & 7) << 4);
#pragma unroll 1
      for (int e = 0; e < 2; e++) {
        uint32_t ph[16];
        feature_map(v, ph, lq);
#pragma unroll
        for (int ch = 0; ch < 8; ch++) { sts32(rb ^ (ch << 4), ph[2 * ch]); sts32((rb ^ (ch << 4)) + 1024, ph[2 * ch + 1]); }
        rb += 16384;
#pragma unroll
        for (int i = 0; i < 16; i++) v[i] = pp[16 + i];
      }
      fence_async_smem();
      bar_sync(1, 512);
      if (tid == 0) PROF_MARK(7);
      if (nh == 1) {
        float kv0[16], kv1[16];
        const uint64_t dP = make_desc(sb + OFF_PHIK + mh * 8192, 1024, 1024, 1);
        const uint64_t dV = make_desc(sb + OFF_VA + mh * 4096, 512, 512, 2);
        wg_fence();
        wgmma_ss_n32_ta1_tb1<0>(kv0, dP, dV);
        wgmma_ss_n32_ta1_tb1<0>(kv1, dP + 1024, dV + 512);
#pragma unroll
        for (int ks = 1; ks < 4; ks++) {
          wgmma_ss_n32_ta1_tb1<1>(kv0, dP + ks * 128, dV + ks * 64);
          wgmma_ss_n32_ta1_tb1<1>(kv1, dP + 1024 + ks * 128, dV + 512 + ks * 64);
        }
        wg_commit();
        wg_wait<0>();
        fence_regs(kv0); fence_regs(kv1);
        bar_sync(4 + wg, 128);
        const uint32_t sa = sb + OFF_PHIK + mh * 8192 + rowl * 128 + lq * 8;
#pragma unroll
        for (int j = 0; j < 8; j++) {
          sts64(sa + 32 * (j >> 1) + 1024 * (j & 1), __float_as_uint(kv0[2 * j]), __float_as_uint(kv0[2 * j + 1]));
          sts64(sa + 16384 + 32 * (j >> 1) + 1024 * (j & 1), __float_as_uint(kv1[2 * j]), __float_as_uint(kv1[2 * j + 1]));
        }
        fence_async_smem();
        __syncwarp();
        if (lane == 0) mbar_arrive(BAR(B_SIG + 1), 1);
        if (tid == 256) PROF_MARK(28);
      }
    }
    {
      const uint64_t dK = make_desc(sb + OFF_RING, 512, 512, 2);
      const uint64_t dhi = dK & 0xffffffff00000000ull;
      const uint32_t dlo0 = (uint32_t)dK;
      uint32_t ok = 0, q[8];
      float o[16];
#pragma unroll
      for (int i = 0; i < 16; i++) o[i] = 0.f;
      {
        const int r = mh * 64 + wq * 16 + (lane & 7) + ((lane >> 3) & 1) * 8;
        ldsm4(q, sb + OFF_QP + nh * 8192 + sw64_off(r, (lane >> 4) * 8));
        ldsm4(q + 4, sb + OFF_QP + nh * 8192 + sw64_off(r, 16 + (lane >> 4) * 8));
      }
      if (tid == 0) PROF_MARK(10);
      const int qb = QB_AT;
#pragma unroll 1
      for (int it = 0; it <= 8; it++) {
        uint32_t p[16];
        if ((tid & 127) == 0) PROF4(wg * 32 + it * 3);
        if (it == qb || it == 8) {
          float t[16];
          wg_wait<0>();
          fence_regs(o);
          if (it < 8) {
            if (tid == 0) PROF_MARK(11);
            mbar_wait(BAR(B_KVR), 0);
            const uint64_t dR = make_desc(sb + OFF_KVR + nh * 4096, 512, 512, 2);
            const uint64_t dP = make_desc(sb + OFF_PHIQ + nh * 16384 + mh * 8192, 1024, 1024, 1);
            wg_fence();
            wgmma_ss_n32_ta0_tb1<0>(t, dP, dR);
#pragma unroll
            for (int ks = 1; ks < 4; ks++) wgmma_ss_n32_ta0_tb1<1>(t, dP + ks * 2, dR + ks * 64);
            wg_commit();
            wg_wait<0>();
            fence_regs(t);
            if (lane == 0) mbar_arrive(BAR(B_X1FREE), 1);
          } else {
            if (lane == 0) mbar_arrive(BAR(B_EMPTY + prev), 1);
            if (tid == 0) PROF_MARK(13);
            mbar_wait(BAR(B_SLOW), 0);
            if (__builtin_expect(__any_sync(~0u, *(volatile int*)(sgen + OFF_RED)), 0)) {
              uint32_t qz[8];
#pragma unroll
              for (int i = 0; i < 8; i++) qz[i] = (i >= 6 && lq >= 2) ? 0u : q[i];
              float m0 = -3.0e38f, m1 = -3.0e38f, o2[16];
              int sl2 = slot;
              uint32_t par2 = par;
#pragma unroll 1
              for (int j64 = 0; j64 < 32; j64++) {
                float s[32];
                mbar_wait(BAR(B_FULL + sl2), par2);
                const uint32_t lo = dlo0 + sl2 * 2048 + (j64 & 3) * 512;
                wg_fence();
                wgmma_rs_n64_tb0<0>(s, qz[0], qz[1], qz[2], qz[3], dhi | lo);
                wgmma_rs_n64_tb0<1>(s, qz[4], qz[5], qz[6], qz[7], dhi | (lo + 2));
                wg_commit();
                wg_wait<0>();
                fence_regs(s);
#pragma unroll
                for (int j = 0; j < 8; j++) {
                  const float sc = ((POLY_PAT >> j) & 1) ? 0.5f : 1.f;
                  m0 = fmaxf(m0, fmaxf(s[4 * j], s[4 * j + 1]) * sc);
                  m1 = fmaxf(m1, fmaxf(s[4 * j + 2], s[4 * j + 3]) * sc);
                }
                if ((j64 & 3) == 3) {
                  if (lane == 0) mbar_arrive(BAR(B_EMPTY + sl2), 1);
                  if (++sl2 == 3) { sl2 = 0; par2 ^= 1; }
                }
              }
              m0 = quad_max(m0); m1 = quad_max(m1);
#pragma unroll
              for (int i = 0; i < 16; i++) o2[i] = 0.f;
#pragma unroll 1
              for (int j64 = 0; j64 < 32; j64++) {
                float s[32];
                mbar_wait(BAR(B_FULL + sl2), par2);
                const uint32_t lo = dlo0 + sl2 * 2048 + (j64 & 3) * 512;
                wg_fence();
                wgmma_rs_n64_tb0<0>(s, qz[0], qz[1], qz[2], qz[3], dhi | lo);
                wgmma_rs_n64_tb0<1>(s, qz[4], qz[5], qz[6], qz[7], dhi | (lo + 2));
                wg_commit();
                wg_wait<0>();
                fence_regs(s);
                uint32_t ps[16];
#pragma unroll
                for (int j = 0; j < 8; j++) {
                  const float sc = ((POLY_PAT >> j) & 1) ? 0.5f : 1.f;
                  ps[2 * j] = pack_bf16(ex2f(fmaf(s[4 * j], sc, -m0)), ex2f(fmaf(s[4 * j + 1], sc, -m0)));
                  ps[2 * j + 1] = pack_bf16(ex2f(fmaf(s[4 * j + 2], sc, -m1)), ex2f(fmaf(s[4 * j + 3], sc, -m1)));
                }
                wg_fence();
#pragma unroll
                for (int ks = 0; ks < 4; ks++)
                  wgmma_rs_n32_tb1<1>(o2, ps[4 * ks], ps[4 * ks + 1], ps[4 * ks + 2], ps[4 * ks + 3], dhi | (lo + 256 + ks * 64));
                wg_commit();
                wg_wait<0>();
                fence_regs(o2);
                if ((j64 & 3) == 3) {
                  if (lane == 0) mbar_arrive(BAR(B_EMPTY + sl2), 1);
                  if (++sl2 == 3) { sl2 = 0; par2 ^= 1; }
                }
              }
#pragma unroll 1
              for (int j = 0; j < 2; j++) {
                mbar_wait(BAR(B_FULL + sl2), par2);
                __syncwarp();
                if (lane == 0) mbar_arrive(BAR(B_EMPTY + sl2), 1);
                if (++sl2 == 3) { sl2 = 0; par2 ^= 1; }
              }
#pragma unroll
              for (int i = 0; i < 16; i++) o[i] = o2[i];
            }
#pragma unroll
            for (int i = 0; i < 16; i++) t[i] = o[i];
          }
          const int br = it == 8;
          const float eps = br ? 0.f : 1e-6f;
          const float g0 = ((const float*)(sgen + OFF_GATE))[row0], g1 = ((const float*)(sgen + OFF_GATE))[row0 + 8];
          const float d0 = __shfl_sync(~0u, t[12], (lane & ~3) | 2), d1 = __shfl_sync(~0u, t[14], (lane & ~3) | 2);
          const float r0 = (br ? 1.f - g0 : g0) * rcpf(d0 + eps), r1 = (br ? 1.f - g1 : g1) * rcpf(d1 + eps);
          uint8_t* img = g_o_img + (size_t)((pt * 2 + br) * 14 + mh) * 8192 + rowl * 128;
          const int col0 = (2 * hp + nh) * DH + 2 * lq;
#pragma unroll
          for (int j = 0; j < 4; j++) {
            const int col = col0 + 8 * j;
            uint8_t* gp = img + (uint32_t)((col >> 6) * 16384 + ((((col >> 3) ^ rowl) & 7) << 4) + (col & 7) * 2);
            const uint32_t v0 = pack_bf16(t[4 * j] * r0, t[4 * j + 1] * r0), v1 = pack_bf16(t[4 * j + 2] * r1, t[4 * j + 3] * r1);
            if (j < 3 || lq < 2) { *(uint32_t*)gp = v0; *(uint32_t*)(gp + 1024) = v1; }
          }
          __syncwarp();
          if (lane == 0) mbar_arrive(BAR(B_SIG + 2 + br), 1);
          if (tid == 0) PROF_MARK(12 + 2 * br);
          if (br) break;
        }
        const uint32_t lo = dlo0 + slot * 2048;
        if ((tid & 127) == 0) PROF4(wg * 32 + it * 3 + 1);
        if (!ok) mbar_wait(BAR(B_FULL + slot), par);
        if ((tid & 127) == 0) PROF4(wg * 32 + it * 3 + 2);
        int nslot = slot + 1;
        uint32_t npar = par;
        if (nslot == 3) { nslot = 0; npar ^= 1; }
        {
          float s[32];
          wg_fence();
          wgmma_rs_n64_tb0<0>(s, q[0], q[1], q[2], q[3], dhi | lo);
          wgmma_rs_n64_tb0<1>(s, q[4], q[5], q[6], q[7], dhi | (lo + 2));
          wg_commit();
#pragma unroll
          for (int u = 0; u < 4; u++) {
            wg_wait<0>();
            fence_regs(s);
            if (u == 0 && lane == 0 && it > 0) mbar_arrive(BAR(B_EMPTY + prev), 1);
            if (u == 2) ok = mbar_test(BAR(B_FULL + nslot), npar);
#pragma unroll
            for (int j = 0; j < 8; j++) {
              if ((POLY_PAT >> j) & 1) {
                p[2 * j] = exp2_pair_fma(s[4 * j], s[4 * j + 1], 0x3F003F00u, 0x00030003u);
                p[2 * j + 1] = exp2_pair_fma(s[4 * j + 2], s[4 * j + 3], 0x3F003F00u, 0x00030003u);
              } else {
                p[2 * j] = pack_bf16(ex2f(s[4 * j]), ex2f(s[4 * j + 1]));
                p[2 * j + 1] = pack_bf16(ex2f(s[4 * j + 2]), ex2f(s[4 * j + 3]));
              }
            }
            wg_fence();
#pragma unroll
            for (int ks = 0; ks < 4; ks++)
              wgmma_rs_n32_tb1<1>(o, p[4 * ks], p[4 * ks + 1], p[4 * ks + 2], p[4 * ks + 3], dhi | (lo + u * 512 + 256 + ks * 64));
            if (u < 3) {
              wgmma_rs_n64_tb0<0>(s, q[0], q[1], q[2], q[3], dhi | (lo + (u + 1) * 512));
              wgmma_rs_n64_tb0<1>(s, q[4], q[5], q[6], q[7], dhi | (lo + (u + 1) * 512 + 2));
            }
            wg_commit();
          }
        }
        prev = slot; slot = nslot; par = npar;
      }
      wg_wait<0>();
    }
    if (nh == 1) return;
    {
      float acc0[28], acc1[28];
#pragma unroll
      for (int i = 0; i < 28; i++) acc0[i] = acc1[i] = 0.f;
      const uint64_t dS = make_desc(sb + OFF_WO, 1024, 1024, 1);
      const uint64_t dR = make_desc(sb + OFF_RING + mh * 8192, 1024, 1024, 1);
#pragma unroll 1
      for (int c = 0; c < 7; c++) {
        mbar_wait(BAR(B_WO + (c >= 3)), 0);
        mbar_wait(BAR(B_FULL + slot), par);
        const uint64_t dA = dR + slot * 2048, dB = dS + c * 1024;
        wg_fence();
#pragma unroll
        for (int ks = 0; ks < 4; ks++) {
          wgmma_ss_n56_ta0_tb1<1>(acc0, dA + ks * 2, dB + ks * 128);
          wgmma_ss_n56_ta0_tb1<1>(acc1, dA + 1024 + ks * 2, dB + 512 + ks * 128);
        }
        wg_commit();
        if (c < 4) {
          wg_wait<0>();
          if (lane == 0) mbar_arrive(BAR(B_EMPTY + slot), 2);
        }
        if (++slot == 3) { slot = 0; par ^= 1; }
      }
      wg_wait<0>();
      fence_regs(acc0); fence_regs(acc1);
      if (tid == 0) PROF_MARK(17);
      __nv_bfloat16* op = prm.out + (size_t)(pt * 128 + row0) * DM + hp * 56 + 2 * lq;
#pragma unroll
      for (int j = 0; j < 7; j++) {
        *(uint32_t*)(op + 8 * j) = pack_bf16(acc0[4 * j] + acc1[4 * j], acc0[4 * j + 1] + acc1[4 * j + 1]);
        *(uint32_t*)(op + 8 * DM + 8 * j) = pack_bf16(acc0[4 * j + 2] + acc1[4 * j + 2], acc0[4 * j + 3] + acc1[4 * j + 3]);
      }
      if (tid == 0) { PROF_MARK(18); PROF_CLK(31); }
    }
  }
}

typedef CUresult (*EncodeFn)(CUtensorMap*, CUtensorMapDataType, cuuint32_t, void*, const cuuint64_t*, const cuuint64_t*,
                             const cuuint32_t*, const cuuint32_t*, CUtensorMapInterleave, CUtensorMapSwizzle,
                             CUtensorMapL2promotion, CUtensorMapFloatOOBfill);

void make_map(EncodeFn enc, CUtensorMap* tm, const void* ptr, uint64_t cols, uint64_t rows, uint32_t box_rows) {
  cuuint64_t dims[2] = {cols, rows};
  cuuint64_t strides[1] = {cols * 2};
  cuuint32_t box[2] = {64, box_rows};
  cuuint32_t es[2] = {1, 1};
  enc(tm, CU_TENSOR_MAP_DATA_TYPE_BFLOAT16, 2, const_cast<void*>(ptr), dims, strides, box, es, CU_TENSOR_MAP_INTERLEAVE_NONE,
      CU_TENSOR_MAP_SWIZZLE_128B, CU_TENSOR_MAP_L2_PROMOTION_L2_128B, CU_TENSOR_MAP_FLOAT_OOB_FILL_NONE);
}

}

extern "C" void kernel_launch(void* const* d_in, const int* in_sizes, int n_in, void* d_out, int out_size) {
  (void)in_sizes; (void)n_in; (void)out_size;
  static EncodeFn enc = nullptr;
  if (!enc) {
    void* fn = nullptr;
    cudaDriverEntryPointQueryResult qr;
    cudaGetDriverEntryPoint("cuTensorMapEncodeTiled", &fn, cudaEnableDefault, &qr);
    enc = (EncodeFn)fn;
    cudaFuncSetAttribute(fused_kernel, cudaFuncAttributeMaxDynamicSharedMemorySize, SMEM_BYTES);
  }
  CUtensorMap tm_x, tm_wqkv, tm_wq, tm_woa, tm_wob;
  make_map(enc, &tm_x, d_in[0], DM, S_LEN, 128);
  make_map(enc, &tm_wqkv, d_in[1], 3 * DM, DM, 64);
  make_map(enc, &tm_wq, d_in[5], DM, DM, 64);
  make_map(enc, &tm_woa, d_in[3], DM, DM, 64);
  make_map(enc, &tm_wob, d_in[8], DM, DM, 64);
  Params prm;
  prm.w_phi = (const __nv_bfloat16*)d_in[2];
  prm.wk = (const __nv_bfloat16*)d_in[6];
  prm.wv = (const __nv_bfloat16*)d_in[7];
  prm.gate_w = (const __nv_bfloat16*)d_in[9];
  prm.out = (__nv_bfloat16*)d_out;
  fused_kernel<<<NCTA, NTHREADS, SMEM_BYTES>>>(tm_x, tm_wqkv, tm_wq, tm_woa, tm_wob, prm);
}
```

```cpp
#include <cuda_runtime.h>
#include <cuda_bf16.h>
#include <cuda.h>
#include <stdint.h>

namespace {

constexpr int S_LEN = 2048, DM = 448, DH = 28;
constexpr int NCTA = 128;
constexpr int NTHREADS = 640;
constexpr uint32_t POLY_PAT = 0x57;

#define QB_AT (4 + nh)

constexpr int OFF_X = 0;
constexpr int OFF_PHIK = 0;
constexpr int OFF_VA = 32768;
constexpr int OFF_PHIQ = 57344;
constexpr int OFF_KVR = 90112;
constexpr int OFF_QP = 98304;
constexpr int OFF_WO = 0;
constexpr int OFF_RING = 114688;
constexpr int OFF_WBD = 212992;
constexpr int OFF_SLC = 221184;
constexpr int OFF_QSQ = 228352;
constexpr int OFF_GATE = 229376;
constexpr int OFF_RED = 229888;
constexpr int OFF_BAR = 229952;
constexpr int SMEM_BYTES = 230400 + 1024;

constexpr int B_FULL = 0, B_EMPTY = 3, B_WO = 6  , B_KVR = 8, B_X1FREE = 10, B_QSQ = 11, B_SLOW = 12,
              B_BUILD = 13, B_SIG = 14  , B_N = 18;

constexpr int C_KV = 0, C_PART = 1, C_DONE = 3, C_OA = 4, C_OB = 20, C_N = 36;

__device__ __align__(1024) uint8_t g_kv_img[32 * 8192];
__device__ __align__(16) float g_ksq[512];
__device__ __align__(16) float g_vsq[512];
__device__ __align__(16) float g_gate[S_LEN];
__device__ __align__(1024) float g_kvacc[2][16 * 64 * 32];
__device__ unsigned g_epoch;
__device__ __align__(1024) uint8_t g_o_img[2 * 16 * 14 * 8192];
__device__ unsigned g_cnt[C_N * 32];

#define PROF4(i) do { } while (0)
#define PROF3(i) do { } while (0)
#define PROF2(i) do { } while (0)
#define PROF_CLK(i) do { } while (0)
#define PROF_MARK(i) do { } while (0)
__device__ __forceinline__ uint32_t smem_u32(const void* p) { return (uint32_t)__cvta_generic_to_shared(p); }
__device__ __forceinline__ void mbar_init(uint32_t a, int cnt) {
  asm volatile("mbarrier.init.shared::cta.b64 [%0], %1;" ::"r"(a), "r"(cnt) : "memory");
}
__device__ __forceinline__ void mbar_expect_tx(uint32_t a, uint32_t bytes) {
  asm volatile("mbarrier.arrive.expect_tx.shared::cta.b64 _, [%0], %1;" ::"r"(a), "r"(bytes) : "memory");
}
__device__ __forceinline__ void mbar_arrive(uint32_t a, uint32_t cnt) {
  asm volatile("mbarrier.arrive.shared::cta.b64 _, [%0], %1;" ::"r"(a), "r"(cnt) : "memory");
}
__device__ __forceinline__ void mbar_wait(uint32_t a, uint32_t parity) {
  asm volatile(
      "{\n.reg .pred p;\n.reg .u32 c;\nmov.u32 c, 0;\n"
      "W_%=:\nmbarrier.try_wait.parity.shared::cta.b64 p, [%0], %1;\n"
      "add.u32 c, c, 1;\nsetp.lt.and.u32 p, c, 0x40000, !p;\n@p bra W_%=;\n}"
      ::"r"(a), "r"(parity) : "memory");
}
__device__ __forceinline__ uint32_t mbar_test(uint32_t a, uint32_t parity) {
  uint32_t ok;
  asm volatile("{\n.reg .pred p;\nmbarrier.test_wait.parity.shared::cta.b64 p, [%1], %2;\nselp.u32 %0, 1, 0, p;\n}"
               : "=r"(ok) : "r"(a), "r"(parity) : "memory");
  return ok;
}
__device__ __forceinline__ bool elect_one() {
  uint32_t r;
  asm volatile("{\n.reg .pred p;\nelect.sync _|p, 0xffffffff;\nselp.u32 %0, 1, 0, p;\n}" : "=r"(r));
  return r != 0;
}
__device__ __forceinline__ void tma_2d(uint32_t dst, const CUtensorMap* tm, int c0, int c1, uint32_t bar) {
  asm volatile("cp.async.bulk.tensor.2d.shared::cluster.global.mbarrier::complete_tx::bytes [%0], [%1, {%3, %4}], [%2];"
               ::"r"(dst), "l"(tm), "r"(bar), "r"(c0), "r"(c1) : "memory");
}
__device__ __forceinline__ void bulk_g2s(uint32_t dst, const void* src, uint32_t bytes, uint32_t bar) {
  asm volatile("cp.async.bulk.shared::cluster.global.mbarrier::complete_tx::bytes [%0], [%1], %2, [%3];"
               ::"r"(dst), "l"(src), "r"(bytes), "r"(bar) : "memory");
}
__device__ __forceinline__ void cp_async8(uint32_t dst, const void* src) {
  asm volatile("cp.async.ca.shared.global [%0], [%1], 8;" ::"r"(dst), "l"(src) : "memory");
}
__device__ __forceinline__ void fence_async_smem() { asm volatile("fence.proxy.async.shared::cta;" ::: "memory"); }
__device__ __forceinline__ void fence_async_all() { asm volatile("fence.proxy.async.global;" ::: "memory"); }

__device__ __forceinline__ void bar_sync(int id, int n) { asm volatile("bar.sync %0, %1;" ::"r"(id), "r"(n) : "memory"); }
__device__ __forceinline__ void cnt_arrive(int idx) {
  asm volatile("red.release.gpu.global.add.u32 [%0], 1;" ::"l"(&g_cnt[idx * 32]) : "memory");
}
__device__ __forceinline__ void cnt_wait(int idx, unsigned target) {
  unsigned v, n = 0;
#pragma unroll 1
  while (true) {
    asm volatile("ld.acquire.gpu.global.u32 %0, [%1];" : "=r"(v) : "l"(&g_cnt[idx * 32]) : "memory");
    if (v >= target || ++n >= (1u << 18)) break;
    __nanosleep(32);
  }
}
__device__ __forceinline__ void wg_fence() { asm volatile("wgmma.fence.sync.aligned;" ::: "memory"); }
__device__ __forceinline__ void wg_commit() { asm volatile("wgmma.commit_group.sync.aligned;" ::: "memory"); }
template <int N> __device__ __forceinline__ void wg_wait() { asm volatile("wgmma.wait_group.sync.aligned %0;" ::"n"(N) : "memory"); }
template <int N> __device__ __forceinline__ void fence_regs(float (&d)[N]) {
#pragma unroll
  for (int i = 0; i < N; i++) asm volatile("" : "+f"(d[i])::"memory");
}
__device__ __forceinline__ uint64_t make_desc(uint32_t saddr, uint32_t lbo, uint32_t sbo, uint32_t swz) {
  return (uint64_t)((saddr & 0x3FFFF) >> 4) | ((uint64_t)(lbo >> 4) << 16) | ((uint64_t)(sbo >> 4) << 32) | ((uint64_t)swz << 62);
}
__device__ __forceinline__ float ex2f(float x) { float y; asm("ex2.approx.ftz.f32 %0, %1;" : "=f"(y) : "f"(x)); return y; }
__device__ __forceinline__ float rcpf(float x) { float y; asm("rcp.approx.ftz.f32 %0, %1;" : "=f"(y) : "f"(x)); return y; }
__device__ __forceinline__ uint32_t pack_bf16(float lo, float hi) {
  uint32_t r; asm("cvt.rn.bf16x2.f32 %0, %1, %2;" : "=r"(r) : "f"(hi), "f"(lo)); return r;
}
__device__ __forceinline__ uint32_t lop_and_or(uint32_t a, uint32_t m, uint32_t c) {
  uint32_t r; asm("lop3.b32 %0, %1, %2, %3, 0xEA;" : "=r"(r) : "r"(a), "r"(m), "r"(c)); return r;
}
__device__ __forceinline__ void sts32(uint32_t a, uint32_t v) { asm volatile("st.shared.b32 [%0], %1;" ::"r"(a), "r"(v) : "memory"); }
__device__ __forceinline__ void sts64(uint32_t a, uint32_t v0, uint32_t v1) { asm volatile("st.shared.v2.b32 [%0], {%1, %2};" ::"r"(a), "r"(v0), "r"(v1) : "memory"); }
__device__ __forceinline__ void sts128(uint32_t a, uint4 v) {
  asm volatile("st.shared.v4.b32 [%0], {%1, %2, %3, %4};" ::"r"(a), "r"(v.x), "r"(v.y), "r"(v.z), "r"(v.w) : "memory");
}
__device__ __forceinline__ float4 ldcg_f4(const float* p) {
  float4 v; asm volatile("ld.global.cg.v4.f32 {%0, %1, %2, %3}, [%4];" : "=f"(v.x), "=f"(v.y), "=f"(v.z), "=f"(v.w) : "l"(p) : "memory"); return v;
}
__device__ __forceinline__ void ldsm4(uint32_t* r, uint32_t a) {
  asm volatile("ldmatrix.sync.aligned.m8n8.x4.shared.b16 {%0, %1, %2, %3}, [%4];"
               : "=r"(r[0]), "=r"(r[1]), "=r"(r[2]), "=r"(r[3]) : "r"(a) : "memory");
}
__device__ __forceinline__ float quad_sum(float v) { v += __shfl_xor_sync(~0u, v, 1); v += __shfl_xor_sync(~0u, v, 2); return v; }
__device__ __forceinline__ float quad_max(float v) { v = fmaxf(v, __shfl_xor_sync(~0u, v, 1)); v = fmaxf(v, __shfl_xor_sync(~0u, v, 2)); return v; }

template <int SD> __device__ __forceinline__ void wgmma_ss_n56_ta0_tb1(float (&d)[28], uint64_t da, uint64_t db) {
  if (SD) asm volatile("wgmma.mma_async.sync.aligned.m64n56k16.f32.bf16.bf16 {%0, %1, %2, %3, %4, %5, %6, %7, %8, %9, %10, %11, %12, %13, %14, %15, %16, %17, %18, %19, %20, %21, %22, %23, %24, %25, %26, %27}, %28, %29, 1, 1, 1, 0, 1;\n"
    : "+f"(d[0]), "+f"(d[1]), "+f"(d[2]), "+f"(d[3]), "+f"(d[4]), "+f"(d[5]), "+f"(d[6]), "+f"(d[7]), "+f"(d[8]), "+f"(d[9]), "+f"(d[10]), "+f"(d[11]), "+f"(d[12]), "+f"(d[13]), "+f"(d[14]), "+f"(d[15]), "+f"(d[16]), "+f"(d[17]), "+f"(d[18]), "+f"(d[19]), "+f"(d[20]), "+f"(d[21]), "+f"(d[22]), "+f"(d[23]), "+f"(d[24]), "+f"(d[25]), "+f"(d[26]), "+f"(d[27])
    : "l"(da), "l"(db));
  else asm volatile("wgmma.mma_async.sync.aligned.m64n56k16.f32.bf16.bf16 {%0, %1, %2, %3, %4, %5, %6, %7, %8, %9, %10, %11, %12, %13, %14, %15, %16, %17, %18, %19, %20, %21, %22, %23, %24, %25, %26, %27}, %28, %29, 0, 1, 1, 0, 1;\n"
    : "=f"(d[0]), "=f"(d[1]), "=f"(d[2]), "=f"(d[3]), "=f"(d[4]), "=f"(d[5]), "=f"(d[6]), "=f"(d[7]), "=f"(d[8]), "=f"(d[9]), "=f"(d[10]), "=f"(d[11]), "=f"(d[12]), "=f"(d[13]), "=f"(d[14]), "=f"(d[15]), "=f"(d[16]), "=f"(d[17]), "=f"(d[18]), "=f"(d[19]), "=f"(d[20]), "=f"(d[21]), "=f"(d[22]), "=f"(d[23]), "=f"(d[24]), "=f"(d[25]), "=f"(d[26]), "=f"(d[27])
    : "l"(da), "l"(db));
}
template <int SD> __device__ __forceinline__ void wgmma_rs_n56_tb1(float (&d)[28], uint32_t a0, uint32_t a1, uint32_t a2, uint32_t a3, uint64_t db) {
  if (SD) asm volatile("wgmma.mma_async.sync.aligned.m64n56k16.f32.bf16.bf16 {%0, %1, %2, %3, %4, %5, %6, %7, %8, %9, %10, %11, %12, %13, %14, %15, %16, %17, %18, %19, %20, %21, %22, %23, %24, %25, %26, %27}, {%28, %29, %30, %31}, %32, 1, 1, 1, 1;\n"
    : "+f"(d[0]), "+f"(d[1]), "+f"(d[2]), "+f"(d[3]), "+f"(d[4]), "+f"(d[5]), "+f"(d[6]), "+f"(d[7]), "+f"(d[8]), "+f"(d[9]), "+f"(d[10]), "+f"(d[11]), "+f"(d[12]), "+f"(d[13]), "+f"(d[14]), "+f"(d[15]), "+f"(d[16]), "+f"(d[17]), "+f"(d[18]), "+f"(d[19]), "+f"(d[20]), "+f"(d[21]), "+f"(d[22]), "+f"(d[23]), "+f"(d[24]), "+f"(d[25]), "+f"(d[26]), "+f"(d[27])
    : "r"(a0), "r"(a1), "r"(a2), "r"(a3), "l"(db));
  else asm volatile("wgmma.mma_async.sync.aligned.m64n56k16.f32.bf16.bf16 {%0, %1, %2, %3, %4, %5, %6, %7, %8, %9, %10, %11, %12, %13, %14, %15, %16, %17, %18, %19, %20, %21, %22, %23, %24, %25, %26, %27}, {%28, %29, %30, %31}, %32, 0, 1, 1, 1;\n"
    : "=f"(d[0]), "=f"(d[1]), "=f"(d[2]), "=f"(d[3]), "=f"(d[4]), "=f"(d[5]), "=f"(d[6]), "=f"(d[7]), "=f"(d[8]), "=f"(d[9]), "=f"(d[10]), "=f"(d[11]), "=f"(d[12]), "=f"(d[13]), "=f"(d[14]), "=f"(d[15]), "=f"(d[16]), "=f"(d[17]), "=f"(d[18]), "=f"(d[19]), "=f"(d[20]), "=f"(d[21]), "=f"(d[22]), "=f"(d[23]), "=f"(d[24]), "=f"(d[25]), "=f"(d[26]), "=f"(d[27])
    : "r"(a0), "r"(a1), "r"(a2), "r"(a3), "l"(db));
}
template <int SD> __device__ __forceinline__ void wgmma_rs_n8_tb1(float (&d)[4], uint32_t a0, uint32_t a1, uint32_t a2, uint32_t a3, uint64_t db) {
  if (SD) asm volatile("wgmma.mma_async.sync.aligned.m64n8k16.f32.bf16.bf16 {%0, %1, %2, %3}, {%4, %5, %6, %7}, %8, 1, 1, 1, 1;\n"
    : "+f"(d[0]), "+f"(d[1]), "+f"(d[2]), "+f"(d[3])
    : "r"(a0), "r"(a1), "r"(a2), "r"(a3), "l"(db));
  else asm volatile("wgmma.mma_async.sync.aligned.m64n8k16.f32.bf16.bf16 {%0, %1, %2, %3}, {%4, %5, %6, %7}, %8, 0, 1, 1, 1;\n"
    : "=f"(d[0]), "=f"(d[1]), "=f"(d[2]), "=f"(d[3])
    : "r"(a0), "r"(a1), "r"(a2), "r"(a3), "l"(db));
}
template <int SD> __device__ __forceinline__ void wgmma_rs_n64_tb1(float (&d)[32], uint32_t a0, uint32_t a1, uint32_t a2, uint32_t a3, uint64_t db) {
  if (SD) asm volatile("wgmma.mma_async.sync.aligned.m64n64k16.f32.bf16.bf16 {%0, %1, %2, %3, %4, %5, %6, %7, %8, %9, %10, %11, %12, %13, %14, %15, %16, %17, %18, %19, %20, %21, %22, %23, %24, %25, %26, %27, %28, %29, %30, %31}, {%32, %33, %34, %35}, %36, 1, 1, 1, 1;\n"
    : "+f"(d[0]), "+f"(d[1]), "+f"(d[2]), "+f"(d[3]), "+f"(d[4]), "+f"(d[5]), "+f"(d[6]), "+f"(d[7]), "+f"(d[8]), "+f"(d[9]), "+f"(d[10]), "+f"(d[11]), "+f"(d[12]), "+f"(d[13]), "+f"(d[14]), "+f"(d[15]), "+f"(d[16]), "+f"(d[17]), "+f"(d[18]), "+f"(d[19]), "+f"(d[20]), "+f"(d[21]), "+f"(d[22]), "+f"(d[23]), "+f"(d[24]), "+f"(d[25]), "+f"(d[26]), "+f"(d[27]), "+f"(d[28]), "+f"(d[29]), "+f"(d[30]), "+f"(d[31])
    : "r"(a0), "r"(a1), "r"(a2), "r"(a3), "l"(db));
  else asm volatile("wgmma.mma_async.sync.aligned.m64n64k16.f32.bf16.bf16 {%0, %1, %2, %3, %4, %5, %6, %7, %8, %9, %10, %11, %12, %13, %14, %15, %16, %17, %18, %19, %20, %21, %22, %23, %24, %25, %26, %27, %28, %29, %30, %31}, {%32, %33, %34, %35}, %36, 0, 1, 1, 1;\n"
    : "=f"(d[0]), "=f"(d[1]), "=f"(d[2]), "=f"(d[3]), "=f"(d[4]), "=f"(d[5]), "=f"(d[6]), "=f"(d[7]), "=f"(d[8]), "=f"(d[9]), "=f"(d[10]), "=f"(d[11]), "=f"(d[12]), "=f"(d[13]), "=f"(d[14]), "=f"(d[15]), "=f"(d[16]), "=f"(d[17]), "=f"(d[18]), "=f"(d[19]), "=f"(d[20]), "=f"(d[21]), "=f"(d[22]), "=f"(d[23]), "=f"(d[24]), "=f"(d[25]), "=f"(d[26]), "=f"(d[27]), "=f"(d[28]), "=f"(d[29]), "=f"(d[30]), "=f"(d[31])
    : "r"(a0), "r"(a1), "r"(a2), "r"(a3), "l"(db));
}
template <int SD> __device__ __forceinline__ void wgmma_ss_n32_ta1_tb1(float (&d)[16], uint64_t da, uint64_t db) {
  if (SD) asm volatile("wgmma.mma_async.sync.aligned.m64n32k16.f32.bf16.bf16 {%0, %1, %2, %3, %4, %5, %6, %7, %8, %9, %10, %11, %12, %13, %14, %15}, %16, %17, 1, 1, 1, 1, 1;\n"
    : "+f"(d[0]), "+f"(d[1]), "+f"(d[2]), "+f"(d[3]), "+f"(d[4]), "+f"(d[5]), "+f"(d[6]), "+f"(d[7]), "+f"(d[8]), "+f"(d[9]), "+f"(d[10]), "+f"(d[11]), "+f"(d[12]), "+f"(d[13]), "+f"(d[14]), "+f"(d[15])
    : "l"(da), "l"(db));
  else asm volatile("wgmma.mma_async.sync.aligned.m64n32k16.f32.bf16.bf16 {%0, %1, %2, %3, %4, %5, %6, %7, %8, %9, %10, %11, %12, %13, %14, %15}, %16, %17, 0, 1, 1, 1, 1;\n"
    : "=f"(d[0]), "=f"(d[1]), "=f"(d[2]), "=f"(d[3]), "=f"(d[4]), "=f"(d[5]), "=f"(d[6]), "=f"(d[7]), "=f"(d[8]), "=f"(d[9]), "=f"(d[10]), "=f"(d[11]), "=f"(d[12]), "=f"(d[13]), "=f"(d[14]), "=f"(d[15])
    : "l"(da), "l"(db));
}
template <int SD> __device__ __forceinline__ void wgmma_ss_n32_ta0_tb1(float (&d)[16], uint64_t da, uint64_t db) {
  if (SD) asm volatile("wgmma.mma_async.sync.aligned.m64n32k16.f32.bf16.bf16 {%0, %1, %2, %3, %4, %5, %6, %7, %8, %9, %10, %11, %12, %13, %14, %15}, %16, %17, 1, 1, 1, 0, 1;\n"
    : "+f"(d[0]), "+f"(d[1]), "+f"(d[2]), "+f"(d[3]), "+f"(d[4]), "+f"(d[5]), "+f"(d[6]), "+f"(d[7]), "+f"(d[8]), "+f"(d[9]), "+f"(d[10]), "+f"(d[11]), "+f"(d[12]), "+f"(d[13]), "+f"(d[14]), "+f"(d[15])
    : "l"(da), "l"(db));
  else asm volatile("wgmma.mma_async.sync.aligned.m64n32k16.f32.bf16.bf16 {%0, %1, %2, %3, %4, %5, %6, %7, %8, %9, %10, %11, %12, %13, %14, %15}, %16, %17, 0, 1, 1, 0, 1;\n"
    : "=f"(d[0]), "=f"(d[1]), "=f"(d[2]), "=f"(d[3]), "=f"(d[4]), "=f"(d[5]), "=f"(d[6]), "=f"(d[7]), "=f"(d[8]), "=f"(d[9]), "=f"(d[10]), "=f"(d[11]), "=f"(d[12]), "=f"(d[13]), "=f"(d[14]), "=f"(d[15])
    : "l"(da), "l"(db));
}
template <int SD> __device__ __forceinline__ void wgmma_rs_n64_tb0(float (&d)[32], uint32_t a0, uint32_t a1, uint32_t a2, uint32_t a3, uint64_t db) {
  if (SD) asm volatile("wgmma.mma_async.sync.aligned.m64n64k16.f32.bf16.bf16 {%0, %1, %2, %3, %4, %5, %6, %7, %8, %9, %10, %11, %12, %13, %14, %15, %16, %17, %18, %19, %20, %21, %22, %23, %24, %25, %26, %27, %28, %29, %30, %31}, {%32, %33, %34, %35}, %36, 1, 1, 1, 0;\n"
    : "+f"(d[0]), "+f"(d[1]), "+f"(d[2]), "+f"(d[3]), "+f"(d[4]), "+f"(d[5]), "+f"(d[6]), "+f"(d[7]), "+f"(d[8]), "+f"(d[9]), "+f"(d[10]), "+f"(d[11]), "+f"(d[12]), "+f"(d[13]), "+f"(d[14]), "+f"(d[15]), "+f"(d[16]), "+f"(d[17]), "+f"(d[18]), "+f"(d[19]), "+f"(d[20]), "+f"(d[21]), "+f"(d[22]), "+f"(d[23]), "+f"(d[24]), "+f"(d[25]), "+f"(d[26]), "+f"(d[27]), "+f"(d[28]), "+f"(d[29]), "+f"(d[30]), "+f"(d[31])
    : "r"(a0), "r"(a1), "r"(a2), "r"(a3), "l"(db));
  else asm volatile("wgmma.mma_async.sync.aligned.m64n64k16.f32.bf16.bf16 {%0, %1, %2, %3, %4, %5, %6, %7, %8, %9, %10, %11, %12, %13, %14, %15, %16, %17, %18, %19, %20, %21, %22, %23, %24, %25, %26, %27, %28, %29, %30, %31}, {%32, %33, %34, %35}, %36, 0, 1, 1, 0;\n"
    : "=f"(d[0]), "=f"(d[1]), "=f"(d[2]), "=f"(d[3]), "=f"(d[4]), "=f"(d[5]), "=f"(d[6]), "=f"(d[7]), "=f"(d[8]), "=f"(d[9]), "=f"(d[10]), "=f"(d[11]), "=f"(d[12]), "=f"(d[13]), "=f"(d[14]), "=f"(d[15]), "=f"(d[16]), "=f"(d[17]), "=f"(d[18]), "=f"(d[19]), "=f"(d[20]), "=f"(d[21]), "=f"(d[22]), "=f"(d[23]), "=f"(d[24]), "=f"(d[25]), "=f"(d[26]), "=f"(d[27]), "=f"(d[28]), "=f"(d[29]), "=f"(d[30]), "=f"(d[31])
    : "r"(a0), "r"(a1), "r"(a2), "r"(a3), "l"(db));
}
template <int SD> __device__ __forceinline__ void wgmma_rs_n32_tb1(float (&d)[16], uint32_t a0, uint32_t a1, uint32_t a2, uint32_t a3, uint64_t db) {
  if (SD) asm volatile("wgmma.mma_async.sync.aligned.m64n32k16.f32.bf16.bf16 {%0, %1, %2, %3, %4, %5, %6, %7, %8, %9, %10, %11, %12, %13, %14, %15}, {%16, %17, %18, %19}, %20, 1, 1, 1, 1;\n"
    : "+f"(d[0]), "+f"(d[1]), "+f"(d[2]), "+f"(d[3]), "+f"(d[4]), "+f"(d[5]), "+f"(d[6]), "+f"(d[7]), "+f"(d[8]), "+f"(d[9]), "+f"(d[10]), "+f"(d[11]), "+f"(d[12]), "+f"(d[13]), "+f"(d[14]), "+f"(d[15])
    : "r"(a0), "r"(a1), "r"(a2), "r"(a3), "l"(db));
  else asm volatile("wgmma.mma_async.sync.aligned.m64n32k16.f32.bf16.bf16 {%0, %1, %2, %3, %4, %5, %6, %7, %8, %9, %10, %11, %12, %13, %14, %15}, {%16, %17, %18, %19}, %20, 0, 1, 1, 1;\n"
    : "=f"(d[0]), "=f"(d[1]), "=f"(d[2]), "=f"(d[3]), "=f"(d[4]), "=f"(d[5]), "=f"(d[6]), "=f"(d[7]), "=f"(d[8]), "=f"(d[9]), "=f"(d[10]), "=f"(d[11]), "=f"(d[12]), "=f"(d[13]), "=f"(d[14]), "=f"(d[15])
    : "r"(a0), "r"(a1), "r"(a2), "r"(a3), "l"(db));
}

__device__ __forceinline__ uint32_t sw64_off(int row, int d) { return row * 64 + ((((d >> 3) ^ (row >> 1)) & 3) << 4) + (d & 7) * 2; }

__device__ __forceinline__ uint32_t exp2_pair_fma(float t0, float t1, uint32_t c_half, uint32_t c_3) {
  uint32_t y0, y;
  asm("prmt.b32 %0, %1, %2, 0x6521;" : "=r"(y0) : "r"(__float_as_uint(t0)), "r"(__float_as_uint(t1)));
  uint32_t h = lop_and_or(y0, 0x007F007Fu, c_half);
  uint32_t e = lop_and_or(y0, 0xFF80FF80u, c_3);
  asm("fma.rn.bf16x2 %0, %1, %2, %3;" : "=r"(y) : "r"(y0), "r"(h), "r"(e));
  return y;
}

__device__ __forceinline__ void feature_map(float (&v)[16], uint32_t (&ph)[16], int lq) {
  const float L2E = 1.4426950408889634f;
  const bool tail_ok = lq < 2;
  float mx[2], mn[2], b[16], sa[2], sn[2];
#pragma unroll
  for (int r = 0; r < 2; r++) {
    const int o = 2 * r;
    if (!tail_ok) { v[o + 12] = v[o]; v[o + 13] = v[o]; }
    mx[r] = fmaxf(fmaxf(fmaxf(v[o], v[o + 1]), fmaxf(v[o + 4], v[o + 5])), fmaxf(fmaxf(v[o + 8], v[o + 9]), fmaxf(v[o + 12], v[o + 13])));
    mn[r] = fminf(fminf(fminf(v[o], v[o + 1]), fminf(v[o + 4], v[o + 5])), fminf(fminf(v[o + 8], v[o + 9]), fminf(v[o + 12], v[o + 13])));
  }
#pragma unroll
  for (int o = 1; o <= 2; o <<= 1)
#pragma unroll
    for (int r = 0; r < 2; r++) { mx[r] = fmaxf(mx[r], __shfl_xor_sync(~0u, mx[r], o)); mn[r] = fminf(mn[r], __shfl_xor_sync(~0u, mn[r], o)); }
#pragma unroll
  for (int r = 0; r < 2; r++) {
    const int o = 2 * r;
    const float cx = -mx[r] * L2E, cn = mn[r] * L2E;
#pragma unroll
    for (int i = 0; i < 8; i++) {
      const int k = o + 4 * (i >> 1) + (i & 1);
      b[k] = ex2f(fmaf(v[k], -L2E, cn));
      v[k] = ex2f(fmaf(v[k], L2E, cx));
    }
    if (!tail_ok) { v[o + 12] = v[o + 13] = b[o + 12] = b[o + 13] = 0.f; }
    sa[r] = ((v[o] + v[o + 1]) + (v[o + 4] + v[o + 5])) + ((v[o + 8] + v[o + 9]) + (v[o + 12] + v[o + 13]));
    sn[r] = ((b[o] + b[o + 1]) + (b[o + 4] + b[o + 5])) + ((b[o + 8] + b[o + 9]) + (b[o + 12] + b[o + 13]));
  }
#pragma unroll
  for (int o = 1; o <= 2; o <<= 1)
#pragma unroll
    for (int r = 0; r < 2; r++) { sa[r] += __shfl_xor_sync(~0u, sa[r], o); sn[r] += __shfl_xor_sync(~0u, sn[r], o); }
#pragma unroll
  for (int r = 0; r < 2; r++) {
    const float ra = rcpf(sa[r]), rb = rcpf(sn[r]);
#pragma unroll
    for (int jj = 0; jj < 4; jj++) {
      ph[jj * 2 + r] = pack_bf16(v[2 * r + 4 * jj] * ra, v[2 * r + 4 * jj + 1] * ra);
      ph[(4 + jj) * 2 + r] = pack_bf16(b[2 * r + 4 * jj] * rb, b[2 * r + 4 * jj + 1] * rb);
    }
  }
}

__device__ __forceinline__ void store_heads(uint32_t base, const uint32_t (&a)[14], uint32_t pad0, uint32_t pad1, int row0, int lq) {
  const uint32_t rb = base + row0 * 64 + (((row0 >> 1) & 3) << 4);
  const uint32_t b0 = rb + lq * 4;
  const uint32_t b1 = (rb + 8192 + ((lq * 4 + 8) & 15)) ^ ((lq >> 1) << 4);
#pragma unroll
  for (int j = 0; j < 7; j++) {
    uint32_t ad;
    if (j < 3) ad = b0 ^ (j << 4);
    else if (j == 3) ad = (lq < 2) ? (b0 ^ 48u) : (b1 ^ 16u);
    else ad = (lq < 2) ? (b1 ^ ((j - 4) << 4)) : ((b1 ^ 16u) ^ ((j - 3) << 4));
    sts32(ad, a[2 * j]);
    sts32(ad + 512, a[2 * j + 1]);
  }
  sts64((rb ^ 48u) + 8 + (lq & 1) * 8192 + (lq >> 1) * 512, pad0, pad1);
}

struct Params {
  const __nv_bfloat16* w_phi;
  const __nv_bfloat16* wk;
  const __nv_bfloat16* wv;
  const __nv_bfloat16* gate_w;
  __nv_bfloat16* out;
};

__global__ void __launch_bounds__(NTHREADS, 1)
fused_kernel(const __grid_constant__ CUtensorMap tm_x, const __grid_constant__ CUtensorMap tm_wqkv,
             const __grid_constant__ CUtensorMap tm_wq, const __grid_constant__ CUtensorMap tm_woa,
             const __grid_constant__ CUtensorMap tm_wob, const Params prm) {
  extern __shared__ uint8_t smem_raw[];
  uint32_t sb = (smem_u32(smem_raw) + 1023u) & ~1023u;
  uint8_t* sgen = smem_raw + (sb - smem_u32(smem_raw));
  asm volatile("mov.u32 %0, %0;" : "+r"(sb));
  const int tid = threadIdx.x, lane = tid & 31;
  const int warp = __shfl_sync(~0u, tid >> 5, 0), wg = warp >> 2;
  const int pt = blockIdx.x >> 3, hp = blockIdx.x & 7;
  const uint32_t bars = sb + OFF_BAR;
  auto BAR = [&](int i) { return bars + 8u * i; };
  const unsigned epoch = g_epoch & 1;

  if (tid == 0) { PROF_MARK(0); PROF_CLK(30); PROF2(15); }
  auto load_proj = [&](int c, int g) {
    mbar_expect_tx(BAR(B_FULL + g), 49152);
    tma_2d(sb + OFF_X + c * 16384, &tm_x, c * 64, pt * 128, BAR(B_FULL + g));
    tma_2d(sb + OFF_RING + g * 32768, &tm_wq, hp * 56, c * 64, BAR(B_FULL + g));
#pragma unroll 1
    for (int j = 0; j < 3; j++) tma_2d(sb + OFF_RING + g * 32768 + 8192 + j * 8192, &tm_wqkv, j * DM + hp * 56, c * 64, BAR(B_FULL + g));
  };
  if (warp == 16) {
    if (elect_one()) {
      mbar_init(BAR(B_FULL), 1); mbar_init(BAR(B_FULL + 1), 1); mbar_init(BAR(B_FULL + 2), 1);
      fence_async_smem();
      load_proj(0, 0);
    }
    __syncwarp();
    asm volatile("bar.arrive 0, %0;" ::"n"(NTHREADS) : "memory");
  } else {
    if (elect_one()) {
      const int i = warp + 3 - (warp > 16);
      if (i < B_N) {
        int cnt = i < B_WO || i > B_SIG || i == B_X1FREE ? 16 : 1;
        if (i == B_BUILD) cnt = 512;
        if (i == B_SIG || i == B_SIG + 1 || i == B_QSQ) cnt = 8;
        if (i == B_KVR) cnt = 2;
        mbar_init(BAR(i), cnt);
        fence_async_smem();
      }
    }
    bar_sync(0, NTHREADS);
  }
  if (tid == 0) PROF2(14);

  if (wg == 4) {
    asm volatile("setmaxnreg.dec.sync.aligned.u32 32;");
    if (warp == 16) {
      if (elect_one()) { PROF2(18); load_proj(1, 1); load_proj(2, 2); PROF2(19); }
      __syncwarp();
      bar_sync(3, 64);
      if (elect_one()) {
        int g = 0, nkv = 8;
        uint32_t par = 0;
#pragma unroll 1
        for (int n = 3; n < 14 + nkv; n++) {
          if (n == 7) { PROF_MARK(20); cnt_wait(C_KV, NCTA); PROF_MARK(21); fence_async_all(); }
          if (n == 15) {
            mbar_wait(BAR(B_SLOW), 0);
            if (*(volatile int*)(sgen + OFF_RED)) nkv = 26;
          }
          const int j = n - 7 - nkv;
          if (j == 0 || j == 3) {
            PROF3(j ? 11 : 8);
            cnt_wait((j ? C_OB : C_OA) + pt, 8);
            PROF3(j ? 12 : 9);
            PROF_MARK(26);
            fence_async_all();
          }
          mbar_wait(BAR(B_EMPTY + g), par);
          if (n < 7) load_proj(n, g);
          else {
            mbar_expect_tx(BAR(B_FULL + g), 32768);
            bulk_g2s(sb + OFF_RING + g * 32768, j < 0 ? g_kv_img + ((n - 7) & 7) * 32768 : g_o_img + (size_t)(pt * 7 + j) * 32768, 32768,
                     BAR(B_FULL + g));
          }
          if (++g == 3) { g = 0; par ^= 1; }
        }
        if (atomicAdd(&g_cnt[C_DONE * 32], 1u) == NCTA - 1) {
#pragma unroll 1
          for (int i = 0; i < C_N; i++) g_cnt[i * 32] = 0;
          g_epoch = epoch ^ 1;
        }
      }
    } else {
      if (warp == 18) {
        if (elect_one()) {
#pragma unroll 1
          for (int i = 0; i < 4; i++) {
            mbar_wait(BAR(B_SIG + i), 0);
            PROF3(2 * i);
            if (i == 1) {
#pragma unroll 1
              for (int j = 0; j < 4; j++)
                asm volatile("cp.reduce.async.bulk.global.shared::cta.bulk_group.add.f32 [%0], [%1], 8192;"
                             ::"l"(g_kvacc[epoch] + hp * 4096 + (j >> 1) * 2048), "r"(sb + OFF_PHIK + j * 8192) : "memory");
              asm volatile("cp.async.bulk.commit_group;\ncp.async.bulk.wait_group 0;" ::: "memory");
            }
            cnt_arrive(i == 0 ? C_KV : i == 1 ? C_PART : (i == 2 ? C_OA : C_OB) + pt);
            PROF3(2 * i + 1);
            if (i == 1 || i == 2) {
              if (i == 2) mbar_wait(BAR(B_X1FREE), 0);
              mbar_expect_tx(BAR(B_WO + i - 1), 57344);
#pragma unroll 1
              for (int c = 0; c < 7; c++)
                tma_2d(sb + OFF_WO + (i - 1) * 57344 + c * 8192, i == 1 ? &tm_woa : &tm_wob, hp * 56, c * 64, BAR(B_WO + i - 1));
            }
          }
        }
      } else if (warp == 19) {
        if (lane == 0) {
          mbar_wait(BAR(B_SIG + 0), 0);
          cnt_wait(C_KV, NCTA);
        }
        __syncwarp();
        float ksq = 0.f, vsq = 0.f;
#pragma unroll
        for (int sl = 0; sl < 4; sl++) {
          float4 a = ldcg_f4(g_ksq + sl * 128 + lane * 4), b = ldcg_f4(g_vsq + sl * 128 + lane * 4);
          float m = fmaxf(fmaxf(a.x, a.y), fmaxf(a.z, a.w));
          m = __uint_as_float(__reduce_max_sync(~0u, __float_as_uint(m)));
          ksq += m;
          vsq = fmaxf(vsq, fmaxf(fmaxf(b.x, b.y), fmaxf(b.z, b.w)));
        }
        mbar_wait(BAR(B_QSQ), 0);
        const float4 qa4 = ((const float4*)(sgen + OFF_QSQ))[lane], qb4 = ((const float4*)(sgen + OFF_QSQ))[32 + lane];
        const float qmax = fmaxf(fmaxf(fmaxf(qa4.x, qa4.y), fmaxf(qa4.z, qa4.w)), fmaxf(fmaxf(qb4.x, qb4.y), fmaxf(qb4.z, qb4.w)));
        const bool slow = __any_sync(~0u, !(qmax * ksq <= 98.f * 98.f) || !(vsq <= 2.0e8f));
        if (lane == 0) {
          *(volatile int*)(sgen + OFF_RED) = slow;
          mbar_arrive(BAR(B_SLOW), 1);
        }
      } else {
        float4* z = (float4*)(g_kvacc[epoch ^ 1] + blockIdx.x * 256) + lane;
        z[0] = make_float4(0.f, 0.f, 0.f, 0.f);
        z[32] = make_float4(0.f, 0.f, 0.f, 0.f);
        bar_sync(3, 64);
        if (lane == 0) {
          mbar_wait(BAR(B_SIG + 0), 0);
          cnt_wait(C_KV, NCTA);
        }
        __syncwarp();
        ((float4*)(sgen + OFF_GATE))[lane] = ldcg_f4(g_gate + pt * 128 + lane * 4);
      }
      if (warp != 18) {
        if (lane == 0) {
          mbar_wait(BAR(B_SIG + 1), 0);
          cnt_wait(C_PART, NCTA);
          PROF_MARK(23);
        }
        __syncwarp();
        const int e = warp == 19;
        const float* src = g_kvacc[epoch] + hp * 4096 + e * 2048 + lane * 8;
#pragma unroll 1
        for (int i = 0; i < 8; i += 2) {
          const float4 a = ldcg_f4(src + i * 256), b = ldcg_f4(src + i * 256 + 4), c = ldcg_f4(src + i * 256 + 256), d = ldcg_f4(src + i * 256 + 260);
          const uint32_t ad = sb + OFF_KVR + e * 4096 + sw64_off(i * 8 + (lane >> 2), (lane & 3) * 8);
          sts128(ad, make_uint4(pack_bf16(a.x, a.y), pack_bf16(a.z, a.w), pack_bf16(b.x, b.y), pack_bf16(b.z, b.w)));
          sts128(ad + 512, make_uint4(pack_bf16(c.x, c.y), pack_bf16(c.z, c.w), pack_bf16(d.x, d.y), pack_bf16(d.z, d.w)));
        }
        fence_async_smem();
        __syncwarp();
        if (lane == 0) mbar_arrive(BAR(B_KVR), 1);
        PROF_MARK(24);
      }
    }
  } else {
    asm volatile("setmaxnreg.inc.sync.aligned.u32 112;");
    const int mh = wg & 1, nh = wg >> 1, wq = warp & 3;
    const int lq = lane & 3;
    const int rowl = wq * 16 + (lane >> 2);
    const int row0 = mh * 64 + rowl;
    int slot = 0, prev = 0;
    uint32_t par = 0;
    {
      float acc0[28], acc1[28], accs[4];
      const uint64_t dR = make_desc(sb + OFF_RING + nh * 16384, 1024, 1024, 1);
      const int lr = wq * 16 + (lane & 7) + ((lane >> 3) & 1) * 8;
      const uint32_t xa = sb + OFF_X + mh * 8192 + lr * 128 + (((lane >> 4) ^ (lr & 7)) << 4);
#pragma unroll
      for (int i = 0; i < 28; i++) acc0[i] = acc1[i] = 0.f;
#pragma unroll
      for (int i = 0; i < 4; i++) accs[i] = 0.f;
      const uint64_t dSlc = make_desc(sb + OFF_SLC, 128, 128, 0);
      uint32_t a[16], an[16];
      if (tid == 0) PROF2(16);
      mbar_wait(BAR(B_FULL), 0);
      if (tid == 0) PROF2(17);
#pragma unroll
      for (int ks = 0; ks < 4; ks++) ldsm4(an + 4 * ks, xa ^ (ks << 5));
#pragma unroll 1
      for (int c = 0; c < 10; c++) {
        if (c >= 7 && nh == 0) break;
#pragma unroll
        for (int i = 0; i < 16; i++) a[i] = an[i];
        const uint64_t dB = dR + slot * 2048;
        if (nh == 1 && c == 3) { mbar_wait(BAR(B_BUILD), 0); fence_async_smem(); }
        wg_fence();
        if (c < 7) {
#pragma unroll
          for (int ks = 0; ks < 4; ks++) {
            wgmma_rs_n56_tb1<1>(acc0, a[4 * ks], a[4 * ks + 1], a[4 * ks + 2], a[4 * ks + 3], dB + ks * 128);
            wgmma_rs_n56_tb1<1>(acc1, a[4 * ks], a[4 * ks + 1], a[4 * ks + 2], a[4 * ks + 3], dB + 512 + ks * 128);
          }
        }
        if (nh == 1 && c >= 3) {
#pragma unroll
          for (int ks = 0; ks < 4; ks++)
            wgmma_rs_n8_tb1<1>(accs, a[4 * ks], a[4 * ks + 1], a[4 * ks + 2], a[4 * ks + 3], dSlc + (c < 7 ? c : c - 7) * 64 + ks * 16);
        }
        wg_commit();
        if (c == 0) {
          {
            const int k = tid >> 3, cn = tid & 7, e = k >= DH;
            const bool data = k < 56 && (cn >> 2) == e;
            const uint32_t ad = sb + OFF_WBD + k * 128 + ((cn ^ (k & 7)) << 4);
            const __nv_bfloat16* wsrc = prm.w_phi + (2 * hp * DH + k) * DH + (cn & 3) * 8;
            if (data) cp_async8(ad, wsrc); else sts64(ad, 0u, 0u);
            if (data && (cn & 3) != 3) cp_async8(ad + 8, wsrc + 4); else sts64(ad + 8, 0u, 0u);
            if (tid < DM) {
              const __nv_bfloat16* src = (hp < 4 ? prm.wk : prm.wv) + tid * DH + (hp & 3) * 8;
              cp_async8(sb + OFF_SLC + tid * 16, src);
              if ((hp & 3) != 3) cp_async8(sb + OFF_SLC + tid * 16 + 8, src + 4);
              else sts64(sb + OFF_SLC + tid * 16 + 8, hp == 3 ? (uint32_t)((const unsigned short*)prm.gate_w)[tid] : 0u, 0u);
            }
          }
          asm volatile("cp.async.mbarrier.arrive.noinc.shared::cta.b64 [%0];" ::"r"(BAR(B_BUILD)) : "memory");
        }
        const int cur = slot;
        if (c < 7 && ++slot == 3) { slot = 0; par ^= 1; }
        if (c >= 6) {
#pragma unroll
          for (int ks = 0; ks < 4; ks++) ldsm4(an + 4 * ks, (xa + (c - 6) * 16384) ^ (ks << 5));
        } else {
          if (tid == 0 || tid == 256) PROF2(c * 2 + (tid >> 3));
          mbar_wait(BAR(B_FULL + slot), par);
          if (tid == 0 || tid == 256) PROF2(c * 2 + 1 + (tid >> 3));
#pragma unroll
          for (int ks = 0; ks < 4; ks++) ldsm4(an + 4 * ks, (xa + (c + 1) * 16384) ^ (ks << 5));
        }
        wg_wait<0>();
#pragma unroll
        for (int i = 0; i < 16; i++) asm volatile("" : "+r"(a[i])::"memory");
        if (lane == 0 && c < 7) mbar_arrive(BAR(B_EMPTY + cur), 1);
      }
      fence_regs(acc0); fence_regs(acc1); fence_regs(accs);
      if (tid == 0) PROF_MARK(2);
      if (tid == 256) PROF_MARK(3);
      if (nh == 0) {
        float sq[4] = {0.f, 0.f, 0.f, 0.f};
#pragma unroll
        for (int i = 0; i < 28; i++) acc0[i] *= 0.18898223650461362f * 1.4426950408889634f;
#pragma unroll
        for (int j = 0; j < 7; j++) {
#pragma unroll
          for (int rr = 0; rr < 2; rr++) {
            const float s2 = acc0[4 * j + 2 * rr] * acc0[4 * j + 2 * rr] + acc0[4 * j + 2 * rr + 1] * acc0[4 * j + 2 * rr + 1];
            if (j < 3) sq[rr] += s2;
            else if (j > 3) sq[2 + rr] += s2;
            else { sq[rr] += (lq < 2) ? s2 : 0.f; sq[2 + rr] += (lq < 2) ? 0.f : s2; }
          }
        }
#pragma unroll
        for (int i = 0; i < 4; i++) sq[i] = quad_sum(sq[i]);
        const float mine = lq == 0 ? sq[0] : lq == 1 ? sq[1] : lq == 2 ? sq[2] : sq[3];
        ((float*)(sgen + OFF_QSQ))[(mh + (lq & 2)) * 64 + rowl + 8 * (lq & 1)] = mine <= 3.0e38f ? mine : __int_as_float(0x7f800000);
        __syncwarp();
        if (lane == 0) mbar_arrive(BAR(B_QSQ), 1);
      } else {
        const int sl = hp & 3;
        const bool isk = hp < 4, real = (sl < 3) || (lq < 2);
        const int pos = pt * 128 + row0, kr = pos & 63;
        uint8_t* dst = g_kv_img + (pos >> 6) * 8192 + (isk ? 0 : 4096) + sw64_off(kr, sl * 8 + 2 * lq);
        const uint32_t pat = isk ? POLY_PAT >> (kr >> 3) : 0u;
        float mxv = 0.f;
#pragma unroll
        for (int rr = 0; rr < 2; rr++) {
          const float v0 = accs[2 * rr], v1 = accs[2 * rr + 1];
          const bool poly = (pat >> rr) & 1;
          const float sc = poly ? 2.f : 1.f;
          const float s2 = quad_sum(real ? v0 * v0 + v1 * v1 : 0.f);
          mxv = fmaxf(mxv, s2 <= 3.0e38f ? s2 : __int_as_float(0x7f800000));
          const uint32_t padv = lq == 2 ? (poly ? 0x443F4000u : 0x00003F80u) : (poly ? 0x3AB03F4Du : 0u);
          *(uint32_t*)(dst + rr * 512) = real ? pack_bf16(sc * v0, sc * v1) : padv;
          if (hp == 3 && lq == 2) g_gate[pos + 8 * rr] = rcpf(1.f + ex2f(-1.4426950408889634f * v0));
        }
        mxv = __uint_as_float(__reduce_max_sync(~0u, __float_as_uint(mxv)));
        if (lane == 0) (isk ? g_ksq : g_vsq)[sl * 128 + pt * 8 + mh * 4 + wq] = mxv;
        __syncwarp();
        if (lane == 0) mbar_arrive(BAR(B_SIG + 0), 1);
      }
      if (tid == 0) PROF_MARK(4);
      if (tid == 256) PROF_MARK(5);
      uint32_t h[14];
      float pp[32];
      {
#pragma unroll
        for (int i = 0; i < 14; i++) {
          const uint32_t u0 = pack_bf16(acc0[2 * i], acc0[2 * i + 1]), u1 = pack_bf16(acc1[2 * i], acc1[2 * i + 1]);
          h[i] = nh ? u1 : u0;
          a[i] = nh ? u0 : u1;
        }
        a[14] = a[0] ^ 0x80008000u;
        a[15] = a[1] ^ 0x80008000u;
        const uint64_t dW = make_desc(sb + OFF_WBD, 1024, 1024, 1);
        if (nh == 0) { mbar_wait(BAR(B_BUILD), 0); fence_async_smem(); }
        wg_fence();
        wgmma_rs_n64_tb1<0>(pp, a[0], a[1], a[2], a[3], dW);
#pragma unroll
        for (int ks = 1; ks < 4; ks++) wgmma_rs_n64_tb1<1>(pp, a[4 * ks], a[4 * ks + 1], a[4 * ks + 2], a[4 * ks + 3], dW + ks * 128);
        wg_commit();
        bar_sync(1, 512);
        if (tid == 0) PROF_MARK(6);
        store_heads(sb + (nh ? OFF_VA : OFF_QP), h, nh ? 0x00003F80u : 0x3F800000u, nh ? 0u : 0x3F803F80u, row0, lq);
        wg_wait<0>();
        fence_regs(pp);
      }
      float v[16];
#pragma unroll
      for (int i = 0; i < 16; i++) v[i] = pp[i];
      uint32_t rb = sb + (nh ? OFF_PHIK : OFF_PHIQ) + row0 * 128 + lq * 4 + ((rowl & 7) << 4);
#pragma unroll 1
      for (int e = 0; e < 2; e++) {
        uint32_t ph[16];
        feature_map(v, ph, lq);
#pragma unroll
        for (int ch = 0; ch < 8; ch++) { sts32(rb ^ (ch << 4), ph[2 * ch]); sts32((rb ^ (ch << 4)) + 1024, ph[2 * ch + 1]); }
        rb += 16384;
#pragma unroll
        for (int i = 0; i < 16; i++) v[i] = pp[16 + i];
      }
      fence_async_smem();
      bar_sync(1, 512);
      if (tid == 0) PROF_MARK(7);
      if (nh == 1) {
        float kv0[16], kv1[16];
        const uint64_t dP = make_desc(sb + OFF_PHIK + mh * 8192, 1024, 1024, 1);
        const uint64_t dV = make_desc(sb + OFF_VA + mh * 4096, 512, 512, 2);
        wg_fence();
        wgmma_ss_n32_ta1_tb1<0>(kv0, dP, dV);
        wgmma_ss_n32_ta1_tb1<0>(kv1, dP + 1024, dV + 512);
#pragma unroll
        for (int ks = 1; ks < 4; ks++) {
          wgmma_ss_n32_ta1_tb1<1>(kv0, dP + ks * 128, dV + ks * 64);
          wgmma_ss_n32_ta1_tb1<1>(kv1, dP + 1024 + ks * 128, dV + 512 + ks * 64);
        }
        wg_commit();
        wg_wait<0>();
        fence_regs(kv0); fence_regs(kv1);
        bar_sync(4 + wg, 128);
        const uint32_t sa = sb + OFF_PHIK + mh * 8192 + rowl * 128 + lq * 8;
#pragma unroll
        for (int j = 0; j < 8; j++) {
          sts64(sa + 32 * (j >> 1) + 1024 * (j & 1), __float_as_uint(kv0[2 * j]), __float_as_uint(kv0[2 * j + 1]));
          sts64(sa + 16384 + 32 * (j >> 1) + 1024 * (j & 1), __float_as_uint(kv1[2 * j]), __float_as_uint(kv1[2 * j + 1]));
        }
        fence_async_smem();
        __syncwarp();
        if (lane == 0) mbar_arrive(BAR(B_SIG + 1), 1);
        if (tid == 256) PROF_MARK(28);
      }
    }
    {
      const uint64_t dK = make_desc(sb + OFF_RING, 512, 512, 2);
      const uint64_t dhi = dK & 0xffffffff00000000ull;
      const uint32_t dlo0 = (uint32_t)dK;
      uint32_t ok = 0, q[8];
      float o[16];
#pragma unroll
      for (int i = 0; i < 16; i++) o[i] = 0.f;
      {
        const int r = mh * 64 + wq * 16 + (lane & 7) + ((lane >> 3) & 1) * 8;
        ldsm4(q, sb + OFF_QP + nh * 8192 + sw64_off(r, (lane >> 4) * 8));
        ldsm4(q + 4, sb + OFF_QP + nh * 8192 + sw64_off(r, 16 + (lane >> 4) * 8));
      }
      if (tid == 0) PROF_MARK(10);
      const int qb = QB_AT;
#pragma unroll 1
      for (int it = 0; it <= 8; it++) {
        uint32_t p[16];
        if ((tid & 127) == 0) PROF4(wg * 32 + it * 3);
        if (it == qb || it == 8) {
          float t[16];
          wg_wait<0>();
          fence_regs(o);
          if (it < 8) {
            if (tid == 0) PROF_MARK(11);
            mbar_wait(BAR(B_KVR), 0);
            const uint64_t dR = make_desc(sb + OFF_KVR + nh * 4096, 512, 512, 2);
            const uint64_t dP = make_desc(sb + OFF_PHIQ + nh * 16384 + mh * 8192, 1024, 1024, 1);
            wg_fence();
            wgmma_ss_n32_ta0_tb1<0>(t, dP, dR);
#pragma unroll
            for (int ks = 1; ks < 4; ks++) wgmma_ss_n32_ta0_tb1<1>(t, dP + ks * 2, dR + ks * 64);
            wg_commit();
            wg_wait<0>();
            fence_regs(t);
            if (lane == 0) mbar_arrive(BAR(B_X1FREE), 1);
          } else {
            if (lane == 0) mbar_arrive(BAR(B_EMPTY + prev), 1);
            if (tid == 0) PROF_MARK(13);
            mbar_wait(BAR(B_SLOW), 0);
            if (__builtin_expect(__any_sync(~0u, *(volatile int*)(sgen + OFF_RED)), 0)) {
              uint32_t qz[8];
#pragma unroll
              for (int i = 0; i < 8; i++) qz[i] = (i >= 6 && lq >= 2) ? 0u : q[i];
              float m0 = -3.0e38f, m1 = -3.0e38f, o2[16];
              int sl2 = slot;
              uint32_t par2 = par;
#pragma unroll 1
              for (int j64 = 0; j64 < 32; j64++) {
                float s[32];
                mbar_wait(BAR(B_FULL + sl2), par2);
                const uint32_t lo = dlo0 + sl2 * 2048 + (j64 & 3) * 512;
                wg_fence();
                wgmma_rs_n64_tb0<0>(s, qz[0], qz[1], qz[2], qz[3], dhi | lo);
                wgmma_rs_n64_tb0<1>(s, qz[4], qz[5], qz[6], qz[7], dhi | (lo + 2));
                wg_commit();
                wg_wait<0>();
                fence_regs(s);
#pragma unroll
                for (int j = 0; j < 8; j++) {
                  const float sc = ((POLY_PAT >> j) & 1) ? 0.5f : 1.f;
                  m0 = fmaxf(m0, fmaxf(s[4 * j], s[4 * j + 1]) * sc);
                  m1 = fmaxf(m1, fmaxf(s[4 * j + 2], s[4 * j + 3]) * sc);
                }
                if ((j64 & 3) == 3) {
                  if (lane == 0) mbar_arrive(BAR(B_EMPTY + sl2), 1);
                  if (++sl2 == 3) { sl2 = 0; par2 ^= 1; }
                }
              }
              m0 = quad_max(m0); m1 = quad_max(m1);
#pragma unroll
              for (int i = 0; i < 16; i++) o2[i] = 0.f;
#pragma unroll 1
              for (int j64 = 0; j64 < 32; j64++) {
                float s[32];
                mbar_wait(BAR(B_FULL + sl2), par2);
                const uint32_t lo = dlo0 + sl2 * 2048 + (j64 & 3) * 512;
                wg_fence();
                wgmma_rs_n64_tb0<0>(s, qz[0], qz[1], qz[2], qz[3], dhi | lo);
                wgmma_rs_n64_tb0<1>(s, qz[4], qz[5], qz[6], qz[7], dhi | (lo + 2));
                wg_commit();
                wg_wait<0>();
                fence_regs(s);
                uint32_t ps[16];
#pragma unroll
                for (int j = 0; j < 8; j++) {
                  const float sc = ((POLY_PAT >> j) & 1) ? 0.5f : 1.f;
                  ps[2 * j] = pack_bf16(ex2f(fmaf(s[4 * j], sc, -m0)), ex2f(fmaf(s[4 * j + 1], sc, -m0)));
                  ps[2 * j + 1] = pack_bf16(ex2f(fmaf(s[4 * j + 2], sc, -m1)), ex2f(fmaf(s[4 * j + 3], sc, -m1)));
                }
                wg_fence();
#pragma unroll
                for (int ks = 0; ks < 4; ks++)
                  wgmma_rs_n32_tb1<1>(o2, ps[4 * ks], ps[4 * ks + 1], ps[4 * ks + 2], ps[4 * ks + 3], dhi | (lo + 256 + ks * 64));
                wg_commit();
                wg_wait<0>();
                fence_regs(o2);
                if ((j64 & 3) == 3) {
                  if (lane == 0) mbar_arrive(BAR(B_EMPTY + sl2), 1);
                  if (++sl2 == 3) { sl2 = 0; par2 ^= 1; }
                }
              }
#pragma unroll 1
              for (int j = 0; j < 2; j++) {
                mbar_wait(BAR(B_FULL + sl2), par2);
                __syncwarp();
                if (lane == 0) mbar_arrive(BAR(B_EMPTY + sl2), 1);
                if (++sl2 == 3) { sl2 = 0; par2 ^= 1; }
              }
#pragma unroll
              for (int i = 0; i < 16; i++) o[i] = o2[i];
            }
#pragma unroll
            for (int i = 0; i < 16; i++) t[i] = o[i];
          }
          const int br = it == 8;
          const float eps = br ? 0.f : 1e-6f;
          const float g0 = ((const float*)(sgen + OFF_GATE))[row0], g1 = ((const float*)(sgen + OFF_GATE))[row0 + 8];
          const float d0 = __shfl_sync(~0u, t[12], (lane & ~3) | 2), d1 = __shfl_sync(~0u, t[14], (lane & ~3) | 2);
          const float r0 = (br ? 1.f - g0 : g0) * rcpf(d0 + eps), r1 = (br ? 1.f - g1 : g1) * rcpf(d1 + eps);
          uint8_t* img = g_o_img + (size_t)((pt * 2 + br) * 14 + mh) * 8192 + rowl * 128;
          const int col0 = (2 * hp + nh) * DH + 2 * lq;
#pragma unroll
          for (int j = 0; j < 4; j++) {
            const int col = col0 + 8 * j;
            uint8_t* gp = img + (uint32_t)((col >> 6) * 16384 + ((((col >> 3) ^ rowl) & 7) << 4) + (col & 7) * 2);
            const uint32_t v0 = pack_bf16(t[4 * j] * r0, t[4 * j + 1] * r0), v1 = pack_bf16(t[4 * j + 2] * r1, t[4 * j + 3] * r1);
            if (j < 3 || lq < 2) { *(uint32_t*)gp = v0; *(uint32_t*)(gp + 1024) = v1; }
          }
          __syncwarp();
          if (lane == 0) mbar_arrive(BAR(B_SIG + 2 + br), 1);
          if (tid == 0) PROF_MARK(12 + 2 * br);
          if (br) break;
        }
        const uint32_t lo = dlo0 + slot * 2048;
        if ((tid & 127) == 0) PROF4(wg * 32 + it * 3 + 1);
        if (!ok) mbar_wait(BAR(B_FULL + slot), par);
        if ((tid & 127) == 0) PROF4(wg * 32 + it * 3 + 2);
        int nslot = slot + 1;
        uint32_t npar = par;
        if (nslot == 3) { nslot = 0; npar ^= 1; }
        {
          float s[32];
          wg_fence();
          wgmma_rs_n64_tb0<0>(s, q[0], q[1], q[2], q[3], dhi | lo);
          wgmma_rs_n64_tb0<1>(s, q[4], q[5], q[6], q[7], dhi | (lo + 2));
          wg_commit();
#pragma unroll
          for (int u = 0; u < 4; u++) {
            wg_wait<0>();
            fence_regs(s);
            if (u == 0 && lane == 0 && it > 0) mbar_arrive(BAR(B_EMPTY + prev), 1);
            if (u == 2) ok = mbar_test(BAR(B_FULL + nslot), npar);
#pragma unroll
            for (int j = 0; j < 8; j++) {
              if ((POLY_PAT >> j) & 1) {
                p[2 * j] = exp2_pair_fma(s[4 * j], s[4 * j + 1], 0x3F003F00u, 0x00030003u);
                p[2 * j + 1] = exp2_pair_fma(s[4 * j + 2], s[4 * j + 3], 0x3F003F00u, 0x00030003u);
              } else {
                p[2 * j] = pack_bf16(ex2f(s[4 * j]), ex2f(s[4 * j + 1]));
                p[2 * j + 1] = pack_bf16(ex2f(s[4 * j + 2]), ex2f(s[4 * j + 3]));
              }
            }
            wg_fence();
#pragma unroll
            for (int ks = 0; ks < 4; ks++)
              wgmma_rs_n32_tb1<1>(o, p[4 * ks], p[4 * ks + 1], p[4 * ks + 2], p[4 * ks + 3], dhi | (lo + u * 512 + 256 + ks * 64));
            if (u < 3) {
              wgmma_rs_n64_tb0<0>(s, q[0], q[1], q[2], q[3], dhi | (lo + (u + 1) * 512));
              wgmma_rs_n64_tb0<1>(s, q[4], q[5], q[6], q[7], dhi | (lo + (u + 1) * 512 + 2));
            }
            wg_commit();
          }
        }
        prev = slot; slot = nslot; par = npar;
      }
      wg_wait<0>();
    }
    if (nh == 1) return;
    {
      float acc0[28], acc1[28];
#pragma unroll
      for (int i = 0; i < 28; i++) acc0[i] = acc1[i] = 0.f;
      const uint64_t dS = make_desc(sb + OFF_WO, 1024, 1024, 1);
      const uint64_t dR = make_desc(sb + OFF_RING + mh * 8192, 1024, 1024, 1);
#pragma unroll 1
      for (int c = 0; c < 7; c++) {
        mbar_wait(BAR(B_WO + (c >= 3)), 0);
        mbar_wait(BAR(B_FULL + slot), par);
        const uint64_t dA = dR + slot * 2048, dB = dS + c * 1024;
        wg_fence();
#pragma unroll
        for (int ks = 0; ks < 4; ks++) {
          wgmma_ss_n56_ta0_tb1<1>(acc0, dA + ks * 2, dB + ks * 128);
          wgmma_ss_n56_ta0_tb1<1>(acc1, dA + 1024 + ks * 2, dB + 512 + ks * 128);
        }
        wg_commit();
        if (c < 4) {
          wg_wait<0>();
          if (lane == 0) mbar_arrive(BAR(B_EMPTY + slot), 2);
        }
        if (++slot == 3) { slot = 0; par ^= 1; }
      }
      wg_wait<0>();
      fence_regs(acc0); fence_regs(acc1);
      if (tid == 0) PROF_MARK(17);
      __nv_bfloat16* op = prm.out + (size_t)(pt * 128 + row0) * DM + hp * 56 + 2 * lq;
#pragma unroll
      for (int j = 0; j < 7; j++) {
        *(uint32_t*)(op + 8 * j) = pack_bf16(acc0[4 * j] + acc1[4 * j], acc0[4 * j + 1] + acc1[4 * j + 1]);
        *(uint32_t*)(op + 8 * DM + 8 * j) = pack_bf16(acc0[4 * j + 2] + acc1[4 * j + 2], acc0[4 * j + 3] + acc1[4 * j + 3]);
      }
      if (tid == 0) { PROF_MARK(18); PROF_CLK(31); }
    }
  }
}

typedef CUresult (*EncodeFn)(CUtensorMap*, CUtensorMapDataType, cuuint32_t, void*, const cuuint64_t*, const cuuint64_t*,
                             const cuuint32_t*, const cuuint32_t*, CUtensorMapInterleave, CUtensorMapSwizzle,
                             CUtensorMapL2promotion, CUtensorMapFloatOOBfill);

void make_map(EncodeFn enc, CUtensorMap* tm, const void* ptr, uint64_t cols, uint64_t rows, uint32_t box_rows) {
  cuuint64_t dims[2] = {cols, rows};
  cuuint64_t strides[1] = {cols * 2};
  cuuint32_t box[2] = {64, box_rows};
  cuuint32_t es[2] = {1, 1};
  enc(tm, CU_TENSOR_MAP_DATA_TYPE_BFLOAT16, 2, const_cast<void*>(ptr), dims, strides, box, es, CU_TENSOR_MAP_INTERLEAVE_NONE,
      CU_TENSOR_MAP_SWIZZLE_128B, CU_TENSOR_MAP_L2_PROMOTION_L2_128B, CU_TENSOR_MAP_FLOAT_OOB_FILL_NONE);
}

}

extern "C" void kernel_launch(void* const* d_in, const int* in_sizes, int n_in, void* d_out, int out_size) {
  (void)in_sizes; (void)n_in; (void)out_size;
  static EncodeFn enc = nullptr;
  if (!enc) {
    void* fn = nullptr;
    cudaDriverEntryPointQueryResult qr;
    cudaGetDriverEntryPoint("cuTensorMapEncodeTiled", &fn, cudaEnableDefault, &qr);
    enc = (EncodeFn)fn;
    cudaFuncSetAttribute(fused_kernel, cudaFuncAttributeMaxDynamicSharedMemorySize, SMEM_BYTES);
  }
  CUtensorMap tm_x, tm_wqkv, tm_wq, tm_woa, tm_wob;
  make_map(enc, &tm_x, d_in[0], DM, S_LEN, 128);
  make_map(enc, &tm_wqkv, d_in[1], 3 * DM, DM, 64);
  make_map(enc, &tm_wq, d_in[5], DM, DM, 64);
  make_map(enc, &tm_woa, d_in[3], DM, DM, 64);
  make_map(enc, &tm_wob, d_in[8], DM, DM, 64);
  Params prm;
  prm.w_phi = (const __nv_bfloat16*)d_in[2];
  prm.wk = (const __nv_bfloat16*)d_in[6];
  prm.wv = (const __nv_bfloat16*)d_in[7];
  prm.gate_w = (const __nv_bfloat16*)d_in[9];
  prm.out = (__nv_bfloat16*)d_out;
  fused_kernel<<<NCTA, NTHREADS, SMEM_BYTES>>>(tm_x, tm_wqkv, tm_wq, tm_woa, tm_wob, prm);
}
```

```cpp
#include <cuda_runtime.h>
#include <cuda_bf16.h>
#include <cuda.h>
#include <stdint.h>

namespace {

constexpr int S_LEN = 2048, DM = 448, DH = 28;
constexpr int NCTA = 128;
constexpr int NTHREADS = 640;
constexpr uint32_t POLY_PAT = 0x57;

#define QB_AT (4 + nh)

constexpr int OFF_X = 0;
constexpr int OFF_PHIK = 0;
constexpr int OFF_VA = 32768;
constexpr int OFF_PHIQ = 57344;
constexpr int OFF_KVR = 90112;
constexpr int OFF_QP = 98304;
constexpr int OFF_RAW = 81920;
constexpr int OFF_WO = 0;
constexpr int OFF_RING = 114688;
constexpr int OFF_WBD = 212992;
constexpr int OFF_SLC = 221184;
constexpr int OFF_QSQ = 228352;
constexpr int OFF_GATE = 229376;
constexpr int OFF_RED = 229888;
constexpr int OFF_BAR = 229952;
constexpr int SMEM_BYTES = 230400 + 1024;

constexpr int B_FULL = 0, B_EMPTY = 3, B_WO = 6  , B_KVR = 8, B_RAW = 9, B_X1FREE = 10, B_QSQ = 11, B_SLOW = 12,
              B_BUILD = 13, B_SIG = 14  , B_N = 18;

constexpr int C_KV = 0, C_PART = 1, C_DONE = 3, C_OA = 4, C_OB = 20, C_N = 36;

__device__ __align__(1024) uint8_t g_kv_img[32 * 8192];
__device__ __align__(16) float g_ksq[512];
__device__ __align__(16) float g_vsq[512];
__device__ __align__(16) float g_gate[S_LEN];
__device__ __align__(1024) float g_kvacc[2][16 * 64 * 32];
__device__ unsigned g_epoch;
__device__ __align__(1024) uint8_t g_o_img[2 * 16 * 14 * 8192];
__device__ unsigned g_cnt[C_N * 32];

#define PROF4(i) do { } while (0)
#define PROF3(i) do { } while (0)
#define PROF2(i) do { } while (0)
#define PROF_CLK(i) do { } while (0)
#define PROF_MARK(i) do { } while (0)
__device__ __forceinline__ uint32_t smem_u32(const void* p) { return (uint32_t)__cvta_generic_to_shared(p); }
__device__ __forceinline__ void mbar_init(uint32_t a, int cnt) {
  asm volatile("mbarrier.init.shared::cta.b64 [%0], %1;" ::"r"(a), "r"(cnt) : "memory");
}
__device__ __forceinline__ void mbar_expect_tx(uint32_t a, uint32_t bytes) {
  asm volatile("mbarrier.arrive.expect_tx.shared::cta.b64 _, [%0], %1;" ::"r"(a), "r"(bytes) : "memory");
}
__device__ __forceinline__ void mbar_arrive(uint32_t a, uint32_t cnt) {
  asm volatile("mbarrier.arrive.shared::cta.b64 _, [%0], %1;" ::"r"(a), "r"(cnt) : "memory");
}
__device__ __forceinline__ void mbar_wait(uint32_t a, uint32_t parity) {
  asm volatile(
      "{\n.reg .pred p;\n.reg .u32 c;\nmov.u32 c, 0;\n"
      "W_%=:\nmbarrier.try_wait.parity.shared::cta.b64 p, [%0], %1;\n"
      "add.u32 c, c, 1;\nsetp.lt.and.u32 p, c, 0x40000, !p;\n@p bra W_%=;\n}"
      ::"r"(a), "r"(parity) : "memory");
}
__device__ __forceinline__ uint32_t mbar_test(uint32_t a, uint32_t parity) {
  uint32_t ok;
  asm volatile("{\n.reg .pred p;\nmbarrier.test_wait.parity.shared::cta.b64 p, [%1], %2;\nselp.u32 %0, 1, 0, p;\n}"
               : "=r"(ok) : "r"(a), "r"(parity) : "memory");
  return ok;
}
__device__ __forceinline__ bool elect_one() {
  uint32_t r;
  asm volatile("{\n.reg .pred p;\nelect.sync _|p, 0xffffffff;\nselp.u32 %0, 1, 0, p;\n}" : "=r"(r));
  return r != 0;
}
__device__ __forceinline__ void tma_2d(uint32_t dst, const CUtensorMap* tm, int c0, int c1, uint32_t bar) {
  asm volatile("cp.async.bulk.tensor.2d.shared::cluster.global.mbarrier::complete_tx::bytes [%0], [%1, {%3, %4}], [%2];"
               ::"r"(dst), "l"(tm), "r"(bar), "r"(c0), "r"(c1) : "memory");
}
__device__ __forceinline__ void bulk_g2s(uint32_t dst, const void* src, uint32_t bytes, uint32_t bar) {
  asm volatile("cp.async.bulk.shared::cluster.global.mbarrier::complete_tx::bytes [%0], [%1], %2, [%3];"
               ::"r"(dst), "l"(src), "r"(bytes), "r"(bar) : "memory");
}
__device__ __forceinline__ void fence_async_smem() { asm volatile("fence.proxy.async.shared::cta;" ::: "memory"); }
__device__ __forceinline__ void fence_async_all() { asm volatile("fence.proxy.async.global;" ::: "memory"); }

__device__ __forceinline__ void bar_sync(int id, int n) { asm volatile("bar.sync %0, %1;" ::"r"(id), "r"(n) : "memory"); }
__device__ __forceinline__ void cnt_arrive(int idx) {
  asm volatile("red.release.gpu.global.add.u32 [%0], 1;" ::"l"(&g_cnt[idx * 32]) : "memory");
}
__device__ __forceinline__ void cnt_wait(int idx, unsigned target) {
  unsigned v, n = 0;
#pragma unroll 1
  while (true) {
    asm volatile("ld.acquire.gpu.global.u32 %0, [%1];" : "=r"(v) : "l"(&g_cnt[idx * 32]) : "memory");
    if (v >= target || ++n >= (1u << 18)) break;
    __nanosleep(32);
  }
}
__device__ __forceinline__ void wg_fence() { asm volatile("wgmma.fence.sync.aligned;" ::: "memory"); }
__device__ __forceinline__ void wg_commit() { asm volatile("wgmma.commit_group.sync.aligned;" ::: "memory"); }
template <int N> __device__ __forceinline__ void wg_wait() { asm volatile("wgmma.wait_group.sync.aligned %0;" ::"n"(N) : "memory"); }
template <int N> __device__ __forceinline__ void fence_regs(float (&d)[N]) {
#pragma unroll
  for (int i = 0; i < N; i++) asm volatile("" : "+f"(d[i])::"memory");
}
__device__ __forceinline__ uint64_t make_desc(uint32_t saddr, uint32_t lbo, uint32_t sbo, uint32_t swz) {
  return (uint64_t)((saddr & 0x3FFFF) >> 4) | ((uint64_t)(lbo >> 4) << 16) | ((uint64_t)(sbo >> 4) << 32) | ((uint64_t)swz << 62);
}
__device__ __forceinline__ float ex2f(float x) { float y; asm("ex2.approx.ftz.f32 %0, %1;" : "=f"(y) : "f"(x)); return y; }
__device__ __forceinline__ float rcpf(float x) { float y; asm("rcp.approx.ftz.f32 %0, %1;" : "=f"(y) : "f"(x)); return y; }
__device__ __forceinline__ uint32_t pack_bf16(float lo, float hi) {
  uint32_t r; asm("cvt.rn.bf16x2.f32 %0, %1, %2;" : "=r"(r) : "f"(hi), "f"(lo)); return r;
}
__device__ __forceinline__ uint32_t lop_and_or(uint32_t a, uint32_t m, uint32_t c) {
  uint32_t r; asm("lop3.b32 %0, %1, %2, %3, 0xEA;" : "=r"(r) : "r"(a), "r"(m), "r"(c)); return r;
}
__device__ __forceinline__ void sts32(uint32_t a, uint32_t v) { asm volatile("st.shared.b32 [%0], %1;" ::"r"(a), "r"(v) : "memory"); }
__device__ __forceinline__ void sts64(uint32_t a, uint32_t v0, uint32_t v1) { asm volatile("st.shared.v2.b32 [%0], {%1, %2};" ::"r"(a), "r"(v0), "r"(v1) : "memory"); }
__device__ __forceinline__ void sts128(uint32_t a, uint4 v) {
  asm volatile("st.shared.v4.b32 [%0], {%1, %2, %3, %4};" ::"r"(a), "r"(v.x), "r"(v.y), "r"(v.z), "r"(v.w) : "memory");
}
__device__ __forceinline__ float4 ldcg_f4(const float* p) {
  float4 v; asm volatile("ld.global.cg.v4.f32 {%0, %1, %2, %3}, [%4];" : "=f"(v.x), "=f"(v.y), "=f"(v.z), "=f"(v.w) : "l"(p) : "memory"); return v;
}
__device__ __forceinline__ void ldsm4(uint32_t* r, uint32_t a) {
  asm volatile("ldmatrix.sync.aligned.m8n8.x4.shared.b16 {%0, %1, %2, %3}, [%4];"
               : "=r"(r[0]), "=r"(r[1]), "=r"(r[2]), "=r"(r[3]) : "r"(a) : "memory");
}
__device__ __forceinline__ float quad_sum(float v) { v += __shfl_xor_sync(~0u, v, 1); v += __shfl_xor_sync(~0u, v, 2); return v; }
__device__ __forceinline__ float quad_max(float v) { v = fmaxf(v, __shfl_xor_sync(~0u, v, 1)); v = fmaxf(v, __shfl_xor_sync(~0u, v, 2)); return v; }

template <int SD> __device__ __forceinline__ void wgmma_ss_n56_ta0_tb1(float (&d)[28], uint64_t da, uint64_t db) {
  if (SD) asm volatile("wgmma.mma_async.sync.aligned.m64n56k16.f32.bf16.bf16 {%0, %1, %2, %3, %4, %5, %6, %7, %8, %9, %10, %11, %12, %13, %14, %15, %16, %17, %18, %19, %20, %21, %22, %23, %24, %25, %26, %27}, %28, %29, 1, 1, 1, 0, 1;\n"
    : "+f"(d[0]), "+f"(d[1]), "+f"(d[2]), "+f"(d[3]), "+f"(d[4]), "+f"(d[5]), "+f"(d[6]), "+f"(d[7]), "+f"(d[8]), "+f"(d[9]), "+f"(d[10]), "+f"(d[11]), "+f"(d[12]), "+f"(d[13]), "+f"(d[14]), "+f"(d[15]), "+f"(d[16]), "+f"(d[17]), "+f"(d[18]), "+f"(d[19]), "+f"(d[20]), "+f"(d[21]), "+f"(d[22]), "+f"(d[23]), "+f"(d[24]), "+f"(d[25]), "+f"(d[26]), "+f"(d[27])
    : "l"(da), "l"(db));
  else asm volatile("wgmma.mma_async.sync.aligned.m64n56k16.f32.bf16.bf16 {%0, %1, %2, %3, %4, %5, %6, %7, %8, %9, %10, %11, %12, %13, %14, %15, %16, %17, %18, %19, %20, %21, %22, %23, %24, %25, %26, %27}, %28, %29, 0, 1, 1, 0, 1;\n"
    : "=f"(d[0]), "=f"(d[1]), "=f"(d[2]), "=f"(d[3]), "=f"(d[4]), "=f"(d[5]), "=f"(d[6]), "=f"(d[7]), "=f"(d[8]), "=f"(d[9]), "=f"(d[10]), "=f"(d[11]), "=f"(d[12]), "=f"(d[13]), "=f"(d[14]), "=f"(d[15]), "=f"(d[16]), "=f"(d[17]), "=f"(d[18]), "=f"(d[19]), "=f"(d[20]), "=f"(d[21]), "=f"(d[22]), "=f"(d[23]), "=f"(d[24]), "=f"(d[25]), "=f"(d[26]), "=f"(d[27])
    : "l"(da), "l"(db));
}
template <int SD> __device__ __forceinline__ void wgmma_rs_n56_tb1(float (&d)[28], uint32_t a0, uint32_t a1, uint32_t a2, uint32_t a3, uint64_t db) {
  if (SD) asm volatile("wgmma.mma_async.sync.aligned.m64n56k16.f32.bf16.bf16 {%0, %1, %2, %3, %4, %5, %6, %7, %8, %9, %10, %11, %12, %13, %14, %15, %16, %17, %18, %19, %20, %21, %22, %23, %24, %25, %26, %27}, {%28, %29, %30, %31}, %32, 1, 1, 1, 1;\n"
    : "+f"(d[0]), "+f"(d[1]), "+f"(d[2]), "+f"(d[3]), "+f"(d[4]), "+f"(d[5]), "+f"(d[6]), "+f"(d[7]), "+f"(d[8]), "+f"(d[9]), "+f"(d[10]), "+f"(d[11]), "+f"(d[12]), "+f"(d[13]), "+f"(d[14]), "+f"(d[15]), "+f"(d[16]), "+f"(d[17]), "+f"(d[18]), "+f"(d[19]), "+f"(d[20]), "+f"(d[21]), "+f"(d[22]), "+f"(d[23]), "+f"(d[24]), "+f"(d[25]), "+f"(d[26]), "+f"(d[27])
    : "r"(a0), "r"(a1), "r"(a2), "r"(a3), "l"(db));
  else asm volatile("wgmma.mma_async.sync.aligned.m64n56k16.f32.bf16.bf16 {%0, %1, %2, %3, %4, %5, %6, %7, %8, %9, %10, %11, %12, %13, %14, %15, %16, %17, %18, %19, %20, %21, %22, %23, %24, %25, %26, %27}, {%28, %29, %30, %31}, %32, 0, 1, 1, 1;\n"
    : "=f"(d[0]), "=f"(d[1]), "=f"(d[2]), "=f"(d[3]), "=f"(d[4]), "=f"(d[5]), "=f"(d[6]), "=f"(d[7]), "=f"(d[8]), "=f"(d[9]), "=f"(d[10]), "=f"(d[11]), "=f"(d[12]), "=f"(d[13]), "=f"(d[14]), "=f"(d[15]), "=f"(d[16]), "=f"(d[17]), "=f"(d[18]), "=f"(d[19]), "=f"(d[20]), "=f"(d[21]), "=f"(d[22]), "=f"(d[23]), "=f"(d[24]), "=f"(d[25]), "=f"(d[26]), "=f"(d[27])
    : "r"(a0), "r"(a1), "r"(a2), "r"(a3), "l"(db));
}
template <int SD> __device__ __forceinline__ void wgmma_rs_n8_tb1(float (&d)[4], uint32_t a0, uint32_t a1, uint32_t a2, uint32_t a3, uint64_t db) {
  if (SD) asm volatile("wgmma.mma_async.sync.aligned.m64n8k16.f32.bf16.bf16 {%0, %1, %2, %3}, {%4, %5, %6, %7}, %8, 1, 1, 1, 1;\n"
    : "+f"(d[0]), "+f"(d[1]), "+f"(d[2]), "+f"(d[3])
    : "r"(a0), "r"(a1), "r"(a2), "r"(a3), "l"(db));
  else asm volatile("wgmma.mma_async.sync.aligned.m64n8k16.f32.bf16.bf16 {%0, %1, %2, %3}, {%4, %5, %6, %7}, %8, 0, 1, 1, 1;\n"
    : "=f"(d[0]), "=f"(d[1]), "=f"(d[2]), "=f"(d[3])
    : "r"(a0), "r"(a1), "r"(a2), "r"(a3), "l"(db));
}
template <int SD> __device__ __forceinline__ void wgmma_rs_n64_tb1(float (&d)[32], uint32_t a0, uint32_t a1, uint32_t a2, uint32_t a3, uint64_t db) {
  if (SD) asm volatile("wgmma.mma_async.sync.aligned.m64n64k16.f32.bf16.bf16 {%0, %1, %2, %3, %4, %5, %6, %7, %8, %9, %10, %11, %12, %13, %14, %15, %16, %17, %18, %19, %20, %21, %22, %23, %24, %25, %26, %27, %28, %29, %30, %31}, {%32, %33, %34, %35}, %36, 1, 1, 1, 1;\n"
    : "+f"(d[0]), "+f"(d[1]), "+f"(d[2]), "+f"(d[3]), "+f"(d[4]), "+f"(d[5]), "+f"(d[6]), "+f"(d[7]), "+f"(d[8]), "+f"(d[9]), "+f"(d[10]), "+f"(d[11]), "+f"(d[12]), "+f"(d[13]), "+f"(d[14]), "+f"(d[15]), "+f"(d[16]), "+f"(d[17]), "+f"(d[18]), "+f"(d[19]), "+f"(d[20]), "+f"(d[21]), "+f"(d[22]), "+f"(d[23]), "+f"(d[24]), "+f"(d[25]), "+f"(d[26]), "+f"(d[27]), "+f"(d[28]), "+f"(d[29]), "+f"(d[30]), "+f"(d[31])
    : "r"(a0), "r"(a1), "r"(a2), "r"(a3), "l"(db));
  else asm volatile("wgmma.mma_async.sync.aligned.m64n64k16.f32.bf16.bf16 {%0, %1, %2, %3, %4, %5, %6, %7, %8, %9, %10, %11, %12, %13, %14, %15, %16, %17, %18, %19, %20, %21, %22, %23, %24, %25, %26, %27, %28, %29, %30, %31}, {%32, %33, %34, %35}, %36, 0, 1, 1, 1;\n"
    : "=f"(d[0]), "=f"(d[1]), "=f"(d[2]), "=f"(d[3]), "=f"(d[4]), "=f"(d[5]), "=f"(d[6]), "=f"(d[7]), "=f"(d[8]), "=f"(d[9]), "=f"(d[10]), "=f"(d[11]), "=f"(d[12]), "=f"(d[13]), "=f"(d[14]), "=f"(d[15]), "=f"(d[16]), "=f"(d[17]), "=f"(d[18]), "=f"(d[19]), "=f"(d[20]), "=f"(d[21]), "=f"(d[22]), "=f"(d[23]), "=f"(d[24]), "=f"(d[25]), "=f"(d[26]), "=f"(d[27]), "=f"(d[28]), "=f"(d[29]), "=f"(d[30]), "=f"(d[31])
    : "r"(a0), "r"(a1), "r"(a2), "r"(a3), "l"(db));
}
template <int SD> __device__ __forceinline__ void wgmma_ss_n32_ta1_tb1(float (&d)[16], uint64_t da, uint64_t db) {
  if (SD) asm volatile("wgmma.mma_async.sync.aligned.m64n32k16.f32.bf16.bf16 {%0, %1, %2, %3, %4, %5, %6, %7, %8, %9, %10, %11, %12, %13, %14, %15}, %16, %17, 1, 1, 1, 1, 1;\n"
    : "+f"(d[0]), "+f"(d[1]), "+f"(d[2]), "+f"(d[3]), "+f"(d[4]), "+f"(d[5]), "+f"(d[6]), "+f"(d[7]), "+f"(d[8]), "+f"(d[9]), "+f"(d[10]), "+f"(d[11]), "+f"(d[12]), "+f"(d[13]), "+f"(d[14]), "+f"(d[15])
    : "l"(da), "l"(db));
  else asm volatile("wgmma.mma_async.sync.aligned.m64n32k16.f32.bf16.bf16 {%0, %1, %2, %3, %4, %5, %6, %7, %8, %9, %10, %11, %12, %13, %14, %15}, %16, %17, 0, 1, 1, 1, 1;\n"
    : "=f"(d[0]), "=f"(d[1]), "=f"(d[2]), "=f"(d[3]), "=f"(d[4]), "=f"(d[5]), "=f"(d[6]), "=f"(d[7]), "=f"(d[8]), "=f"(d[9]), "=f"(d[10]), "=f"(d[11]), "=f"(d[12]), "=f"(d[13]), "=f"(d[14]), "=f"(d[15])
    : "l"(da), "l"(db));
}
template <int SD> __device__ __forceinline__ void wgmma_ss_n32_ta0_tb1(float (&d)[16], uint64_t da, uint64_t db) {
  if (SD) asm volatile("wgmma.mma_async.sync.aligned.m64n32k16.f32.bf16.bf16 {%0, %1, %2, %3, %4, %5, %6, %7, %8, %9, %10, %11, %12, %13, %14, %15}, %16, %17, 1, 1, 1, 0, 1;\n"
    : "+f"(d[0]), "+f"(d[1]), "+f"(d[2]), "+f"(d[3]), "+f"(d[4]), "+f"(d[5]), "+f"(d[6]), "+f"(d[7]), "+f"(d[8]), "+f"(d[9]), "+f"(d[10]), "+f"(d[11]), "+f"(d[12]), "+f"(d[13]), "+f"(d[14]), "+f"(d[15])
    : "l"(da), "l"(db));
  else asm volatile("wgmma.mma_async.sync.aligned.m64n32k16.f32.bf16.bf16 {%0, %1, %2, %3, %4, %5, %6, %7, %8, %9, %10, %11, %12, %13, %14, %15}, %16, %17, 0, 1, 1, 0, 1;\n"
    : "=f"(d[0]), "=f"(d[1]), "=f"(d[2]), "=f"(d[3]), "=f"(d[4]), "=f"(d[5]), "=f"(d[6]), "=f"(d[7]), "=f"(d[8]), "=f"(d[9]), "=f"(d[10]), "=f"(d[11]), "=f"(d[12]), "=f"(d[13]), "=f"(d[14]), "=f"(d[15])
    : "l"(da), "l"(db));
}
template <int SD> __device__ __forceinline__ void wgmma_rs_n64_tb0(float (&d)[32], uint32_t a0, uint32_t a1, uint32_t a2, uint32_t a3, uint64_t db) {
  if (SD) asm volatile("wgmma.mma_async.sync.aligned.m64n64k16.f32.bf16.bf16 {%0, %1, %2, %3, %4, %5, %6, %7, %8, %9, %10, %11, %12, %13, %14, %15, %16, %17, %18, %19, %20, %21, %22, %23, %24, %25, %26, %27, %28, %29, %30, %31}, {%32, %33, %34, %35}, %36, 1, 1, 1, 0;\n"
    : "+f"(d[0]), "+f"(d[1]), "+f"(d[2]), "+f"(d[3]), "+f"(d[4]), "+f"(d[5]), "+f"(d[6]), "+f"(d[7]), "+f"(d[8]), "+f"(d[9]), "+f"(d[10]), "+f"(d[11]), "+f"(d[12]), "+f"(d[13]), "+f"(d[14]), "+f"(d[15]), "+f"(d[16]), "+f"(d[17]), "+f"(d[18]), "+f"(d[19]), "+f"(d[20]), "+f"(d[21]), "+f"(d[22]), "+f"(d[23]), "+f"(d[24]), "+f"(d[25]), "+f"(d[26]), "+f"(d[27]), "+f"(d[28]), "+f"(d[29]), "+f"(d[30]), "+f"(d[31])
    : "r"(a0), "r"(a1), "r"(a2), "r"(a3), "l"(db));
  else asm volatile("wgmma.mma_async.sync.aligned.m64n64k16.f32.bf16.bf16 {%0, %1, %2, %3, %4, %5, %6, %7, %8, %9, %10, %11, %12, %13, %14, %15, %16, %17, %18, %19, %20, %21, %22, %23, %24, %25, %26, %27, %28, %29, %30, %31}, {%32, %33, %34, %35}, %36, 0, 1, 1, 0;\n"
    : "=f"(d[0]), "=f"(d[1]), "=f"(d[2]), "=f"(d[3]), "=f"(d[4]), "=f"(d[5]), "=f"(d[6]), "=f"(d[7]), "=f"(d[8]), "=f"(d[9]), "=f"(d[10]), "=f"(d[11]), "=f"(d[12]), "=f"(d[13]), "=f"(d[14]), "=f"(d[15]), "=f"(d[16]), "=f"(d[17]), "=f"(d[18]), "=f"(d[19]), "=f"(d[20]), "=f"(d[21]), "=f"(d[22]), "=f"(d[23]), "=f"(d[24]), "=f"(d[25]), "=f"(d[26]), "=f"(d[27]), "=f"(d[28]), "=f"(d[29]), "=f"(d[30]), "=f"(d[31])
    : "r"(a0), "r"(a1), "r"(a2), "r"(a3), "l"(db));
}
template <int SD> __device__ __forceinline__ void wgmma_rs_n32_tb1(float (&d)[16], uint32_t a0, uint32_t a1, uint32_t a2, uint32_t a3, uint64_t db) {
  if (SD) asm volatile("wgmma.mma_async.sync.aligned.m64n32k16.f32.bf16.bf16 {%0, %1, %2, %3, %4, %5, %6, %7, %8, %9, %10, %11, %12, %13, %14, %15}, {%16, %17, %18, %19}, %20, 1, 1, 1, 1;\n"
    : "+f"(d[0]), "+f"(d[1]), "+f"(d[2]), "+f"(d[3]), "+f"(d[4]), "+f"(d[5]), "+f"(d[6]), "+f"(d[7]), "+f"(d[8]), "+f"(d[9]), "+f"(d[10]), "+f"(d[11]), "+f"(d[12]), "+f"(d[13]), "+f"(d[14]), "+f"(d[15])
    : "r"(a0), "r"(a1), "r"(a2), "r"(a3), "l"(db));
  else asm volatile("wgmma.mma_async.sync.aligned.m64n32k16.f32.bf16.bf16 {%0, %1, %2, %3, %4, %5, %6, %7, %8, %9, %10, %11, %12, %13, %14, %15}, {%16, %17, %18, %19}, %20, 0, 1, 1, 1;\n"
    : "=f"(d[0]), "=f"(d[1]), "=f"(d[2]), "=f"(d[3]), "=f"(d[4]), "=f"(d[5]), "=f"(d[6]), "=f"(d[7]), "=f"(d[8]), "=f"(d[9]), "=f"(d[10]), "=f"(d[11]), "=f"(d[12]), "=f"(d[13]), "=f"(d[14]), "=f"(d[15])
    : "r"(a0), "r"(a1), "r"(a2), "r"(a3), "l"(db));
}

__device__ __forceinline__ uint32_t sw64_off(int row, int d) { return row * 64 + ((((d >> 3) ^ (row >> 1)) & 3) << 4) + (d & 7) * 2; }

__device__ __forceinline__ uint32_t exp2_pair_fma(float t0, float t1, uint32_t c_half, uint32_t c_3) {
  uint32_t y0, y;
  asm("prmt.b32 %0, %1, %2, 0x6521;" : "=r"(y0) : "r"(__float_as_uint(t0)), "r"(__float_as_uint(t1)));
  uint32_t h = lop_and_or(y0, 0x007F007Fu, c_half);
  uint32_t e = lop_and_or(y0, 0xFF80FF80u, c_3);
  asm("fma.rn.bf16x2 %0, %1, %2, %3;" : "=r"(y) : "r"(y0), "r"(h), "r"(e));
  return y;
}

__device__ __forceinline__ void feature_map(float (&v)[16], uint32_t (&ph)[16], int lq) {
  const float L2E = 1.4426950408889634f;
  const bool tail_ok = lq < 2;
  float mx[2], mn[2], b[16], sa[2], sn[2];
#pragma unroll
  for (int r = 0; r < 2; r++) {
    const int o = 2 * r;
    if (!tail_ok) { v[o + 12] = v[o]; v[o + 13] = v[o]; }
    mx[r] = fmaxf(fmaxf(fmaxf(v[o], v[o + 1]), fmaxf(v[o + 4], v[o + 5])), fmaxf(fmaxf(v[o + 8], v[o + 9]), fmaxf(v[o + 12], v[o + 13])));
    mn[r] = fminf(fminf(fminf(v[o], v[o + 1]), fminf(v[o + 4], v[o + 5])), fminf(fminf(v[o + 8], v[o + 9]), fminf(v[o + 12], v[o + 13])));
  }
#pragma unroll
  for (int o = 1; o <= 2; o <<= 1)
#pragma unroll
    for (int r = 0; r < 2; r++) { mx[r] = fmaxf(mx[r], __shfl_xor_sync(~0u, mx[r], o)); mn[r] = fminf(mn[r], __shfl_xor_sync(~0u, mn[r], o)); }
#pragma unroll
  for (int r = 0; r < 2; r++) {
    const int o = 2 * r;
    const float cx = -mx[r] * L2E, cn = mn[r] * L2E;
#pragma unroll
    for (int i = 0; i < 8; i++) {
      const int k = o + 4 * (i >> 1) + (i & 1);
      b[k] = ex2f(fmaf(v[k], -L2E, cn));
      v[k] = ex2f(fmaf(v[k], L2E, cx));
    }
    if (!tail_ok) { v[o + 12] = v[o + 13] = b[o + 12] = b[o + 13] = 0.f; }
    sa[r] = ((v[o] + v[o + 1]) + (v[o + 4] + v[o + 5])) + ((v[o + 8] + v[o + 9]) + (v[o + 12] + v[o + 13]));
    sn[r] = ((b[o] + b[o + 1]) + (b[o + 4] + b[o + 5])) + ((b[o + 8] + b[o + 9]) + (b[o + 12] + b[o + 13]));
  }
#pragma unroll
  for (int o = 1; o <= 2; o <<= 1)
#pragma unroll
    for (int r = 0; r < 2; r++) { sa[r] += __shfl_xor_sync(~0u, sa[r], o); sn[r] += __shfl_xor_sync(~0u, sn[r], o); }
#pragma unroll
  for (int r = 0; r < 2; r++) {
    const float ra = rcpf(sa[r]), rb = rcpf(sn[r]);
#pragma unroll
    for (int jj = 0; jj < 4; jj++) {
      ph[jj * 2 + r] = pack_bf16(v[2 * r + 4 * jj] * ra, v[2 * r + 4 * jj + 1] * ra);
      ph[(4 + jj) * 2 + r] = pack_bf16(b[2 * r + 4 * jj] * rb, b[2 * r + 4 * jj + 1] * rb);
    }
  }
}

__device__ __forceinline__ void store_heads(uint32_t base, const uint32_t (&a)[14], uint32_t pad0, uint32_t pad1, int row0, int lq) {
  const uint32_t rb = base + row0 * 64 + (((row0 >> 1) & 3) << 4);
  const uint32_t b0 = rb + lq * 4;
  const uint32_t b1 = (rb + 8192 + ((lq * 4 + 8) & 15)) ^ ((lq >> 1) << 4);
#pragma unroll
  for (int j = 0; j < 7; j++) {
    uint32_t ad;
    if (j < 3) ad = b0 ^ (j << 4);
    else if (j == 3) ad = (lq < 2) ? (b0 ^ 48u) : (b1 ^ 16u);
    else ad = (lq < 2) ? (b1 ^ ((j - 4) << 4)) : ((b1 ^ 16u) ^ ((j - 3) << 4));
    sts32(ad, a[2 * j]);
    sts32(ad + 512, a[2 * j + 1]);
  }
  sts64((rb ^ 48u) + 8 + (lq & 1) * 8192 + (lq >> 1) * 512, pad0, pad1);
}

struct Params {
  const __nv_bfloat16* w_phi;
  const __nv_bfloat16* wk;
  const __nv_bfloat16* wv;
  const __nv_bfloat16* gate_w;
  __nv_bfloat16* out;
};

__global__ void __launch_bounds__(NTHREADS, 1)
fused_kernel(const __grid_constant__ CUtensorMap tm_x, const __grid_constant__ CUtensorMap tm_wqkv,
             const __grid_constant__ CUtensorMap tm_wq, const __grid_constant__ CUtensorMap tm_woa,
             const __grid_constant__ CUtensorMap tm_wob, const Params prm) {
  extern __shared__ uint8_t smem_raw[];
  uint32_t sb = (smem_u32(smem_raw) + 1023u) & ~1023u;
  uint8_t* sgen = smem_raw + (sb - smem_u32(smem_raw));
  asm volatile("mov.u32 %0, %0;" : "+r"(sb));
  const int tid = threadIdx.x, lane = tid & 31;
  const int warp = __shfl_sync(~0u, tid >> 5, 0), wg = warp >> 2;
  const int pt = blockIdx.x >> 3, hp = blockIdx.x & 7;
  const uint32_t bars = sb + OFF_BAR;
  auto BAR = [&](int i) { return bars + 8u * i; };
  const unsigned epoch = g_epoch & 1;

  if (tid == 0) { PROF_MARK(0); PROF_CLK(30); PROF2(15); }
  auto load_proj = [&](int c, int g) {
    mbar_expect_tx(BAR(B_FULL + g), 49152);
    tma_2d(sb + OFF_X + c * 16384, &tm_x, c * 64, pt * 128, BAR(B_FULL + g));
    tma_2d(sb + OFF_RING + g * 32768, &tm_wq, hp * 56, c * 64, BAR(B_FULL + g));
#pragma unroll 1
    for (int j = 0; j < 3; j++) tma_2d(sb + OFF_RING + g * 32768 + 8192 + j * 8192, &tm_wqkv, j * DM + hp * 56, c * 64, BAR(B_FULL + g));
  };
  if (warp == 16) {
    if (elect_one()) {
      mbar_init(BAR(B_FULL), 1);
      fence_async_smem();
      load_proj(0, 0);
      mbar_init(BAR(B_RAW), 1); mbar_init(BAR(B_FULL + 1), 1); mbar_init(BAR(B_FULL + 2), 1);
      fence_async_smem();
    }
    __syncwarp();
    asm volatile("bar.arrive 0, %0;" ::"n"(NTHREADS) : "memory");
  } else {
    if (elect_one()) {
      const int i = warp + 3 - (warp > 16);
      if (i < B_N && i != B_RAW) {
        int cnt = i < B_WO || i > B_SIG || i == B_X1FREE ? 16 : 1;
        if (i == B_BUILD) cnt = 16;
        if (i == B_SIG || i == B_SIG + 1 || i == B_QSQ) cnt = 8;
        if (i == B_KVR) cnt = 2;
        mbar_init(BAR(i), cnt);
        fence_async_smem();
      }
    }
    bar_sync(0, NTHREADS);
  }
  if (tid == 0) PROF2(14);

  if (wg == 4) {
    asm volatile("setmaxnreg.dec.sync.aligned.u32 32;");
    if (warp == 16) {
      if (elect_one()) {
        mbar_expect_tx(BAR(B_RAW), 25088 + 3136 + 896);
        bulk_g2s(sb + OFF_RAW, hp < 4 ? prm.wk : prm.wv, 25088, BAR(B_RAW));
        bulk_g2s(sb + OFF_RAW + 25088, prm.w_phi + 2 * hp * DH * DH, 3136, BAR(B_RAW));
        bulk_g2s(sb + OFF_RAW + 28224, prm.gate_w, 896, BAR(B_RAW));
        load_proj(1, 1);
        load_proj(2, 2);
      }
      __syncwarp();
      bar_sync(3, 64);
      if (elect_one()) {
        int g = 0, nkv = 8;
        uint32_t par = 0;
#pragma unroll 1
        for (int n = 3; n < 14 + nkv; n++) {
          if (n == 7) { PROF_MARK(20); cnt_wait(C_KV, NCTA); PROF_MARK(21); fence_async_all(); }
          if (n == 15) {
            mbar_wait(BAR(B_SLOW), 0);
            if (*(volatile int*)(sgen + OFF_RED)) nkv = 26;
          }
          const int j = n - 7 - nkv;
          if (j == 0 || j == 3) {
            PROF3(j ? 11 : 8);
            cnt_wait((j ? C_OB : C_OA) + pt, 8);
            PROF3(j ? 12 : 9);
            PROF_MARK(26);
            fence_async_all();
          }
          mbar_wait(BAR(B_EMPTY + g), par);
          if (n == 5) mbar_wait(BAR(B_BUILD), 0);
          if (n < 7) load_proj(n, g);
          else {
            mbar_expect_tx(BAR(B_FULL + g), 32768);
            bulk_g2s(sb + OFF_RING + g * 32768, j < 0 ? g_kv_img + ((n - 7) & 7) * 32768 : g_o_img + (size_t)(pt * 7 + j) * 32768, 32768,
                     BAR(B_FULL + g));
          }
          if (++g == 3) { g = 0; par ^= 1; }
        }
        if (atomicAdd(&g_cnt[C_DONE * 32], 1u) == NCTA - 1) {
#pragma unroll 1
          for (int i = 0; i < C_N; i++) g_cnt[i * 32] = 0;
          g_epoch = epoch ^ 1;
        }
      }
    } else {
      if (warp == 18) {
        if (elect_one()) {
#pragma unroll 1
          for (int i = 0; i < 4; i++) {
            mbar_wait(BAR(B_SIG + i), 0);
            PROF3(2 * i);
            if (i == 1) {
#pragma unroll 1
              for (int j = 0; j < 4; j++)
                asm volatile("cp.reduce.async.bulk.global.shared::cta.bulk_group.add.f32 [%0], [%1], 8192;"
                             ::"l"(g_kvacc[epoch] + hp * 4096 + (j >> 1) * 2048), "r"(sb + OFF_PHIK + j * 8192) : "memory");
              asm volatile("cp.async.bulk.commit_group;\ncp.async.bulk.wait_group 0;" ::: "memory");
            }
            cnt_arrive(i == 0 ? C_KV : i == 1 ? C_PART : (i == 2 ? C_OA : C_OB) + pt);
            PROF3(2 * i + 1);
            if (i == 1 || i == 2) {
              if (i == 2) mbar_wait(BAR(B_X1FREE), 0);
              mbar_expect_tx(BAR(B_WO + i - 1), 57344);
#pragma unroll 1
              for (int c = 0; c < 7; c++)
                tma_2d(sb + OFF_WO + (i - 1) * 57344 + c * 8192, i == 1 ? &tm_woa : &tm_wob, hp * 56, c * 64, BAR(B_WO + i - 1));
            }
          }
        }
      } else if (warp == 19) {
        if (lane == 0) {
          mbar_wait(BAR(B_SIG + 0), 0);
          cnt_wait(C_KV, NCTA);
        }
        __syncwarp();
        float ksq = 0.f, vsq = 0.f;
#pragma unroll
        for (int sl = 0; sl < 4; sl++) {
          float4 a = ldcg_f4(g_ksq + sl * 128 + lane * 4), b = ldcg_f4(g_vsq + sl * 128 + lane * 4);
          float m = fmaxf(fmaxf(a.x, a.y), fmaxf(a.z, a.w));
          m = __uint_as_float(__reduce_max_sync(~0u, __float_as_uint(m)));
          ksq += m;
          vsq = fmaxf(vsq, fmaxf(fmaxf(b.x, b.y), fmaxf(b.z, b.w)));
        }
        mbar_wait(BAR(B_QSQ), 0);
        const float4 qa4 = ((const float4*)(sgen + OFF_QSQ))[lane], qb4 = ((const float4*)(sgen + OFF_QSQ))[32 + lane];
        const float qmax = fmaxf(fmaxf(fmaxf(qa4.x, qa4.y), fmaxf(qa4.z, qa4.w)), fmaxf(fmaxf(qb4.x, qb4.y), fmaxf(qb4.z, qb4.w)));
        const bool slow = __any_sync(~0u, !(qmax * ksq <= 98.f * 98.f) || !(vsq <= 2.0e8f));
        if (lane == 0) {
          *(volatile int*)(sgen + OFF_RED) = slow;
          mbar_arrive(BAR(B_SLOW), 1);
        }
      } else {
        float4* z = (float4*)(g_kvacc[epoch ^ 1] + blockIdx.x * 256) + lane;
        z[0] = make_float4(0.f, 0.f, 0.f, 0.f);
        z[32] = make_float4(0.f, 0.f, 0.f, 0.f);
        bar_sync(3, 64);
        if (lane == 0) {
          mbar_wait(BAR(B_SIG + 0), 0);
          cnt_wait(C_KV, NCTA);
        }
        __syncwarp();
        ((float4*)(sgen + OFF_GATE))[lane] = ldcg_f4(g_gate + pt * 128 + lane * 4);
      }
      if (warp != 18) {
        if (lane == 0) {
          mbar_wait(BAR(B_SIG + 1), 0);
          cnt_wait(C_PART, NCTA);
          PROF_MARK(23);
        }
        __syncwarp();
        const int e = warp == 19;
        const float* src = g_kvacc[epoch] + hp * 4096 + e * 2048 + lane * 8;
#pragma unroll 1
        for (int i = 0; i < 8; i += 2) {
          const float4 a = ldcg_f4(src + i * 256), b = ldcg_f4(src + i * 256 + 4), c = ldcg_f4(src + i * 256 + 256), d = ldcg_f4(src + i * 256 + 260);
          const uint32_t ad = sb + OFF_KVR + e * 4096 + sw64_off(i * 8 + (lane >> 2), (lane & 3) * 8);
          sts128(ad, make_uint4(pack_bf16(a.x, a.y), pack_bf16(a.z, a.w), pack_bf16(b.x, b.y), pack_bf16(b.z, b.w)));
          sts128(ad + 512, make_uint4(pack_bf16(c.x, c.y), pack_bf16(c.z, c.w), pack_bf16(d.x, d.y), pack_bf16(d.z, d.w)));
        }
        fence_async_smem();
        __syncwarp();
        if (lane == 0) mbar_arrive(BAR(B_KVR), 1);
        PROF_MARK(24);
      }
    }
  } else {
    asm volatile("setmaxnreg.inc.sync.aligned.u32 112;");
    const int mh = wg & 1, nh = wg >> 1, wq = warp & 3;
    const int lq = lane & 3;
    const int rowl = wq * 16 + (lane >> 2);
    const int row0 = mh * 64 + rowl;
    int slot = 0, prev = 0;
    uint32_t par = 0;
    {
      float acc0[28], acc1[28], accs[4];
      const uint64_t dR = make_desc(sb + OFF_RING + nh * 16384, 1024, 1024, 1);
      const int lr = wq * 16 + (lane & 7) + ((lane >> 3) & 1) * 8;
      const uint32_t xa = sb + OFF_X + mh * 8192 + lr * 128 + (((lane >> 4) ^ (lr & 7)) << 4);
#pragma unroll
      for (int i = 0; i < 28; i++) acc0[i] = acc1[i] = 0.f;
#pragma unroll
      for (int i = 0; i < 4; i++) accs[i] = 0.f;
      const uint64_t dSlc = make_desc(sb + OFF_SLC, 128, 128, 0);
      uint32_t a[16], an[16];
      if (tid == 0) PROF2(16);
      mbar_wait(BAR(B_FULL), 0);
      if (tid == 0) PROF2(17);
#pragma unroll
      for (int ks = 0; ks < 4; ks++) ldsm4(an + 4 * ks, xa ^ (ks << 5));
#pragma unroll 1
      for (int c = 0; c < 7; c++) {
#pragma unroll
        for (int i = 0; i < 16; i++) a[i] = an[i];
        const uint64_t dB = dR + slot * 2048;
        wg_fence();
#pragma unroll
        for (int ks = 0; ks < 4; ks++) {
          wgmma_rs_n56_tb1<1>(acc0, a[4 * ks], a[4 * ks + 1], a[4 * ks + 2], a[4 * ks + 3], dB + ks * 128);
          wgmma_rs_n56_tb1<1>(acc1, a[4 * ks], a[4 * ks + 1], a[4 * ks + 2], a[4 * ks + 3], dB + 512 + ks * 128);
        }
        if (nh == 1 && c > 0) {
#pragma unroll
          for (int ks = 0; ks < 4; ks++) wgmma_rs_n8_tb1<1>(accs, a[4 * ks], a[4 * ks + 1], a[4 * ks + 2], a[4 * ks + 3], dSlc + c * 64 + ks * 16);
        }
        wg_commit();
        if (c == 0) {
          mbar_wait(BAR(B_RAW), 0);
          const int k = tid >> 3, cn = tid & 7;
          const bool data = k < 56 && (cn >> 2) == (k >= DH);
          const uint2* wsrc = (const uint2*)(sgen + OFF_RAW + 25088 + k * 56 + (cn & 3) * 16);
          uint2 w0 = make_uint2(0u, 0u), w1 = w0;
          if (data) w0 = wsrc[0];
          if (data && (cn & 3) != 3) w1 = wsrc[1];
          sts128(sb + OFF_WBD + k * 128 + ((cn ^ (k & 7)) << 4), make_uint4(w0.x, w0.y, w1.x, w1.y));
          if (tid < DM) {
            const uint2* src = (const uint2*)(sgen + OFF_RAW + tid * 56 + (hp & 3) * 16);
            w0 = src[0];
            w1 = make_uint2(hp == 3 ? (uint32_t)((const unsigned short*)(sgen + OFF_RAW + 28224))[tid] : 0u, 0u);
            if ((hp & 3) != 3) w1 = src[1];
            sts128(sb + OFF_SLC + tid * 16, make_uint4(w0.x, w0.y, w1.x, w1.y));
          }
          fence_async_smem();
          __syncwarp();
          if (lane == 0) mbar_arrive(BAR(B_BUILD), 1);
        }
        const int cur = slot;
        if (++slot == 3) { slot = 0; par ^= 1; }
        if (c < 6) mbar_wait(BAR(B_FULL + slot), par);
#pragma unroll
        for (int ks = 0; ks < 4; ks++) ldsm4(an + 4 * ks, (xa + (c < 6 ? c + 1 : 0) * 16384) ^ (ks << 5));
        if (c == 0) mbar_wait(BAR(B_BUILD), 0);
        wg_wait<0>();
#pragma unroll
        for (int i = 0; i < 16; i++) asm volatile("" : "+r"(a[i])::"memory");
        if (lane == 0) mbar_arrive(BAR(B_EMPTY + cur), 1);
      }
      if (nh == 1) {
        wg_fence();
#pragma unroll
        for (int ks = 0; ks < 4; ks++) wgmma_rs_n8_tb1<1>(accs, an[4 * ks], an[4 * ks + 1], an[4 * ks + 2], an[4 * ks + 3], dSlc + ks * 16);
        wg_commit();
      }
      wg_wait<0>();
      fence_regs(acc0); fence_regs(acc1); fence_regs(accs);
      if (tid == 0) PROF_MARK(2);
      if (tid == 256) PROF_MARK(3);
      if (nh == 0) {
        float sq[4] = {0.f, 0.f, 0.f, 0.f};
#pragma unroll
        for (int i = 0; i < 28; i++) acc0[i] *= 0.18898223650461362f * 1.4426950408889634f;
#pragma unroll
        for (int j = 0; j < 7; j++) {
#pragma unroll
          for (int rr = 0; rr < 2; rr++) {
            const float s2 = acc0[4 * j + 2 * rr] * acc0[4 * j + 2 * rr] + acc0[4 * j + 2 * rr + 1] * acc0[4 * j + 2 * rr + 1];
            if (j < 3) sq[rr] += s2;
            else if (j > 3) sq[2 + rr] += s2;
            else { sq[rr] += (lq < 2) ? s2 : 0.f; sq[2 + rr] += (lq < 2) ? 0.f : s2; }
          }
        }
#pragma unroll
        for (int i = 0; i < 4; i++) sq[i] = quad_sum(sq[i]);
        const float mine = lq == 0 ? sq[0] : lq == 1 ? sq[1] : lq == 2 ? sq[2] : sq[3];
        ((float*)(sgen + OFF_QSQ))[(mh + (lq & 2)) * 64 + rowl + 8 * (lq & 1)] = mine <= 3.0e38f ? mine : __int_as_float(0x7f800000);
        __syncwarp();
        if (lane == 0) mbar_arrive(BAR(B_QSQ), 1);
      } else {
        const int sl = hp & 3;
        const bool isk = hp < 4, real = (sl < 3) || (lq < 2);
        const int pos = pt * 128 + row0, kr = pos & 63;
        uint8_t* dst = g_kv_img + (pos >> 6) * 8192 + (isk ? 0 : 4096) + sw64_off(kr, sl * 8 + 2 * lq);
        const uint32_t pat = isk ? POLY_PAT >> (kr >> 3) : 0u;
        float mxv = 0.f;
#pragma unroll
        for (int rr = 0; rr < 2; rr++) {
          const float v0 = accs[2 * rr], v1 = accs[2 * rr + 1];
          const bool poly = (pat >> rr) & 1;
          const float sc = poly ? 2.f : 1.f;
          const float s2 = quad_sum(real ? v0 * v0 + v1 * v1 : 0.f);
          mxv = fmaxf(mxv, s2 <= 3.0e38f ? s2 : __int_as_float(0x7f800000));
          const uint32_t padv = lq == 2 ? (poly ? 0x443F4000u : 0x00003F80u) : (poly ? 0x3AB03F4Du : 0u);
          *(uint32_t*)(dst + rr * 512) = real ? pack_bf16(sc * v0, sc * v1) : padv;
          if (hp == 3 && lq == 2) g_gate[pos + 8 * rr] = rcpf(1.f + ex2f(-1.4426950408889634f * v0));
        }
        mxv = __uint_as_float(__reduce_max_sync(~0u, __float_as_uint(mxv)));
        if (lane == 0) (isk ? g_ksq : g_vsq)[sl * 128 + pt * 8 + mh * 4 + wq] = mxv;
        __syncwarp();
        if (lane == 0) mbar_arrive(BAR(B_SIG + 0), 1);
      }
      if (tid == 0) PROF_MARK(4);
      if (tid == 256) PROF_MARK(5);
      uint32_t h[14];
      float pp[32];
      {
#pragma unroll
        for (int i = 0; i < 14; i++) {
          const uint32_t u0 = pack_bf16(acc0[2 * i], acc0[2 * i + 1]), u1 = pack_bf16(acc1[2 * i], acc1[2 * i + 1]);
          h[i] = nh ? u1 : u0;
          a[i] = nh ? u0 : u1;
        }
        a[14] = a[0] ^ 0x80008000u;
        a[15] = a[1] ^ 0x80008000u;
        const uint64_t dW = make_desc(sb + OFF_WBD, 1024, 1024, 1);
        wg_fence();
        wgmma_rs_n64_tb1<0>(pp, a[0], a[1], a[2], a[3], dW);
#pragma unroll
        for (int ks = 1; ks < 4; ks++) wgmma_rs_n64_tb1<1>(pp, a[4 * ks], a[4 * ks + 1], a[4 * ks + 2], a[4 * ks + 3], dW + ks * 128);
        wg_commit();
        bar_sync(1, 512);
        if (tid == 0) PROF_MARK(6);
        store_heads(sb + (nh ? OFF_VA : OFF_QP), h, nh ? 0x00003F80u : 0x3F800000u, nh ? 0u : 0x3F803F80u, row0, lq);
        wg_wait<0>();
        fence_regs(pp);
      }
      float v[16];
#pragma unroll
      for (int i = 0; i < 16; i++) v[i] = pp[i];
      uint32_t rb = sb + (nh ? OFF_PHIK : OFF_PHIQ) + row0 * 128 + lq * 4 + ((rowl & 7) << 4);
#pragma unroll 1
      for (int e = 0; e < 2; e++) {
        uint32_t ph[16];
        feature_map(v, ph, lq);
#pragma unroll
        for (int ch = 0; ch < 8; ch++) { sts32(rb ^ (ch << 4), ph[2 * ch]); sts32((rb ^ (ch << 4)) + 1024, ph[2 * ch + 1]); }
        rb += 16384;
#pragma unroll
        for (int i = 0; i < 16; i++) v[i] = pp[16 + i];
      }
      fence_async_smem();
      bar_sync(1, 512);
      if (tid == 0) PROF_MARK(7);
      if (nh == 1) {
        float kv0[16], kv1[16];
        const uint64_t dP = make_desc(sb + OFF_PHIK + mh * 8192, 1024, 1024, 1);
        const uint64_t dV = make_desc(sb + OFF_VA + mh * 4096, 512, 512, 2);
        wg_fence();
        wgmma_ss_n32_ta1_tb1<0>(kv0, dP, dV);
        wgmma_ss_n32_ta1_tb1<0>(kv1, dP + 1024, dV + 512);
#pragma unroll
        for (int ks = 1; ks < 4; ks++) {
          wgmma_ss_n32_ta1_tb1<1>(kv0, dP + ks * 128, dV + ks * 64);
          wgmma_ss_n32_ta1_tb1<1>(kv1, dP + 1024 + ks * 128, dV + 512 + ks * 64);
        }
        wg_commit();
        wg_wait<0>();
        fence_regs(kv0); fence_regs(kv1);
        bar_sync(4 + wg, 128);
        const uint32_t sa = sb + OFF_PHIK + mh * 8192 + rowl * 128 + lq * 8;
#pragma unroll
        for (int j = 0; j < 8; j++) {
          sts64(sa + 32 * (j >> 1) + 1024 * (j & 1), __float_as_uint(kv0[2 * j]), __float_as_uint(kv0[2 * j + 1]));
          sts64(sa + 16384 + 32 * (j >> 1) + 1024 * (j & 1), __float_as_uint(kv1[2 * j]), __float_as_uint(kv1[2 * j + 1]));
        }
        fence_async_smem();
        __syncwarp();
        if (lane == 0) mbar_arrive(BAR(B_SIG + 1), 1);
        if (tid == 256) PROF_MARK(28);
      }
    }
    {
      const uint64_t dK = make_desc(sb + OFF_RING, 512, 512, 2);
      const uint64_t dhi = dK & 0xffffffff00000000ull;
      const uint32_t dlo0 = (uint32_t)dK;
      uint32_t ok = 0, q[8];
      float o[16];
#pragma unroll
      for (int i = 0; i < 16; i++) o[i] = 0.f;
      {
        const int r = mh * 64 + wq * 16 + (lane & 7) + ((lane >> 3) & 1) * 8;
        ldsm4(q, sb + OFF_QP + nh * 8192 + sw64_off(r, (lane >> 4) * 8));
        ldsm4(q + 4, sb + OFF_QP + nh * 8192 + sw64_off(r, 16 + (lane >> 4) * 8));
      }
      if (tid == 0) PROF_MARK(10);
      const int qb = QB_AT;
#pragma unroll 1
      for (int it = 0; it <= 8; it++) {
        uint32_t p[16];
        if ((tid & 127) == 0) PROF4(wg * 32 + it * 3);
        if (it == qb || it == 8) {
          float t[16];
          wg_wait<0>();
          fence_regs(o);
          if (it < 8) {
            if (tid == 0) PROF_MARK(11);
            mbar_wait(BAR(B_KVR), 0);
            const uint64_t dR = make_desc(sb + OFF_KVR + nh * 4096, 512, 512, 2);
            const uint64_t dP = make_desc(sb + OFF_PHIQ + nh * 16384 + mh * 8192, 1024, 1024, 1);
            wg_fence();
            wgmma_ss_n32_ta0_tb1<0>(t, dP, dR);
#pragma unroll
            for (int ks = 1; ks < 4; ks++) wgmma_ss_n32_ta0_tb1<1>(t, dP + ks * 2, dR + ks * 64);
            wg_commit();
            wg_wait<0>();
            fence_regs(t);
            if (lane == 0) mbar_arrive(BAR(B_X1FREE), 1);
          } else {
            if (lane == 0) mbar_arrive(BAR(B_EMPTY + prev), 1);
            if (tid == 0) PROF_MARK(13);
            mbar_wait(BAR(B_SLOW), 0);
            if (__builtin_expect(__any_sync(~0u, *(volatile int*)(sgen + OFF_RED)), 0)) {
              uint32_t qz[8];
#pragma unroll
              for (int i = 0; i < 8; i++) qz[i] = (i >= 6 && lq >= 2) ? 0u : q[i];
              float m0 = -3.0e38f, m1 = -3.0e38f, o2[16];
              int sl2 = slot;
              uint32_t par2 = par;
#pragma unroll 1
              for (int j64 = 0; j64 < 32; j64++) {
                float s[32];
                mbar_wait(BAR(B_FULL + sl2), par2);
                const uint32_t lo = dlo0 + sl2 * 2048 + (j64 & 3) * 512;
                wg_fence();
                wgmma_rs_n64_tb0<0>(s, qz[0], qz[1], qz[2], qz[3], dhi | lo);
                wgmma_rs_n64_tb0<1>(s, qz[4], qz[5], qz[6], qz[7], dhi | (lo + 2));
                wg_commit();
                wg_wait<0>();
                fence_regs(s);
#pragma unroll
                for (int j = 0; j < 8; j++) {
                  const float sc = ((POLY_PAT >> j) & 1) ? 0.5f : 1.f;
                  m0 = fmaxf(m0, fmaxf(s[4 * j], s[4 * j + 1]) * sc);
                  m1 = fmaxf(m1, fmaxf(s[4 * j + 2], s[4 * j + 3]) * sc);
                }
                if ((j64 & 3) == 3) {
                  if (lane == 0) mbar_arrive(BAR(B_EMPTY + sl2), 1);
                  if (++sl2 == 3) { sl2 = 0; par2 ^= 1; }
                }
              }
              m0 = quad_max(m0); m1 = quad_max(m1);
#pragma unroll
              for (int i = 0; i < 16; i++) o2[i] = 0.f;
#pragma unroll 1
              for (int j64 = 0; j64 < 32; j64++) {
                float s[32];
                mbar_wait(BAR(B_FULL + sl2), par2);
                const uint32_t lo = dlo0 + sl2 * 2048 + (j64 & 3) * 512;
                wg_fence();
                wgmma_rs_n64_tb0<0>(s, qz[0], qz[1], qz[2], qz[3], dhi | lo);
                wgmma_rs_n64_tb0<1>(s, qz[4], qz[5], qz[6], qz[7], dhi | (lo + 2));
                wg_commit();
                wg_wait<0>();
                fence_regs(s);
                uint32_t ps[16];
#pragma unroll
                for (int j = 0; j < 8; j++) {
                  const float sc = ((POLY_PAT >> j) & 1) ? 0.5f : 1.f;
                  ps[2 * j] = pack_bf16(ex2f(fmaf(s[4 * j], sc, -m0)), ex2f(fmaf(s[4 * j + 1], sc, -m0)));
                  ps[2 * j + 1] = pack_bf16(ex2f(fmaf(s[4 * j + 2], sc, -m1)), ex2f(fmaf(s[4 * j + 3], sc, -m1)));
                }
                wg_fence();
#pragma unroll
                for (int ks = 0; ks < 4; ks++)
                  wgmma_rs_n32_tb1<1>(o2, ps[4 * ks], ps[4 * ks + 1], ps[4 * ks + 2], ps[4 * ks + 3], dhi | (lo + 256 + ks * 64));
                wg_commit();
                wg_wait<0>();
                fence_regs(o2);
                if ((j64 & 3) == 3) {
                  if (lane == 0) mbar_arrive(BAR(B_EMPTY + sl2), 1);
                  if (++sl2 == 3) { sl2 = 0; par2 ^= 1; }
                }
              }
#pragma unroll 1
              for (int j = 0; j < 2; j++) {
                mbar_wait(BAR(B_FULL + sl2), par2);
                __syncwarp();
                if (lane == 0) mbar_arrive(BAR(B_EMPTY + sl2), 1);
                if (++sl2 == 3) { sl2 = 0; par2 ^= 1; }
              }
#pragma unroll
              for (int i = 0; i < 16; i++) o[i] = o2[i];
            }
#pragma unroll
            for (int i = 0; i < 16; i++) t[i] = o[i];
          }
          const int br = it == 8;
          const float eps = br ? 0.f : 1e-6f;
          const float g0 = ((const float*)(sgen + OFF_GATE))[row0], g1 = ((const float*)(sgen + OFF_GATE))[row0 + 8];
          const float d0 = __shfl_sync(~0u, t[12], (lane & ~3) | 2), d1 = __shfl_sync(~0u, t[14], (lane & ~3) | 2);
          const float r0 = (br ? 1.f - g0 : g0) * rcpf(d0 + eps), r1 = (br ? 1.f - g1 : g1) * rcpf(d1 + eps);
          uint8_t* img = g_o_img + (size_t)((pt * 2 + br) * 14 + mh) * 8192 + rowl * 128;
          const int col0 = (2 * hp + nh) * DH + 2 * lq;
#pragma unroll
          for (int j = 0; j < 4; j++) {
            const int col = col0 + 8 * j;
            uint8_t* gp = img + (uint32_t)((col >> 6) * 16384 + ((((col >> 3) ^ rowl) & 7) << 4) + (col & 7) * 2);
            const uint32_t v0 = pack_bf16(t[4 * j] * r0, t[4 * j + 1] * r0), v1 = pack_bf16(t[4 * j + 2] * r1, t[4 * j + 3] * r1);
            if (j < 3 || lq < 2) { *(uint32_t*)gp = v0; *(uint32_t*)(gp + 1024) = v1; }
          }
          __syncwarp();
          if (lane == 0) mbar_arrive(BAR(B_SIG + 2 + br), 1);
          if (tid == 0) PROF_MARK(12 + 2 * br);
          if (br) break;
        }
        const uint32_t lo = dlo0 + slot * 2048;
        if ((tid & 127) == 0) PROF4(wg * 32 + it * 3 + 1);
        if (!ok) mbar_wait(BAR(B_FULL + slot), par);
        if ((tid & 127) == 0) PROF4(wg * 32 + it * 3 + 2);
        int nslot = slot + 1;
        uint32_t npar = par;
        if (nslot == 3) { nslot = 0; npar ^= 1; }
        {
          float s[32];
          wg_fence();
          wgmma_rs_n64_tb0<0>(s, q[0], q[1], q[2], q[3], dhi | lo);
          wgmma_rs_n64_tb0<1>(s, q[4], q[5], q[6], q[7], dhi | (lo + 2));
          wg_commit();
#pragma unroll
          for (int u = 0; u < 4; u++) {
            wg_wait<0>();
            fence_regs(s);
            if (u == 0 && lane == 0 && it > 0) mbar_arrive(BAR(B_EMPTY + prev), 1);
            if (u == 2) ok = mbar_test(BAR(B_FULL + nslot), npar);
#pragma unroll
            for (int j = 0; j < 8; j++) {
              if ((POLY_PAT >> j) & 1) {
                p[2 * j] = exp2_pair_fma(s[4 * j], s[4 * j + 1], 0x3F003F00u, 0x00030003u);
                p[2 * j + 1] = exp2_pair_fma(s[4 * j + 2], s[4 * j + 3], 0x3F003F00u, 0x00030003u);
              } else {
                p[2 * j] = pack_bf16(ex2f(s[4 * j]), ex2f(s[4 * j + 1]));
                p[2 * j + 1] = pack_bf16(ex2f(s[4 * j + 2]), ex2f(s[4 * j + 3]));
              }
            }
            wg_fence();
#pragma unroll
            for (int ks = 0; ks < 4; ks++)
              wgmma_rs_n32_tb1<1>(o, p[4 * ks], p[4 * ks + 1], p[4 * ks + 2], p[4 * ks + 3], dhi | (lo + u * 512 + 256 + ks * 64));
            if (u < 3) {
              wgmma_rs_n64_tb0<0>(s, q[0], q[1], q[2], q[3], dhi | (lo + (u + 1) * 512));
              wgmma_rs_n64_tb0<1>(s, q[4], q[5], q[6], q[7], dhi | (lo + (u + 1) * 512 + 2));
            }
            wg_commit();
          }
        }
        prev = slot; slot = nslot; par = npar;
      }
      wg_wait<0>();
    }
    if (nh == 1) return;
    {
      float acc0[28], acc1[28];
#pragma unroll
      for (int i = 0; i < 28; i++) acc0[i] = acc1[i] = 0.f;
      const uint64_t dS = make_desc(sb + OFF_WO, 1024, 1024, 1);
      const uint64_t dR = make_desc(sb + OFF_RING + mh * 8192, 1024, 1024, 1);
#pragma unroll 1
      for (int c = 0; c < 7; c++) {
        mbar_wait(BAR(B_WO + (c >= 3)), 0);
        mbar_wait(BAR(B_FULL + slot), par);
        const uint64_t dA = dR + slot * 2048, dB = dS + c * 1024;
        wg_fence();
#pragma unroll
        for (int ks = 0; ks < 4; ks++) {
          wgmma_ss_n56_ta0_tb1<1>(acc0, dA + ks * 2, dB + ks * 128);
          wgmma_ss_n56_ta0_tb1<1>(acc1, dA + 1024 + ks * 2, dB + 512 + ks * 128);
        }
        wg_commit();
        if (c < 4) {
          wg_wait<0>();
          if (lane == 0) mbar_arrive(BAR(B_EMPTY + slot), 2);
        }
        if (++slot == 3) { slot = 0; par ^= 1; }
      }
      wg_wait<0>();
      fence_regs(acc0); fence_regs(acc1);
      if (tid == 0) PROF_MARK(17);
      __nv_bfloat16* op = prm.out + (size_t)(pt * 128 + row0) * DM + hp * 56 + 2 * lq;
#pragma unroll
      for (int j = 0; j < 7; j++) {
        *(uint32_t*)(op + 8 * j) = pack_bf16(acc0[4 * j] + acc1[4 * j], acc0[4 * j + 1] + acc1[4 * j + 1]);
        *(uint32_t*)(op + 8 * DM + 8 * j) = pack_bf16(acc0[4 * j + 2] + acc1[4 * j + 2], acc0[4 * j + 3] + acc1[4 * j + 3]);
      }
      if (tid == 0) { PROF_MARK(18); PROF_CLK(31); }
    }
  }
}

typedef CUresult (*EncodeFn)(CUtensorMap*, CUtensorMapDataType, cuuint32_t, void*, const cuuint64_t*, const cuuint64_t*,
                             const cuuint32_t*, const cuuint32_t*, CUtensorMapInterleave, CUtensorMapSwizzle,
                             CUtensorMapL2promotion, CUtensorMapFloatOOBfill);

void make_map(EncodeFn enc, CUtensorMap* tm, const void* ptr, uint64_t cols, uint64_t rows, uint32_t box_rows) {
  cuuint64_t dims[2] = {cols, rows};
  cuuint64_t strides[1] = {cols * 2};
  cuuint32_t box[2] = {64, box_rows};
  cuuint32_t es[2] = {1, 1};
  enc(tm, CU_TENSOR_MAP_DATA_TYPE_BFLOAT16, 2, const_cast<void*>(ptr), dims, strides, box, es, CU_TENSOR_MAP_INTERLEAVE_NONE,
      CU_TENSOR_MAP_SWIZZLE_128B, CU_TENSOR_MAP_L2_PROMOTION_L2_128B, CU_TENSOR_MAP_FLOAT_OOB_FILL_NONE);
}

}

extern "C" void kernel_launch(void* const* d_in, const int* in_sizes, int n_in, void* d_out, int out_size) {
  (void)in_sizes; (void)n_in; (void)out_size;
  static EncodeFn enc = nullptr;
  if (!enc) {
    void* fn = nullptr;
    cudaDriverEntryPointQueryResult qr;
    cudaGetDriverEntryPoint("cuTensorMapEncodeTiled", &fn, cudaEnableDefault, &qr);
    enc = (EncodeFn)fn;
    cudaFuncSetAttribute(fused_kernel, cudaFuncAttributeMaxDynamicSharedMemorySize, SMEM_BYTES);
  }
  CUtensorMap tm_x, tm_wqkv, tm_wq, tm_woa, tm_wob;
  make_map(enc, &tm_x, d_in[0], DM, S_LEN, 128);
  make_map(enc, &tm_wqkv, d_in[1], 3 * DM, DM, 64);
  make_map(enc, &tm_wq, d_in[5], DM, DM, 64);
  make_map(enc, &tm_woa, d_in[3], DM, DM, 64);
  make_map(enc, &tm_wob, d_in[8], DM, DM, 64);
  Params prm;
  prm.w_phi = (const __nv_bfloat16*)d_in[2];
  prm.wk = (const __nv_bfloat16*)d_in[6];
  prm.wv = (const __nv_bfloat16*)d_in[7];
  prm.gate_w = (const __nv_bfloat16*)d_in[9];
  prm.out = (__nv_bfloat16*)d_out;
  fused_kernel<<<NCTA, NTHREADS, SMEM_BYTES>>>(tm_x, tm_wqkv, tm_wq, tm_woa, tm_wob, prm);
}
```

```cpp
#include <cuda_runtime.h>
#include <cuda_bf16.h>
#include <cuda.h>
#include <stdint.h>

namespace {

constexpr int S_LEN = 2048, DM = 448, DH = 28;
constexpr int NCTA = 128;
constexpr int NTHREADS = 640;
constexpr uint32_t POLY_PAT = 0x57;

#define QB_AT (4 + nh)

constexpr int OFF_X = 0;
constexpr int OFF_PHIK = 0;
constexpr int OFF_VA = 32768;
constexpr int OFF_PHIQ = 57344;
constexpr int OFF_KVR = 90112;
constexpr int OFF_QP = 98304;
constexpr int OFF_RAW = 81920;
constexpr int OFF_WO = 0;
constexpr int OFF_RING = 114688;
constexpr int OFF_WBD = 212992;
constexpr int OFF_SLC = 221184;
constexpr int OFF_QSQ = 228352;
constexpr int OFF_GATE = 229376;
constexpr int OFF_RED = 229888;
constexpr int OFF_BAR = 229952;
constexpr int SMEM_BYTES = 230400 + 1024;

constexpr int B_FULL = 0, B_EMPTY = 3, B_WO = 6  , B_KVR = 8, B_RAW = 9, B_X1FREE = 10, B_QSQ = 11, B_SLOW = 12,
              B_BUILD = 13, B_SIG = 14  , B_N = 18;

constexpr int C_KV = 0, C_PART = 1, C_DONE = 3, C_OA = 4, C_OB = 20, C_N = 36;

__device__ __align__(1024) uint8_t g_kv_img[32 * 8192];
__device__ __align__(16) float g_ksq[512];
__device__ __align__(16) float g_vsq[512];
__device__ __align__(16) float g_gate[S_LEN];
__device__ __align__(1024) float g_kvacc[2][16 * 64 * 32];
__device__ unsigned g_epoch;
__device__ __align__(1024) uint8_t g_o_img[2 * 16 * 14 * 8192];
__device__ unsigned g_cnt[C_N * 32];

#define PROF4(i) do { } while (0)
#define PROF3(i) do { } while (0)
#define PROF2(i) do { } while (0)
#define PROF_CLK(i) do { } while (0)
#define PROF_MARK(i) do { } while (0)
__device__ __forceinline__ uint32_t smem_u32(const void* p) { return (uint32_t)__cvta_generic_to_shared(p); }
__device__ __forceinline__ void mbar_init(uint32_t a, int cnt) {
  asm volatile("mbarrier.init.shared::cta.b64 [%0], %1;" ::"r"(a), "r"(cnt) : "memory");
}
__device__ __forceinline__ void mbar_expect_tx(uint32_t a, uint32_t bytes) {
  asm volatile("mbarrier.arrive.expect_tx.shared::cta.b64 _, [%0], %1;" ::"r"(a), "r"(bytes) : "memory");
}
__device__ __forceinline__ void mbar_arrive(uint32_t a, uint32_t cnt) {
  asm volatile("mbarrier.arrive.shared::cta.b64 _, [%0], %1;" ::"r"(a), "r"(cnt) : "memory");
}
__device__ __forceinline__ void mbar_wait(uint32_t a, uint32_t parity) {
  asm volatile(
      "{\n.reg .pred p;\n.reg .u32 c;\nmov.u32 c, 0;\n"
      "W_%=:\nmbarrier.try_wait.parity.shared::cta.b64 p, [%0], %1;\n"
      "add.u32 c, c, 1;\nsetp.lt.and.u32 p, c, 0x40000, !p;\n@p bra W_%=;\n}"
      ::"r"(a), "r"(parity) : "memory");
}
__device__ __forceinline__ uint32_t mbar_test(uint32_t a, uint32_t parity) {
  uint32_t ok;
  asm volatile("{\n.reg .pred p;\nmbarrier.test_wait.parity.shared::cta.b64 p, [%1], %2;\nselp.u32 %0, 1, 0, p;\n}"
               : "=r"(ok) : "r"(a), "r"(parity) : "memory");
  return ok;
}
__device__ __forceinline__ bool elect_one() {
  uint32_t r;
  asm volatile("{\n.reg .pred p;\nelect.sync _|p, 0xffffffff;\nselp.u32 %0, 1, 0, p;\n}" : "=r"(r));
  return r != 0;
}
__device__ __forceinline__ void tma_2d(uint32_t dst, const CUtensorMap* tm, int c0, int c1, uint32_t bar) {
  asm volatile("cp.async.bulk.tensor.2d.shared::cluster.global.mbarrier::complete_tx::bytes [%0], [%1, {%3, %4}], [%2];"
               ::"r"(dst), "l"(tm), "r"(bar), "r"(c0), "r"(c1) : "memory");
}
__device__ __forceinline__ void bulk_g2s(uint32_t dst, const void* src, uint32_t bytes, uint32_t bar) {
  asm volatile("cp.async.bulk.shared::cluster.global.mbarrier::complete_tx::bytes [%0], [%1], %2, [%3];"
               ::"r"(dst), "l"(src), "r"(bytes), "r"(bar) : "memory");
}
__device__ __forceinline__ void fence_async_smem() { asm volatile("fence.proxy.async.shared::cta;" ::: "memory"); }
__device__ __forceinline__ void fence_async_all() { asm volatile("fence.proxy.async.global;" ::: "memory"); }

__device__ __forceinline__ void bar_sync(int id, int n) { asm volatile("bar.sync %0, %1;" ::"r"(id), "r"(n) : "memory"); }
__device__ __forceinline__ void cnt_arrive(int idx) {
  asm volatile("red.release.gpu.global.add.u32 [%0], 1;" ::"l"(&g_cnt[idx * 32]) : "memory");
}
__device__ __forceinline__ void cnt_wait(int idx, unsigned target) {
  unsigned v, n = 0;
#pragma unroll 1
  while (true) {
    asm volatile("ld.acquire.gpu.global.u32 %0, [%1];" : "=r"(v) : "l"(&g_cnt[idx * 32]) : "memory");
    if (v >= target || ++n >= (1u << 18)) break;
    __nanosleep(32);
  }
}
__device__ __forceinline__ void wg_fence() { asm volatile("wgmma.fence.sync.aligned;" ::: "memory"); }
__device__ __forceinline__ void wg_commit() { asm volatile("wgmma.commit_group.sync.aligned;" ::: "memory"); }
template <int N> __device__ __forceinline__ void wg_wait() { asm volatile("wgmma.wait_group.sync.aligned %0;" ::"n"(N) : "memory"); }
template <int N> __device__ __forceinline__ void fence_regs(float (&d)[N]) {
#pragma unroll
  for (int i = 0; i < N; i++) asm volatile("" : "+f"(d[i])::"memory");
}
__device__ __forceinline__ uint64_t make_desc(uint32_t saddr, uint32_t lbo, uint32_t sbo, uint32_t swz) {
  return (uint64_t)((saddr & 0x3FFFF) >> 4) | ((uint64_t)(lbo >> 4) << 16) | ((uint64_t)(sbo >> 4) << 32) | ((uint64_t)swz << 62);
}
__device__ __forceinline__ float ex2f(float x) { float y; asm("ex2.approx.ftz.f32 %0, %1;" : "=f"(y) : "f"(x)); return y; }
__device__ __forceinline__ float rcpf(float x) { float y; asm("rcp.approx.ftz.f32 %0, %1;" : "=f"(y) : "f"(x)); return y; }
__device__ __forceinline__ uint32_t pack_bf16(float lo, float hi) {
  uint32_t r; asm("cvt.rn.bf16x2.f32 %0, %1, %2;" : "=r"(r) : "f"(hi), "f"(lo)); return r;
}
__device__ __forceinline__ uint32_t lop_and_or(uint32_t a, uint32_t m, uint32_t c) {
  uint32_t r; asm("lop3.b32 %0, %1, %2, %3, 0xEA;" : "=r"(r) : "r"(a), "r"(m), "r"(c)); return r;
}
__device__ __forceinline__ void sts32(uint32_t a, uint32_t v) { asm volatile("st.shared.b32 [%0], %1;" ::"r"(a), "r"(v) : "memory"); }
__device__ __forceinline__ void sts64(uint32_t a, uint32_t v0, uint32_t v1) { asm volatile("st.shared.v2.b32 [%0], {%1, %2};" ::"r"(a), "r"(v0), "r"(v1) : "memory"); }
__device__ __forceinline__ void sts128(uint32_t a, uint4 v) {
  asm volatile("st.shared.v4.b32 [%0], {%1, %2, %3, %4};" ::"r"(a), "r"(v.x), "r"(v.y), "r"(v.z), "r"(v.w) : "memory");
}
__device__ __forceinline__ float4 ldcg_f4(const float* p) {
  float4 v; asm volatile("ld.global.cg.v4.f32 {%0, %1, %2, %3}, [%4];" : "=f"(v.x), "=f"(v.y), "=f"(v.z), "=f"(v.w) : "l"(p) : "memory"); return v;
}
__device__ __forceinline__ void ldsm4(uint32_t* r, uint32_t a) {
  asm volatile("ldmatrix.sync.aligned.m8n8.x4.shared.b16 {%0, %1, %2, %3}, [%4];"
               : "=r"(r[0]), "=r"(r[1]), "=r"(r[2]), "=r"(r[3]) : "r"(a) : "memory");
}
__device__ __forceinline__ float quad_sum(float v) { v += __shfl_xor_sync(~0u, v, 1); v += __shfl_xor_sync(~0u, v, 2); return v; }
__device__ __forceinline__ float quad_max(float v) { v = fmaxf(v, __shfl_xor_sync(~0u, v, 1)); v = fmaxf(v, __shfl_xor_sync(~0u, v, 2)); return v; }

template <int SD> __device__ __forceinline__ void wgmma_ss_n56_ta0_tb1(float (&d)[28], uint64_t da, uint64_t db) {
  if (SD) asm volatile("wgmma.mma_async.sync.aligned.m64n56k16.f32.bf16.bf16 {%0, %1, %2, %3, %4, %5, %6, %7, %8, %9, %10, %11, %12, %13, %14, %15, %16, %17, %18, %19, %20, %21, %22, %23, %24, %25, %26, %27}, %28, %29, 1, 1, 1, 0, 1;\n"
    : "+f"(d[0]), "+f"(d[1]), "+f"(d[2]), "+f"(d[3]), "+f"(d[4]), "+f"(d[5]), "+f"(d[6]), "+f"(d[7]), "+f"(d[8]), "+f"(d[9]), "+f"(d[10]), "+f"(d[11]), "+f"(d[12]), "+f"(d[13]), "+f"(d[14]), "+f"(d[15]), "+f"(d[16]), "+f"(d[17]), "+f"(d[18]), "+f"(d[19]), "+f"(d[20]), "+f"(d[21]), "+f"(d[22]), "+f"(d[23]), "+f"(d[24]), "+f"(d[25]), "+f"(d[26]), "+f"(d[27])
    : "l"(da), "l"(db));
  else asm volatile("wgmma.mma_async.sync.aligned.m64n56k16.f32.bf16.bf16 {%0, %1, %2, %3, %4, %5, %6, %7, %8, %9, %10, %11, %12, %13, %14, %15, %16, %17, %18, %19, %20, %21, %22, %23, %24, %25, %26, %27}, %28, %29, 0, 1, 1, 0, 1;\n"
    : "=f"(d[0]), "=f"(d[1]), "=f"(d[2]), "=f"(d[3]), "=f"(d[4]), "=f"(d[5]), "=f"(d[6]), "=f"(d[7]), "=f"(d[8]), "=f"(d[9]), "=f"(d[10]), "=f"(d[11]), "=f"(d[12]), "=f"(d[13]), "=f"(d[14]), "=f"(d[15]), "=f"(d[16]), "=f"(d[17]), "=f"(d[18]), "=f"(d[19]), "=f"(d[20]), "=f"(d[21]), "=f"(d[22]), "=f"(d[23]), "=f"(d[24]), "=f"(d[25]), "=f"(d[26]), "=f"(d[27])
    : "l"(da), "l"(db));
}
template <int SD> __device__ __forceinline__ void wgmma_rs_n56_tb1(float (&d)[28], uint32_t a0, uint32_t a1, uint32_t a2, uint32_t a3, uint64_t db) {
  if (SD) asm volatile("wgmma.mma_async.sync.aligned.m64n56k16.f32.bf16.bf16 {%0, %1, %2, %3, %4, %5, %6, %7, %8, %9, %10, %11, %12, %13, %14, %15, %16, %17, %18, %19, %20, %21, %22, %23, %24, %25, %26, %27}, {%28, %29, %30, %31}, %32, 1, 1, 1, 1;\n"
    : "+f"(d[0]), "+f"(d[1]), "+f"(d[2]), "+f"(d[3]), "+f"(d[4]), "+f"(d[5]), "+f"(d[6]), "+f"(d[7]), "+f"(d[8]), "+f"(d[9]), "+f"(d[10]), "+f"(d[11]), "+f"(d[12]), "+f"(d[13]), "+f"(d[14]), "+f"(d[15]), "+f"(d[16]), "+f"(d[17]), "+f"(d[18]), "+f"(d[19]), "+f"(d[20]), "+f"(d[21]), "+f"(d[22]), "+f"(d[23]), "+f"(d[24]), "+f"(d[25]), "+f"(d[26]), "+f"(d[27])
    : "r"(a0), "r"(a1), "r"(a2), "r"(a3), "l"(db));
  else asm volatile("wgmma.mma_async.sync.aligned.m64n56k16.f32.bf16.bf16 {%0, %1, %2, %3, %4, %5, %6, %7, %8, %9, %10, %11, %12, %13, %14, %15, %16, %17, %18, %19, %20, %21, %22, %23, %24, %25, %26, %27}, {%28, %29, %30, %31}, %32, 0, 1, 1, 1;\n"
    : "=f"(d[0]), "=f"(d[1]), "=f"(d[2]), "=f"(d[3]), "=f"(d[4]), "=f"(d[5]), "=f"(d[6]), "=f"(d[7]), "=f"(d[8]), "=f"(d[9]), "=f"(d[10]), "=f"(d[11]), "=f"(d[12]), "=f"(d[13]), "=f"(d[14]), "=f"(d[15]), "=f"(d[16]), "=f"(d[17]), "=f"(d[18]), "=f"(d[19]), "=f"(d[20]), "=f"(d[21]), "=f"(d[22]), "=f"(d[23]), "=f"(d[24]), "=f"(d[25]), "=f"(d[26]), "=f"(d[27])
    : "r"(a0), "r"(a1), "r"(a2), "r"(a3), "l"(db));
}
template <int SD> __device__ __forceinline__ void wgmma_rs_n8_tb1(float (&d)[4], uint32_t a0, uint32_t a1, uint32_t a2, uint32_t a3, uint64_t db) {
  if (SD) asm volatile("wgmma.mma_async.sync.aligned.m64n8k16.f32.bf16.bf16 {%0, %1, %2, %3}, {%4, %5, %6, %7}, %8, 1, 1, 1, 1;\n"
    : "+f"(d[0]), "+f"(d[1]), "+f"(d[2]), "+f"(d[3])
    : "r"(a0), "r"(a1), "r"(a2), "r"(a3), "l"(db));
  else asm volatile("wgmma.mma_async.sync.aligned.m64n8k16.f32.bf16.bf16 {%0, %1, %2, %3}, {%4, %5, %6, %7}, %8, 0, 1, 1, 1;\n"
    : "=f"(d[0]), "=f"(d[1]), "=f"(d[2]), "=f"(d[3])
    : "r"(a0), "r"(a1), "r"(a2), "r"(a3), "l"(db));
}
template <int SD> __device__ __forceinline__ void wgmma_rs_n64_tb1(float (&d)[32], uint32_t a0, uint32_t a1, uint32_t a2, uint32_t a3, uint64_t db) {
  if (SD) asm volatile("wgmma.mma_async.sync.aligned.m64n64k16.f32.bf16.bf16 {%0, %1, %2, %3, %4, %5, %6, %7, %8, %9, %10, %11, %12, %13, %14, %15, %16, %17, %18, %19, %20, %21, %22, %23, %24, %25, %26, %27, %28, %29, %30, %31}, {%32, %33, %34, %35}, %36, 1, 1, 1, 1;\n"
    : "+f"(d[0]), "+f"(d[1]), "+f"(d[2]), "+f"(d[3]), "+f"(d[4]), "+f"(d[5]), "+f"(d[6]), "+f"(d[7]), "+f"(d[8]), "+f"(d[9]), "+f"(d[10]), "+f"(d[11]), "+f"(d[12]), "+f"(d[13]), "+f"(d[14]), "+f"(d[15]), "+f"(d[16]), "+f"(d[17]), "+f"(d[18]), "+f"(d[19]), "+f"(d[20]), "+f"(d[21]), "+f"(d[22]), "+f"(d[23]), "+f"(d[24]), "+f"(d[25]), "+f"(d[26]), "+f"(d[27]), "+f"(d[28]), "+f"(d[29]), "+f"(d[30]), "+f"(d[31])
    : "r"(a0), "r"(a1), "r"(a2), "r"(a3), "l"(db));
  else asm volatile("wgmma.mma_async.sync.aligned.m64n64k16.f32.bf16.bf16 {%0, %1, %2, %3, %4, %5, %6, %7, %8, %9, %10, %11, %12, %13, %14, %15, %16, %17, %18, %19, %20, %21, %22, %23, %24, %25, %26, %27, %28, %29, %30, %31}, {%32, %33, %34, %35}, %36, 0, 1, 1, 1;\n"
    : "=f"(d[0]), "=f"(d[1]), "=f"(d[2]), "=f"(d[3]), "=f"(d[4]), "=f"(d[5]), "=f"(d[6]), "=f"(d[7]), "=f"(d[8]), "=f"(d[9]), "=f"(d[10]), "=f"(d[11]), "=f"(d[12]), "=f"(d[13]), "=f"(d[14]), "=f"(d[15]), "=f"(d[16]), "=f"(d[17]), "=f"(d[18]), "=f"(d[19]), "=f"(d[20]), "=f"(d[21]), "=f"(d[22]), "=f"(d[23]), "=f"(d[24]), "=f"(d[25]), "=f"(d[26]), "=f"(d[27]), "=f"(d[28]), "=f"(d[29]), "=f"(d[30]), "=f"(d[31])
    : "r"(a0), "r"(a1), "r"(a2), "r"(a3), "l"(db));
}
template <int SD> __device__ __forceinline__ void wgmma_ss_n32_ta1_tb1(float (&d)[16], uint64_t da, uint64_t db) {
  if (SD) asm volatile("wgmma.mma_async.sync.aligned.m64n32k16.f32.bf16.bf16 {%0, %1, %2, %3, %4, %5, %6, %7, %8, %9, %10, %11, %12, %13, %14, %15}, %16, %17, 1, 1, 1, 1, 1;\n"
    : "+f"(d[0]), "+f"(d[1]), "+f"(d[2]), "+f"(d[3]), "+f"(d[4]), "+f"(d[5]), "+f"(d[6]), "+f"(d[7]), "+f"(d[8]), "+f"(d[9]), "+f"(d[10]), "+f"(d[11]), "+f"(d[12]), "+f"(d[13]), "+f"(d[14]), "+f"(d[15])
    : "l"(da), "l"(db));
  else asm volatile("wgmma.mma_async.sync.aligned.m64n32k16.f32.bf16.bf16 {%0, %1, %2, %3, %4, %5, %6, %7, %8, %9, %10, %11, %12, %13, %14, %15}, %16, %17, 0, 1, 1, 1, 1;\n"
    : "=f"(d[0]), "=f"(d[1]), "=f"(d[2]), "=f"(d[3]), "=f"(d[4]), "=f"(d[5]), "=f"(d[6]), "=f"(d[7]), "=f"(d[8]), "=f"(d[9]), "=f"(d[10]), "=f"(d[11]), "=f"(d[12]), "=f"(d[13]), "=f"(d[14]), "=f"(d[15])
    : "l"(da), "l"(db));
}
template <int SD> __device__ __forceinline__ void wgmma_ss_n32_ta0_tb1(float (&d)[16], uint64_t da, uint64_t db) {
  if (SD) asm volatile("wgmma.mma_async.sync.aligned.m64n32k16.f32.bf16.bf16 {%0, %1, %2, %3, %4, %5, %6, %7, %8, %9, %10, %11, %12, %13, %14, %15}, %16, %17, 1, 1, 1, 0, 1;\n"
    : "+f"(d[0]), "+f"(d[1]), "+f"(d[2]), "+f"(d[3]), "+f"(d[4]), "+f"(d[5]), "+f"(d[6]), "+f"(d[7]), "+f"(d[8]), "+f"(d[9]), "+f"(d[10]), "+f"(d[11]), "+f"(d[12]), "+f"(d[13]), "+f"(d[14]), "+f"(d[15])
    : "l"(da), "l"(db));
  else asm volatile("wgmma.mma_async.sync.aligned.m64n32k16.f32.bf16.bf16 {%0, %1, %2, %3, %4, %5, %6, %7, %8, %9, %10, %11, %12, %13, %14, %15}, %16, %17, 0, 1, 1, 0, 1;\n"
    : "=f"(d[0]), "=f"(d[1]), "=f"(d[2]), "=f"(d[3]), "=f"(d[4]), "=f"(d[5]), "=f"(d[6]), "=f"(d[7]), "=f"(d[8]), "=f"(d[9]), "=f"(d[10]), "=f"(d[11]), "=f"(d[12]), "=f"(d[13]), "=f"(d[14]), "=f"(d[15])
    : "l"(da), "l"(db));
}
template <int SD> __device__ __forceinline__ void wgmma_rs_n64_tb0(float (&d)[32], uint32_t a0, uint32_t a1, uint32_t a2, uint32_t a3, uint64_t db) {
  if (SD) asm volatile("wgmma.mma_async.sync.aligned.m64n64k16.f32.bf16.bf16 {%0, %1, %2, %3, %4, %5, %6, %7, %8, %9, %10, %11, %12, %13, %14, %15, %16, %17, %18, %19, %20, %21, %22, %23, %24, %25, %26, %27, %28, %29, %30, %31}, {%32, %33, %34, %35}, %36, 1, 1, 1, 0;\n"
    : "+f"(d[0]), "+f"(d[1]), "+f"(d[2]), "+f"(d[3]), "+f"(d[4]), "+f"(d[5]), "+f"(d[6]), "+f"(d[7]), "+f"(d[8]), "+f"(d[9]), "+f"(d[10]), "+f"(d[11]), "+f"(d[12]), "+f"(d[13]), "+f"(d[14]), "+f"(d[15]), "+f"(d[16]), "+f"(d[17]), "+f"(d[18]), "+f"(d[19]), "+f"(d[20]), "+f"(d[21]), "+f"(d[22]), "+f"(d[23]), "+f"(d[24]), "+f"(d[25]), "+f"(d[26]), "+f"(d[27]), "+f"(d[28]), "+f"(d[29]), "+f"(d[30]), "+f"(d[31])
    : "r"(a0), "r"(a1), "r"(a2), "r"(a3), "l"(db));
  else asm volatile("wgmma.mma_async.sync.aligned.m64n64k16.f32.bf16.bf16 {%0, %1, %2, %3, %4, %5, %6, %7, %8, %9, %10, %11, %12, %13, %14, %15, %16, %17, %18, %19, %20, %21, %22, %23, %24, %25, %26, %27, %28, %29, %30, %31}, {%32, %33, %34, %35}, %36, 0, 1, 1, 0;\n"
    : "=f"(d[0]), "=f"(d[1]), "=f"(d[2]), "=f"(d[3]), "=f"(d[4]), "=f"(d[5]), "=f"(d[6]), "=f"(d[7]), "=f"(d[8]), "=f"(d[9]), "=f"(d[10]), "=f"(d[11]), "=f"(d[12]), "=f"(d[13]), "=f"(d[14]), "=f"(d[15]), "=f"(d[16]), "=f"(d[17]), "=f"(d[18]), "=f"(d[19]), "=f"(d[20]), "=f"(d[21]), "=f"(d[22]), "=f"(d[23]), "=f"(d[24]), "=f"(d[25]), "=f"(d[26]), "=f"(d[27]), "=f"(d[28]), "=f"(d[29]), "=f"(d[30]), "=f"(d[31])
    : "r"(a0), "r"(a1), "r"(a2), "r"(a3), "l"(db));
}
template <int SD> __device__ __forceinline__ void wgmma_rs_n32_tb1(float (&d)[16], uint32_t a0, uint32_t a1, uint32_t a2, uint32_t a3, uint64_t db) {
  if (SD) asm volatile("wgmma.mma_async.sync.aligned.m64n32k16.f32.bf16.bf16 {%0, %1, %2, %3, %4, %5, %6, %7, %8, %9, %10, %11, %12, %13, %14, %15}, {%16, %17, %18, %19}, %20, 1, 1, 1, 1;\n"
    : "+f"(d[0]), "+f"(d[1]), "+f"(d[2]), "+f"(d[3]), "+f"(d[4]), "+f"(d[5]), "+f"(d[6]), "+f"(d[7]), "+f"(d[8]), "+f"(d[9]), "+f"(d[10]), "+f"(d[11]), "+f"(d[12]), "+f"(d[13]), "+f"(d[14]), "+f"(d[15])
    : "r"(a0), "r"(a1), "r"(a2), "r"(a3), "l"(db));
  else asm volatile("wgmma.mma_async.sync.aligned.m64n32k16.f32.bf16.bf16 {%0, %1, %2, %3, %4, %5, %6, %7, %8, %9, %10, %11, %12, %13, %14, %15}, {%16, %17, %18, %19}, %20, 0, 1, 1, 1;\n"
    : "=f"(d[0]), "=f"(d[1]), "=f"(d[2]), "=f"(d[3]), "=f"(d[4]), "=f"(d[5]), "=f"(d[6]), "=f"(d[7]), "=f"(d[8]), "=f"(d[9]), "=f"(d[10]), "=f"(d[11]), "=f"(d[12]), "=f"(d[13]), "=f"(d[14]), "=f"(d[15])
    : "r"(a0), "r"(a1), "r"(a2), "r"(a3), "l"(db));
}

__device__ __forceinline__ uint32_t sw64_off(int row, int d) { return row * 64 + ((((d >> 3) ^ (row >> 1)) & 3) << 4) + (d & 7) * 2; }

__device__ __forceinline__ uint32_t exp2_pair_fma(float t0, float t1, uint32_t c_half, uint32_t c_3) {
  uint32_t y0, y;
  asm("prmt.b32 %0, %1, %2, 0x6521;" : "=r"(y0) : "r"(__float_as_uint(t0)), "r"(__float_as_uint(t1)));
  uint32_t h = lop_and_or(y0, 0x007F007Fu, c_half);
  uint32_t e = lop_and_or(y0, 0xFF80FF80u, c_3);
  asm("fma.rn.bf16x2 %0, %1, %2, %3;" : "=r"(y) : "r"(y0), "r"(h), "r"(e));
  return y;
}

__device__ __forceinline__ void feature_map(float (&v)[16], uint32_t (&ph)[16], int lq) {
  const float L2E = 1.4426950408889634f;
  const bool tail_ok = lq < 2;
  float mx[2], mn[2], b[16], sa[2], sn[2];
#pragma unroll
  for (int r = 0; r < 2; r++) {
    const int o = 2 * r;
    if (!tail_ok) { v[o + 12] = v[o]; v[o + 13] = v[o]; }
    mx[r] = fmaxf(fmaxf(fmaxf(v[o], v[o + 1]), fmaxf(v[o + 4], v[o + 5])), fmaxf(fmaxf(v[o + 8], v[o + 9]), fmaxf(v[o + 12], v[o + 13])));
    mn[r] = fminf(fminf(fminf(v[o], v[o + 1]), fminf(v[o + 4], v[o + 5])), fminf(fminf(v[o + 8], v[o + 9]), fminf(v[o + 12], v[o + 13])));
  }
#pragma unroll
  for (int o = 1; o <= 2; o <<= 1)
#pragma unroll
    for (int r = 0; r < 2; r++) { mx[r] = fmaxf(mx[r], __shfl_xor_sync(~0u, mx[r], o)); mn[r] = fminf(mn[r], __shfl_xor_sync(~0u, mn[r], o)); }
#pragma unroll
  for (int r = 0; r < 2; r++) {
    const int o = 2 * r;
    const float cx = -mx[r] * L2E, cn = mn[r] * L2E;
#pragma unroll
    for (int i = 0; i < 8; i++) {
      const int k = o + 4 * (i >> 1) + (i & 1);
      b[k] = ex2f(fmaf(v[k], -L2E, cn));
      v[k] = ex2f(fmaf(v[k], L2E, cx));
    }
    if (!tail_ok) { v[o + 12] = v[o + 13] = b[o + 12] = b[o + 13] = 0.f; }
    sa[r] = ((v[o] + v[o + 1]) + (v[o + 4] + v[o + 5])) + ((v[o + 8] + v[o + 9]) + (v[o + 12] + v[o + 13]));
    sn[r] = ((b[o] + b[o + 1]) + (b[o + 4] + b[o + 5])) + ((b[o + 8] + b[o + 9]) + (b[o + 12] + b[o + 13]));
  }
#pragma unroll
  for (int o = 1; o <= 2; o <<= 1)
#pragma unroll
    for (int r = 0; r < 2; r++) { sa[r] += __shfl_xor_sync(~0u, sa[r], o); sn[r] += __shfl_xor_sync(~0u, sn[r], o); }
#pragma unroll
  for (int r = 0; r < 2; r++) {
    const float ra = rcpf(sa[r]), rb = rcpf(sn[r]);
#pragma unroll
    for (int jj = 0; jj < 4; jj++) {
      ph[jj * 2 + r] = pack_bf16(v[2 * r + 4 * jj] * ra, v[2 * r + 4 * jj + 1] * ra);
      ph[(4 + jj) * 2 + r] = pack_bf16(b[2 * r + 4 * jj] * rb, b[2 * r + 4 * jj + 1] * rb);
    }
  }
}

__device__ __forceinline__ void store_heads(uint32_t base, const uint32_t (&a)[14], uint32_t pad0, uint32_t pad1, int row0, int lq) {
  const uint32_t rb = base + row0 * 64 + (((row0 >> 1) & 3) << 4);
  const uint32_t b0 = rb + lq * 4;
  const uint32_t b1 = (rb + 8192 + ((lq * 4 + 8) & 15)) ^ ((lq >> 1) << 4);
#pragma unroll
  for (int j = 0; j < 7; j++) {
    uint32_t ad;
    if (j < 3) ad = b0 ^ (j << 4);
    else if (j == 3) ad = (lq < 2) ? (b0 ^ 48u) : (b1 ^ 16u);
    else ad = (lq < 2) ? (b1 ^ ((j - 4) << 4)) : ((b1 ^ 16u) ^ ((j - 3) << 4));
    sts32(ad, a[2 * j]);
    sts32(ad + 512, a[2 * j + 1]);
  }
  sts64((rb ^ 48u) + 8 + (lq & 1) * 8192 + (lq >> 1) * 512, pad0, pad1);
}

struct Params {
  const __nv_bfloat16* w_phi;
  const __nv_bfloat16* wk;
  const __nv_bfloat16* wv;
  const __nv_bfloat16* gate_w;
  __nv_bfloat16* out;
};

__global__ void __launch_bounds__(NTHREADS, 1)
fused_kernel(const __grid_constant__ CUtensorMap tm_x, const __grid_constant__ CUtensorMap tm_wqkv,
             const __grid_constant__ CUtensorMap tm_wq, const __grid_constant__ CUtensorMap tm_woa,
             const __grid_constant__ CUtensorMap tm_wob, const Params prm) {
  extern __shared__ uint8_t smem_raw[];
  uint32_t sb = (smem_u32(smem_raw) + 1023u) & ~1023u;
  uint8_t* sgen = smem_raw + (sb - smem_u32(smem_raw));
  asm volatile("mov.u32 %0, %0;" : "+r"(sb));
  const int tid = threadIdx.x, lane = tid & 31;
  const int warp = __shfl_sync(~0u, tid >> 5, 0), wg = warp >> 2;
  const int pt = blockIdx.x >> 3, hp = blockIdx.x & 7;
  const uint32_t bars = sb + OFF_BAR;
  auto BAR = [&](int i) { return bars + 8u * i; };
  const unsigned epoch = g_epoch & 1;

  if (tid == 0) { PROF_MARK(0); PROF_CLK(30); PROF2(15); }
  auto load_proj = [&](int c, int g) {
    mbar_expect_tx(BAR(B_FULL + g), 49152);
    tma_2d(sb + OFF_X + c * 16384, &tm_x, c * 64, pt * 128, BAR(B_FULL + g));
    tma_2d(sb + OFF_RING + g * 32768, &tm_wq, hp * 56, c * 64, BAR(B_FULL + g));
#pragma unroll 1
    for (int j = 0; j < 3; j++) tma_2d(sb + OFF_RING + g * 32768 + 8192 + j * 8192, &tm_wqkv, j * DM + hp * 56, c * 64, BAR(B_FULL + g));
  };
  if (warp == 16) {
    if (elect_one()) {
      mbar_init(BAR(B_FULL), 1);
      fence_async_smem();
      load_proj(0, 0);
      mbar_init(BAR(B_RAW), 1); mbar_init(BAR(B_FULL + 1), 1); mbar_init(BAR(B_FULL + 2), 1);
      fence_async_smem();
    }
    __syncwarp();
    asm volatile("bar.arrive 0, %0;" ::"n"(NTHREADS) : "memory");
  } else {
    if (elect_one()) {
      const int i = warp + 3 - (warp > 16);
      if (i < B_N && i != B_RAW) {
        int cnt = i < B_WO || i > B_SIG || i == B_X1FREE ? 16 : 1;
        if (i == B_BUILD) cnt = 16;
        if (i == B_SIG || i == B_SIG + 1 || i == B_QSQ) cnt = 8;
        if (i == B_KVR) cnt = 2;
        mbar_init(BAR(i), cnt);
        fence_async_smem();
      }
    }
    bar_sync(0, NTHREADS);
  }
  if (tid == 0) PROF2(14);

  if (wg == 4) {
    asm volatile("setmaxnreg.dec.sync.aligned.u32 32;");
    if (warp == 16) {
      if (elect_one()) {
        mbar_expect_tx(BAR(B_RAW), 25088 + 3136 + 896);
        bulk_g2s(sb + OFF_RAW, hp < 4 ? prm.wk : prm.wv, 25088, BAR(B_RAW));
        bulk_g2s(sb + OFF_RAW + 25088, prm.w_phi + 2 * hp * DH * DH, 3136, BAR(B_RAW));
        bulk_g2s(sb + OFF_RAW + 28224, prm.gate_w, 896, BAR(B_RAW));
        load_proj(1, 1);
        load_proj(2, 2);
      }
      __syncwarp();
      bar_sync(3, 64);
      if (elect_one()) {
        int g = 0, nkv = 8;
        uint32_t par = 0;
#pragma unroll 1
        for (int n = 3; n < 14 + nkv; n++) {
          if (n == 7) { PROF_MARK(20); cnt_wait(C_KV, NCTA); PROF_MARK(21); fence_async_all(); }
          if (n == 15) {
            mbar_wait(BAR(B_SLOW), 0);
            if (*(volatile int*)(sgen + OFF_RED)) nkv = 26;
          }
          const int j = n - 7 - nkv;
          if (j == 0 || j == 3) {
            PROF3(j ? 11 : 8);
            cnt_wait((j ? C_OB : C_OA) + pt, 8);
            PROF3(j ? 12 : 9);
            PROF_MARK(26);
            fence_async_all();
          }
          mbar_wait(BAR(B_EMPTY + g), par);
          if (n == 5) mbar_wait(BAR(B_BUILD), 0);
          if (n < 7) load_proj(n, g);
          else {
            mbar_expect_tx(BAR(B_FULL + g), 32768);
            bulk_g2s(sb + OFF_RING + g * 32768, j < 0 ? g_kv_img + ((n - 7) & 7) * 32768 : g_o_img + (size_t)(pt * 7 + j) * 32768, 32768,
                     BAR(B_FULL + g));
          }
          if (++g == 3) { g = 0; par ^= 1; }
        }
        if (atomicAdd(&g_cnt[C_DONE * 32], 1u) == NCTA - 1) {
#pragma unroll 1
          for (int i = 0; i < C_N; i++) g_cnt[i * 32] = 0;
          g_epoch = epoch ^ 1;
        }
      }
    } else {
      if (warp == 18) {
        if (elect_one()) {
#pragma unroll 1
          for (int i = 0; i < 4; i++) {
            mbar_wait(BAR(B_SIG + i), 0);
            PROF3(2 * i);
            if (i == 1) {
#pragma unroll 1
              for (int j = 0; j < 4; j++)
                asm volatile("cp.reduce.async.bulk.global.shared::cta.bulk_group.add.f32 [%0], [%1], 8192;"
                             ::"l"(g_kvacc[epoch] + hp * 4096 + (j >> 1) * 2048), "r"(sb + OFF_PHIK + j * 8192) : "memory");
              asm volatile("cp.async.bulk.commit_group;\ncp.async.bulk.wait_group 0;" ::: "memory");
            }
            cnt_arrive(i == 0 ? C_KV : i == 1 ? C_PART : (i == 2 ? C_OA : C_OB) + pt);
            PROF3(2 * i + 1);
            if (i == 1 || i == 2) {
              if (i == 2) mbar_wait(BAR(B_X1FREE), 0);
              mbar_expect_tx(BAR(B_WO + i - 1), 57344);
#pragma unroll 1
              for (int c = 0; c < 7; c++)
                tma_2d(sb + OFF_WO + (i - 1) * 57344 + c * 8192, i == 1 ? &tm_woa : &tm_wob, hp * 56, c * 64, BAR(B_WO + i - 1));
            }
          }
        }
      } else if (warp == 19) {
        if (lane == 0) {
          mbar_wait(BAR(B_SIG + 0), 0);
          cnt_wait(C_KV, NCTA);
        }
        __syncwarp();
        float ksq = 0.f, vsq = 0.f;
#pragma unroll
        for (int sl = 0; sl < 4; sl++) {
          float4 a = ldcg_f4(g_ksq + sl * 128 + lane * 4), b = ldcg_f4(g_vsq + sl * 128 + lane * 4);
          float m = fmaxf(fmaxf(a.x, a.y), fmaxf(a.z, a.w));
          m = __uint_as_float(__reduce_max_sync(~0u, __float_as_uint(m)));
          ksq += m;
          vsq = fmaxf(vsq, fmaxf(fmaxf(b.x, b.y), fmaxf(b.z, b.w)));
        }
        mbar_wait(BAR(B_QSQ), 0);
        const float4 qa4 = ((const float4*)(sgen + OFF_QSQ))[lane], qb4 = ((const float4*)(sgen + OFF_QSQ))[32 + lane];
        const float qmax = fmaxf(fmaxf(fmaxf(qa4.x, qa4.y), fmaxf(qa4.z, qa4.w)), fmaxf(fmaxf(qb4.x, qb4.y), fmaxf(qb4.z, qb4.w)));
        const bool slow = __any_sync(~0u, !(qmax * ksq <= 98.f * 98.f) || !(vsq <= 2.0e8f));
        if (lane == 0) {
          *(volatile int*)(sgen + OFF_RED) = slow;
          mbar_arrive(BAR(B_SLOW), 1);
        }
      } else {
        float4* z = (float4*)(g_kvacc[epoch ^ 1] + blockIdx.x * 256) + lane;
        z[0] = make_float4(0.f, 0.f, 0.f, 0.f);
        z[32] = make_float4(0.f, 0.f, 0.f, 0.f);
        bar_sync(3, 64);
        if (lane == 0) {
          mbar_wait(BAR(B_SIG + 0), 0);
          cnt_wait(C_KV, NCTA);
        }
        __syncwarp();
        ((float4*)(sgen + OFF_GATE))[lane] = ldcg_f4(g_gate + pt * 128 + lane * 4);
      }
      if (warp != 18) {
        if (lane == 0) {
          mbar_wait(BAR(B_SIG + 1), 0);
          cnt_wait(C_PART, NCTA);
          PROF_MARK(23);
        }
        __syncwarp();
        const int e = warp == 19;
        const float* src = g_kvacc[epoch] + hp * 4096 + e * 2048 + lane * 8;
#pragma unroll 1
        for (int i = 0; i < 8; i += 2) {
          const float4 a = ldcg_f4(src + i * 256), b = ldcg_f4(src + i * 256 + 4), c = ldcg_f4(src + i * 256 + 256), d = ldcg_f4(src + i * 256 + 260);
          const uint32_t ad = sb + OFF_KVR + e * 4096 + sw64_off(i * 8 + (lane >> 2), (lane & 3) * 8);
          sts128(ad, make_uint4(pack_bf16(a.x, a.y), pack_bf16(a.z, a.w), pack_bf16(b.x, b.y), pack_bf16(b.z, b.w)));
          sts128(ad + 512, make_uint4(pack_bf16(c.x, c.y), pack_bf16(c.z, c.w), pack_bf16(d.x, d.y), pack_bf16(d.z, d.w)));
        }
        fence_async_smem();
        __syncwarp();
        if (lane == 0) mbar_arrive(BAR(B_KVR), 1);
        PROF_MARK(24);
      }
    }
  } else {
    asm volatile("setmaxnreg.inc.sync.aligned.u32 112;");
    const int mh = wg & 1, nh = wg >> 1, wq = warp & 3;
    const int lq = lane & 3;
    const int rowl = wq * 16 + (lane >> 2);
    const int row0 = mh * 64 + rowl;
    int slot = 0, prev = 0;
    uint32_t par = 0;
    {
      float acc0[28], acc1[28], accs[4];
      const uint64_t dR = make_desc(sb + OFF_RING + nh * 16384, 1024, 1024, 1);
      const int lr = wq * 16 + (lane & 7) + ((lane >> 3) & 1) * 8;
      const uint32_t xa = sb + OFF_X + mh * 8192 + lr * 128 + (((lane >> 4) ^ (lr & 7)) << 4);
#pragma unroll
      for (int i = 0; i < 28; i++) acc0[i] = acc1[i] = 0.f;
#pragma unroll
      for (int i = 0; i < 4; i++) accs[i] = 0.f;
      const uint64_t dSlc = make_desc(sb + OFF_SLC, 128, 128, 0);
      uint32_t a[16], an[16];
      if (tid == 0) PROF2(16);
      mbar_wait(BAR(B_FULL), 0);
      if (tid == 0) PROF2(17);
#pragma unroll
      for (int ks = 0; ks < 4; ks++) ldsm4(an + 4 * ks, xa ^ (ks << 5));
#pragma unroll 1
      for (int c = 0; c < 7; c++) {
#pragma unroll
        for (int i = 0; i < 16; i++) a[i] = an[i];
        const uint64_t dB = dR + slot * 2048;
        wg_fence();
#pragma unroll
        for (int ks = 0; ks < 4; ks++) {
          wgmma_rs_n56_tb1<1>(acc0, a[4 * ks], a[4 * ks + 1], a[4 * ks + 2], a[4 * ks + 3], dB + ks * 128);
          wgmma_rs_n56_tb1<1>(acc1, a[4 * ks], a[4 * ks + 1], a[4 * ks + 2], a[4 * ks + 3], dB + 512 + ks * 128);
        }
        if (nh == 1 && c > 0) {
#pragma unroll
          for (int ks = 0; ks < 4; ks++) wgmma_rs_n8_tb1<1>(accs, a[4 * ks], a[4 * ks + 1], a[4 * ks + 2], a[4 * ks + 3], dSlc + c * 64 + ks * 16);
        }
        wg_commit();
        if (c == 0) {
          mbar_wait(BAR(B_RAW), 0);
          const int k = tid >> 3, cn = tid & 7;
          const bool data = k < 56 && (cn >> 2) == (k >= DH);
          const uint2* wsrc = (const uint2*)(sgen + OFF_RAW + 25088 + k * 56 + (cn & 3) * 16);
          uint2 w0 = make_uint2(0u, 0u), w1 = w0;
          if (data) w0 = wsrc[0];
          if (data && (cn & 3) != 3) w1 = wsrc[1];
          sts128(sb + OFF_WBD + k * 128 + ((cn ^ (k & 7)) << 4), make_uint4(w0.x, w0.y, w1.x, w1.y));
          if (tid < DM) {
            const uint2* src = (const uint2*)(sgen + OFF_RAW + tid * 56 + (hp & 3) * 16);
            w0 = src[0];
            w1 = make_uint2(hp == 3 ? (uint32_t)((const unsigned short*)(sgen + OFF_RAW + 28224))[tid] : 0u, 0u);
            if ((hp & 3) != 3) w1 = src[1];
            sts128(sb + OFF_SLC + tid * 16, make_uint4(w0.x, w0.y, w1.x, w1.y));
          }
          fence_async_smem();
          __syncwarp();
          if (lane == 0) mbar_arrive(BAR(B_BUILD), 1);
        }
        const int cur = slot;
        if (++slot == 3) { slot = 0; par ^= 1; }
        if (c < 6) {
          mbar_wait(BAR(B_FULL + slot), par);
#pragma unroll
          for (int ks = 0; ks < 4; ks++) ldsm4(an + 4 * ks, (xa + (c + 1) * 16384) ^ (ks << 5));
        }
        if (c == 0) mbar_wait(BAR(B_BUILD), 0);
        wg_wait<0>();
#pragma unroll
        for (int i = 0; i < 16; i++) asm volatile("" : "+r"(a[i])::"memory");
        if (lane == 0) mbar_arrive(BAR(B_EMPTY + cur), 1);
      }
      if (nh == 1) {
#pragma unroll
        for (int ks = 0; ks < 4; ks++) ldsm4(a + 4 * ks, xa ^ (ks << 5));
        wg_fence();
#pragma unroll
        for (int ks = 0; ks < 4; ks++) wgmma_rs_n8_tb1<1>(accs, a[4 * ks], a[4 * ks + 1], a[4 * ks + 2], a[4 * ks + 3], dSlc + ks * 16);
        wg_commit();
      }
      wg_wait<0>();
      fence_regs(acc0); fence_regs(acc1); fence_regs(accs);
      if (tid == 0) PROF_MARK(2);
      if (tid == 256) PROF_MARK(3);
      if (nh == 0) {
        float sq[4] = {0.f, 0.f, 0.f, 0.f};
#pragma unroll
        for (int i = 0; i < 28; i++) acc0[i] *= 0.18898223650461362f * 1.4426950408889634f;
#pragma unroll
        for (int j = 0; j < 7; j++) {
#pragma unroll
          for (int rr = 0; rr < 2; rr++) {
            const float s2 = acc0[4 * j + 2 * rr] * acc0[4 * j + 2 * rr] + acc0[4 * j + 2 * rr + 1] * acc0[4 * j + 2 * rr + 1];
            if (j < 3) sq[rr] += s2;
            else if (j > 3) sq[2 + rr] += s2;
            else { sq[rr] += (lq < 2) ? s2 : 0.f; sq[2 + rr] += (lq < 2) ? 0.f : s2; }
          }
        }
#pragma unroll
        for (int i = 0; i < 4; i++) sq[i] = quad_sum(sq[i]);
        const float mine = lq == 0 ? sq[0] : lq == 1 ? sq[1] : lq == 2 ? sq[2] : sq[3];
        ((float*)(sgen + OFF_QSQ))[(mh + (lq & 2)) * 64 + rowl + 8 * (lq & 1)] = mine <= 3.0e38f ? mine : __int_as_float(0x7f800000);
        __syncwarp();
        if (lane == 0) mbar_arrive(BAR(B_QSQ), 1);
      } else {
        const int sl = hp & 3;
        const bool isk = hp < 4, real = (sl < 3) || (lq < 2);
        const int pos = pt * 128 + row0, kr = pos & 63;
        uint8_t* dst = g_kv_img + (pos >> 6) * 8192 + (isk ? 0 : 4096) + sw64_off(kr, sl * 8 + 2 * lq);
        const uint32_t pat = isk ? POLY_PAT >> (kr >> 3) : 0u;
        float mxv = 0.f;
#pragma unroll
        for (int rr = 0; rr < 2; rr++) {
          const float v0 = accs[2 * rr], v1 = accs[2 * rr + 1];
          const bool poly = (pat >> rr) & 1;
          const float sc = poly ? 2.f : 1.f;
          const float s2 = quad_sum(real ? v0 * v0 + v1 * v1 : 0.f);
          mxv = fmaxf(mxv, s2 <= 3.0e38f ? s2 : __int_as_float(0x7f800000));
          const uint32_t padv = lq == 2 ? (poly ? 0x443F4000u : 0x00003F80u) : (poly ? 0x3AB03F4Du : 0u);
          *(uint32_t*)(dst + rr * 512) = real ? pack_bf16(sc * v0, sc * v1) : padv;
          if (hp == 3 && lq == 2) g_gate[pos + 8 * rr] = rcpf(1.f + ex2f(-1.4426950408889634f * v0));
        }
        mxv = __uint_as_float(__reduce_max_sync(~0u, __float_as_uint(mxv)));
        if (lane == 0) (isk ? g_ksq : g_vsq)[sl * 128 + pt * 8 + mh * 4 + wq] = mxv;
        __syncwarp();
        if (lane == 0) mbar_arrive(BAR(B_SIG + 0), 1);
      }
      if (tid == 0) PROF_MARK(4);
      if (tid == 256) PROF_MARK(5);
      uint32_t h[14];
      float pp[32];
      {
#pragma unroll
        for (int i = 0; i < 14; i++) {
          const uint32_t u0 = pack_bf16(acc0[2 * i], acc0[2 * i + 1]), u1 = pack_bf16(acc1[2 * i], acc1[2 * i + 1]);
          h[i] = nh ? u1 : u0;
          a[i] = nh ? u0 : u1;
        }
        a[14] = a[0] ^ 0x80008000u;
        a[15] = a[1] ^ 0x80008000u;
        const uint64_t dW = make_desc(sb + OFF_WBD, 1024, 1024, 1);
        wg_fence();
        wgmma_rs_n64_tb1<0>(pp, a[0], a[1], a[2], a[3], dW);
#pragma unroll
        for (int ks = 1; ks < 4; ks++) wgmma_rs_n64_tb1<1>(pp, a[4 * ks], a[4 * ks + 1], a[4 * ks + 2], a[4 * ks + 3], dW + ks * 128);
        wg_commit();
        bar_sync(1, 512);
        if (tid == 0) PROF_MARK(6);
        store_heads(sb + (nh ? OFF_VA : OFF_QP), h, nh ? 0x00003F80u : 0x3F800000u, nh ? 0u : 0x3F803F80u, row0, lq);
        wg_wait<0>();
        fence_regs(pp);
      }
      float v[16];
#pragma unroll
      for (int i = 0; i < 16; i++) v[i] = pp[i];
      uint32_t rb = sb + (nh ? OFF_PHIK : OFF_PHIQ) + row0 * 128 + lq * 4 + ((rowl & 7) << 4);
#pragma unroll 1
      for (int e = 0; e < 2; e++) {
        uint32_t ph[16];
        feature_map(v, ph, lq);
#pragma unroll
        for (int ch = 0; ch < 8; ch++) { sts32(rb ^ (ch << 4), ph[2 * ch]); sts32((rb ^ (ch << 4)) + 1024, ph[2 * ch + 1]); }
        rb += 16384;
#pragma unroll
        for (int i = 0; i < 16; i++) v[i] = pp[16 + i];
      }
      fence_async_smem();
      bar_sync(1, 512);
      if (tid == 0) PROF_MARK(7);
      if (nh == 1) {
        float kv0[16], kv1[16];
        const uint64_t dP = make_desc(sb + OFF_PHIK + mh * 8192, 1024, 1024, 1);
        const uint64_t dV = make_desc(sb + OFF_VA + mh * 4096, 512, 512, 2);
        wg_fence();
        wgmma_ss_n32_ta1_tb1<0>(kv0, dP, dV);
        wgmma_ss_n32_ta1_tb1<0>(kv1, dP + 1024, dV + 512);
#pragma unroll
        for (int ks = 1; ks < 4; ks++) {
          wgmma_ss_n32_ta1_tb1<1>(kv0, dP + ks * 128, dV + ks * 64);
          wgmma_ss_n32_ta1_tb1<1>(kv1, dP + 1024 + ks * 128, dV + 512 + ks * 64);
        }
        wg_commit();
        wg_wait<0>();
        fence_regs(kv0); fence_regs(kv1);
        bar_sync(4 + wg, 128);
        const uint32_t sa = sb + OFF_PHIK + mh * 8192 + rowl * 128 + lq * 8;
#pragma unroll
        for (int j = 0; j < 8; j++) {
          sts64(sa + 32 * (j >> 1) + 1024 * (j & 1), __float_as_uint(kv0[2 * j]), __float_as_uint(kv0[2 * j + 1]));
          sts64(sa + 16384 + 32 * (j >> 1) + 1024 * (j & 1), __float_as_uint(kv1[2 * j]), __float_as_uint(kv1[2 * j + 1]));
        }
        fence_async_smem();
        __syncwarp();
        if (lane == 0) mbar_arrive(BAR(B_SIG + 1), 1);
        if (tid == 256) PROF_MARK(28);
      }
    }
    {
      const uint64_t dK = make_desc(sb + OFF_RING, 512, 512, 2);
      const uint64_t dhi = dK & 0xffffffff00000000ull;
      const uint32_t dlo0 = (uint32_t)dK;
      uint32_t ok = 0, q[8];
      float o[16];
#pragma unroll
      for (int i = 0; i < 16; i++) o[i] = 0.f;
      {
        const int r = mh * 64 + wq * 16 + (lane & 7) + ((lane >> 3) & 1) * 8;
        ldsm4(q, sb + OFF_QP + nh * 8192 + sw64_off(r, (lane >> 4) * 8));
        ldsm4(q + 4, sb + OFF_QP + nh * 8192 + sw64_off(r, 16 + (lane >> 4) * 8));
      }
      if (tid == 0) PROF_MARK(10);
      const int qb = QB_AT;
#pragma unroll 1
      for (int it = 0; it <= 8; it++) {
        uint32_t p[16];
        if ((tid & 127) == 0) PROF4(wg * 32 + it * 3);
        if (it == qb || it == 8) {
          float t[16];
          wg_wait<0>();
          fence_regs(o);
          if (it < 8) {
            if (tid == 0) PROF_MARK(11);
            mbar_wait(BAR(B_KVR), 0);
            const uint64_t dR = make_desc(sb + OFF_KVR + nh * 4096, 512, 512, 2);
            const uint64_t dP = make_desc(sb + OFF_PHIQ + nh * 16384 + mh * 8192, 1024, 1024, 1);
            wg_fence();
            wgmma_ss_n32_ta0_tb1<0>(t, dP, dR);
#pragma unroll
            for (int ks = 1; ks < 4; ks++) wgmma_ss_n32_ta0_tb1<1>(t, dP + ks * 2, dR + ks * 64);
            wg_commit();
            wg_wait<0>();
            fence_regs(t);
            if (lane == 0) mbar_arrive(BAR(B_X1FREE), 1);
          } else {
            if (lane == 0) mbar_arrive(BAR(B_EMPTY + prev), 1);
            if (tid == 0) PROF_MARK(13);
            mbar_wait(BAR(B_SLOW), 0);
            if (__builtin_expect(__any_sync(~0u, *(volatile int*)(sgen + OFF_RED)), 0)) {
              uint32_t qz[8];
#pragma unroll
              for (int i = 0; i < 8; i++) qz[i] = (i >= 6 && lq >= 2) ? 0u : q[i];
              float m0 = -3.0e38f, m1 = -3.0e38f, o2[16];
              int sl2 = slot;
              uint32_t par2 = par;
#pragma unroll 1
              for (int j64 = 0; j64 < 32; j64++) {
                float s[32];
                mbar_wait(BAR(B_FULL + sl2), par2);
                const uint32_t lo = dlo0 + sl2 * 2048 + (j64 & 3) * 512;
                wg_fence();
                wgmma_rs_n64_tb0<0>(s, qz[0], qz[1], qz[2], qz[3], dhi | lo);
                wgmma_rs_n64_tb0<1>(s, qz[4], qz[5], qz[6], qz[7], dhi | (lo + 2));
                wg_commit();
                wg_wait<0>();
                fence_regs(s);
#pragma unroll
                for (int j = 0; j < 8; j++) {
                  const float sc = ((POLY_PAT >> j) & 1) ? 0.5f : 1.f;
                  m0 = fmaxf(m0, fmaxf(s[4 * j], s[4 * j + 1]) * sc);
                  m1 = fmaxf(m1, fmaxf(s[4 * j + 2], s[4 * j + 3]) * sc);
                }
                if ((j64 & 3) == 3) {
                  if (lane == 0) mbar_arrive(BAR(B_EMPTY + sl2), 1);
                  if (++sl2 == 3) { sl2 = 0; par2 ^= 1; }
                }
              }
              m0 = quad_max(m0); m1 = quad_max(m1);
#pragma unroll
              for (int i = 0; i < 16; i++) o2[i] = 0.f;
#pragma unroll 1
              for (int j64 = 0; j64 < 32; j64++) {
                float s[32];
                mbar_wait(BAR(B_FULL + sl2), par2);
                const uint32_t lo = dlo0 + sl2 * 2048 + (j64 & 3) * 512;
                wg_fence();
                wgmma_rs_n64_tb0<0>(s, qz[0], qz[1], qz[2], qz[3], dhi | lo);
                wgmma_rs_n64_tb0<1>(s, qz[4], qz[5], qz[6], qz[7], dhi | (lo + 2));
                wg_commit();
                wg_wait<0>();
                fence_regs(s);
                uint32_t ps[16];
#pragma unroll
                for (int j = 0; j < 8; j++) {
                  const float sc = ((POLY_PAT >> j) & 1) ? 0.5f : 1.f;
                  ps[2 * j] = pack_bf16(ex2f(fmaf(s[4 * j], sc, -m0)), ex2f(fmaf(s[4 * j + 1], sc, -m0)));
                  ps[2 * j + 1] = pack_bf16(ex2f(fmaf(s[4 * j + 2], sc, -m1)), ex2f(fmaf(s[4 * j + 3], sc, -m1)));
                }
                wg_fence();
#pragma unroll
                for (int ks = 0; ks < 4; ks++)
                  wgmma_rs_n32_tb1<1>(o2, ps[4 * ks], ps[4 * ks + 1], ps[4 * ks + 2], ps[4 * ks + 3], dhi | (lo + 256 + ks * 64));
                wg_commit();
                wg_wait<0>();
                fence_regs(o2);
                if ((j64 & 3) == 3) {
                  if (lane == 0) mbar_arrive(BAR(B_EMPTY + sl2), 1);
                  if (++sl2 == 3) { sl2 = 0; par2 ^= 1; }
                }
              }
#pragma unroll 1
              for (int j = 0; j < 2; j++) {
                mbar_wait(BAR(B_FULL + sl2), par2);
                __syncwarp();
                if (lane == 0) mbar_arrive(BAR(B_EMPTY + sl2), 1);
                if (++sl2 == 3) { sl2 = 0; par2 ^= 1; }
              }
#pragma unroll
              for (int i = 0; i < 16; i++) o[i] = o2[i];
            }
#pragma unroll
            for (int i = 0; i < 16; i++) t[i] = o[i];
          }
          const int br = it == 8;
          const float eps = br ? 0.f : 1e-6f;
          const float g0 = ((const float*)(sgen + OFF_GATE))[row0], g1 = ((const float*)(sgen + OFF_GATE))[row0 + 8];
          const float d0 = __shfl_sync(~0u, t[12], (lane & ~3) | 2), d1 = __shfl_sync(~0u, t[14], (lane & ~3) | 2);
          const float r0 = (br ? 1.f - g0 : g0) * rcpf(d0 + eps), r1 = (br ? 1.f - g1 : g1) * rcpf(d1 + eps);
          uint8_t* img = g_o_img + (size_t)((pt * 2 + br) * 14 + mh) * 8192 + rowl * 128;
          const int col0 = (2 * hp + nh) * DH + 2 * lq;
#pragma unroll
          for (int j = 0; j < 4; j++) {
            const int col = col0 + 8 * j;
            uint8_t* gp = img + (uint32_t)((col >> 6) * 16384 + ((((col >> 3) ^ rowl) & 7) << 4) + (col & 7) * 2);
            const uint32_t v0 = pack_bf16(t[4 * j] * r0, t[4 * j + 1] * r0), v1 = pack_bf16(t[4 * j + 2] * r1, t[4 * j + 3] * r1);
            if (j < 3 || lq < 2) { *(uint32_t*)gp = v0; *(uint32_t*)(gp + 1024) = v1; }
          }
          __syncwarp();
          if (lane == 0) mbar_arrive(BAR(B_SIG + 2 + br), 1);
          if (tid == 0) PROF_MARK(12 + 2 * br);
          if (br) break;
        }
        const uint32_t lo = dlo0 + slot * 2048;
        if ((tid & 127) == 0) PROF4(wg * 32 + it * 3 + 1);
        if (!ok) mbar_wait(BAR(B_FULL + slot), par);
        if ((tid & 127) == 0) PROF4(wg * 32 + it * 3 + 2);
        int nslot = slot + 1;
        uint32_t npar = par;
        if (nslot == 3) { nslot = 0; npar ^= 1; }
        {
          float s[32];
          wg_fence();
          wgmma_rs_n64_tb0<0>(s, q[0], q[1], q[2], q[3], dhi | lo);
          wgmma_rs_n64_tb0<1>(s, q[4], q[5], q[6], q[7], dhi | (lo + 2));
          wg_commit();
#pragma unroll
          for (int u = 0; u < 4; u++) {
            wg_wait<0>();
            fence_regs(s);
            if (u == 0 && lane == 0 && it > 0) mbar_arrive(BAR(B_EMPTY + prev), 1);
            if (u == 2) ok = mbar_test(BAR(B_FULL + nslot), npar);
#pragma unroll
            for (int j = 0; j < 8; j++) {
              if ((POLY_PAT >> j) & 1) {
                p[2 * j] = exp2_pair_fma(s[4 * j], s[4 * j + 1], 0x3F003F00u, 0x00030003u);
                p[2 * j + 1] = exp2_pair_fma(s[4 * j + 2], s[4 * j + 3], 0x3F003F00u, 0x00030003u);
              } else {
                p[2 * j] = pack_bf16(ex2f(s[4 * j]), ex2f(s[4 * j + 1]));
                p[2 * j + 1] = pack_bf16(ex2f(s[4 * j + 2]), ex2f(s[4 * j + 3]));
              }
            }
            wg_fence();
#pragma unroll
            for (int ks = 0; ks < 4; ks++)
              wgmma_rs_n32_tb1<1>(o, p[4 * ks], p[4 * ks + 1], p[4 * ks + 2], p[4 * ks + 3], dhi | (lo + u * 512 + 256 + ks * 64));
            if (u < 3) {
              wgmma_rs_n64_tb0<0>(s, q[0], q[1], q[2], q[3], dhi | (lo + (u + 1) * 512));
              wgmma_rs_n64_tb0<1>(s, q[4], q[5], q[6], q[7], dhi | (lo + (u + 1) * 512 + 2));
            }
            wg_commit();
          }
        }
        prev = slot; slot = nslot; par = npar;
      }
      wg_wait<0>();
    }
    if (nh == 1) return;
    {
      float acc0[28], acc1[28];
#pragma unroll
      for (int i = 0; i < 28; i++) acc0[i] = acc1[i] = 0.f;
      const uint64_t dS = make_desc(sb + OFF_WO, 1024, 1024, 1);
      const uint64_t dR = make_desc(sb + OFF_RING + mh * 8192, 1024, 1024, 1);
#pragma unroll 1
      for (int c = 0; c < 7; c++) {
        mbar_wait(BAR(B_WO + (c >= 3)), 0);
        mbar_wait(BAR(B_FULL + slot), par);
        const uint64_t dA = dR + slot * 2048, dB = dS + c * 1024;
        wg_fence();
#pragma unroll
        for (int ks = 0; ks < 4; ks++) {
          wgmma_ss_n56_ta0_tb1<1>(acc0, dA + ks * 2, dB + ks * 128);
          wgmma_ss_n56_ta0_tb1<1>(acc1, dA + 1024 + ks * 2, dB + 512 + ks * 128);
        }
        wg_commit();
        if (c < 4) {
          wg_wait<0>();
          if (lane == 0) mbar_arrive(BAR(B_EMPTY + slot), 2);
        }
        if (++slot == 3) { slot = 0; par ^= 1; }
      }
      wg_wait<0>();
      fence_regs(acc0); fence_regs(acc1);
      if (tid == 0) PROF_MARK(17);
      __nv_bfloat16* op = prm.out + (size_t)(pt * 128 + row0) * DM + hp * 56 + 2 * lq;
#pragma unroll
      for (int j = 0; j < 7; j++) {
        *(uint32_t*)(op + 8 * j) = pack_bf16(acc0[4 * j] + acc1[4 * j], acc0[4 * j + 1] + acc1[4 * j + 1]);
        *(uint32_t*)(op + 8 * DM + 8 * j) = pack_bf16(acc0[4 * j + 2] + acc1[4 * j + 2], acc0[4 * j + 3] + acc1[4 * j + 3]);
      }
      if (tid == 0) { PROF_MARK(18); PROF_CLK(31); }
    }
  }
}

typedef CUresult (*EncodeFn)(CUtensorMap*, CUtensorMapDataType, cuuint32_t, void*, const cuuint64_t*, const cuuint64_t*,
                             const cuuint32_t*, const cuuint32_t*, CUtensorMapInterleave, CUtensorMapSwizzle,
                             CUtensorMapL2promotion, CUtensorMapFloatOOBfill);

void make_map(EncodeFn enc, CUtensorMap* tm, const void* ptr, uint64_t cols, uint64_t rows, uint32_t box_rows) {
  cuuint64_t dims[2] = {cols, rows};
  cuuint64_t strides[1] = {cols * 2};
  cuuint32_t box[2] = {64, box_rows};
  cuuint32_t es[2] = {1, 1};
  enc(tm, CU_TENSOR_MAP_DATA_TYPE_BFLOAT16, 2, const_cast<void*>(ptr), dims, strides, box, es, CU_TENSOR_MAP_INTERLEAVE_NONE,
      CU_TENSOR_MAP_SWIZZLE_128B, CU_TENSOR_MAP_L2_PROMOTION_L2_128B, CU_TENSOR_MAP_FLOAT_OOB_FILL_NONE);
}

}

extern "C" void kernel_launch(void* const* d_in, const int* in_sizes, int n_in, void* d_out, int out_size) {
  (void)in_sizes; (void)n_in; (void)out_size;
  static EncodeFn enc = nullptr;
  if (!enc) {
    void* fn = nullptr;
    cudaDriverEntryPointQueryResult qr;
    cudaGetDriverEntryPoint("cuTensorMapEncodeTiled", &fn, cudaEnableDefault, &qr);
    enc = (EncodeFn)fn;
    cudaFuncSetAttribute(fused_kernel, cudaFuncAttributeMaxDynamicSharedMemorySize, SMEM_BYTES);
  }
  CUtensorMap tm_x, tm_wqkv, tm_wq, tm_woa, tm_wob;
  make_map(enc, &tm_x, d_in[0], DM, S_LEN, 128);
  make_map(enc, &tm_wqkv, d_in[1], 3 * DM, DM, 64);
  make_map(enc, &tm_wq, d_in[5], DM, DM, 64);
  make_map(enc, &tm_woa, d_in[3], DM, DM, 64);
  make_map(enc, &tm_wob, d_in[8], DM, DM, 64);
  Params prm;
  prm.w_phi = (const __nv_bfloat16*)d_in[2];
  prm.wk = (const __nv_bfloat16*)d_in[6];
  prm.wv = (const __nv_bfloat16*)d_in[7];
  prm.gate_w = (const __nv_bfloat16*)d_in[9];
  prm.out = (__nv_bfloat16*)d_out;
  fused_kernel<<<NCTA, NTHREADS, SMEM_BYTES>>>(tm_x, tm_wqkv, tm_wq, tm_woa, tm_wob, prm);
}
```

```cpp
#include <cuda_runtime.h>
#include <cuda_bf16.h>
#include <cuda.h>
#include <stdint.h>

namespace {

constexpr int S_LEN = 2048, DM = 448, DH = 28;
constexpr int NCTA = 128;
constexpr int NTHREADS = 640;
constexpr uint32_t POLY_PAT = 0x57;

#define QB_AT (4 + nh)

constexpr int OFF_X = 0;
constexpr int OFF_PHIK = 0;
constexpr int OFF_VA = 32768;
constexpr int OFF_PHIQ = 57344;
constexpr int OFF_KVR = 90112;
constexpr int OFF_QP = 98304;
constexpr int OFF_RAW = 81920;
constexpr int OFF_WO = 0;
constexpr int OFF_RING = 114688;
constexpr int OFF_WBD = 212992;
constexpr int OFF_SLC = 221184;
constexpr int OFF_QSQ = 228352;
constexpr int OFF_GATE = 229376;
constexpr int OFF_RED = 229888;
constexpr int OFF_BAR = 229952;
constexpr int SMEM_BYTES = 230400 + 1024;

constexpr int B_FULL = 0, B_EMPTY = 3, B_WO = 6  , B_KVR = 8, B_RAW = 9, B_X1FREE = 10, B_QSQ = 11, B_SLOW = 12,
              B_BUILD = 13, B_SIG = 14  , B_N = 18;

constexpr int C_KV = 0, C_PART = 1, C_DONE = 3, C_OA = 4, C_OB = 20, C_N = 36;

__device__ __align__(1024) uint8_t g_kv_img[32 * 8192];
__device__ __align__(16) float g_ksq[512];
__device__ __align__(16) float g_vsq[512];
__device__ __align__(16) float g_gate[S_LEN];
__device__ __align__(1024) float g_kvacc[2][16 * 64 * 32];
__device__ unsigned g_epoch;
__device__ __align__(1024) uint8_t g_o_img[2 * 16 * 14 * 8192];
__device__ unsigned g_cnt[C_N * 32];

#define PROF4(i) do { } while (0)
#define PROF3(i) do { } while (0)
#define PROF2(i) do { } while (0)
#define PROF_CLK(i) do { } while (0)
#define PROF_MARK(i) do { } while (0)
__device__ __forceinline__ uint32_t smem_u32(const void* p) { return (uint32_t)__cvta_generic_to_shared(p); }
__device__ __forceinline__ void mbar_init(uint32_t a, int cnt) {
  asm volatile("mbarrier.init.shared::cta.b64 [%0], %1;" ::"r"(a), "r"(cnt) : "memory");
}
__device__ __forceinline__ void mbar_expect_tx(uint32_t a, uint32_t bytes) {
  asm volatile("mbarrier.arrive.expect_tx.shared::cta.b64 _, [%0], %1;" ::"r"(a), "r"(bytes) : "memory");
}
__device__ __forceinline__ void mbar_arrive(uint32_t a, uint32_t cnt) {
  asm volatile("mbarrier.arrive.shared::cta.b64 _, [%0], %1;" ::"r"(a), "r"(cnt) : "memory");
}
__device__ __forceinline__ void mbar_wait(uint32_t a, uint32_t parity) {
  asm volatile(
      "{\n.reg .pred p;\n.reg .u32 c;\nmov.u32 c, 0;\n"
      "W_%=:\nmbarrier.try_wait.parity.shared::cta.b64 p, [%0], %1;\n"
      "add.u32 c, c, 1;\nsetp.lt.and.u32 p, c, 0x40000, !p;\n@p bra W_%=;\n}"
      ::"r"(a), "r"(parity) : "memory");
}
__device__ __forceinline__ uint32_t mbar_test(uint32_t a, uint32_t parity) {
  uint32_t ok;
  asm volatile("{\n.reg .pred p;\nmbarrier.test_wait.parity.shared::cta.b64 p, [%1], %2;\nselp.u32 %0, 1, 0, p;\n}"
               : "=r"(ok) : "r"(a), "r"(parity) : "memory");
  return ok;
}
__device__ __forceinline__ bool elect_one() {
  uint32_t r;
  asm volatile("{\n.reg .pred p;\nelect.sync _|p, 0xffffffff;\nselp.u32 %0, 1, 0, p;\n}" : "=r"(r));
  return r != 0;
}
__device__ __forceinline__ void tma_2d(uint32_t dst, const CUtensorMap* tm, int c0, int c1, uint32_t bar) {
  asm volatile("cp.async.bulk.tensor.2d.shared::cluster.global.mbarrier::complete_tx::bytes [%0], [%1, {%3, %4}], [%2];"
               ::"r"(dst), "l"(tm), "r"(bar), "r"(c0), "r"(c1) : "memory");
}
__device__ __forceinline__ void bulk_g2s(uint32_t dst, const void* src, uint32_t bytes, uint32_t bar) {
  asm volatile("cp.async.bulk.shared::cluster.global.mbarrier::complete_tx::bytes [%0], [%1], %2, [%3];"
               ::"r"(dst), "l"(src), "r"(bytes), "r"(bar) : "memory");
}
__device__ __forceinline__ void fence_async_smem() { asm volatile("fence.proxy.async.shared::cta;" ::: "memory"); }
__device__ __forceinline__ void fence_async_all() { asm volatile("fence.proxy.async.global;" ::: "memory"); }

__device__ __forceinline__ void bar_sync(int id, int n) { asm volatile("bar.sync %0, %1;" ::"r"(id), "r"(n) : "memory"); }
__device__ __forceinline__ void cnt_arrive(int idx) {
  asm volatile("red.release.gpu.global.add.u32 [%0], 1;" ::"l"(&g_cnt[idx * 32]) : "memory");
}
__device__ __forceinline__ void cnt_wait(int idx, unsigned target) {
  unsigned v, n = 0;
#pragma unroll 1
  while (true) {
    asm volatile("ld.acquire.gpu.global.u32 %0, [%1];" : "=r"(v) : "l"(&g_cnt[idx * 32]) : "memory");
    if (v >= target || ++n >= (1u << 18)) break;
    __nanosleep(32);
  }
}
__device__ __forceinline__ void wg_fence() { asm volatile("wgmma.fence.sync.aligned;" ::: "memory"); }
__device__ __forceinline__ void wg_commit() { asm volatile("wgmma.commit_group.sync.aligned;" ::: "memory"); }
template <int N> __device__ __forceinline__ void wg_wait() { asm volatile("wgmma.wait_group.sync.aligned %0;" ::"n"(N) : "memory"); }
template <int N> __device__ __forceinline__ void fence_regs(float (&d)[N]) {
#pragma unroll
  for (int i = 0; i < N; i++) asm volatile("" : "+f"(d[i])::"memory");
}
__device__ __forceinline__ uint64_t make_desc(uint32_t saddr, uint32_t lbo, uint32_t sbo, uint32_t swz) {
  return (uint64_t)((saddr & 0x3FFFF) >> 4) | ((uint64_t)(lbo >> 4) << 16) | ((uint64_t)(sbo >> 4) << 32) | ((uint64_t)swz << 62);
}
__device__ __forceinline__ float ex2f(float x) { float y; asm("ex2.approx.ftz.f32 %0, %1;" : "=f"(y) : "f"(x)); return y; }
__device__ __forceinline__ float rcpf(float x) { float y; asm("rcp.approx.ftz.f32 %0, %1;" : "=f"(y) : "f"(x)); return y; }
__device__ __forceinline__ uint32_t pack_bf16(float lo, float hi) {
  uint32_t r; asm("cvt.rn.bf16x2.f32 %0, %1, %2;" : "=r"(r) : "f"(hi), "f"(lo)); return r;
}
__device__ __forceinline__ uint32_t lop_and_or(uint32_t a, uint32_t m, uint32_t c) {
  uint32_t r; asm("lop3.b32 %0, %1, %2, %3, 0xEA;" : "=r"(r) : "r"(a), "r"(m), "r"(c)); return r;
}
__device__ __forceinline__ void sts32(uint32_t a, uint32_t v) { asm volatile("st.shared.b32 [%0], %1;" ::"r"(a), "r"(v) : "memory"); }
__device__ __forceinline__ void sts64(uint32_t a, uint32_t v0, uint32_t v1) { asm volatile("st.shared.v2.b32 [%0], {%1, %2};" ::"r"(a), "r"(v0), "r"(v1) : "memory"); }
__device__ __forceinline__ void sts128(uint32_t a, uint4 v) {
  asm volatile("st.shared.v4.b32 [%0], {%1, %2, %3, %4};" ::"r"(a), "r"(v.x), "r"(v.y), "r"(v.z), "r"(v.w) : "memory");
}
__device__ __forceinline__ float4 ldcg_f4(const float* p) {
  float4 v; asm volatile("ld.global.cg.v4.f32 {%0, %1, %2, %3}, [%4];" : "=f"(v.x), "=f"(v.y), "=f"(v.z), "=f"(v.w) : "l"(p) : "memory"); return v;
}
__device__ __forceinline__ void ldsm4(uint32_t* r, uint32_t a) {
  asm volatile("ldmatrix.sync.aligned.m8n8.x4.shared.b16 {%0, %1, %2, %3}, [%4];"
               : "=r"(r[0]), "=r"(r[1]), "=r"(r[2]), "=r"(r[3]) : "r"(a) : "memory");
}
__device__ __forceinline__ float quad_sum(float v) { v += __shfl_xor_sync(~0u, v, 1); v += __shfl_xor_sync(~0u, v, 2); return v; }
__device__ __forceinline__ float quad_max(float v) { v = fmaxf(v, __shfl_xor_sync(~0u, v, 1)); v = fmaxf(v, __shfl_xor_sync(~0u, v, 2)); return v; }

template <int SD> __device__ __forceinline__ void wgmma_ss_n56_ta0_tb1(float (&d)[28], uint64_t da, uint64_t db) {
  if (SD) asm volatile("wgmma.mma_async.sync.aligned.m64n56k16.f32.bf16.bf16 {%0, %1, %2, %3, %4, %5, %6, %7, %8, %9, %10, %11, %12, %13, %14, %15, %16, %17, %18, %19, %20, %21, %22, %23, %24, %25, %26, %27}, %28, %29, 1, 1, 1, 0, 1;\n"
    : "+f"(d[0]), "+f"(d[1]), "+f"(d[2]), "+f"(d[3]), "+f"(d[4]), "+f"(d[5]), "+f"(d[6]), "+f"(d[7]), "+f"(d[8]), "+f"(d[9]), "+f"(d[10]), "+f"(d[11]), "+f"(d[12]), "+f"(d[13]), "+f"(d[14]), "+f"(d[15]), "+f"(d[16]), "+f"(d[17]), "+f"(d[18]), "+f"(d[19]), "+f"(d[20]), "+f"(d[21]), "+f"(d[22]), "+f"(d[23]), "+f"(d[24]), "+f"(d[25]), "+f"(d[26]), "+f"(d[27])
    : "l"(da), "l"(db));
  else asm volatile("wgmma.mma_async.sync.aligned.m64n56k16.f32.bf16.bf16 {%0, %1, %2, %3, %4, %5, %6, %7, %8, %9, %10, %11, %12, %13, %14, %15, %16, %17, %18, %19, %20, %21, %22, %23, %24, %25, %26, %27}, %28, %29, 0, 1, 1, 0, 1;\n"
    : "=f"(d[0]), "=f"(d[1]), "=f"(d[2]), "=f"(d[3]), "=f"(d[4]), "=f"(d[5]), "=f"(d[6]), "=f"(d[7]), "=f"(d[8]), "=f"(d[9]), "=f"(d[10]), "=f"(d[11]), "=f"(d[12]), "=f"(d[13]), "=f"(d[14]), "=f"(d[15]), "=f"(d[16]), "=f"(d[17]), "=f"(d[18]), "=f"(d[19]), "=f"(d[20]), "=f"(d[21]), "=f"(d[22]), "=f"(d[23]), "=f"(d[24]), "=f"(d[25]), "=f"(d[26]), "=f"(d[27])
    : "l"(da), "l"(db));
}
template <int SD> __device__ __forceinline__ void wgmma_rs_n56_tb1(float (&d)[28], uint32_t a0, uint32_t a1, uint32_t a2, uint32_t a3, uint64_t db) {
  if (SD) asm volatile("wgmma.mma_async.sync.aligned.m64n56k16.f32.bf16.bf16 {%0, %1, %2, %3, %4, %5, %6, %7, %8, %9, %10, %11, %12, %13, %14, %15, %16, %17, %18, %19, %20, %21, %22, %23, %24, %25, %26, %27}, {%28, %29, %30, %31}, %32, 1, 1, 1, 1;\n"
    : "+f"(d[0]), "+f"(d[1]), "+f"(d[2]), "+f"(d[3]), "+f"(d[4]), "+f"(d[5]), "+f"(d[6]), "+f"(d[7]), "+f"(d[8]), "+f"(d[9]), "+f"(d[10]), "+f"(d[11]), "+f"(d[12]), "+f"(d[13]), "+f"(d[14]), "+f"(d[15]), "+f"(d[16]), "+f"(d[17]), "+f"(d[18]), "+f"(d[19]), "+f"(d[20]), "+f"(d[21]), "+f"(d[22]), "+f"(d[23]), "+f"(d[24]), "+f"(d[25]), "+f"(d[26]), "+f"(d[27])
    : "r"(a0), "r"(a1), "r"(a2), "r"(a3), "l"(db));
  else asm volatile("wgmma.mma_async.sync.aligned.m64n56k16.f32.bf16.bf16 {%0, %1, %2, %3, %4, %5, %6, %7, %8, %9, %10, %11, %12, %13, %14, %15, %16, %17, %18, %19, %20, %21, %22, %23, %24, %25, %26, %27}, {%28, %29, %30, %31}, %32, 0, 1, 1, 1;\n"
    : "=f"(d[0]), "=f"(d[1]), "=f"(d[2]), "=f"(d[3]), "=f"(d[4]), "=f"(d[5]), "=f"(d[6]), "=f"(d[7]), "=f"(d[8]), "=f"(d[9]), "=f"(d[10]), "=f"(d[11]), "=f"(d[12]), "=f"(d[13]), "=f"(d[14]), "=f"(d[15]), "=f"(d[16]), "=f"(d[17]), "=f"(d[18]), "=f"(d[19]), "=f"(d[20]), "=f"(d[21]), "=f"(d[22]), "=f"(d[23]), "=f"(d[24]), "=f"(d[25]), "=f"(d[26]), "=f"(d[27])
    : "r"(a0), "r"(a1), "r"(a2), "r"(a3), "l"(db));
}
template <int SD> __device__ __forceinline__ void wgmma_rs_n8_tb1(float (&d)[4], uint32_t a0, uint32_t a1, uint32_t a2, uint32_t a3, uint64_t db) {
  if (SD) asm volatile("wgmma.mma_async.sync.aligned.m64n8k16.f32.bf16.bf16 {%0, %1, %2, %3}, {%4, %5, %6, %7}, %8, 1, 1, 1, 1;\n"
    : "+f"(d[0]), "+f"(d[1]), "+f"(d[2]), "+f"(d[3])
    : "r"(a0), "r"(a1), "r"(a2), "r"(a3), "l"(db));
  else asm volatile("wgmma.mma_async.sync.aligned.m64n8k16.f32.bf16.bf16 {%0, %1, %2, %3}, {%4, %5, %6, %7}, %8, 0, 1, 1, 1;\n"
    : "=f"(d[0]), "=f"(d[1]), "=f"(d[2]), "=f"(d[3])
    : "r"(a0), "r"(a1), "r"(a2), "r"(a3), "l"(db));
}
template <int SD> __device__ __forceinline__ void wgmma_rs_n64_tb1(float (&d)[32], uint32_t a0, uint32_t a1, uint32_t a2, uint32_t a3, uint64_t db) {
  if (SD) asm volatile("wgmma.mma_async.sync.aligned.m64n64k16.f32.bf16.bf16 {%0, %1, %2, %3, %4, %5, %6, %7, %8, %9, %10, %11, %12, %13, %14, %15, %16, %17, %18, %19, %20, %21, %22, %23, %24, %25, %26, %27, %28, %29, %30, %31}, {%32, %33, %34, %35}, %36, 1, 1, 1, 1;\n"
    : "+f"(d[0]), "+f"(d[1]), "+f"(d[2]), "+f"(d[3]), "+f"(d[4]), "+f"(d[5]), "+f"(d[6]), "+f"(d[7]), "+f"(d[8]), "+f"(d[9]), "+f"(d[10]), "+f"(d[11]), "+f"(d[12]), "+f"(d[13]), "+f"(d[14]), "+f"(d[15]), "+f"(d[16]), "+f"(d[17]), "+f"(d[18]), "+f"(d[19]), "+f"(d[20]), "+f"(d[21]), "+f"(d[22]), "+f"(d[23]), "+f"(d[24]), "+f"(d[25]), "+f"(d[26]), "+f"(d[27]), "+f"(d[28]), "+f"(d[29]), "+f"(d[30]), "+f"(d[31])
    : "r"(a0), "r"(a1), "r"(a2), "r"(a3), "l"(db));
  else asm volatile("wgmma.mma_async.sync.aligned.m64n64k16.f32.bf16.bf16 {%0, %1, %2, %3, %4, %5, %6, %7, %8, %9, %10, %11, %12, %13, %14, %15, %16, %17, %18, %19, %20, %21, %22, %23, %24, %25, %26, %27, %28, %29, %30, %31}, {%32, %33, %34, %35}, %36, 0, 1, 1, 1;\n"
    : "=f"(d[0]), "=f"(d[1]), "=f"(d[2]), "=f"(d[3]), "=f"(d[4]), "=f"(d[5]), "=f"(d[6]), "=f"(d[7]), "=f"(d[8]), "=f"(d[9]), "=f"(d[10]), "=f"(d[11]), "=f"(d[12]), "=f"(d[13]), "=f"(d[14]), "=f"(d[15]), "=f"(d[16]), "=f"(d[17]), "=f"(d[18]), "=f"(d[19]), "=f"(d[20]), "=f"(d[21]), "=f"(d[22]), "=f"(d[23]), "=f"(d[24]), "=f"(d[25]), "=f"(d[26]), "=f"(d[27]), "=f"(d[28]), "=f"(d[29]), "=f"(d[30]), "=f"(d[31])
    : "r"(a0), "r"(a1), "r"(a2), "r"(a3), "l"(db));
}
template <int SD> __device__ __forceinline__ void wgmma_ss_n32_ta1_tb1(float (&d)[16], uint64_t da, uint64_t db) {
  if (SD) asm volatile("wgmma.mma_async.sync.aligned.m64n32k16.f32.bf16.bf16 {%0, %1, %2, %3, %4, %5, %6, %7, %8, %9, %10, %11, %12, %13, %14, %15}, %16, %17, 1, 1, 1, 1, 1;\n"
    : "+f"(d[0]), "+f"(d[1]), "+f"(d[2]), "+f"(d[3]), "+f"(d[4]), "+f"(d[5]), "+f"(d[6]), "+f"(d[7]), "+f"(d[8]), "+f"(d[9]), "+f"(d[10]), "+f"(d[11]), "+f"(d[12]), "+f"(d[13]), "+f"(d[14]), "+f"(d[15])
    : "l"(da), "l"(db));
  else asm volatile("wgmma.mma_async.sync.aligned.m64n32k16.f32.bf16.bf16 {%0, %1, %2, %3, %4, %5, %6, %7, %8, %9, %10, %11, %12, %13, %14, %15}, %16, %17, 0, 1, 1, 1, 1;\n"
    : "=f"(d[0]), "=f"(d[1]), "=f"(d[2]), "=f"(d[3]), "=f"(d[4]), "=f"(d[5]), "=f"(d[6]), "=f"(d[7]), "=f"(d[8]), "=f"(d[9]), "=f"(d[10]), "=f"(d[11]), "=f"(d[12]), "=f"(d[13]), "=f"(d[14]), "=f"(d[15])
    : "l"(da), "l"(db));
}
template <int SD> __device__ __forceinline__ void wgmma_ss_n32_ta0_tb1(float (&d)[16], uint64_t da, uint64_t db) {
  if (SD) asm volatile("wgmma.mma_async.sync.aligned.m64n32k16.f32.bf16.bf16 {%0, %1, %2, %3, %4, %5, %6, %7, %8, %9, %10, %11, %12, %13, %14, %15}, %16, %17, 1, 1, 1, 0, 1;\n"
    : "+f"(d[0]), "+f"(d[1]), "+f"(d[2]), "+f"(d[3]), "+f"(d[4]), "+f"(d[5]), "+f"(d[6]), "+f"(d[7]), "+f"(d[8]), "+f"(d[9]), "+f"(d[10]), "+f"(d[11]), "+f"(d[12]), "+f"(d[13]), "+f"(d[14]), "+f"(d[15])
    : "l"(da), "l"(db));
  else asm volatile("wgmma.mma_async.sync.aligned.m64n32k16.f32.bf16.bf16 {%0, %1, %2, %3, %4, %5, %6, %7, %8, %9, %10, %11, %12, %13, %14, %15}, %16, %17, 0, 1, 1, 0, 1;\n"
    : "=f"(d[0]), "=f"(d[1]), "=f"(d[2]), "=f"(d[3]), "=f"(d[4]), "=f"(d[5]), "=f"(d[6]), "=f"(d[7]), "=f"(d[8]), "=f"(d[9]), "=f"(d[10]), "=f"(d[11]), "=f"(d[12]), "=f"(d[13]), "=f"(d[14]), "=f"(d[15])
    : "l"(da), "l"(db));
}
template <int SD> __device__ __forceinline__ void wgmma_rs_n64_tb0(float (&d)[32], uint32_t a0, uint32_t a1, uint32_t a2, uint32_t a3, uint64_t db) {
  if (SD) asm volatile("wgmma.mma_async.sync.aligned.m64n64k16.f32.bf16.bf16 {%0, %1, %2, %3, %4, %5, %6, %7, %8, %9, %10, %11, %12, %13, %14, %15, %16, %17, %18, %19, %20, %21, %22, %23, %24, %25, %26, %27, %28, %29, %30, %31}, {%32, %33, %34, %35}, %36, 1, 1, 1, 0;\n"
    : "+f"(d[0]), "+f"(d[1]), "+f"(d[2]), "+f"(d[3]), "+f"(d[4]), "+f"(d[5]), "+f"(d[6]), "+f"(d[7]), "+f"(d[8]), "+f"(d[9]), "+f"(d[10]), "+f"(d[11]), "+f"(d[12]), "+f"(d[13]), "+f"(d[14]), "+f"(d[15]), "+f"(d[16]), "+f"(d[17]), "+f"(d[18]), "+f"(d[19]), "+f"(d[20]), "+f"(d[21]), "+f"(d[22]), "+f"(d[23]), "+f"(d[24]), "+f"(d[25]), "+f"(d[26]), "+f"(d[27]), "+f"(d[28]), "+f"(d[29]), "+f"(d[30]), "+f"(d[31])
    : "r"(a0), "r"(a1), "r"(a2), "r"(a3), "l"(db));
  else asm volatile("wgmma.mma_async.sync.aligned.m64n64k16.f32.bf16.bf16 {%0, %1, %2, %3, %4, %5, %6, %7, %8, %9, %10, %11, %12, %13, %14, %15, %16, %17, %18, %19, %20, %21, %22, %23, %24, %25, %26, %27, %28, %29, %30, %31}, {%32, %33, %34, %35}, %36, 0, 1, 1, 0;\n"
    : "=f"(d[0]), "=f"(d[1]), "=f"(d[2]), "=f"(d[3]), "=f"(d[4]), "=f"(d[5]), "=f"(d[6]), "=f"(d[7]), "=f"(d[8]), "=f"(d[9]), "=f"(d[10]), "=f"(d[11]), "=f"(d[12]), "=f"(d[13]), "=f"(d[14]), "=f"(d[15]), "=f"(d[16]), "=f"(d[17]), "=f"(d[18]), "=f"(d[19]), "=f"(d[20]), "=f"(d[21]), "=f"(d[22]), "=f"(d[23]), "=f"(d[24]), "=f"(d[25]), "=f"(d[26]), "=f"(d[27]), "=f"(d[28]), "=f"(d[29]), "=f"(d[30]), "=f"(d[31])
    : "r"(a0), "r"(a1), "r"(a2), "r"(a3), "l"(db));
}
template <int SD> __device__ __forceinline__ void wgmma_rs_n32_tb1(float (&d)[16], uint32_t a0, uint32_t a1, uint32_t a2, uint32_t a3, uint64_t db) {
  if (SD) asm volatile("wgmma.mma_async.sync.aligned.m64n32k16.f32.bf16.bf16 {%0, %1, %2, %3, %4, %5, %6, %7, %8, %9, %10, %11, %12, %13, %14, %15}, {%16, %17, %18, %19}, %20, 1, 1, 1, 1;\n"
    : "+f"(d[0]), "+f"(d[1]), "+f"(d[2]), "+f"(d[3]), "+f"(d[4]), "+f"(d[5]), "+f"(d[6]), "+f"(d[7]), "+f"(d[8]), "+f"(d[9]), "+f"(d[10]), "+f"(d[11]), "+f"(d[12]), "+f"(d[13]), "+f"(d[14]), "+f"(d[15])
    : "r"(a0), "r"(a1), "r"(a2), "r"(a3), "l"(db));
  else asm volatile("wgmma.mma_async.sync.aligned.m64n32k16.f32.bf16.bf16 {%0, %1, %2, %3, %4, %5, %6, %7, %8, %9, %10, %11, %12, %13, %14, %15}, {%16, %17, %18, %19}, %20, 0, 1, 1, 1;\n"
    : "=f"(d[0]), "=f"(d[1]), "=f"(d[2]), "=f"(d[3]), "=f"(d[4]), "=f"(d[5]), "=f"(d[6]), "=f"(d[7]), "=f"(d[8]), "=f"(d[9]), "=f"(d[10]), "=f"(d[11]), "=f"(d[12]), "=f"(d[13]), "=f"(d[14]), "=f"(d[15])
    : "r"(a0), "r"(a1), "r"(a2), "r"(a3), "l"(db));
}

__device__ __forceinline__ uint32_t sw64_off(int row, int d) { return row * 64 + ((((d >> 3) ^ (row >> 1)) & 3) << 4) + (d & 7) * 2; }

__device__ __forceinline__ uint32_t exp2_pair_fma(float t0, float t1, uint32_t c_half, uint32_t c_3) {
  uint32_t y0, y;
  asm("prmt.b32 %0, %1, %2, 0x6521;" : "=r"(y0) : "r"(__float_as_uint(t0)), "r"(__float_as_uint(t1)));
  uint32_t h = lop_and_or(y0, 0x007F007Fu, c_half);
  uint32_t e = lop_and_or(y0, 0xFF80FF80u, c_3);
  asm("fma.rn.bf16x2 %0, %1, %2, %3;" : "=r"(y) : "r"(y0), "r"(h), "r"(e));
  return y;
}

__device__ __forceinline__ void feature_map(float (&v)[16], uint32_t (&ph)[16], int lq) {
  const float L2E = 1.4426950408889634f;
  const bool tail_ok = lq < 2;
  float mx[2], mn[2], b[16], sa[2], sn[2];
#pragma unroll
  for (int r = 0; r < 2; r++) {
    const int o = 2 * r;
    if (!tail_ok) { v[o + 12] = v[o]; v[o + 13] = v[o]; }
    mx[r] = fmaxf(fmaxf(fmaxf(v[o], v[o + 1]), fmaxf(v[o + 4], v[o + 5])), fmaxf(fmaxf(v[o + 8], v[o + 9]), fmaxf(v[o + 12], v[o + 13])));
    mn[r] = fminf(fminf(fminf(v[o], v[o + 1]), fminf(v[o + 4], v[o + 5])), fminf(fminf(v[o + 8], v[o + 9]), fminf(v[o + 12], v[o + 13])));
  }
#pragma unroll
  for (int o = 1; o <= 2; o <<= 1)
#pragma unroll
    for (int r = 0; r < 2; r++) { mx[r] = fmaxf(mx[r], __shfl_xor_sync(~0u, mx[r], o)); mn[r] = fminf(mn[r], __shfl_xor_sync(~0u, mn[r], o)); }
#pragma unroll
  for (int r = 0; r < 2; r++) {
    const int o = 2 * r;
    const float cx = -mx[r] * L2E, cn = mn[r] * L2E;
#pragma unroll
    for (int i = 0; i < 8; i++) {
      const int k = o + 4 * (i >> 1) + (i & 1);
      b[k] = ex2f(fmaf(v[k], -L2E, cn));
      v[k] = ex2f(fmaf(v[k], L2E, cx));
    }
    if (!tail_ok) { v[o + 12] = v[o + 13] = b[o + 12] = b[o + 13] = 0.f; }
    sa[r] = ((v[o] + v[o + 1]) + (v[o + 4] + v[o + 5])) + ((v[o + 8] + v[o + 9]) + (v[o + 12] + v[o + 13]));
    sn[r] = ((b[o] + b[o + 1]) + (b[o + 4] + b[o + 5])) + ((b[o + 8] + b[o + 9]) + (b[o + 12] + b[o + 13]));
  }
#pragma unroll
  for (int o = 1; o <= 2; o <<= 1)
#pragma unroll
    for (int r = 0; r < 2; r++) { sa[r] += __shfl_xor_sync(~0u, sa[r], o); sn[r] += __shfl_xor_sync(~0u, sn[r], o); }
#pragma unroll
  for (int r = 0; r < 2; r++) {
    const float ra = rcpf(sa[r]), rb = rcpf(sn[r]);
#pragma unroll
    for (int jj = 0; jj < 4; jj++) {
      ph[jj * 2 + r] = pack_bf16(v[2 * r + 4 * jj] * ra, v[2 * r + 4 * jj + 1] * ra);
      ph[(4 + jj) * 2 + r] = pack_bf16(b[2 * r + 4 * jj] * rb, b[2 * r + 4 * jj + 1] * rb);
    }
  }
}

__device__ __forceinline__ void store_heads(uint32_t base, const uint32_t (&a)[14], uint32_t pad0, uint32_t pad1, int row0, int lq) {
  const uint32_t rb = base + row0 * 64 + (((row0 >> 1) & 3) << 4);
  const uint32_t b0 = rb + lq * 4;
  const uint32_t b1 = (rb + 8192 + ((lq * 4 + 8) & 15)) ^ ((lq >> 1) << 4);
#pragma unroll
  for (int j = 0; j < 7; j++) {
    uint32_t ad;
    if (j < 3) ad = b0 ^ (j << 4);
    else if (j == 3) ad = (lq < 2) ? (b0 ^ 48u) : (b1 ^ 16u);
    else ad = (lq < 2) ? (b1 ^ ((j - 4) << 4)) : ((b1 ^ 16u) ^ ((j - 3) << 4));
    sts32(ad, a[2 * j]);
    sts32(ad + 512, a[2 * j + 1]);
  }
  sts64((rb ^ 48u) + 8 + (lq & 1) * 8192 + (lq >> 1) * 512, pad0, pad1);
}

struct Params {
  const __nv_bfloat16* w_phi;
  const __nv_bfloat16* wk;
  const __nv_bfloat16* wv;
  const __nv_bfloat16* gate_w;
  __nv_bfloat16* out;
};

__global__ void __launch_bounds__(NTHREADS, 1)
fused_kernel(const __grid_constant__ CUtensorMap tm_x, const __grid_constant__ CUtensorMap tm_wqkv,
             const __grid_constant__ CUtensorMap tm_wq, const __grid_constant__ CUtensorMap tm_woa,
             const __grid_constant__ CUtensorMap tm_wob, const Params prm) {
  extern __shared__ uint8_t smem_raw[];
  uint32_t sb = (smem_u32(smem_raw) + 1023u) & ~1023u;
  uint8_t* sgen = smem_raw + (sb - smem_u32(smem_raw));
  asm volatile("mov.u32 %0, %0;" : "+r"(sb));
  const int tid = threadIdx.x, lane = tid & 31;
  const int warp = __shfl_sync(~0u, tid >> 5, 0), wg = warp >> 2;
  const int pt = blockIdx.x >> 3, hp = blockIdx.x & 7;
  const uint32_t bars = sb + OFF_BAR;
  auto BAR = [&](int i) { return bars + 8u * i; };
  const unsigned epoch = g_epoch & 1;

  if (tid == 0) { PROF_MARK(0); PROF_CLK(30); PROF2(15); }
  auto load_proj = [&](int c, int g) {
    mbar_expect_tx(BAR(B_FULL + g), 16384 + 4 * 7168);
    tma_2d(sb + OFF_X + c * 16384, &tm_x, c * 64, pt * 128, BAR(B_FULL + g));
    tma_2d(sb + OFF_RING + g * 32768, &tm_wq, hp * 56, c * 64, BAR(B_FULL + g));
#pragma unroll 1
    for (int j = 0; j < 3; j++) tma_2d(sb + OFF_RING + g * 32768 + 8192 + j * 8192, &tm_wqkv, j * DM + hp * 56, c * 64, BAR(B_FULL + g));
  };
  if (warp == 16) {
    if (elect_one()) {
      mbar_init(BAR(B_FULL), 1);
      fence_async_smem();
      load_proj(0, 0);
      mbar_init(BAR(B_RAW), 1); mbar_init(BAR(B_FULL + 1), 1); mbar_init(BAR(B_FULL + 2), 1);
      fence_async_smem();
    }
    __syncwarp();
    asm volatile("bar.arrive 0, %0;" ::"n"(NTHREADS) : "memory");
  } else {
    if (elect_one()) {
      const int i = warp + 3 - (warp > 16);
      if (i < B_N && i != B_RAW) {
        int cnt = i < B_WO || i > B_SIG || i == B_X1FREE ? 16 : 1;
        if (i == B_BUILD) cnt = 16;
        if (i == B_SIG || i == B_SIG + 1 || i == B_QSQ) cnt = 8;
        if (i == B_KVR) cnt = 2;
        mbar_init(BAR(i), cnt);
        fence_async_smem();
      }
    }
    bar_sync(0, NTHREADS);
  }
  if (tid == 0) PROF2(14);

  if (wg == 4) {
    asm volatile("setmaxnreg.dec.sync.aligned.u32 32;");
    if (warp == 16) {
      if (elect_one()) {
        mbar_expect_tx(BAR(B_RAW), 25088 + 3136 + 896);
        bulk_g2s(sb + OFF_RAW, hp < 4 ? prm.wk : prm.wv, 25088, BAR(B_RAW));
        bulk_g2s(sb + OFF_RAW + 25088, prm.w_phi + 2 * hp * DH * DH, 3136, BAR(B_RAW));
        bulk_g2s(sb + OFF_RAW + 28224, prm.gate_w, 896, BAR(B_RAW));
        load_proj(1, 1);
        load_proj(2, 2);
      }
      __syncwarp();
      bar_sync(3, 64);
      if (elect_one()) {
        int g = 0, nkv = 8;
        uint32_t par = 0;
#pragma unroll 1
        for (int n = 3; n < 14 + nkv; n++) {
          if (n == 7) { PROF_MARK(20); cnt_wait(C_KV, NCTA); PROF_MARK(21); fence_async_all(); }
          if (n == 15) {
            mbar_wait(BAR(B_SLOW), 0);
            if (*(volatile int*)(sgen + OFF_RED)) nkv = 26;
          }
          const int j = n - 7 - nkv;
          if (j == 0 || j == 3) {
            PROF3(j ? 11 : 8);
            cnt_wait((j ? C_OB : C_OA) + pt, 8);
            PROF3(j ? 12 : 9);
            PROF_MARK(26);
            fence_async_all();
          }
          mbar_wait(BAR(B_EMPTY + g), par);
          if (n == 5) mbar_wait(BAR(B_BUILD), 0);
          if (n < 7) load_proj(n, g);
          else {
            mbar_expect_tx(BAR(B_FULL + g), 32768);
            bulk_g2s(sb + OFF_RING + g * 32768, j < 0 ? g_kv_img + ((n - 7) & 7) * 32768 : g_o_img + (size_t)(pt * 7 + j) * 32768, 32768,
                     BAR(B_FULL + g));
          }
          if (++g == 3) { g = 0; par ^= 1; }
        }
        if (atomicAdd(&g_cnt[C_DONE * 32], 1u) == NCTA - 1) {
#pragma unroll 1
          for (int i = 0; i < C_N; i++) g_cnt[i * 32] = 0;
          g_epoch = epoch ^ 1;
        }
      }
    } else {
      if (warp == 18) {
        if (elect_one()) {
#pragma unroll 1
          for (int i = 0; i < 4; i++) {
            mbar_wait(BAR(B_SIG + i), 0);
            PROF3(2 * i);
            if (i == 1) {
#pragma unroll 1
              for (int j = 0; j < 4; j++)
                asm volatile("cp.reduce.async.bulk.global.shared::cta.bulk_group.add.f32 [%0], [%1], 8192;"
                             ::"l"(g_kvacc[epoch] + hp * 4096 + (j >> 1) * 2048), "r"(sb + OFF_PHIK + j * 8192) : "memory");
              asm volatile("cp.async.bulk.commit_group;\ncp.async.bulk.wait_group 0;" ::: "memory");
            }
            cnt_arrive(i == 0 ? C_KV : i == 1 ? C_PART : (i == 2 ? C_OA : C_OB) + pt);
            PROF3(2 * i + 1);
            if (i == 1 || i == 2) {
              if (i == 2) mbar_wait(BAR(B_X1FREE), 0);
              mbar_expect_tx(BAR(B_WO + i - 1), 7 * 7168);
#pragma unroll 1
              for (int c = 0; c < 7; c++)
                tma_2d(sb + OFF_WO + (i - 1) * 57344 + c * 8192, i == 1 ? &tm_woa : &tm_wob, hp * 56, c * 64, BAR(B_WO + i - 1));
            }
          }
        }
      } else if (warp == 19) {
        if (lane == 0) {
          mbar_wait(BAR(B_SIG + 0), 0);
          cnt_wait(C_KV, NCTA);
        }
        __syncwarp();
        float ksq = 0.f, vsq = 0.f;
#pragma unroll
        for (int sl = 0; sl < 4; sl++) {
          float4 a = ldcg_f4(g_ksq + sl * 128 + lane * 4), b = ldcg_f4(g_vsq + sl * 128 + lane * 4);
          float m = fmaxf(fmaxf(a.x, a.y), fmaxf(a.z, a.w));
          m = __uint_as_float(__reduce_max_sync(~0u, __float_as_uint(m)));
          ksq += m;
          vsq = fmaxf(vsq, fmaxf(fmaxf(b.x, b.y), fmaxf(b.z, b.w)));
        }
        mbar_wait(BAR(B_QSQ), 0);
        const float4 qa4 = ((const float4*)(sgen + OFF_QSQ))[lane], qb4 = ((const float4*)(sgen + OFF_QSQ))[32 + lane];
        const float qmax = fmaxf(fmaxf(fmaxf(qa4.x, qa4.y), fmaxf(qa4.z, qa4.w)), fmaxf(fmaxf(qb4.x, qb4.y), fmaxf(qb4.z, qb4.w)));
        const bool slow = __any_sync(~0u, !(qmax * ksq <= 98.f * 98.f) || !(vsq <= 2.0e8f));
        if (lane == 0) {
          *(volatile int*)(sgen + OFF_RED) = slow;
          mbar_arrive(BAR(B_SLOW), 1);
        }
      } else {
        float4* z = (float4*)(g_kvacc[epoch ^ 1] + blockIdx.x * 256) + lane;
        z[0] = make_float4(0.f, 0.f, 0.f, 0.f);
        z[32] = make_float4(0.f, 0.f, 0.f, 0.f);
        bar_sync(3, 64);
        if (lane == 0) {
          mbar_wait(BAR(B_SIG + 0), 0);
          cnt_wait(C_KV, NCTA);
        }
        __syncwarp();
        ((float4*)(sgen + OFF_GATE))[lane] = ldcg_f4(g_gate + pt * 128 + lane * 4);
      }
      if (warp != 18) {
        if (lane == 0) {
          mbar_wait(BAR(B_SIG + 1), 0);
          cnt_wait(C_PART, NCTA);
          PROF_MARK(23);
        }
        __syncwarp();
        const int e = warp == 19;
        const float* src = g_kvacc[epoch] + hp * 4096 + e * 2048 + lane * 8;
#pragma unroll 1
        for (int i = 0; i < 8; i += 2) {
          const float4 a = ldcg_f4(src + i * 256), b = ldcg_f4(src + i * 256 + 4), c = ldcg_f4(src + i * 256 + 256), d = ldcg_f4(src + i * 256 + 260);
          const uint32_t ad = sb + OFF_KVR + e * 4096 + sw64_off(i * 8 + (lane >> 2), (lane & 3) * 8);
          sts128(ad, make_uint4(pack_bf16(a.x, a.y), pack_bf16(a.z, a.w), pack_bf16(b.x, b.y), pack_bf16(b.z, b.w)));
          sts128(ad + 512, make_uint4(pack_bf16(c.x, c.y), pack_bf16(c.z, c.w), pack_bf16(d.x, d.y), pack_bf16(d.z, d.w)));
        }
        fence_async_smem();
        __syncwarp();
        if (lane == 0) mbar_arrive(BAR(B_KVR), 1);
        PROF_MARK(24);
      }
    }
  } else {
    asm volatile("setmaxnreg.inc.sync.aligned.u32 112;");
    const int mh = wg & 1, nh = wg >> 1, wq = warp & 3;
    const int lq = lane & 3;
    const int rowl = wq * 16 + (lane >> 2);
    const int row0 = mh * 64 + rowl;
    int slot = 0, prev = 0;
    uint32_t par = 0;
    {
      float acc0[28], acc1[28], accs[4];
      const uint64_t dR = make_desc(sb + OFF_RING + nh * 16384, 1024, 1024, 1);
      const int lr = wq * 16 + (lane & 7) + ((lane >> 3) & 1) * 8;
      const uint32_t xa = sb + OFF_X + mh * 8192 + lr * 128 + (((lane >> 4) ^ (lr & 7)) << 4);
#pragma unroll
      for (int i = 0; i < 28; i++) acc0[i] = acc1[i] = 0.f;
#pragma unroll
      for (int i = 0; i < 4; i++) accs[i] = 0.f;
      const uint64_t dSlc = make_desc(sb + OFF_SLC, 128, 128, 0);
      uint32_t a[16], an[16];
      if (tid == 0) PROF2(16);
      mbar_wait(BAR(B_FULL), 0);
      if (tid == 0) PROF2(17);
#pragma unroll
      for (int ks = 0; ks < 4; ks++) ldsm4(an + 4 * ks, xa ^ (ks << 5));
#pragma unroll 1
      for (int c = 0; c < 7; c++) {
#pragma unroll
        for (int i = 0; i < 16; i++) a[i] = an[i];
        const uint64_t dB = dR + slot * 2048;
        wg_fence();
#pragma unroll
        for (int ks = 0; ks < 4; ks++) {
          wgmma_rs_n56_tb1<1>(acc0, a[4 * ks], a[4 * ks + 1], a[4 * ks + 2], a[4 * ks + 3], dB + ks * 128);
          wgmma_rs_n56_tb1<1>(acc1, a[4 * ks], a[4 * ks + 1], a[4 * ks + 2], a[4 * ks + 3], dB + 512 + ks * 128);
        }
        if (nh == 1 && c > 0) {
#pragma unroll
          for (int ks = 0; ks < 4; ks++) wgmma_rs_n8_tb1<1>(accs, a[4 * ks], a[4 * ks + 1], a[4 * ks + 2], a[4 * ks + 3], dSlc + c * 64 + ks * 16);
        }
        wg_commit();
        if (c == 0) {
          mbar_wait(BAR(B_RAW), 0);
          const int k = tid >> 3, cn = tid & 7;
          const bool data = k < 56 && (cn >> 2) == (k >= DH);
          const uint2* wsrc = (const uint2*)(sgen + OFF_RAW + 25088 + k * 56 + (cn & 3) * 16);
          uint2 w0 = make_uint2(0u, 0u), w1 = w0;
          if (data) w0 = wsrc[0];
          if (data && (cn & 3) != 3) w1 = wsrc[1];
          sts128(sb + OFF_WBD + k * 128 + ((cn ^ (k & 7)) << 4), make_uint4(w0.x, w0.y, w1.x, w1.y));
          if (tid < DM) {
            const uint2* src = (const uint2*)(sgen + OFF_RAW + tid * 56 + (hp & 3) * 16);
            w0 = src[0];
            w1 = make_uint2(hp == 3 ? (uint32_t)((const unsigned short*)(sgen + OFF_RAW + 28224))[tid] : 0u, 0u);
            if ((hp & 3) != 3) w1 = src[1];
            sts128(sb + OFF_SLC + tid * 16, make_uint4(w0.x, w0.y, w1.x, w1.y));
          }
          fence_async_smem();
          __syncwarp();
          if (lane == 0) mbar_arrive(BAR(B_BUILD), 1);
        }
        const int cur = slot;
        if (++slot == 3) { slot = 0; par ^= 1; }
        if (c < 6) {
          mbar_wait(BAR(B_FULL + slot), par);
#pragma unroll
          for (int ks = 0; ks < 4; ks++) ldsm4(an + 4 * ks, (xa + (c + 1) * 16384) ^ (ks << 5));
        }
        if (c == 0) mbar_wait(BAR(B_BUILD), 0);
        wg_wait<0>();
#pragma unroll
        for (int i = 0; i < 16; i++) asm volatile("" : "+r"(a[i])::"memory");
        if (lane == 0) mbar_arrive(BAR(B_EMPTY + cur), 1);
      }
      if (nh == 1) {
#pragma unroll
        for (int ks = 0; ks < 4; ks++) ldsm4(a + 4 * ks, xa ^ (ks << 5));
        wg_fence();
#pragma unroll
        for (int ks = 0; ks < 4; ks++) wgmma_rs_n8_tb1<1>(accs, a[4 * ks], a[4 * ks + 1], a[4 * ks + 2], a[4 * ks + 3], dSlc + ks * 16);
        wg_commit();
      }
      wg_wait<0>();
      fence_regs(acc0); fence_regs(acc1); fence_regs(accs);
      if (tid == 0) PROF_MARK(2);
      if (tid == 256) PROF_MARK(3);
      if (nh == 0) {
        float sq[4] = {0.f, 0.f, 0.f, 0.f};
#pragma unroll
        for (int i = 0; i < 28; i++) acc0[i] *= 0.18898223650461362f * 1.4426950408889634f;
#pragma unroll
        for (int j = 0; j < 7; j++) {
#pragma unroll
          for (int rr = 0; rr < 2; rr++) {
            const float s2 = acc0[4 * j + 2 * rr] * acc0[4 * j + 2 * rr] + acc0[4 * j + 2 * rr + 1] * acc0[4 * j + 2 * rr + 1];
            if (j < 3) sq[rr] += s2;
            else if (j > 3) sq[2 + rr] += s2;
            else { sq[rr] += (lq < 2) ? s2 : 0.f; sq[2 + rr] += (lq < 2) ? 0.f : s2; }
          }
        }
#pragma unroll
        for (int i = 0; i < 4; i++) sq[i] = quad_sum(sq[i]);
        const float mine = lq == 0 ? sq[0] : lq == 1 ? sq[1] : lq == 2 ? sq[2] : sq[3];
        ((float*)(sgen + OFF_QSQ))[(mh + (lq & 2)) * 64 + rowl + 8 * (lq & 1)] = mine <= 3.0e38f ? mine : __int_as_float(0x7f800000);
        __syncwarp();
        if (lane == 0) mbar_arrive(BAR(B_QSQ), 1);
      } else {
        const int sl = hp & 3;
        const bool isk = hp < 4, real = (sl < 3) || (lq < 2);
        const int pos = pt * 128 + row0, kr = pos & 63;
        uint8_t* dst = g_kv_img + (pos >> 6) * 8192 + (isk ? 0 : 4096) + sw64_off(kr, sl * 8 + 2 * lq);
        const uint32_t pat = isk ? POLY_PAT >> (kr >> 3) : 0u;
        float mxv = 0.f;
#pragma unroll
        for (int rr = 0; rr < 2; rr++) {
          const float v0 = accs[2 * rr], v1 = accs[2 * rr + 1];
          const bool poly = (pat >> rr) & 1;
          const float sc = poly ? 2.f : 1.f;
          const float s2 = quad_sum(real ? v0 * v0 + v1 * v1 : 0.f);
          mxv = fmaxf(mxv, s2 <= 3.0e38f ? s2 : __int_as_float(0x7f800000));
          const uint32_t padv = lq == 2 ? (poly ? 0x443F4000u : 0x00003F80u) : (poly ? 0x3AB03F4Du : 0u);
          *(uint32_t*)(dst + rr * 512) = real ? pack_bf16(sc * v0, sc * v1) : padv;
          if (hp == 3 && lq == 2) g_gate[pos + 8 * rr] = rcpf(1.f + ex2f(-1.4426950408889634f * v0));
        }
        mxv = __uint_as_float(__reduce_max_sync(~0u, __float_as_uint(mxv)));
        if (lane == 0) (isk ? g_ksq : g_vsq)[sl * 128 + pt * 8 + mh * 4 + wq] = mxv;
        __syncwarp();
        if (lane == 0) mbar_arrive(BAR(B_SIG + 0), 1);
      }
      if (tid == 0) PROF_MARK(4);
      if (tid == 256) PROF_MARK(5);
      uint32_t h[14];
      float pp[32];
      {
#pragma unroll
        for (int i = 0; i < 14; i++) {
          const uint32_t u0 = pack_bf16(acc0[2 * i], acc0[2 * i + 1]), u1 = pack_bf16(acc1[2 * i], acc1[2 * i + 1]);
          h[i] = nh ? u1 : u0;
          a[i] = nh ? u0 : u1;
        }
        a[14] = a[0] ^ 0x80008000u;
        a[15] = a[1] ^ 0x80008000u;
        const uint64_t dW = make_desc(sb + OFF_WBD, 1024, 1024, 1);
        wg_fence();
        wgmma_rs_n64_tb1<0>(pp, a[0], a[1], a[2], a[3], dW);
#pragma unroll
        for (int ks = 1; ks < 4; ks++) wgmma_rs_n64_tb1<1>(pp, a[4 * ks], a[4 * ks + 1], a[4 * ks + 2], a[4 * ks + 3], dW + ks * 128);
        wg_commit();
        bar_sync(1, 512);
        if (tid == 0) PROF_MARK(6);
        store_heads(sb + (nh ? OFF_VA : OFF_QP), h, nh ? 0x00003F80u : 0x3F800000u, nh ? 0u : 0x3F803F80u, row0, lq);
        wg_wait<0>();
        fence_regs(pp);
      }
      float v[16];
#pragma unroll
      for (int i = 0; i < 16; i++) v[i] = pp[i];
      uint32_t rb = sb + (nh ? OFF_PHIK : OFF_PHIQ) + row0 * 128 + lq * 4 + ((rowl & 7) << 4);
#pragma unroll 1
      for (int e = 0; e < 2; e++) {
        uint32_t ph[16];
        feature_map(v, ph, lq);
#pragma unroll
        for (int ch = 0; ch < 8; ch++) { sts32(rb ^ (ch << 4), ph[2 * ch]); sts32((rb ^ (ch << 4)) + 1024, ph[2 * ch + 1]); }
        rb += 16384;
#pragma unroll
        for (int i = 0; i < 16; i++) v[i] = pp[16 + i];
      }
      fence_async_smem();
      bar_sync(1, 512);
      if (tid == 0) PROF_MARK(7);
      if (nh == 1) {
        float kv0[16], kv1[16];
        const uint64_t dP = make_desc(sb + OFF_PHIK + mh * 8192, 1024, 1024, 1);
        const uint64_t dV = make_desc(sb + OFF_VA + mh * 4096, 512, 512, 2);
        wg_fence();
        wgmma_ss_n32_ta1_tb1<0>(kv0, dP, dV);
        wgmma_ss_n32_ta1_tb1<0>(kv1, dP + 1024, dV + 512);
#pragma unroll
        for (int ks = 1; ks < 4; ks++) {
          wgmma_ss_n32_ta1_tb1<1>(kv0, dP + ks * 128, dV + ks * 64);
          wgmma_ss_n32_ta1_tb1<1>(kv1, dP + 1024 + ks * 128, dV + 512 + ks * 64);
        }
        wg_commit();
        wg_wait<0>();
        fence_regs(kv0); fence_regs(kv1);
        bar_sync(4 + wg, 128);
        const uint32_t sa = sb + OFF_PHIK + mh * 8192 + rowl * 128 + lq * 8;
#pragma unroll
        for (int j = 0; j < 8; j++) {
          sts64(sa + 32 * (j >> 1) + 1024 * (j & 1), __float_as_uint(kv0[2 * j]), __float_as_uint(kv0[2 * j + 1]));
          sts64(sa + 16384 + 32 * (j >> 1) + 1024 * (j & 1), __float_as_uint(kv1[2 * j]), __float_as_uint(kv1[2 * j + 1]));
        }
        fence_async_smem();
        __syncwarp();
        if (lane == 0) mbar_arrive(BAR(B_SIG + 1), 1);
        if (tid == 256) PROF_MARK(28);
      }
    }
    {
      const uint64_t dK = make_desc(sb + OFF_RING, 512, 512, 2);
      const uint64_t dhi = dK & 0xffffffff00000000ull;
      const uint32_t dlo0 = (uint32_t)dK;
      uint32_t ok = 0, q[8];
      float o[16];
#pragma unroll
      for (int i = 0; i < 16; i++) o[i] = 0.f;
      {
        const int r = mh * 64 + wq * 16 + (lane & 7) + ((lane >> 3) & 1) * 8;
        ldsm4(q, sb + OFF_QP + nh * 8192 + sw64_off(r, (lane >> 4) * 8));
        ldsm4(q + 4, sb + OFF_QP + nh * 8192 + sw64_off(r, 16 + (lane >> 4) * 8));
      }
      if (tid == 0) PROF_MARK(10);
      const int qb = QB_AT;
#pragma unroll 1
      for (int it = 0; it <= 8; it++) {
        uint32_t p[16];
        if ((tid & 127) == 0) PROF4(wg * 32 + it * 3);
        if (it == qb || it == 8) {
          float t[16];
          wg_wait<0>();
          fence_regs(o);
          if (it < 8) {
            if (tid == 0) PROF_MARK(11);
            mbar_wait(BAR(B_KVR), 0);
            const uint64_t dR = make_desc(sb + OFF_KVR + nh * 4096, 512, 512, 2);
            const uint64_t dP = make_desc(sb + OFF_PHIQ + nh * 16384 + mh * 8192, 1024, 1024, 1);
            wg_fence();
            wgmma_ss_n32_ta0_tb1<0>(t, dP, dR);
#pragma unroll
            for (int ks = 1; ks < 4; ks++) wgmma_ss_n32_ta0_tb1<1>(t, dP + ks * 2, dR + ks * 64);
            wg_commit();
            wg_wait<0>();
            fence_regs(t);
            if (lane == 0) mbar_arrive(BAR(B_X1FREE), 1);
          } else {
            if (lane == 0) mbar_arrive(BAR(B_EMPTY + prev), 1);
            if (tid == 0) PROF_MARK(13);
            mbar_wait(BAR(B_SLOW), 0);
            if (__builtin_expect(__any_sync(~0u, *(volatile int*)(sgen + OFF_RED)), 0)) {
              uint32_t qz[8];
#pragma unroll
              for (int i = 0; i < 8; i++) qz[i] = (i >= 6 && lq >= 2) ? 0u : q[i];
              float m0 = -3.0e38f, m1 = -3.0e38f, o2[16];
              int sl2 = slot;
              uint32_t par2 = par;
#pragma unroll 1
              for (int j64 = 0; j64 < 32; j64++) {
                float s[32];
                mbar_wait(BAR(B_FULL + sl2), par2);
                const uint32_t lo = dlo0 + sl2 * 2048 + (j64 & 3) * 512;
                wg_fence();
                wgmma_rs_n64_tb0<0>(s, qz[0], qz[1], qz[2], qz[3], dhi | lo);
                wgmma_rs_n64_tb0<1>(s, qz[4], qz[5], qz[6], qz[7], dhi | (lo + 2));
                wg_commit();
                wg_wait<0>();
                fence_regs(s);
#pragma unroll
                for (int j = 0; j < 8; j++) {
                  const float sc = ((POLY_PAT >> j) & 1) ? 0.5f : 1.f;
                  m0 = fmaxf(m0, fmaxf(s[4 * j], s[4 * j + 1]) * sc);
                  m1 = fmaxf(m1, fmaxf(s[4 * j + 2], s[4 * j + 3]) * sc);
                }
                if ((j64 & 3) == 3) {
                  if (lane == 0) mbar_arrive(BAR(B_EMPTY + sl2), 1);
                  if (++sl2 == 3) { sl2 = 0; par2 ^= 1; }
                }
              }
              m0 = quad_max(m0); m1 = quad_max(m1);
#pragma unroll
              for (int i = 0; i < 16; i++) o2[i] = 0.f;
#pragma unroll 1
              for (int j64 = 0; j64 < 32; j64++) {
                float s[32];
                mbar_wait(BAR(B_FULL + sl2), par2);
                const uint32_t lo = dlo0 + sl2 * 2048 + (j64 & 3) * 512;
                wg_fence();
                wgmma_rs_n64_tb0<0>(s, qz[0], qz[1], qz[2], qz[3], dhi | lo);
                wgmma_rs_n64_tb0<1>(s, qz[4], qz[5], qz[6], qz[7], dhi | (lo + 2));
                wg_commit();
                wg_wait<0>();
                fence_regs(s);
                uint32_t ps[16];
#pragma unroll
                for (int j = 0; j < 8; j++) {
                  const float sc = ((POLY_PAT >> j) & 1) ? 0.5f : 1.f;
                  ps[2 * j] = pack_bf16(ex2f(fmaf(s[4 * j], sc, -m0)), ex2f(fmaf(s[4 * j + 1], sc, -m0)));
                  ps[2 * j + 1] = pack_bf16(ex2f(fmaf(s[4 * j + 2], sc, -m1)), ex2f(fmaf(s[4 * j + 3], sc, -m1)));
                }
                wg_fence();
#pragma unroll
                for (int ks = 0; ks < 4; ks++)
                  wgmma_rs_n32_tb1<1>(o2, ps[4 * ks], ps[4 * ks + 1], ps[4 * ks + 2], ps[4 * ks + 3], dhi | (lo + 256 + ks * 64));
                wg_commit();
                wg_wait<0>();
                fence_regs(o2);
                if ((j64 & 3) == 3) {
                  if (lane == 0) mbar_arrive(BAR(B_EMPTY + sl2), 1);
                  if (++sl2 == 3) { sl2 = 0; par2 ^= 1; }
                }
              }
#pragma unroll 1
              for (int j = 0; j < 2; j++) {
                mbar_wait(BAR(B_FULL + sl2), par2);
                __syncwarp();
                if (lane == 0) mbar_arrive(BAR(B_EMPTY + sl2), 1);
                if (++sl2 == 3) { sl2 = 0; par2 ^= 1; }
              }
#pragma unroll
              for (int i = 0; i < 16; i++) o[i] = o2[i];
            }
#pragma unroll
            for (int i = 0; i < 16; i++) t[i] = o[i];
          }
          const int br = it == 8;
          const float eps = br ? 0.f : 1e-6f;
          const float g0 = ((const float*)(sgen + OFF_GATE))[row0], g1 = ((const float*)(sgen + OFF_GATE))[row0 + 8];
          const float d0 = __shfl_sync(~0u, t[12], (lane & ~3) | 2), d1 = __shfl_sync(~0u, t[14], (lane & ~3) | 2);
          const float r0 = (br ? 1.f - g0 : g0) * rcpf(d0 + eps), r1 = (br ? 1.f - g1 : g1) * rcpf(d1 + eps);
          uint8_t* img = g_o_img + (size_t)((pt * 2 + br) * 14 + mh) * 8192 + rowl * 128;
          const int col0 = (2 * hp + nh) * DH + 2 * lq;
#pragma unroll
          for (int j = 0; j < 4; j++) {
            const int col = col0 + 8 * j;
            uint8_t* gp = img + (uint32_t)((col >> 6) * 16384 + ((((col >> 3) ^ rowl) & 7) << 4) + (col & 7) * 2);
            const uint32_t v0 = pack_bf16(t[4 * j] * r0, t[4 * j + 1] * r0), v1 = pack_bf16(t[4 * j + 2] * r1, t[4 * j + 3] * r1);
            if (j < 3 || lq < 2) { *(uint32_t*)gp = v0; *(uint32_t*)(gp + 1024) = v1; }
          }
          __syncwarp();
          if (lane == 0) mbar_arrive(BAR(B_SIG + 2 + br), 1);
          if (tid == 0) PROF_MARK(12 + 2 * br);
          if (br) break;
        }
        const uint32_t lo = dlo0 + slot * 2048;
        if ((tid & 127) == 0) PROF4(wg * 32 + it * 3 + 1);
        if (!ok) mbar_wait(BAR(B_FULL + slot), par);
        if ((tid & 127) == 0) PROF4(wg * 32 + it * 3 + 2);
        int nslot = slot + 1;
        uint32_t npar = par;
        if (nslot == 3) { nslot = 0; npar ^= 1; }
        {
          float s[32];
          wg_fence();
          wgmma_rs_n64_tb0<0>(s, q[0], q[1], q[2], q[3], dhi | lo);
          wgmma_rs_n64_tb0<1>(s, q[4], q[5], q[6], q[7], dhi | (lo + 2));
          wg_commit();
#pragma unroll
          for (int u = 0; u < 4; u++) {
            wg_wait<0>();
            fence_regs(s);
            if (u == 0 && lane == 0 && it > 0) mbar_arrive(BAR(B_EMPTY + prev), 1);
            if (u == 2) ok = mbar_test(BAR(B_FULL + nslot), npar);
#pragma unroll
            for (int j = 0; j < 8; j++) {
              if ((POLY_PAT >> j) & 1) {
                p[2 * j] = exp2_pair_fma(s[4 * j], s[4 * j + 1], 0x3F003F00u, 0x00030003u);
                p[2 * j + 1] = exp2_pair_fma(s[4 * j + 2], s[4 * j + 3], 0x3F003F00u, 0x00030003u);
              } else {
                p[2 * j] = pack_bf16(ex2f(s[4 * j]), ex2f(s[4 * j + 1]));
                p[2 * j + 1] = pack_bf16(ex2f(s[4 * j + 2]), ex2f(s[4 * j + 3]));
              }
            }
            wg_fence();
#pragma unroll
            for (int ks = 0; ks < 4; ks++)
              wgmma_rs_n32_tb1<1>(o, p[4 * ks], p[4 * ks + 1], p[4 * ks + 2], p[4 * ks + 3], dhi | (lo + u * 512 + 256 + ks * 64));
            if (u < 3) {
              wgmma_rs_n64_tb0<0>(s, q[0], q[1], q[2], q[3], dhi | (lo + (u + 1) * 512));
              wgmma_rs_n64_tb0<1>(s, q[4], q[5], q[6], q[7], dhi | (lo + (u + 1) * 512 + 2));
            }
            wg_commit();
          }
        }
        prev = slot; slot = nslot; par = npar;
      }
      wg_wait<0>();
    }
    if (nh == 1) return;
    {
      float acc0[28], acc1[28];
#pragma unroll
      for (int i = 0; i < 28; i++) acc0[i] = acc1[i] = 0.f;
      const uint64_t dS = make_desc(sb + OFF_WO, 1024, 1024, 1);
      const uint64_t dR = make_desc(sb + OFF_RING + mh * 8192, 1024, 1024, 1);
#pragma unroll 1
      for (int c = 0; c < 7; c++) {
        mbar_wait(BAR(B_WO + (c >= 3)), 0);
        mbar_wait(BAR(B_FULL + slot), par);
        const uint64_t dA = dR + slot * 2048, dB = dS + c * 1024;
        wg_fence();
#pragma unroll
        for (int ks = 0; ks < 4; ks++) {
          wgmma_ss_n56_ta0_tb1<1>(acc0, dA + ks * 2, dB + ks * 128);
          wgmma_ss_n56_ta0_tb1<1>(acc1, dA + 1024 + ks * 2, dB + 512 + ks * 128);
        }
        wg_commit();
        if (c < 4) {
          wg_wait<0>();
          if (lane == 0) mbar_arrive(BAR(B_EMPTY + slot), 2);
        }
        if (++slot == 3) { slot = 0; par ^= 1; }
      }
      wg_wait<0>();
      fence_regs(acc0); fence_regs(acc1);
      if (tid == 0) PROF_MARK(17);
      __nv_bfloat16* op = prm.out + (size_t)(pt * 128 + row0) * DM + hp * 56 + 2 * lq;
#pragma unroll
      for (int j = 0; j < 7; j++) {
        *(uint32_t*)(op + 8 * j) = pack_bf16(acc0[4 * j] + acc1[4 * j], acc0[4 * j + 1] + acc1[4 * j + 1]);
        *(uint32_t*)(op + 8 * DM + 8 * j) = pack_bf16(acc0[4 * j + 2] + acc1[4 * j + 2], acc0[4 * j + 3] + acc1[4 * j + 3]);
      }
      if (tid == 0) { PROF_MARK(18); PROF_CLK(31); }
    }
  }
}

typedef CUresult (*EncodeFn)(CUtensorMap*, CUtensorMapDataType, cuuint32_t, void*, const cuuint64_t*, const cuuint64_t*,
                             const cuuint32_t*, const cuuint32_t*, CUtensorMapInterleave, CUtensorMapSwizzle,
                             CUtensorMapL2promotion, CUtensorMapFloatOOBfill);

void make_map(EncodeFn enc, CUtensorMap* tm, const void* ptr, uint64_t cols, uint64_t rows, uint32_t box_cols, uint32_t box_rows) {
  cuuint64_t dims[2] = {cols, rows};
  cuuint64_t strides[1] = {cols * 2};
  cuuint32_t box[2] = {box_cols, box_rows};
  cuuint32_t es[2] = {1, 1};
  enc(tm, CU_TENSOR_MAP_DATA_TYPE_BFLOAT16, 2, const_cast<void*>(ptr), dims, strides, box, es, CU_TENSOR_MAP_INTERLEAVE_NONE,
      CU_TENSOR_MAP_SWIZZLE_128B, CU_TENSOR_MAP_L2_PROMOTION_L2_128B, CU_TENSOR_MAP_FLOAT_OOB_FILL_NONE);
}

}

extern "C" void kernel_launch(void* const* d_in, const int* in_sizes, int n_in, void* d_out, int out_size) {
  (void)in_sizes; (void)n_in; (void)out_size;
  static EncodeFn enc = nullptr;
  if (!enc) {
    void* fn = nullptr;
    cudaDriverEntryPointQueryResult qr;
    cudaGetDriverEntryPoint("cuTensorMapEncodeTiled", &fn, cudaEnableDefault, &qr);
    enc = (EncodeFn)fn;
    cudaFuncSetAttribute(fused_kernel, cudaFuncAttributeMaxDynamicSharedMemorySize, SMEM_BYTES);
  }
  CUtensorMap tm_x, tm_wqkv, tm_wq, tm_woa, tm_wob;
  make_map(enc, &tm_x, d_in[0], DM, S_LEN, 64, 128);
  make_map(enc, &tm_wqkv, d_in[1], 3 * DM, DM, 56, 64);
  make_map(enc, &tm_wq, d_in[5], DM, DM, 56, 64);
  make_map(enc, &tm_woa, d_in[3], DM, DM, 56, 64);
  make_map(enc, &tm_wob, d_in[8], DM, DM, 56, 64);
  Params prm;
  prm.w_phi = (const __nv_bfloat16*)d_in[2];
  prm.wk = (const __nv_bfloat16*)d_in[6];
  prm.wv = (const __nv_bfloat16*)d_in[7];
  prm.gate_w = (const __nv_bfloat16*)d_in[9];
  prm.out = (__nv_bfloat16*)d_out;
  fused_kernel<<<NCTA, NTHREADS, SMEM_BYTES>>>(tm_x, tm_wqkv, tm_wq, tm_woa, tm_wob, prm);
}
```

```cpp
#include <cuda_runtime.h>
#include <cuda_bf16.h>
#include <cuda.h>
#include <stdint.h>

namespace {

constexpr int S_LEN = 2048, DM = 448, DH = 28;
constexpr int NCTA = 128;
constexpr int NTHREADS = 640;
constexpr uint32_t POLY_PAT = 0x57;

#define QB_AT (4 + nh)

constexpr int OFF_X = 0;
constexpr int OFF_PHIK = 0;
constexpr int OFF_VA = 32768;
constexpr int OFF_PHIQ = 57344;
constexpr int OFF_KVR = 90112;
constexpr int OFF_QP = 98304;
constexpr int OFF_RAW = 81920;
constexpr int OFF_WO = 0;
constexpr int OFF_RING = 114688;
constexpr int OFF_WBD = 212992;
constexpr int OFF_SLC = 221184;
constexpr int OFF_QSQ = 228352;
constexpr int OFF_GATE = 229376;
constexpr int OFF_RED = 229888;
constexpr int OFF_BAR = 229952;
constexpr int SMEM_BYTES = 230400 + 1024;

constexpr int B_FULL = 0, B_EMPTY = 3, B_WO = 6  , B_KVR = 8, B_RAW = 9, B_X1FREE = 10, B_QSQ = 11, B_SLOW = 12,
              B_BUILD = 13, B_SIG = 14  , B_N = 18;

constexpr int C_KV = 0, C_PART = 1, C_DONE = 3, C_OA = 4, C_OB = 20, C_N = 36;

__device__ __align__(1024) uint8_t g_kv_img[32 * 8192];
__device__ __align__(16) float g_ksq[512];
__device__ __align__(16) float g_vsq[512];
__device__ __align__(16) float g_gate[S_LEN];
__device__ __align__(1024) float g_kvacc[2][16 * 64 * 32];
__device__ unsigned g_epoch;
__device__ __align__(1024) uint8_t g_o_img[2 * 16 * 14 * 8192];
__device__ unsigned g_cnt[C_N * 32];

#define PROF4(i) do { } while (0)
#define PROF3(i) do { } while (0)
#define PROF2(i) do { } while (0)
#define PROF_CLK(i) do { } while (0)
#define PROF_MARK(i) do { } while (0)
__device__ __forceinline__ uint32_t smem_u32(const void* p) { return (uint32_t)__cvta_generic_to_shared(p); }
__device__ __forceinline__ void mbar_init(uint32_t a, int cnt) {
  asm volatile("mbarrier.init.shared::cta.b64 [%0], %1;" ::"r"(a), "r"(cnt) : "memory");
}
__device__ __forceinline__ void mbar_expect_tx(uint32_t a, uint32_t bytes) {
  asm volatile("mbarrier.arrive.expect_tx.shared::cta.b64 _, [%0], %1;" ::"r"(a), "r"(bytes) : "memory");
}
__device__ __forceinline__ void mbar_arrive(uint32_t a, uint32_t cnt) {
  asm volatile("mbarrier.arrive.shared::cta.b64 _, [%0], %1;" ::"r"(a), "r"(cnt) : "memory");
}
__device__ __forceinline__ void mbar_wait(uint32_t a, uint32_t parity) {
  asm volatile(
      "{\n.reg .pred p;\n.reg .u32 c;\nmov.u32 c, 0;\n"
      "W_%=:\nmbarrier.try_wait.parity.shared::cta.b64 p, [%0], %1;\n"
      "add.u32 c, c, 1;\nsetp.lt.and.u32 p, c, 0x40000, !p;\n@p bra W_%=;\n}"
      ::"r"(a), "r"(parity) : "memory");
}
__device__ __forceinline__ uint32_t mbar_test(uint32_t a, uint32_t parity) {
  uint32_t ok;
  asm volatile("{\n.reg .pred p;\nmbarrier.test_wait.parity.shared::cta.b64 p, [%1], %2;\nselp.u32 %0, 1, 0, p;\n}"
               : "=r"(ok) : "r"(a), "r"(parity) : "memory");
  return ok;
}
__device__ __forceinline__ bool elect_one() {
  uint32_t r;
  asm volatile("{\n.reg .pred p;\nelect.sync _|p, 0xffffffff;\nselp.u32 %0, 1, 0, p;\n}" : "=r"(r));
  return r != 0;
}
__device__ __forceinline__ void tma_2d(uint32_t dst, const CUtensorMap* tm, int c0, int c1, uint32_t bar) {
  asm volatile("cp.async.bulk.tensor.2d.shared::cluster.global.mbarrier::complete_tx::bytes [%0], [%1, {%3, %4}], [%2];"
               ::"r"(dst), "l"(tm), "r"(bar), "r"(c0), "r"(c1) : "memory");
}
__device__ __forceinline__ void bulk_g2s(uint32_t dst, const void* src, uint32_t bytes, uint32_t bar) {
  asm volatile("cp.async.bulk.shared::cluster.global.mbarrier::complete_tx::bytes [%0], [%1], %2, [%3];"
               ::"r"(dst), "l"(src), "r"(bytes), "r"(bar) : "memory");
}
__device__ __forceinline__ void fence_async_smem() { asm volatile("fence.proxy.async.shared::cta;" ::: "memory"); }
__device__ __forceinline__ void fence_async_all() { asm volatile("fence.proxy.async.global;" ::: "memory"); }

__device__ __forceinline__ void bar_sync(int id, int n) { asm volatile("bar.sync %0, %1;" ::"r"(id), "r"(n) : "memory"); }
__device__ __forceinline__ void cnt_arrive(int idx) {
  asm volatile("red.release.gpu.global.add.u32 [%0], 1;" ::"l"(&g_cnt[idx * 32]) : "memory");
}
__device__ __forceinline__ void cnt_wait(int idx, unsigned target) {
  unsigned v, n = 0;
#pragma unroll 1
  while (true) {
    asm volatile("ld.acquire.gpu.global.u32 %0, [%1];" : "=r"(v) : "l"(&g_cnt[idx * 32]) : "memory");
    if (v >= target || ++n >= (1u << 18)) break;
    __nanosleep(32);
  }
}
__device__ __forceinline__ void wg_fence() { asm volatile("wgmma.fence.sync.aligned;" ::: "memory"); }
__device__ __forceinline__ void wg_commit() { asm volatile("wgmma.commit_group.sync.aligned;" ::: "memory"); }
template <int N> __device__ __forceinline__ void wg_wait() { asm volatile("wgmma.wait_group.sync.aligned %0;" ::"n"(N) : "memory"); }
template <int N> __device__ __forceinline__ void fence_regs(float (&d)[N]) {
#pragma unroll
  for (int i = 0; i < N; i++) asm volatile("" : "+f"(d[i])::"memory");
}
__device__ __forceinline__ uint64_t make_desc(uint32_t saddr, uint32_t lbo, uint32_t sbo, uint32_t swz) {
  return (uint64_t)((saddr & 0x3FFFF) >> 4) | ((uint64_t)(lbo >> 4) << 16) | ((uint64_t)(sbo >> 4) << 32) | ((uint64_t)swz << 62);
}
__device__ __forceinline__ float ex2f(float x) { float y; asm("ex2.approx.ftz.f32 %0, %1;" : "=f"(y) : "f"(x)); return y; }
__device__ __forceinline__ float rcpf(float x) { float y; asm("rcp.approx.ftz.f32 %0, %1;" : "=f"(y) : "f"(x)); return y; }
__device__ __forceinline__ uint32_t pack_bf16(float lo, float hi) {
  uint32_t r; asm("cvt.rn.bf16x2.f32 %0, %1, %2;" : "=r"(r) : "f"(hi), "f"(lo)); return r;
}
__device__ __forceinline__ uint32_t lop_and_or(uint32_t a, uint32_t m, uint32_t c) {
  uint32_t r; asm("lop3.b32 %0, %1, %2, %3, 0xEA;" : "=r"(r) : "r"(a), "r"(m), "r"(c)); return r;
}
__device__ __forceinline__ void sts32(uint32_t a, uint32_t v) { asm volatile("st.shared.b32 [%0], %1;" ::"r"(a), "r"(v) : "memory"); }
__device__ __forceinline__ void sts64(uint32_t a, uint32_t v0, uint32_t v1) { asm volatile("st.shared.v2.b32 [%0], {%1, %2};" ::"r"(a), "r"(v0), "r"(v1) : "memory"); }
__device__ __forceinline__ void sts128(uint32_t a, uint4 v) {
  asm volatile("st.shared.v4.b32 [%0], {%1, %2, %3, %4};" ::"r"(a), "r"(v.x), "r"(v.y), "r"(v.z), "r"(v.w) : "memory");
}
__device__ __forceinline__ float4 ldcg_f4(const float* p) {
  float4 v; asm volatile("ld.global.cg.v4.f32 {%0, %1, %2, %3}, [%4];" : "=f"(v.x), "=f"(v.y), "=f"(v.z), "=f"(v.w) : "l"(p) : "memory"); return v;
}
__device__ __forceinline__ void ldsm4(uint32_t* r, uint32_t a) {
  asm volatile("ldmatrix.sync.aligned.m8n8.x4.shared.b16 {%0, %1, %2, %3}, [%4];"
               : "=r"(r[0]), "=r"(r[1]), "=r"(r[2]), "=r"(r[3]) : "r"(a) : "memory");
}
__device__ __forceinline__ float quad_sum(float v) { v += __shfl_xor_sync(~0u, v, 1); v += __shfl_xor_sync(~0u, v, 2); return v; }
__device__ __forceinline__ float quad_max(float v) { v = fmaxf(v, __shfl_xor_sync(~0u, v, 1)); v = fmaxf(v, __shfl_xor_sync(~0u, v, 2)); return v; }

template <int SD> __device__ __forceinline__ void wgmma_ss_n56_ta0_tb1(float (&d)[28], uint64_t da, uint64_t db) {
  if (SD) asm volatile("wgmma.mma_async.sync.aligned.m64n56k16.f32.bf16.bf16 {%0, %1, %2, %3, %4, %5, %6, %7, %8, %9, %10, %11, %12, %13, %14, %15, %16, %17, %18, %19, %20, %21, %22, %23, %24, %25, %26, %27}, %28, %29, 1, 1, 1, 0, 1;\n"
    : "+f"(d[0]), "+f"(d[1]), "+f"(d[2]), "+f"(d[3]), "+f"(d[4]), "+f"(d[5]), "+f"(d[6]), "+f"(d[7]), "+f"(d[8]), "+f"(d[9]), "+f"(d[10]), "+f"(d[11]), "+f"(d[12]), "+f"(d[13]), "+f"(d[14]), "+f"(d[15]), "+f"(d[16]), "+f"(d[17]), "+f"(d[18]), "+f"(d[19]), "+f"(d[20]), "+f"(d[21]), "+f"(d[22]), "+f"(d[23]), "+f"(d[24]), "+f"(d[25]), "+f"(d[26]), "+f"(d[27])
    : "l"(da), "l"(db));
  else asm volatile("wgmma.mma_async.sync.aligned.m64n56k16.f32.bf16.bf16 {%0, %1, %2, %3, %4, %5, %6, %7, %8, %9, %10, %11, %12, %13, %14, %15, %16, %17, %18, %19, %20, %21, %22, %23, %24, %25, %26, %27}, %28, %29, 0, 1, 1, 0, 1;\n"
    : "=f"(d[0]), "=f"(d[1]), "=f"(d[2]), "=f"(d[3]), "=f"(d[4]), "=f"(d[5]), "=f"(d[6]), "=f"(d[7]), "=f"(d[8]), "=f"(d[9]), "=f"(d[10]), "=f"(d[11]), "=f"(d[12]), "=f"(d[13]), "=f"(d[14]), "=f"(d[15]), "=f"(d[16]), "=f"(d[17]), "=f"(d[18]), "=f"(d[19]), "=f"(d[20]), "=f"(d[21]), "=f"(d[22]), "=f"(d[23]), "=f"(d[24]), "=f"(d[25]), "=f"(d[26]), "=f"(d[27])
    : "l"(da), "l"(db));
}
template <int SD> __device__ __forceinline__ void wgmma_ss_n8_ta0_tb1(float (&d)[4], uint64_t da, uint64_t db) {
  if (SD) asm volatile("wgmma.mma_async.sync.aligned.m64n8k16.f32.bf16.bf16 {%0, %1, %2, %3}, %4, %5, 1, 1, 1, 0, 1;\n"
    : "+f"(d[0]), "+f"(d[1]), "+f"(d[2]), "+f"(d[3])
    : "l"(da), "l"(db));
  else asm volatile("wgmma.mma_async.sync.aligned.m64n8k16.f32.bf16.bf16 {%0, %1, %2, %3}, %4, %5, 0, 1, 1, 0, 1;\n"
    : "=f"(d[0]), "=f"(d[1]), "=f"(d[2]), "=f"(d[3])
    : "l"(da), "l"(db));
}
template <int SD> __device__ __forceinline__ void wgmma_rs_n64_tb1(float (&d)[32], uint32_t a0, uint32_t a1, uint32_t a2, uint32_t a3, uint64_t db) {
  if (SD) asm volatile("wgmma.mma_async.sync.aligned.m64n64k16.f32.bf16.bf16 {%0, %1, %2, %3, %4, %5, %6, %7, %8, %9, %10, %11, %12, %13, %14, %15, %16, %17, %18, %19, %20, %21, %22, %23, %24, %25, %26, %27, %28, %29, %30, %31}, {%32, %33, %34, %35}, %36, 1, 1, 1, 1;\n"
    : "+f"(d[0]), "+f"(d[1]), "+f"(d[2]), "+f"(d[3]), "+f"(d[4]), "+f"(d[5]), "+f"(d[6]), "+f"(d[7]), "+f"(d[8]), "+f"(d[9]), "+f"(d[10]), "+f"(d[11]), "+f"(d[12]), "+f"(d[13]), "+f"(d[14]), "+f"(d[15]), "+f"(d[16]), "+f"(d[17]), "+f"(d[18]), "+f"(d[19]), "+f"(d[20]), "+f"(d[21]), "+f"(d[22]), "+f"(d[23]), "+f"(d[24]), "+f"(d[25]), "+f"(d[26]), "+f"(d[27]), "+f"(d[28]), "+f"(d[29]), "+f"(d[30]), "+f"(d[31])
    : "r"(a0), "r"(a1), "r"(a2), "r"(a3), "l"(db));
  else asm volatile("wgmma.mma_async.sync.aligned.m64n64k16.f32.bf16.bf16 {%0, %1, %2, %3, %4, %5, %6, %7, %8, %9, %10, %11, %12, %13, %14, %15, %16, %17, %18, %19, %20, %21, %22, %23, %24, %25, %26, %27, %28, %29, %30, %31}, {%32, %33, %34, %35}, %36, 0, 1, 1, 1;\n"
    : "=f"(d[0]), "=f"(d[1]), "=f"(d[2]), "=f"(d[3]), "=f"(d[4]), "=f"(d[5]), "=f"(d[6]), "=f"(d[7]), "=f"(d[8]), "=f"(d[9]), "=f"(d[10]), "=f"(d[11]), "=f"(d[12]), "=f"(d[13]), "=f"(d[14]), "=f"(d[15]), "=f"(d[16]), "=f"(d[17]), "=f"(d[18]), "=f"(d[19]), "=f"(d[20]), "=f"(d[21]), "=f"(d[22]), "=f"(d[23]), "=f"(d[24]), "=f"(d[25]), "=f"(d[26]), "=f"(d[27]), "=f"(d[28]), "=f"(d[29]), "=f"(d[30]), "=f"(d[31])
    : "r"(a0), "r"(a1), "r"(a2), "r"(a3), "l"(db));
}
template <int SD> __device__ __forceinline__ void wgmma_ss_n32_ta1_tb1(float (&d)[16], uint64_t da, uint64_t db) {
  if (SD) asm volatile("wgmma.mma_async.sync.aligned.m64n32k16.f32.bf16.bf16 {%0, %1, %2, %3, %4, %5, %6, %7, %8, %9, %10, %11, %12, %13, %14, %15}, %16, %17, 1, 1, 1, 1, 1;\n"
    : "+f"(d[0]), "+f"(d[1]), "+f"(d[2]), "+f"(d[3]), "+f"(d[4]), "+f"(d[5]), "+f"(d[6]), "+f"(d[7]), "+f"(d[8]), "+f"(d[9]), "+f"(d[10]), "+f"(d[11]), "+f"(d[12]), "+f"(d[13]), "+f"(d[14]), "+f"(d[15])
    : "l"(da), "l"(db));
  else asm volatile("wgmma.mma_async.sync.aligned.m64n32k16.f32.bf16.bf16 {%0, %1, %2, %3, %4, %5, %6, %7, %8, %9, %10, %11, %12, %13, %14, %15}, %16, %17, 0, 1, 1, 1, 1;\n"
    : "=f"(d[0]), "=f"(d[1]), "=f"(d[2]), "=f"(d[3]), "=f"(d[4]), "=f"(d[5]), "=f"(d[6]), "=f"(d[7]), "=f"(d[8]), "=f"(d[9]), "=f"(d[10]), "=f"(d[11]), "=f"(d[12]), "=f"(d[13]), "=f"(d[14]), "=f"(d[15])
    : "l"(da), "l"(db));
}
template <int SD> __device__ __forceinline__ void wgmma_ss_n32_ta0_tb1(float (&d)[16], uint64_t da, uint64_t db) {
  if (SD) asm volatile("wgmma.mma_async.sync.aligned.m64n32k16.f32.bf16.bf16 {%0, %1, %2, %3, %4, %5, %6, %7, %8, %9, %10, %11, %12, %13, %14, %15}, %16, %17, 1, 1, 1, 0, 1;\n"
    : "+f"(d[0]), "+f"(d[1]), "+f"(d[2]), "+f"(d[3]), "+f"(d[4]), "+f"(d[5]), "+f"(d[6]), "+f"(d[7]), "+f"(d[8]), "+f"(d[9]), "+f"(d[10]), "+f"(d[11]), "+f"(d[12]), "+f"(d[13]), "+f"(d[14]), "+f"(d[15])
    : "l"(da), "l"(db));
  else asm volatile("wgmma.mma_async.sync.aligned.m64n32k16.f32.bf16.bf16 {%0, %1, %2, %3, %4, %5, %6, %7, %8, %9, %10, %11, %12, %13, %14, %15}, %16, %17, 0, 1, 1, 0, 1;\n"
    : "=f"(d[0]), "=f"(d[1]), "=f"(d[2]), "=f"(d[3]), "=f"(d[4]), "=f"(d[5]), "=f"(d[6]), "=f"(d[7]), "=f"(d[8]), "=f"(d[9]), "=f"(d[10]), "=f"(d[11]), "=f"(d[12]), "=f"(d[13]), "=f"(d[14]), "=f"(d[15])
    : "l"(da), "l"(db));
}
template <int SD> __device__ __forceinline__ void wgmma_rs_n64_tb0(float (&d)[32], uint32_t a0, uint32_t a1, uint32_t a2, uint32_t a3, uint64_t db) {
  if (SD) asm volatile("wgmma.mma_async.sync.aligned.m64n64k16.f32.bf16.bf16 {%0, %1, %2, %3, %4, %5, %6, %7, %8, %9, %10, %11, %12, %13, %14, %15, %16, %17, %18, %19, %20, %21, %22, %23, %24, %25, %26, %27, %28, %29, %30, %31}, {%32, %33, %34, %35}, %36, 1, 1, 1, 0;\n"
    : "+f"(d[0]), "+f"(d[1]), "+f"(d[2]), "+f"(d[3]), "+f"(d[4]), "+f"(d[5]), "+f"(d[6]), "+f"(d[7]), "+f"(d[8]), "+f"(d[9]), "+f"(d[10]), "+f"(d[11]), "+f"(d[12]), "+f"(d[13]), "+f"(d[14]), "+f"(d[15]), "+f"(d[16]), "+f"(d[17]), "+f"(d[18]), "+f"(d[19]), "+f"(d[20]), "+f"(d[21]), "+f"(d[22]), "+f"(d[23]), "+f"(d[24]), "+f"(d[25]), "+f"(d[26]), "+f"(d[27]), "+f"(d[28]), "+f"(d[29]), "+f"(d[30]), "+f"(d[31])
    : "r"(a0), "r"(a1), "r"(a2), "r"(a3), "l"(db));
  else asm volatile("wgmma.mma_async.sync.aligned.m64n64k16.f32.bf16.bf16 {%0, %1, %2, %3, %4, %5, %6, %7, %8, %9, %10, %11, %12, %13, %14, %15, %16, %17, %18, %19, %20, %21, %22, %23, %24, %25, %26, %27, %28, %29, %30, %31}, {%32, %33, %34, %35}, %36, 0, 1, 1, 0;\n"
    : "=f"(d[0]), "=f"(d[1]), "=f"(d[2]), "=f"(d[3]), "=f"(d[4]), "=f"(d[5]), "=f"(d[6]), "=f"(d[7]), "=f"(d[8]), "=f"(d[9]), "=f"(d[10]), "=f"(d[11]), "=f"(d[12]), "=f"(d[13]), "=f"(d[14]), "=f"(d[15]), "=f"(d[16]), "=f"(d[17]), "=f"(d[18]), "=f"(d[19]), "=f"(d[20]), "=f"(d[21]), "=f"(d[22]), "=f"(d[23]), "=f"(d[24]), "=f"(d[25]), "=f"(d[26]), "=f"(d[27]), "=f"(d[28]), "=f"(d[29]), "=f"(d[30]), "=f"(d[31])
    : "r"(a0), "r"(a1), "r"(a2), "r"(a3), "l"(db));
}
template <int SD> __device__ __forceinline__ void wgmma_rs_n32_tb1(float (&d)[16], uint32_t a0, uint32_t a1, uint32_t a2, uint32_t a3, uint64_t db) {
  if (SD) asm volatile("wgmma.mma_async.sync.aligned.m64n32k16.f32.bf16.bf16 {%0, %1, %2, %3, %4, %5, %6, %7, %8, %9, %10, %11, %12, %13, %14, %15}, {%16, %17, %18, %19}, %20, 1, 1, 1, 1;\n"
    : "+f"(d[0]), "+f"(d[1]), "+f"(d[2]), "+f"(d[3]), "+f"(d[4]), "+f"(d[5]), "+f"(d[6]), "+f"(d[7]), "+f"(d[8]), "+f"(d[9]), "+f"(d[10]), "+f"(d[11]), "+f"(d[12]), "+f"(d[13]), "+f"(d[14]), "+f"(d[15])
    : "r"(a0), "r"(a1), "r"(a2), "r"(a3), "l"(db));
  else asm volatile("wgmma.mma_async.sync.aligned.m64n32k16.f32.bf16.bf16 {%0, %1, %2, %3, %4, %5, %6, %7, %8, %9, %10, %11, %12, %13, %14, %15}, {%16, %17, %18, %19}, %20, 0, 1, 1, 1;\n"
    : "=f"(d[0]), "=f"(d[1]), "=f"(d[2]), "=f"(d[3]), "=f"(d[4]), "=f"(d[5]), "=f"(d[6]), "=f"(d[7]), "=f"(d[8]), "=f"(d[9]), "=f"(d[10]), "=f"(d[11]), "=f"(d[12]), "=f"(d[13]), "=f"(d[14]), "=f"(d[15])
    : "r"(a0), "r"(a1), "r"(a2), "r"(a3), "l"(db));
}

__device__ __forceinline__ uint32_t sw64_off(int row, int d) { return row * 64 + ((((d >> 3) ^ (row >> 1)) & 3) << 4) + (d & 7) * 2; }

__device__ __forceinline__ uint32_t exp2_pair_fma(float t0, float t1, uint32_t c_half, uint32_t c_3) {
  uint32_t y0, y;
  asm("prmt.b32 %0, %1, %2, 0x6521;" : "=r"(y0) : "r"(__float_as_uint(t0)), "r"(__float_as_uint(t1)));
  uint32_t h = lop_and_or(y0, 0x007F007Fu, c_half);
  uint32_t e = lop_and_or(y0, 0xFF80FF80u, c_3);
  asm("fma.rn.bf16x2 %0, %1, %2, %3;" : "=r"(y) : "r"(y0), "r"(h), "r"(e));
  return y;
}

__device__ __forceinline__ void feature_map(float (&v)[16], uint32_t (&ph)[16], int lq) {
  const float L2E = 1.4426950408889634f;
  const bool tail_ok = lq < 2;
  float mx[2], mn[2], b[16], sa[2], sn[2];
#pragma unroll
  for (int r = 0; r < 2; r++) {
    const int o = 2 * r;
    if (!tail_ok) { v[o + 12] = v[o]; v[o + 13] = v[o]; }
    mx[r] = fmaxf(fmaxf(fmaxf(v[o], v[o + 1]), fmaxf(v[o + 4], v[o + 5])), fmaxf(fmaxf(v[o + 8], v[o + 9]), fmaxf(v[o + 12], v[o + 13])));
    mn[r] = fminf(fminf(fminf(v[o], v[o + 1]), fminf(v[o + 4], v[o + 5])), fminf(fminf(v[o + 8], v[o + 9]), fminf(v[o + 12], v[o + 13])));
  }
#pragma unroll
  for (int o = 1; o <= 2; o <<= 1)
#pragma unroll
    for (int r = 0; r < 2; r++) { mx[r] = fmaxf(mx[r], __shfl_xor_sync(~0u, mx[r], o)); mn[r] = fminf(mn[r], __shfl_xor_sync(~0u, mn[r], o)); }
#pragma unroll
  for (int r = 0; r < 2; r++) {
    const int o = 2 * r;
    const float cx = -mx[r] * L2E, cn = mn[r] * L2E;
#pragma unroll
    for (int i = 0; i < 8; i++) {
      const int k = o + 4 * (i >> 1) + (i & 1);
      b[k] = ex2f(fmaf(v[k], -L2E, cn));
      v[k] = ex2f(fmaf(v[k], L2E, cx));
    }
    if (!tail_ok) { v[o + 12] = v[o + 13] = b[o + 12] = b[o + 13] = 0.f; }
    sa[r] = ((v[o] + v[o + 1]) + (v[o + 4] + v[o + 5])) + ((v[o + 8] + v[o + 9]) + (v[o + 12] + v[o + 13]));
    sn[r] = ((b[o] + b[o + 1]) + (b[o + 4] + b[o + 5])) + ((b[o + 8] + b[o + 9]) + (b[o + 12] + b[o + 13]));
  }
#pragma unroll
  for (int o = 1; o <= 2; o <<= 1)
#pragma unroll
    for (int r = 0; r < 2; r++) { sa[r] += __shfl_xor_sync(~0u, sa[r], o); sn[r] += __shfl_xor_sync(~0u, sn[r], o); }
#pragma unroll
  for (int r = 0; r < 2; r++) {
    const float ra = rcpf(sa[r]), rb = rcpf(sn[r]);
#pragma unroll
    for (int jj = 0; jj < 4; jj++) {
      ph[jj * 2 + r] = pack_bf16(v[2 * r + 4 * jj] * ra, v[2 * r + 4 * jj + 1] * ra);
      ph[(4 + jj) * 2 + r] = pack_bf16(b[2 * r + 4 * jj] * rb, b[2 * r + 4 * jj + 1] * rb);
    }
  }
}

__device__ __forceinline__ void store_heads(uint32_t base, const uint32_t (&a)[14], uint32_t pad0, uint32_t pad1, int row0, int lq) {
  const uint32_t rb = base + row0 * 64 + (((row0 >> 1) & 3) << 4);
  const uint32_t b0 = rb + lq * 4;
  const uint32_t b1 = (rb + 8192 + ((lq * 4 + 8) & 15)) ^ ((lq >> 1) << 4);
#pragma unroll
  for (int j = 0; j < 7; j++) {
    uint32_t ad;
    if (j < 3) ad = b0 ^ (j << 4);
    else if (j == 3) ad = (lq < 2) ? (b0 ^ 48u) : (b1 ^ 16u);
    else ad = (lq < 2) ? (b1 ^ ((j - 4) << 4)) : ((b1 ^ 16u) ^ ((j - 3) << 4));
    sts32(ad, a[2 * j]);
    sts32(ad + 512, a[2 * j + 1]);
  }
  sts64((rb ^ 48u) + 8 + (lq & 1) * 8192 + (lq >> 1) * 512, pad0, pad1);
}

struct Params {
  const __nv_bfloat16* w_phi;
  const __nv_bfloat16* wk;
  const __nv_bfloat16* wv;
  const __nv_bfloat16* gate_w;
  __nv_bfloat16* out;
};

__global__ void __launch_bounds__(NTHREADS, 1)
fused_kernel(const __grid_constant__ CUtensorMap tm_x, const __grid_constant__ CUtensorMap tm_wqkv,
             const __grid_constant__ CUtensorMap tm_wq, const __grid_constant__ CUtensorMap tm_woa,
             const __grid_constant__ CUtensorMap tm_wob, const Params prm) {
  extern __shared__ uint8_t smem_raw[];
  uint32_t sb = (smem_u32(smem_raw) + 1023u) & ~1023u;
  uint8_t* sgen = smem_raw + (sb - smem_u32(smem_raw));
  asm volatile("mov.u32 %0, %0;" : "+r"(sb));
  const int tid = threadIdx.x, lane = tid & 31;
  const int warp = __shfl_sync(~0u, tid >> 5, 0), wg = warp >> 2;
  const int pt = blockIdx.x >> 3, hp = blockIdx.x & 7;
  const uint32_t bars = sb + OFF_BAR;
  auto BAR = [&](int i) { return bars + 8u * i; };
  const unsigned epoch = g_epoch & 1;

  if (tid == 0) { PROF_MARK(0); PROF_CLK(30); PROF2(15); }
  auto load_proj = [&](int c, int g) {
    mbar_expect_tx(BAR(B_FULL + g), 16384 + 4 * 7168);
    tma_2d(sb + OFF_X + c * 16384, &tm_x, c * 64, pt * 128, BAR(B_FULL + g));
    tma_2d(sb + OFF_RING + g * 32768, &tm_wq, hp * 56, c * 64, BAR(B_FULL + g));
#pragma unroll 1
    for (int j = 0; j < 3; j++) tma_2d(sb + OFF_RING + g * 32768 + 8192 + j * 8192, &tm_wqkv, j * DM + hp * 56, c * 64, BAR(B_FULL + g));
  };
  if (warp == 16) {
    if (elect_one()) {
      mbar_init(BAR(B_FULL), 1);
      fence_async_smem();
      load_proj(0, 0);
      mbar_init(BAR(B_RAW), 1); mbar_init(BAR(B_FULL + 1), 1); mbar_init(BAR(B_FULL + 2), 1);
      fence_async_smem();
    }
    __syncwarp();
    asm volatile("bar.arrive 0, %0;" ::"n"(NTHREADS) : "memory");
  } else {
    if (elect_one()) {
      const int i = warp + 3 - (warp > 16);
      if (i < B_N && i != B_RAW) {
        int cnt = i < B_WO || i > B_SIG || i == B_X1FREE ? 16 : 1;
        if (i == B_BUILD) cnt = 16;
        if (i == B_SIG || i == B_SIG + 1 || i == B_QSQ) cnt = 8;
        if (i == B_KVR) cnt = 2;
        mbar_init(BAR(i), cnt);
        fence_async_smem();
      }
    }
    bar_sync(0, NTHREADS);
  }
  if (tid == 0) PROF2(14);

  if (wg == 4) {
    asm volatile("setmaxnreg.dec.sync.aligned.u32 32;");
    if (warp == 16) {
      if (elect_one()) {
        mbar_expect_tx(BAR(B_RAW), 25088 + 3136 + 896);
        bulk_g2s(sb + OFF_RAW, hp < 4 ? prm.wk : prm.wv, 25088, BAR(B_RAW));
        bulk_g2s(sb + OFF_RAW + 25088, prm.w_phi + 2 * hp * DH * DH, 3136, BAR(B_RAW));
        bulk_g2s(sb + OFF_RAW + 28224, prm.gate_w, 896, BAR(B_RAW));
        load_proj(1, 1);
        load_proj(2, 2);
      }
      __syncwarp();
      bar_sync(3, 64);
      if (elect_one()) {
        int g = 0, nkv = 8;
        uint32_t par = 0;
#pragma unroll 1
        for (int n = 3; n < 14 + nkv; n++) {
          if (n == 7) { PROF_MARK(20); cnt_wait(C_KV, NCTA); PROF_MARK(21); fence_async_all(); }
          if (n == 15) {
            mbar_wait(BAR(B_SLOW), 0);
            if (*(volatile int*)(sgen + OFF_RED)) nkv = 26;
          }
          const int j = n - 7 - nkv;
          if (j == 0 || j == 3) {
            PROF3(j ? 11 : 8);
            cnt_wait((j ? C_OB : C_OA) + pt, 8);
            PROF3(j ? 12 : 9);
            PROF_MARK(26);
            fence_async_all();
          }
          mbar_wait(BAR(B_EMPTY + g), par);
          if (n == 5) mbar_wait(BAR(B_BUILD), 0);
          if (n < 7) { PROF2(20 + n); load_proj(n, g); }
          else {
            mbar_expect_tx(BAR(B_FULL + g), 32768);
            bulk_g2s(sb + OFF_RING + g * 32768, j < 0 ? g_kv_img + ((n - 7) & 7) * 32768 : g_o_img + (size_t)(pt * 7 + j) * 32768, 32768,
                     BAR(B_FULL + g));
          }
          if (++g == 3) { g = 0; par ^= 1; }
        }
        if (atomicAdd(&g_cnt[C_DONE * 32], 1u) == NCTA - 1) {
#pragma unroll 1
          for (int i = 0; i < C_N; i++) g_cnt[i * 32] = 0;
          g_epoch = epoch ^ 1;
        }
      }
    } else {
      if (warp == 18) {
        if (elect_one()) {
#pragma unroll 1
          for (int i = 0; i < 4; i++) {
            mbar_wait(BAR(B_SIG + i), 0);
            PROF3(2 * i);
            if (i == 1) {
#pragma unroll 1
              for (int j = 0; j < 4; j++)
                asm volatile("cp.reduce.async.bulk.global.shared::cta.bulk_group.add.f32 [%0], [%1], 8192;"
                             ::"l"(g_kvacc[epoch] + hp * 4096 + (j >> 1) * 2048), "r"(sb + OFF_PHIK + j * 8192) : "memory");
              asm volatile("cp.async.bulk.commit_group;\ncp.async.bulk.wait_group 0;" ::: "memory");
            }
            cnt_arrive(i == 0 ? C_KV : i == 1 ? C_PART : (i == 2 ? C_OA : C_OB) + pt);
            PROF3(2 * i + 1);
            if (i == 1 || i == 2) {
              if (i == 2) mbar_wait(BAR(B_X1FREE), 0);
              mbar_expect_tx(BAR(B_WO + i - 1), 7 * 7168);
#pragma unroll 1
              for (int c = 0; c < 7; c++)
                tma_2d(sb + OFF_WO + (i - 1) * 57344 + c * 8192, i == 1 ? &tm_woa : &tm_wob, hp * 56, c * 64, BAR(B_WO + i - 1));
            }
          }
        }
      } else if (warp == 19) {
        if (lane == 0) {
          mbar_wait(BAR(B_SIG + 0), 0);
          cnt_wait(C_KV, NCTA);
        }
        __syncwarp();
        float ksq = 0.f, vsq = 0.f;
#pragma unroll
        for (int sl = 0; sl < 4; sl++) {
          float4 a = ldcg_f4(g_ksq + sl * 128 + lane * 4), b = ldcg_f4(g_vsq + sl * 128 + lane * 4);
          float m = fmaxf(fmaxf(a.x, a.y), fmaxf(a.z, a.w));
          m = __uint_as_float(__reduce_max_sync(~0u, __float_as_uint(m)));
          ksq += m;
          vsq = fmaxf(vsq, fmaxf(fmaxf(b.x, b.y), fmaxf(b.z, b.w)));
        }
        mbar_wait(BAR(B_QSQ), 0);
        const float4 qa4 = ((const float4*)(sgen + OFF_QSQ))[lane], qb4 = ((const float4*)(sgen + OFF_QSQ))[32 + lane];
        const float qmax = fmaxf(fmaxf(fmaxf(qa4.x, qa4.y), fmaxf(qa4.z, qa4.w)), fmaxf(fmaxf(qb4.x, qb4.y), fmaxf(qb4.z, qb4.w)));
        const bool slow = __any_sync(~0u, !(qmax * ksq <= 98.f * 98.f) || !(vsq <= 2.0e8f));
        if (lane == 0) {
          *(volatile int*)(sgen + OFF_RED) = slow;
          mbar_arrive(BAR(B_SLOW), 1);
        }
      } else {
        float4* z = (float4*)(g_kvacc[epoch ^ 1] + blockIdx.x * 256) + lane;
        z[0] = make_float4(0.f, 0.f, 0.f, 0.f);
        z[32] = make_float4(0.f, 0.f, 0.f, 0.f);
        bar_sync(3, 64);
        if (lane == 0) {
          mbar_wait(BAR(B_SIG + 0), 0);
          cnt_wait(C_KV, NCTA);
        }
        __syncwarp();
        ((float4*)(sgen + OFF_GATE))[lane] = ldcg_f4(g_gate + pt * 128 + lane * 4);
      }
      if (warp != 18) {
        if (lane == 0) {
          mbar_wait(BAR(B_SIG + 1), 0);
          cnt_wait(C_PART, NCTA);
          PROF_MARK(23);
        }
        __syncwarp();
        const int e = warp == 19;
        const float* src = g_kvacc[epoch] + hp * 4096 + e * 2048 + lane * 8;
#pragma unroll 1
        for (int i = 0; i < 8; i += 2) {
          const float4 a = ldcg_f4(src + i * 256), b = ldcg_f4(src + i * 256 + 4), c = ldcg_f4(src + i * 256 + 256), d = ldcg_f4(src + i * 256 + 260);
          const uint32_t ad = sb + OFF_KVR + e * 4096 + sw64_off(i * 8 + (lane >> 2), (lane & 3) * 8);
          sts128(ad, make_uint4(pack_bf16(a.x, a.y), pack_bf16(a.z, a.w), pack_bf16(b.x, b.y), pack_bf16(b.z, b.w)));
          sts128(ad + 512, make_uint4(pack_bf16(c.x, c.y), pack_bf16(c.z, c.w), pack_bf16(d.x, d.y), pack_bf16(d.z, d.w)));
        }
        fence_async_smem();
        __syncwarp();
        if (lane == 0) mbar_arrive(BAR(B_KVR), 1);
        PROF_MARK(24);
      }
    }
  } else {
    asm volatile("setmaxnreg.inc.sync.aligned.u32 112;");
    const int mh = wg & 1, nh = wg >> 1, wq = warp & 3;
    const int lq = lane & 3;
    const int rowl = wq * 16 + (lane >> 2);
    const int row0 = mh * 64 + rowl;
    int slot = 0, prev = 0;
    uint32_t par = 0;
    {
      float acc0[28], acc1[28], accs[4];
      const uint64_t dR = make_desc(sb + OFF_RING + nh * 16384, 1024, 1024, 1);
      const uint64_t dX = make_desc(sb + OFF_X + mh * 8192, 1024, 1024, 1);
#pragma unroll
      for (int i = 0; i < 28; i++) acc0[i] = acc1[i] = 0.f;
#pragma unroll
      for (int i = 0; i < 4; i++) accs[i] = 0.f;
      const uint64_t dSlc = make_desc(sb + OFF_SLC, 128, 128, 0);
#pragma unroll 1
      for (int c = 0; c < 7; c++) {
        mbar_wait(BAR(B_FULL + slot), par);
        if (c == 0 && tid == 0) PROF2(17);
        const uint64_t dA = dX + c * 1024, dB = dR + slot * 2048;
        wg_fence();
#pragma unroll
        for (int ks = 0; ks < 4; ks++) {
          wgmma_ss_n56_ta0_tb1<1>(acc0, dA + ks * 2, dB + ks * 128);
          wgmma_ss_n56_ta0_tb1<1>(acc1, dA + ks * 2, dB + 512 + ks * 128);
        }
        if (nh == 1 && c > 0) {
#pragma unroll
          for (int ks = 0; ks < 4; ks++) wgmma_ss_n8_ta0_tb1<1>(accs, dA - 1024 + ks * 2, dSlc + (c - 1) * 64 + ks * 16);
        }
        wg_commit();
        if ((tid & 127) == 0) PROF4(wg * 32 + c * 3);
        if (c == 0) {
          mbar_wait(BAR(B_RAW), 0);
          const int k = tid >> 3, cn = tid & 7;
          const bool data = k < 56 && (cn >> 2) == (k >= DH);
          const uint2* wsrc = (const uint2*)(sgen + OFF_RAW + 25088 + k * 56 + (cn & 3) * 16);
          uint2 w0 = make_uint2(0u, 0u), w1 = w0;
          if (data) w0 = wsrc[0];
          if (data && (cn & 3) != 3) w1 = wsrc[1];
          sts128(sb + OFF_WBD + k * 128 + ((cn ^ (k & 7)) << 4), make_uint4(w0.x, w0.y, w1.x, w1.y));
          if (tid < DM) {
            const uint2* src = (const uint2*)(sgen + OFF_RAW + tid * 56 + (hp & 3) * 16);
            w0 = src[0];
            w1 = make_uint2(hp == 3 ? (uint32_t)((const unsigned short*)(sgen + OFF_RAW + 28224))[tid] : 0u, 0u);
            if ((hp & 3) != 3) w1 = src[1];
            sts128(sb + OFF_SLC + tid * 16, make_uint4(w0.x, w0.y, w1.x, w1.y));
          }
          fence_async_smem();
          __syncwarp();
          if (lane == 0) mbar_arrive(BAR(B_BUILD), 1);
          mbar_wait(BAR(B_BUILD), 0);
        }
        else {
          wg_wait<1>();
          if (lane == 0) mbar_arrive(BAR(B_EMPTY + prev), 1);
        }
        if ((tid & 127) == 0) PROF4(wg * 32 + c * 3 + 2);
        prev = slot;
        if (++slot == 3) { slot = 0; par ^= 1; }
      }
      if (nh == 1) {
        wg_fence();
#pragma unroll
        for (int ks = 0; ks < 4; ks++) wgmma_ss_n8_ta0_tb1<1>(accs, dX + 6 * 1024 + ks * 2, dSlc + 6 * 64 + ks * 16);
        wg_commit();
      }
      wg_wait<0>();
      if (lane == 0) mbar_arrive(BAR(B_EMPTY + prev), 1);
      fence_regs(acc0); fence_regs(acc1); fence_regs(accs);
      if (tid == 0) PROF_MARK(2);
      if (tid == 256) PROF_MARK(3);
      if (nh == 0) {
        float sq[4] = {0.f, 0.f, 0.f, 0.f};
#pragma unroll
        for (int i = 0; i < 28; i++) acc0[i] *= 0.18898223650461362f * 1.4426950408889634f;
#pragma unroll
        for (int j = 0; j < 7; j++) {
#pragma unroll
          for (int rr = 0; rr < 2; rr++) {
            const float s2 = acc0[4 * j + 2 * rr] * acc0[4 * j + 2 * rr] + acc0[4 * j + 2 * rr + 1] * acc0[4 * j + 2 * rr + 1];
            if (j < 3) sq[rr] += s2;
            else if (j > 3) sq[2 + rr] += s2;
            else { sq[rr] += (lq < 2) ? s2 : 0.f; sq[2 + rr] += (lq < 2) ? 0.f : s2; }
          }
        }
#pragma unroll
        for (int i = 0; i < 4; i++) sq[i] = quad_sum(sq[i]);
        const float mine = lq == 0 ? sq[0] : lq == 1 ? sq[1] : lq == 2 ? sq[2] : sq[3];
        ((float*)(sgen + OFF_QSQ))[(mh + (lq & 2)) * 64 + rowl + 8 * (lq & 1)] = mine <= 3.0e38f ? mine : __int_as_float(0x7f800000);
        __syncwarp();
        if (lane == 0) mbar_arrive(BAR(B_QSQ), 1);
      } else {
        const int sl = hp & 3;
        const bool isk = hp < 4, real = (sl < 3) || (lq < 2);
        const int pos = pt * 128 + row0, kr = pos & 63;
        uint8_t* dst = g_kv_img + (pos >> 6) * 8192 + (isk ? 0 : 4096) + sw64_off(kr, sl * 8 + 2 * lq);
        const uint32_t pat = isk ? POLY_PAT >> (kr >> 3) : 0u;
        float mxv = 0.f;
#pragma unroll
        for (int rr = 0; rr < 2; rr++) {
          const float v0 = accs[2 * rr], v1 = accs[2 * rr + 1];
          const bool poly = (pat >> rr) & 1;
          const float sc = poly ? 2.f : 1.f;
          const float s2 = quad_sum(real ? v0 * v0 + v1 * v1 : 0.f);
          mxv = fmaxf(mxv, s2 <= 3.0e38f ? s2 : __int_as_float(0x7f800000));
          const uint32_t padv = lq == 2 ? (poly ? 0x443F4000u : 0x00003F80u) : (poly ? 0x3AB03F4Du : 0u);
          *(uint32_t*)(dst + rr * 512) = real ? pack_bf16(sc * v0, sc * v1) : padv;
          if (hp == 3 && lq == 2) g_gate[pos + 8 * rr] = rcpf(1.f + ex2f(-1.4426950408889634f * v0));
        }
        mxv = __uint_as_float(__reduce_max_sync(~0u, __float_as_uint(mxv)));
        if (lane == 0) (isk ? g_ksq : g_vsq)[sl * 128 + pt * 8 + mh * 4 + wq] = mxv;
        __syncwarp();
        if (lane == 0) mbar_arrive(BAR(B_SIG + 0), 1);
      }
      if (tid == 0) PROF_MARK(4);
      if (tid == 256) PROF_MARK(5);
      uint32_t h[14];
      float pp[32];
      {
        uint32_t a[16];
#pragma unroll
        for (int i = 0; i < 14; i++) {
          const uint32_t u0 = pack_bf16(acc0[2 * i], acc0[2 * i + 1]), u1 = pack_bf16(acc1[2 * i], acc1[2 * i + 1]);
          h[i] = nh ? u1 : u0;
          a[i] = nh ? u0 : u1;
        }
        a[14] = a[0] ^ 0x80008000u;
        a[15] = a[1] ^ 0x80008000u;
        const uint64_t dW = make_desc(sb + OFF_WBD, 1024, 1024, 1);
        wg_fence();
        wgmma_rs_n64_tb1<0>(pp, a[0], a[1], a[2], a[3], dW);
#pragma unroll
        for (int ks = 1; ks < 4; ks++) wgmma_rs_n64_tb1<1>(pp, a[4 * ks], a[4 * ks + 1], a[4 * ks + 2], a[4 * ks + 3], dW + ks * 128);
        wg_commit();
        bar_sync(1, 512);
        if (tid == 0) PROF_MARK(6);
        store_heads(sb + (nh ? OFF_VA : OFF_QP), h, nh ? 0x00003F80u : 0x3F800000u, nh ? 0u : 0x3F803F80u, row0, lq);
        wg_wait<0>();
        fence_regs(pp);
      }
      float v[16];
#pragma unroll
      for (int i = 0; i < 16; i++) v[i] = pp[i];
      uint32_t rb = sb + (nh ? OFF_PHIK : OFF_PHIQ) + row0 * 128 + lq * 4 + ((rowl & 7) << 4);
#pragma unroll 1
      for (int e = 0; e < 2; e++) {
        uint32_t ph[16];
        feature_map(v, ph, lq);
#pragma unroll
        for (int ch = 0; ch < 8; ch++) { sts32(rb ^ (ch << 4), ph[2 * ch]); sts32((rb ^ (ch << 4)) + 1024, ph[2 * ch + 1]); }
        rb += 16384;
#pragma unroll
        for (int i = 0; i < 16; i++) v[i] = pp[16 + i];
      }
      fence_async_smem();
      bar_sync(1, 512);
      if (tid == 0) PROF_MARK(7);
      if (nh == 1) {
        float kv0[16], kv1[16];
        const uint64_t dP = make_desc(sb + OFF_PHIK + mh * 8192, 1024, 1024, 1);
        const uint64_t dV = make_desc(sb + OFF_VA + mh * 4096, 512, 512, 2);
        wg_fence();
        wgmma_ss_n32_ta1_tb1<0>(kv0, dP, dV);
        wgmma_ss_n32_ta1_tb1<0>(kv1, dP + 1024, dV + 512);
#pragma unroll
        for (int ks = 1; ks < 4; ks++) {
          wgmma_ss_n32_ta1_tb1<1>(kv0, dP + ks * 128, dV + ks * 64);
          wgmma_ss_n32_ta1_tb1<1>(kv1, dP + 1024 + ks * 128, dV + 512 + ks * 64);
        }
        wg_commit();
        wg_wait<0>();
        fence_regs(kv0); fence_regs(kv1);
        bar_sync(4 + wg, 128);
        const uint32_t sa = sb + OFF_PHIK + mh * 8192 + rowl * 128 + lq * 8;
#pragma unroll
        for (int j = 0; j < 8; j++) {
          sts64(sa + 32 * (j >> 1) + 1024 * (j & 1), __float_as_uint(kv0[2 * j]), __float_as_uint(kv0[2 * j + 1]));
          sts64(sa + 16384 + 32 * (j >> 1) + 1024 * (j & 1), __float_as_uint(kv1[2 * j]), __float_as_uint(kv1[2 * j + 1]));
        }
        fence_async_smem();
        __syncwarp();
        if (lane == 0) mbar_arrive(BAR(B_SIG + 1), 1);
        if (tid == 256) PROF_MARK(28);
      }
    }
    {
      const uint64_t dK = make_desc(sb + OFF_RING, 512, 512, 2);
      const uint64_t dhi = dK & 0xffffffff00000000ull;
      const uint32_t dlo0 = (uint32_t)dK;
      uint32_t ok = 0, q[8];
      float o[16];
#pragma unroll
      for (int i = 0; i < 16; i++) o[i] = 0.f;
      {
        const int r = mh * 64 + wq * 16 + (lane & 7) + ((lane >> 3) & 1) * 8;
        ldsm4(q, sb + OFF_QP + nh * 8192 + sw64_off(r, (lane >> 4) * 8));
        ldsm4(q + 4, sb + OFF_QP + nh * 8192 + sw64_off(r, 16 + (lane >> 4) * 8));
      }
      if (tid == 0) PROF_MARK(10);
      const int qb = QB_AT;
#pragma unroll 1
      for (int it = 0; it <= 8; it++) {
        uint32_t p[16];
        if (it == qb || it == 8) {
          float t[16];
          wg_wait<0>();
          fence_regs(o);
          if (it < 8) {
            if (tid == 0) PROF_MARK(11);
            mbar_wait(BAR(B_KVR), 0);
            const uint64_t dR = make_desc(sb + OFF_KVR + nh * 4096, 512, 512, 2);
            const uint64_t dP = make_desc(sb + OFF_PHIQ + nh * 16384 + mh * 8192, 1024, 1024, 1);
            wg_fence();
            wgmma_ss_n32_ta0_tb1<0>(t, dP, dR);
#pragma unroll
            for (int ks = 1; ks < 4; ks++) wgmma_ss_n32_ta0_tb1<1>(t, dP + ks * 2, dR + ks * 64);
            wg_commit();
            wg_wait<0>();
            fence_regs(t);
            if (lane == 0) mbar_arrive(BAR(B_X1FREE), 1);
          } else {
            if (lane == 0) mbar_arrive(BAR(B_EMPTY + prev), 1);
            if (tid == 0) PROF_MARK(13);
            mbar_wait(BAR(B_SLOW), 0);
            if (__builtin_expect(__any_sync(~0u, *(volatile int*)(sgen + OFF_RED)), 0)) {
              uint32_t qz[8];
#pragma unroll
              for (int i = 0; i < 8; i++) qz[i] = (i >= 6 && lq >= 2) ? 0u : q[i];
              float m0 = -3.0e38f, m1 = -3.0e38f, o2[16];
              int sl2 = slot;
              uint32_t par2 = par;
#pragma unroll 1
              for (int j64 = 0; j64 < 32; j64++) {
                float s[32];
                mbar_wait(BAR(B_FULL + sl2), par2);
                const uint32_t lo = dlo0 + sl2 * 2048 + (j64 & 3) * 512;
                wg_fence();
                wgmma_rs_n64_tb0<0>(s, qz[0], qz[1], qz[2], qz[3], dhi | lo);
                wgmma_rs_n64_tb0<1>(s, qz[4], qz[5], qz[6], qz[7], dhi | (lo + 2));
                wg_commit();
                wg_wait<0>();
                fence_regs(s);
#pragma unroll
                for (int j = 0; j < 8; j++) {
                  const float sc = ((POLY_PAT >> j) & 1) ? 0.5f : 1.f;
                  m0 = fmaxf(m0, fmaxf(s[4 * j], s[4 * j + 1]) * sc);
                  m1 = fmaxf(m1, fmaxf(s[4 * j + 2], s[4 * j + 3]) * sc);
                }
                if ((j64 & 3) == 3) {
                  if (lane == 0) mbar_arrive(BAR(B_EMPTY + sl2), 1);
                  if (++sl2 == 3) { sl2 = 0; par2 ^= 1; }
                }
              }
              m0 = quad_max(m0); m1 = quad_max(m1);
#pragma unroll
              for (int i = 0; i < 16; i++) o2[i] = 0.f;
#pragma unroll 1
              for (int j64 = 0; j64 < 32; j64++) {
                float s[32];
                mbar_wait(BAR(B_FULL + sl2), par2);
                const uint32_t lo = dlo0 + sl2 * 2048 + (j64 & 3) * 512;
                wg_fence();
                wgmma_rs_n64_tb0<0>(s, qz[0], qz[1], qz[2], qz[3], dhi | lo);
                wgmma_rs_n64_tb0<1>(s, qz[4], qz[5], qz[6], qz[7], dhi | (lo + 2));
                wg_commit();
                wg_wait<0>();
                fence_regs(s);
                uint32_t ps[16];
#pragma unroll
                for (int j = 0; j < 8; j++) {
                  const float sc = ((POLY_PAT >> j) & 1) ? 0.5f : 1.f;
                  ps[2 * j] = pack_bf16(ex2f(fmaf(s[4 * j], sc, -m0)), ex2f(fmaf(s[4 * j + 1], sc, -m0)));
                  ps[2 * j + 1] = pack_bf16(ex2f(fmaf(s[4 * j + 2], sc, -m1)), ex2f(fmaf(s[4 * j + 3], sc, -m1)));
                }
                wg_fence();
#pragma unroll
                for (int ks = 0; ks < 4; ks++)
                  wgmma_rs_n32_tb1<1>(o2, ps[4 * ks], ps[4 * ks + 1], ps[4 * ks + 2], ps[4 * ks + 3], dhi | (lo + 256 + ks * 64));
                wg_commit();
                wg_wait<0>();
                fence_regs(o2);
                if ((j64 & 3) == 3) {
                  if (lane == 0) mbar_arrive(BAR(B_EMPTY + sl2), 1);
                  if (++sl2 == 3) { sl2 = 0; par2 ^= 1; }
                }
              }
#pragma unroll 1
              for (int j = 0; j < 2; j++) {
                mbar_wait(BAR(B_FULL + sl2), par2);
                __syncwarp();
                if (lane == 0) mbar_arrive(BAR(B_EMPTY + sl2), 1);
                if (++sl2 == 3) { sl2 = 0; par2 ^= 1; }
              }
#pragma unroll
              for (int i = 0; i < 16; i++) o[i] = o2[i];
            }
#pragma unroll
            for (int i = 0; i < 16; i++) t[i] = o[i];
          }
          const int br = it == 8;
          const float eps = br ? 0.f : 1e-6f;
          const float g0 = ((const float*)(sgen + OFF_GATE))[row0], g1 = ((const float*)(sgen + OFF_GATE))[row0 + 8];
          const float d0 = __shfl_sync(~0u, t[12], (lane & ~3) | 2), d1 = __shfl_sync(~0u, t[14], (lane & ~3) | 2);
          const float r0 = (br ? 1.f - g0 : g0) * rcpf(d0 + eps), r1 = (br ? 1.f - g1 : g1) * rcpf(d1 + eps);
          uint8_t* img = g_o_img + (size_t)((pt * 2 + br) * 14 + mh) * 8192 + rowl * 128;
          const int col0 = (2 * hp + nh) * DH + 2 * lq;
#pragma unroll
          for (int j = 0; j < 4; j++) {
            const int col = col0 + 8 * j;
            uint8_t* gp = img + (uint32_t)((col >> 6) * 16384 + ((((col >> 3) ^ rowl) & 7) << 4) + (col & 7) * 2);
            const uint32_t v0 = pack_bf16(t[4 * j] * r0, t[4 * j + 1] * r0), v1 = pack_bf16(t[4 * j + 2] * r1, t[4 * j + 3] * r1);
            if (j < 3 || lq < 2) { *(uint32_t*)gp = v0; *(uint32_t*)(gp + 1024) = v1; }
          }
          __syncwarp();
          if (lane == 0) mbar_arrive(BAR(B_SIG + 2 + br), 1);
          if (tid == 0) PROF_MARK(12 + 2 * br);
          if (br) break;
        }
        const uint32_t lo = dlo0 + slot * 2048;
        if (!ok) mbar_wait(BAR(B_FULL + slot), par);
        int nslot = slot + 1;
        uint32_t npar = par;
        if (nslot == 3) { nslot = 0; npar ^= 1; }
        {
          float s[32];
          wg_fence();
          wgmma_rs_n64_tb0<0>(s, q[0], q[1], q[2], q[3], dhi | lo);
          wgmma_rs_n64_tb0<1>(s, q[4], q[5], q[6], q[7], dhi | (lo + 2));
          wg_commit();
#pragma unroll
          for (int u = 0; u < 4; u++) {
            wg_wait<0>();
            fence_regs(s);
            if (u == 0 && lane == 0 && it > 0) mbar_arrive(BAR(B_EMPTY + prev), 1);
            if (u == 2) ok = mbar_test(BAR(B_FULL + nslot), npar);
#pragma unroll
            for (int j = 0; j < 8; j++) {
              if ((POLY_PAT >> j) & 1) {
                p[2 * j] = exp2_pair_fma(s[4 * j], s[4 * j + 1], 0x3F003F00u, 0x00030003u);
                p[2 * j + 1] = exp2_pair_fma(s[4 * j + 2], s[4 * j + 3], 0x3F003F00u, 0x00030003u);
              } else {
                p[2 * j] = pack_bf16(ex2f(s[4 * j]), ex2f(s[4 * j + 1]));
                p[2 * j + 1] = pack_bf16(ex2f(s[4 * j + 2]), ex2f(s[4 * j + 3]));
              }
            }
            wg_fence();
#pragma unroll
            for (int ks = 0; ks < 4; ks++)
              wgmma_rs_n32_tb1<1>(o, p[4 * ks], p[4 * ks + 1], p[4 * ks + 2], p[4 * ks + 3], dhi | (lo + u * 512 + 256 + ks * 64));
            if (u < 3) {
              wgmma_rs_n64_tb0<0>(s, q[0], q[1], q[2], q[3], dhi | (lo + (u + 1) * 512));
              wgmma_rs_n64_tb0<1>(s, q[4], q[5], q[6], q[7], dhi | (lo + (u + 1) * 512 + 2));
            }
            wg_commit();
          }
        }
        prev = slot; slot = nslot; par = npar;
      }
      wg_wait<0>();
    }
    if (nh == 1) return;
    {
      float acc0[28], acc1[28];
#pragma unroll
      for (int i = 0; i < 28; i++) acc0[i] = acc1[i] = 0.f;
      const uint64_t dS = make_desc(sb + OFF_WO, 1024, 1024, 1);
      const uint64_t dR = make_desc(sb + OFF_RING + mh * 8192, 1024, 1024, 1);
#pragma unroll 1
      for (int c = 0; c < 7; c++) {
        mbar_wait(BAR(B_WO + (c >= 3)), 0);
        mbar_wait(BAR(B_FULL + slot), par);
        const uint64_t dA = dR + slot * 2048, dB = dS + c * 1024;
        wg_fence();
#pragma unroll
        for (int ks = 0; ks < 4; ks++) {
          wgmma_ss_n56_ta0_tb1<1>(acc0, dA + ks * 2, dB + ks * 128);
          wgmma_ss_n56_ta0_tb1<1>(acc1, dA + 1024 + ks * 2, dB + 512 + ks * 128);
        }
        wg_commit();
        if (c < 4) {
          wg_wait<0>();
          if (lane == 0) mbar_arrive(BAR(B_EMPTY + slot), 2);
        }
        if (++slot == 3) { slot = 0; par ^= 1; }
      }
      wg_wait<0>();
      fence_regs(acc0); fence_regs(acc1);
      if (tid == 0) PROF_MARK(17);
      __nv_bfloat16* op = prm.out + (size_t)(pt * 128 + row0) * DM + hp * 56 + 2 * lq;
#pragma unroll
      for (int j = 0; j < 7; j++) {
        *(uint32_t*)(op + 8 * j) = pack_bf16(acc0[4 * j] + acc1[4 * j], acc0[4 * j + 1] + acc1[4 * j + 1]);
        *(uint32_t*)(op + 8 * DM + 8 * j) = pack_bf16(acc0[4 * j + 2] + acc1[4 * j + 2], acc0[4 * j + 3] + acc1[4 * j + 3]);
      }
      if (tid == 0) { PROF_MARK(18); PROF_CLK(31); }
    }
  }
}

typedef CUresult (*EncodeFn)(CUtensorMap*, CUtensorMapDataType, cuuint32_t, void*, const cuuint64_t*, const cuuint64_t*,
                             const cuuint32_t*, const cuuint32_t*, CUtensorMapInterleave, CUtensorMapSwizzle,
                             CUtensorMapL2promotion, CUtensorMapFloatOOBfill);

void make_map(EncodeFn enc, CUtensorMap* tm, const void* ptr, uint64_t cols, uint64_t rows, uint32_t box_cols, uint32_t box_rows) {
  cuuint64_t dims[2] = {cols, rows};
  cuuint64_t strides[1] = {cols * 2};
  cuuint32_t box[2] = {box_cols, box_rows};
  cuuint32_t es[2] = {1, 1};
  enc(tm, CU_TENSOR_MAP_DATA_TYPE_BFLOAT16, 2, const_cast<void*>(ptr), dims, strides, box, es, CU_TENSOR_MAP_INTERLEAVE_NONE,
      CU_TENSOR_MAP_SWIZZLE_128B, CU_TENSOR_MAP_L2_PROMOTION_L2_128B, CU_TENSOR_MAP_FLOAT_OOB_FILL_NONE);
}

}

extern "C" void kernel_launch(void* const* d_in, const int* in_sizes, int n_in, void* d_out, int out_size) {
  (void)in_sizes; (void)n_in; (void)out_size;
  static EncodeFn enc = nullptr;
  if (!enc) {
    void* fn = nullptr;
    cudaDriverEntryPointQueryResult qr;
    cudaGetDriverEntryPoint("cuTensorMapEncodeTiled", &fn, cudaEnableDefault, &qr);
    enc = (EncodeFn)fn;
    cudaFuncSetAttribute(fused_kernel, cudaFuncAttributeMaxDynamicSharedMemorySize, SMEM_BYTES);
  }
  CUtensorMap tm_x, tm_wqkv, tm_wq, tm_woa, tm_wob;
  make_map(enc, &tm_x, d_in[0], DM, S_LEN, 64, 128);
  make_map(enc, &tm_wqkv, d_in[1], 3 * DM, DM, 56, 64);
  make_map(enc, &tm_wq, d_in[5], DM, DM, 56, 64);
  make_map(enc, &tm_woa, d_in[3], DM, DM, 56, 64);
  make_map(enc, &tm_wob, d_in[8], DM, DM, 56, 64);
  Params prm;
  prm.w_phi = (const __nv_bfloat16*)d_in[2];
  prm.wk = (const __nv_bfloat16*)d_in[6];
  prm.wv = (const __nv_bfloat16*)d_in[7];
  prm.gate_w = (const __nv_bfloat16*)d_in[9];
  prm.out = (__nv_bfloat16*)d_out;
  fused_kernel<<<NCTA, NTHREADS, SMEM_BYTES>>>(tm_x, tm_wqkv, tm_wq, tm_woa, tm_wob, prm);
}
```

```cpp
#include <cuda_runtime.h>
#include <cuda_bf16.h>
#include <cuda.h>
#include <stdint.h>

namespace {

constexpr int S_LEN = 2048, DM = 448, DH = 28;
constexpr int NCTA = 128;
constexpr int NTHREADS = 640;
constexpr uint32_t POLY_PAT = 0x57;

#define QB_AT (4 + nh)

constexpr int OFF_X = 0;
constexpr int OFF_PHIK = 0;
constexpr int OFF_VA = 32768;
constexpr int OFF_PHIQ = 57344;
constexpr int OFF_KVR = 90112;
constexpr int OFF_QP = 98304;
constexpr int OFF_RAW = 81920;
constexpr int OFF_WO = 0;
constexpr int OFF_RING = 114688;
constexpr int OFF_WBD = 212992;
constexpr int OFF_SLC = 221184;
constexpr int OFF_QSQ = 228352;
constexpr int OFF_GATE = 229376;
constexpr int OFF_RED = 229888;
constexpr int OFF_BAR = 229952;
constexpr int SMEM_BYTES = 230400 + 1024;

constexpr int B_FULL = 0, B_EMPTY = 3, B_WO = 6  , B_KVR = 8, B_RAW = 9, B_X1FREE = 10, B_QSQ = 11, B_SLOW = 12,
              B_BUILD = 13, B_SIG = 14  , B_XL = 18  , B_N = 20;

constexpr int C_KV = 0, C_PART = 1, C_DONE = 3, C_OA = 4, C_OB = 20, C_N = 36;

__device__ __align__(1024) uint8_t g_kv_img[32 * 8192];
__device__ __align__(16) float g_ksq[512];
__device__ __align__(16) float g_vsq[512];
__device__ __align__(16) float g_gate[S_LEN];
__device__ __align__(1024) float g_kvacc[2][16 * 64 * 32];
__device__ unsigned g_epoch;
__device__ __align__(1024) uint8_t g_o_img[2 * 16 * 14 * 8192];
__device__ unsigned g_cnt[C_N * 32];

#define PROF4(i) do { } while (0)
#define PROF3(i) do { } while (0)
#define PROF2(i) do { } while (0)
#define PROF_CLK(i) do { } while (0)
#define PROF_MARK(i) do { } while (0)
__device__ __forceinline__ uint32_t smem_u32(const void* p) { return (uint32_t)__cvta_generic_to_shared(p); }
__device__ __forceinline__ void mbar_init(uint32_t a, int cnt) {
  asm volatile("mbarrier.init.shared::cta.b64 [%0], %1;" ::"r"(a), "r"(cnt) : "memory");
}
__device__ __forceinline__ void mbar_expect_tx(uint32_t a, uint32_t bytes) {
  asm volatile("mbarrier.arrive.expect_tx.shared::cta.b64 _, [%0], %1;" ::"r"(a), "r"(bytes) : "memory");
}
__device__ __forceinline__ void mbar_arrive(uint32_t a, uint32_t cnt) {
  asm volatile("mbarrier.arrive.shared::cta.b64 _, [%0], %1;" ::"r"(a), "r"(cnt) : "memory");
}
__device__ __forceinline__ void mbar_wait(uint32_t a, uint32_t parity) {
  asm volatile(
      "{\n.reg .pred p;\n.reg .u32 c;\nmov.u32 c, 0;\n"
      "W_%=:\nmbarrier.try_wait.parity.shared::cta.b64 p, [%0], %1;\n"
      "add.u32 c, c, 1;\nsetp.lt.and.u32 p, c, 0x40000, !p;\n@p bra W_%=;\n}"
      ::"r"(a), "r"(parity) : "memory");
}
__device__ __forceinline__ uint32_t mbar_test(uint32_t a, uint32_t parity) {
  uint32_t ok;
  asm volatile("{\n.reg .pred p;\nmbarrier.test_wait.parity.shared::cta.b64 p, [%1], %2;\nselp.u32 %0, 1, 0, p;\n}"
               : "=r"(ok) : "r"(a), "r"(parity) : "memory");
  return ok;
}
__device__ __forceinline__ bool elect_one() {
  uint32_t r;
  asm volatile("{\n.reg .pred p;\nelect.sync _|p, 0xffffffff;\nselp.u32 %0, 1, 0, p;\n}" : "=r"(r));
  return r != 0;
}
__device__ __forceinline__ void tma_2d(uint32_t dst, const CUtensorMap* tm, int c0, int c1, uint32_t bar) {
  asm volatile("cp.async.bulk.tensor.2d.shared::cluster.global.mbarrier::complete_tx::bytes [%0], [%1, {%3, %4}], [%2];"
               ::"r"(dst), "l"(tm), "r"(bar), "r"(c0), "r"(c1) : "memory");
}
__device__ __forceinline__ void bulk_g2s(uint32_t dst, const void* src, uint32_t bytes, uint32_t bar) {
  asm volatile("cp.async.bulk.shared::cluster.global.mbarrier::complete_tx::bytes [%0], [%1], %2, [%3];"
               ::"r"(dst), "l"(src), "r"(bytes), "r"(bar) : "memory");
}
__device__ __forceinline__ void fence_async_smem() { asm volatile("fence.proxy.async.shared::cta;" ::: "memory"); }
__device__ __forceinline__ void fence_async_all() { asm volatile("fence.proxy.async.global;" ::: "memory"); }

__device__ __forceinline__ void bar_sync(int id, int n) { asm volatile("bar.sync %0, %1;" ::"r"(id), "r"(n) : "memory"); }
__device__ __forceinline__ void cnt_arrive(int idx) {
  asm volatile("red.release.gpu.global.add.u32 [%0], 1;" ::"l"(&g_cnt[idx * 32]) : "memory");
}
__device__ __forceinline__ void cnt_wait(int idx, unsigned target) {
  unsigned v, n = 0;
#pragma unroll 1
  while (true) {
    asm volatile("ld.acquire.gpu.global.u32 %0, [%1];" : "=r"(v) : "l"(&g_cnt[idx * 32]) : "memory");
    if (v >= target || ++n >= (1u << 18)) break;
    __nanosleep(32);
  }
}
__device__ __forceinline__ void wg_fence() { asm volatile("wgmma.fence.sync.aligned;" ::: "memory"); }
__device__ __forceinline__ void wg_commit() { asm volatile("wgmma.commit_group.sync.aligned;" ::: "memory"); }
template <int N> __device__ __forceinline__ void wg_wait() { asm volatile("wgmma.wait_group.sync.aligned %0;" ::"n"(N) : "memory"); }
template <int N> __device__ __forceinline__ void fence_regs(float (&d)[N]) {
#pragma unroll
  for (int i = 0; i < N; i++) asm volatile("" : "+f"(d[i])::"memory");
}
__device__ __forceinline__ uint64_t make_desc(uint32_t saddr, uint32_t lbo, uint32_t sbo, uint32_t swz) {
  return (uint64_t)((saddr & 0x3FFFF) >> 4) | ((uint64_t)(lbo >> 4) << 16) | ((uint64_t)(sbo >> 4) << 32) | ((uint64_t)swz << 62);
}
__device__ __forceinline__ float ex2f(float x) { float y; asm("ex2.approx.ftz.f32 %0, %1;" : "=f"(y) : "f"(x)); return y; }
__device__ __forceinline__ float rcpf(float x) { float y; asm("rcp.approx.ftz.f32 %0, %1;" : "=f"(y) : "f"(x)); return y; }
__device__ __forceinline__ uint32_t pack_bf16(float lo, float hi) {
  uint32_t r; asm("cvt.rn.bf16x2.f32 %0, %1, %2;" : "=r"(r) : "f"(hi), "f"(lo)); return r;
}
__device__ __forceinline__ uint32_t lop_and_or(uint32_t a, uint32_t m, uint32_t c) {
  uint32_t r; asm("lop3.b32 %0, %1, %2, %3, 0xEA;" : "=r"(r) : "r"(a), "r"(m), "r"(c)); return r;
}
__device__ __forceinline__ void sts32(uint32_t a, uint32_t v) { asm volatile("st.shared.b32 [%0], %1;" ::"r"(a), "r"(v) : "memory"); }
__device__ __forceinline__ void sts64(uint32_t a, uint32_t v0, uint32_t v1) { asm volatile("st.shared.v2.b32 [%0], {%1, %2};" ::"r"(a), "r"(v0), "r"(v1) : "memory"); }
__device__ __forceinline__ void sts128(uint32_t a, uint4 v) {
  asm volatile("st.shared.v4.b32 [%0], {%1, %2, %3, %4};" ::"r"(a), "r"(v.x), "r"(v.y), "r"(v.z), "r"(v.w) : "memory");
}
__device__ __forceinline__ float4 ldcg_f4(const float* p) {
  float4 v; asm volatile("ld.global.cg.v4.f32 {%0, %1, %2, %3}, [%4];" : "=f"(v.x), "=f"(v.y), "=f"(v.z), "=f"(v.w) : "l"(p) : "memory"); return v;
}
__device__ __forceinline__ void ldsm4(uint32_t* r, uint32_t a) {
  asm volatile("ldmatrix.sync.aligned.m8n8.x4.shared.b16 {%0, %1, %2, %3}, [%4];"
               : "=r"(r[0]), "=r"(r[1]), "=r"(r[2]), "=r"(r[3]) : "r"(a) : "memory");
}
__device__ __forceinline__ float quad_sum(float v) { v += __shfl_xor_sync(~0u, v, 1); v += __shfl_xor_sync(~0u, v, 2); return v; }
__device__ __forceinline__ float quad_max(float v) { v = fmaxf(v, __shfl_xor_sync(~0u, v, 1)); v = fmaxf(v, __shfl_xor_sync(~0u, v, 2)); return v; }

template <int SD> __device__ __forceinline__ void wgmma_ss_n56_ta0_tb1(float (&d)[28], uint64_t da, uint64_t db) {
  if (SD) asm volatile("wgmma.mma_async.sync.aligned.m64n56k16.f32.bf16.bf16 {%0, %1, %2, %3, %4, %5, %6, %7, %8, %9, %10, %11, %12, %13, %14, %15, %16, %17, %18, %19, %20, %21, %22, %23, %24, %25, %26, %27}, %28, %29, 1, 1, 1, 0, 1;\n"
    : "+f"(d[0]), "+f"(d[1]), "+f"(d[2]), "+f"(d[3]), "+f"(d[4]), "+f"(d[5]), "+f"(d[6]), "+f"(d[7]), "+f"(d[8]), "+f"(d[9]), "+f"(d[10]), "+f"(d[11]), "+f"(d[12]), "+f"(d[13]), "+f"(d[14]), "+f"(d[15]), "+f"(d[16]), "+f"(d[17]), "+f"(d[18]), "+f"(d[19]), "+f"(d[20]), "+f"(d[21]), "+f"(d[22]), "+f"(d[23]), "+f"(d[24]), "+f"(d[25]), "+f"(d[26]), "+f"(d[27])
    : "l"(da), "l"(db));
  else asm volatile("wgmma.mma_async.sync.aligned.m64n56k16.f32.bf16.bf16 {%0, %1, %2, %3, %4, %5, %6, %7, %8, %9, %10, %11, %12, %13, %14, %15, %16, %17, %18, %19, %20, %21, %22, %23, %24, %25, %26, %27}, %28, %29, 0, 1, 1, 0, 1;\n"
    : "=f"(d[0]), "=f"(d[1]), "=f"(d[2]), "=f"(d[3]), "=f"(d[4]), "=f"(d[5]), "=f"(d[6]), "=f"(d[7]), "=f"(d[8]), "=f"(d[9]), "=f"(d[10]), "=f"(d[11]), "=f"(d[12]), "=f"(d[13]), "=f"(d[14]), "=f"(d[15]), "=f"(d[16]), "=f"(d[17]), "=f"(d[18]), "=f"(d[19]), "=f"(d[20]), "=f"(d[21]), "=f"(d[22]), "=f"(d[23]), "=f"(d[24]), "=f"(d[25]), "=f"(d[26]), "=f"(d[27])
    : "l"(da), "l"(db));
}
template <int SD> __device__ __forceinline__ void wgmma_ss_n8_ta0_tb1(float (&d)[4], uint64_t da, uint64_t db) {
  if (SD) asm volatile("wgmma.mma_async.sync.aligned.m64n8k16.f32.bf16.bf16 {%0, %1, %2, %3}, %4, %5, 1, 1, 1, 0, 1;\n"
    : "+f"(d[0]), "+f"(d[1]), "+f"(d[2]), "+f"(d[3])
    : "l"(da), "l"(db));
  else asm volatile("wgmma.mma_async.sync.aligned.m64n8k16.f32.bf16.bf16 {%0, %1, %2, %3}, %4, %5, 0, 1, 1, 0, 1;\n"
    : "=f"(d[0]), "=f"(d[1]), "=f"(d[2]), "=f"(d[3])
    : "l"(da), "l"(db));
}
template <int SD> __device__ __forceinline__ void wgmma_rs_n64_tb1(float (&d)[32], uint32_t a0, uint32_t a1, uint32_t a2, uint32_t a3, uint64_t db) {
  if (SD) asm volatile("wgmma.mma_async.sync.aligned.m64n64k16.f32.bf16.bf16 {%0, %1, %2, %3, %4, %5, %6, %7, %8, %9, %10, %11, %12, %13, %14, %15, %16, %17, %18, %19, %20, %21, %22, %23, %24, %25, %26, %27, %28, %29, %30, %31}, {%32, %33, %34, %35}, %36, 1, 1, 1, 1;\n"
    : "+f"(d[0]), "+f"(d[1]), "+f"(d[2]), "+f"(d[3]), "+f"(d[4]), "+f"(d[5]), "+f"(d[6]), "+f"(d[7]), "+f"(d[8]), "+f"(d[9]), "+f"(d[10]), "+f"(d[11]), "+f"(d[12]), "+f"(d[13]), "+f"(d[14]), "+f"(d[15]), "+f"(d[16]), "+f"(d[17]), "+f"(d[18]), "+f"(d[19]), "+f"(d[20]), "+f"(d[21]), "+f"(d[22]), "+f"(d[23]), "+f"(d[24]), "+f"(d[25]), "+f"(d[26]), "+f"(d[27]), "+f"(d[28]), "+f"(d[29]), "+f"(d[30]), "+f"(d[31])
    : "r"(a0), "r"(a1), "r"(a2), "r"(a3), "l"(db));
  else asm volatile("wgmma.mma_async.sync.aligned.m64n64k16.f32.bf16.bf16 {%0, %1, %2, %3, %4, %5, %6, %7, %8, %9, %10, %11, %12, %13, %14, %15, %16, %17, %18, %19, %20, %21, %22, %23, %24, %25, %26, %27, %28, %29, %30, %31}, {%32, %33, %34, %35}, %36, 0, 1, 1, 1;\n"
    : "=f"(d[0]), "=f"(d[1]), "=f"(d[2]), "=f"(d[3]), "=f"(d[4]), "=f"(d[5]), "=f"(d[6]), "=f"(d[7]), "=f"(d[8]), "=f"(d[9]), "=f"(d[10]), "=f"(d[11]), "=f"(d[12]), "=f"(d[13]), "=f"(d[14]), "=f"(d[15]), "=f"(d[16]), "=f"(d[17]), "=f"(d[18]), "=f"(d[19]), "=f"(d[20]), "=f"(d[21]), "=f"(d[22]), "=f"(d[23]), "=f"(d[24]), "=f"(d[25]), "=f"(d[26]), "=f"(d[27]), "=f"(d[28]), "=f"(d[29]), "=f"(d[30]), "=f"(d[31])
    : "r"(a0), "r"(a1), "r"(a2), "r"(a3), "l"(db));
}
template <int SD> __device__ __forceinline__ void wgmma_ss_n32_ta1_tb1(float (&d)[16], uint64_t da, uint64_t db) {
  if (SD) asm volatile("wgmma.mma_async.sync.aligned.m64n32k16.f32.bf16.bf16 {%0, %1, %2, %3, %4, %5, %6, %7, %8, %9, %10, %11, %12, %13, %14, %15}, %16, %17, 1, 1, 1, 1, 1;\n"
    : "+f"(d[0]), "+f"(d[1]), "+f"(d[2]), "+f"(d[3]), "+f"(d[4]), "+f"(d[5]), "+f"(d[6]), "+f"(d[7]), "+f"(d[8]), "+f"(d[9]), "+f"(d[10]), "+f"(d[11]), "+f"(d[12]), "+f"(d[13]), "+f"(d[14]), "+f"(d[15])
    : "l"(da), "l"(db));
  else asm volatile("wgmma.mma_async.sync.aligned.m64n32k16.f32.bf16.bf16 {%0, %1, %2, %3, %4, %5, %6, %7, %8, %9, %10, %11, %12, %13, %14, %15}, %16, %17, 0, 1, 1, 1, 1;\n"
    : "=f"(d[0]), "=f"(d[1]), "=f"(d[2]), "=f"(d[3]), "=f"(d[4]), "=f"(d[5]), "=f"(d[6]), "=f"(d[7]), "=f"(d[8]), "=f"(d[9]), "=f"(d[10]), "=f"(d[11]), "=f"(d[12]), "=f"(d[13]), "=f"(d[14]), "=f"(d[15])
    : "l"(da), "l"(db));
}
template <int SD> __device__ __forceinline__ void wgmma_ss_n32_ta0_tb1(float (&d)[16], uint64_t da, uint64_t db) {
  if (SD) asm volatile("wgmma.mma_async.sync.aligned.m64n32k16.f32.bf16.bf16 {%0, %1, %2, %3, %4, %5, %6, %7, %8, %9, %10, %11, %12, %13, %14, %15}, %16, %17, 1, 1, 1, 0, 1;\n"
    : "+f"(d[0]), "+f"(d[1]), "+f"(d[2]), "+f"(d[3]), "+f"(d[4]), "+f"(d[5]), "+f"(d[6]), "+f"(d[7]), "+f"(d[8]), "+f"(d[9]), "+f"(d[10]), "+f"(d[11]), "+f"(d[12]), "+f"(d[13]), "+f"(d[14]), "+f"(d[15])
    : "l"(da), "l"(db));
  else asm volatile("wgmma.mma_async.sync.aligned.m64n32k16.f32.bf16.bf16 {%0, %1, %2, %3, %4, %5, %6, %7, %8, %9, %10, %11, %12, %13, %14, %15}, %16, %17, 0, 1, 1, 0, 1;\n"
    : "=f"(d[0]), "=f"(d[1]), "=f"(d[2]), "=f"(d[3]), "=f"(d[4]), "=f"(d[5]), "=f"(d[6]), "=f"(d[7]), "=f"(d[8]), "=f"(d[9]), "=f"(d[10]), "=f"(d[11]), "=f"(d[12]), "=f"(d[13]), "=f"(d[14]), "=f"(d[15])
    : "l"(da), "l"(db));
}
template <int SD> __device__ __forceinline__ void wgmma_rs_n64_tb0(float (&d)[32], uint32_t a0, uint32_t a1, uint32_t a2, uint32_t a3, uint64_t db) {
  if (SD) asm volatile("wgmma.mma_async.sync.aligned.m64n64k16.f32.bf16.bf16 {%0, %1, %2, %3, %4, %5, %6, %7, %8, %9, %10, %11, %12, %13, %14, %15, %16, %17, %18, %19, %20, %21, %22, %23, %24, %25, %26, %27, %28, %29, %30, %31}, {%32, %33, %34, %35}, %36, 1, 1, 1, 0;\n"
    : "+f"(d[0]), "+f"(d[1]), "+f"(d[2]), "+f"(d[3]), "+f"(d[4]), "+f"(d[5]), "+f"(d[6]), "+f"(d[7]), "+f"(d[8]), "+f"(d[9]), "+f"(d[10]), "+f"(d[11]), "+f"(d[12]), "+f"(d[13]), "+f"(d[14]), "+f"(d[15]), "+f"(d[16]), "+f"(d[17]), "+f"(d[18]), "+f"(d[19]), "+f"(d[20]), "+f"(d[21]), "+f"(d[22]), "+f"(d[23]), "+f"(d[24]), "+f"(d[25]), "+f"(d[26]), "+f"(d[27]), "+f"(d[28]), "+f"(d[29]), "+f"(d[30]), "+f"(d[31])
    : "r"(a0), "r"(a1), "r"(a2), "r"(a3), "l"(db));
  else asm volatile("wgmma.mma_async.sync.aligned.m64n64k16.f32.bf16.bf16 {%0, %1, %2, %3, %4, %5, %6, %7, %8, %9, %10, %11, %12, %13, %14, %15, %16, %17, %18, %19, %20, %21, %22, %23, %24, %25, %26, %27, %28, %29, %30, %31}, {%32, %33, %34, %35}, %36, 0, 1, 1, 0;\n"
    : "=f"(d[0]), "=f"(d[1]), "=f"(d[2]), "=f"(d[3]), "=f"(d[4]), "=f"(d[5]), "=f"(d[6]), "=f"(d[7]), "=f"(d[8]), "=f"(d[9]), "=f"(d[10]), "=f"(d[11]), "=f"(d[12]), "=f"(d[13]), "=f"(d[14]), "=f"(d[15]), "=f"(d[16]), "=f"(d[17]), "=f"(d[18]), "=f"(d[19]), "=f"(d[20]), "=f"(d[21]), "=f"(d[22]), "=f"(d[23]), "=f"(d[24]), "=f"(d[25]), "=f"(d[26]), "=f"(d[27]), "=f"(d[28]), "=f"(d[29]), "=f"(d[30]), "=f"(d[31])
    : "r"(a0), "r"(a1), "r"(a2), "r"(a3), "l"(db));
}
template <int SD> __device__ __forceinline__ void wgmma_rs_n32_tb1(float (&d)[16], uint32_t a0, uint32_t a1, uint32_t a2, uint32_t a3, uint64_t db) {
  if (SD) asm volatile("wgmma.mma_async.sync.aligned.m64n32k16.f32.bf16.bf16 {%0, %1, %2, %3, %4, %5, %6, %7, %8, %9, %10, %11, %12, %13, %14, %15}, {%16, %17, %18, %19}, %20, 1, 1, 1, 1;\n"
    : "+f"(d[0]), "+f"(d[1]), "+f"(d[2]), "+f"(d[3]), "+f"(d[4]), "+f"(d[5]), "+f"(d[6]), "+f"(d[7]), "+f"(d[8]), "+f"(d[9]), "+f"(d[10]), "+f"(d[11]), "+f"(d[12]), "+f"(d[13]), "+f"(d[14]), "+f"(d[15])
    : "r"(a0), "r"(a1), "r"(a2), "r"(a3), "l"(db));
  else asm volatile("wgmma.mma_async.sync.aligned.m64n32k16.f32.bf16.bf16 {%0, %1, %2, %3, %4, %5, %6, %7, %8, %9, %10, %11, %12, %13, %14, %15}, {%16, %17, %18, %19}, %20, 0, 1, 1, 1;\n"
    : "=f"(d[0]), "=f"(d[1]), "=f"(d[2]), "=f"(d[3]), "=f"(d[4]), "=f"(d[5]), "=f"(d[6]), "=f"(d[7]), "=f"(d[8]), "=f"(d[9]), "=f"(d[10]), "=f"(d[11]), "=f"(d[12]), "=f"(d[13]), "=f"(d[14]), "=f"(d[15])
    : "r"(a0), "r"(a1), "r"(a2), "r"(a3), "l"(db));
}

__device__ __forceinline__ uint32_t sw64_off(int row, int d) { return row * 64 + ((((d >> 3) ^ (row >> 1)) & 3) << 4) + (d & 7) * 2; }

__device__ __forceinline__ uint32_t exp2_pair_fma(float t0, float t1, uint32_t c_half, uint32_t c_3) {
  uint32_t y0, y;
  asm("prmt.b32 %0, %1, %2, 0x6521;" : "=r"(y0) : "r"(__float_as_uint(t0)), "r"(__float_as_uint(t1)));
  uint32_t h = lop_and_or(y0, 0x007F007Fu, c_half);
  uint32_t e = lop_and_or(y0, 0xFF80FF80u, c_3);
  asm("fma.rn.bf16x2 %0, %1, %2, %3;" : "=r"(y) : "r"(y0), "r"(h), "r"(e));
  return y;
}

__device__ __forceinline__ void feature_map(float (&v)[16], uint32_t (&ph)[16], int lq) {
  const float L2E = 1.4426950408889634f;
  const bool tail_ok = lq < 2;
  float mx[2], mn[2], b[16], sa[2], sn[2];
#pragma unroll
  for (int r = 0; r < 2; r++) {
    const int o = 2 * r;
    if (!tail_ok) { v[o + 12] = v[o]; v[o + 13] = v[o]; }
    mx[r] = fmaxf(fmaxf(fmaxf(v[o], v[o + 1]), fmaxf(v[o + 4], v[o + 5])), fmaxf(fmaxf(v[o + 8], v[o + 9]), fmaxf(v[o + 12], v[o + 13])));
    mn[r] = fminf(fminf(fminf(v[o], v[o + 1]), fminf(v[o + 4], v[o + 5])), fminf(fminf(v[o + 8], v[o + 9]), fminf(v[o + 12], v[o + 13])));
  }
#pragma unroll
  for (int o = 1; o <= 2; o <<= 1)
#pragma unroll
    for (int r = 0; r < 2; r++) { mx[r] = fmaxf(mx[r], __shfl_xor_sync(~0u, mx[r], o)); mn[r] = fminf(mn[r], __shfl_xor_sync(~0u, mn[r], o)); }
#pragma unroll
  for (int r = 0; r < 2; r++) {
    const int o = 2 * r;
    const float cx = -mx[r] * L2E, cn = mn[r] * L2E;
#pragma unroll
    for (int i = 0; i < 8; i++) {
      const int k = o + 4 * (i >> 1) + (i & 1);
      b[k] = ex2f(fmaf(v[k], -L2E, cn));
      v[k] = ex2f(fmaf(v[k], L2E, cx));
    }
    if (!tail_ok) { v[o + 12] = v[o + 13] = b[o + 12] = b[o + 13] = 0.f; }
    sa[r] = ((v[o] + v[o + 1]) + (v[o + 4] + v[o + 5])) + ((v[o + 8] + v[o + 9]) + (v[o + 12] + v[o + 13]));
    sn[r] = ((b[o] + b[o + 1]) + (b[o + 4] + b[o + 5])) + ((b[o + 8] + b[o + 9]) + (b[o + 12] + b[o + 13]));
  }
#pragma unroll
  for (int o = 1; o <= 2; o <<= 1)
#pragma unroll
    for (int r = 0; r < 2; r++) { sa[r] += __shfl_xor_sync(~0u, sa[r], o); sn[r] += __shfl_xor_sync(~0u, sn[r], o); }
#pragma unroll
  for (int r = 0; r < 2; r++) {
    const float ra = rcpf(sa[r]), rb = rcpf(sn[r]);
#pragma unroll
    for (int jj = 0; jj < 4; jj++) {
      ph[jj * 2 + r] = pack_bf16(v[2 * r + 4 * jj] * ra, v[2 * r + 4 * jj + 1] * ra);
      ph[(4 + jj) * 2 + r] = pack_bf16(b[2 * r + 4 * jj] * rb, b[2 * r + 4 * jj + 1] * rb);
    }
  }
}

__device__ __forceinline__ void store_heads(uint32_t base, const uint32_t (&a)[14], uint32_t pad0, uint32_t pad1, int row0, int lq) {
  const uint32_t rb = base + row0 * 64 + (((row0 >> 1) & 3) << 4);
  const uint32_t b0 = rb + lq * 4;
  const uint32_t b1 = (rb + 8192 + ((lq * 4 + 8) & 15)) ^ ((lq >> 1) << 4);
#pragma unroll
  for (int j = 0; j < 7; j++) {
    uint32_t ad;
    if (j < 3) ad = b0 ^ (j << 4);
    else if (j == 3) ad = (lq < 2) ? (b0 ^ 48u) : (b1 ^ 16u);
    else ad = (lq < 2) ? (b1 ^ ((j - 4) << 4)) : ((b1 ^ 16u) ^ ((j - 3) << 4));
    sts32(ad, a[2 * j]);
    sts32(ad + 512, a[2 * j + 1]);
  }
  sts64((rb ^ 48u) + 8 + (lq & 1) * 8192 + (lq >> 1) * 512, pad0, pad1);
}

struct Params {
  const __nv_bfloat16* w_phi;
  const __nv_bfloat16* wk;
  const __nv_bfloat16* wv;
  const __nv_bfloat16* gate_w;
  __nv_bfloat16* out;
};

__global__ void __launch_bounds__(NTHREADS, 1)
fused_kernel(const __grid_constant__ CUtensorMap tm_x, const __grid_constant__ CUtensorMap tm_wqkv,
             const __grid_constant__ CUtensorMap tm_wq, const __grid_constant__ CUtensorMap tm_woa,
             const __grid_constant__ CUtensorMap tm_wob, const Params prm) {
  extern __shared__ uint8_t smem_raw[];
  uint32_t sb = (smem_u32(smem_raw) + 1023u) & ~1023u;
  uint8_t* sgen = smem_raw + (sb - smem_u32(smem_raw));
  asm volatile("mov.u32 %0, %0;" : "+r"(sb));
  const int tid = threadIdx.x, lane = tid & 31;
  const int warp = __shfl_sync(~0u, tid >> 5, 0), wg = warp >> 2;
  const int pt = blockIdx.x >> 3, hp = blockIdx.x & 7;
  const uint32_t bars = sb + OFF_BAR;
  auto BAR = [&](int i) { return bars + 8u * i; };
  const unsigned epoch = g_epoch & 1;

  if (tid == 0) { PROF_MARK(0); PROF_CLK(30); PROF2(15); }
  auto load_proj = [&](int c, int g) {
    mbar_expect_tx(BAR(B_FULL + g), (c < 3 ? 16384 : 0) + 4 * 7168);
    if (c < 3) tma_2d(sb + OFF_X + c * 16384, &tm_x, c * 64, pt * 128, BAR(B_FULL + g));
    tma_2d(sb + OFF_RING + g * 32768, &tm_wq, hp * 56, c * 64, BAR(B_FULL + g));
#pragma unroll 1
    for (int j = 0; j < 3; j++) tma_2d(sb + OFF_RING + g * 32768 + 8192 + j * 8192, &tm_wqkv, j * DM + hp * 56, c * 64, BAR(B_FULL + g));
  };
  if (warp == 16) {
    if (elect_one()) {
      mbar_init(BAR(B_FULL), 1);
      fence_async_smem();
      load_proj(0, 0);
      mbar_init(BAR(B_RAW), 1); mbar_init(BAR(B_FULL + 1), 1); mbar_init(BAR(B_FULL + 2), 1);
      fence_async_smem();
    }
    __syncwarp();
    asm volatile("bar.arrive 0, %0;" ::"n"(NTHREADS) : "memory");
  } else {
    if (elect_one()) {
      const int i = warp + 3 - (warp > 16);
      if (i < B_N && i != B_RAW) {
        int cnt = i < B_WO || (i > B_SIG && i < B_XL) || i == B_X1FREE ? 16 : 1;
        if (i == B_BUILD) cnt = 16;
        if (i == B_SIG || i == B_SIG + 1 || i == B_QSQ) cnt = 8;
        if (i == B_KVR) cnt = 2;
        mbar_init(BAR(i), cnt);
        fence_async_smem();
      }
    }
    bar_sync(0, NTHREADS);
  }
  if (tid == 0) PROF2(14);

  if (wg == 4) {
    asm volatile("setmaxnreg.dec.sync.aligned.u32 32;");
    if (warp == 16) {
      if (elect_one()) {
        mbar_expect_tx(BAR(B_RAW), 25088 + 3136 + 896);
        bulk_g2s(sb + OFF_RAW, hp < 4 ? prm.wk : prm.wv, 25088, BAR(B_RAW));
        bulk_g2s(sb + OFF_RAW + 25088, prm.w_phi + 2 * hp * DH * DH, 3136, BAR(B_RAW));
        bulk_g2s(sb + OFF_RAW + 28224, prm.gate_w, 896, BAR(B_RAW));
        load_proj(1, 1);
        load_proj(2, 2);
      }
      __syncwarp();
      bar_sync(3, 64);
      if (elect_one()) {
        int g = 0, nkv = 8;
        uint32_t par = 0;
#pragma unroll 1
        for (int c = 3; c < 7; c++) {
          if (c == 5) mbar_wait(BAR(B_BUILD), 0);
          if (c & 1) mbar_expect_tx(BAR(B_XL + (c > 4)), 32768);
          tma_2d(sb + OFF_X + c * 16384, &tm_x, c * 64, pt * 128, BAR(B_XL + (c > 4)));
        }
#pragma unroll 1
        for (int n = 3; n < 14 + nkv; n++) {
          if (n == 7) { PROF_MARK(20); cnt_wait(C_KV, NCTA); PROF_MARK(21); fence_async_all(); }
          if (n == 15) {
            mbar_wait(BAR(B_SLOW), 0);
            if (*(volatile int*)(sgen + OFF_RED)) nkv = 26;
          }
          const int j = n - 7 - nkv;
          if (j == 0 || j == 3) {
            PROF3(j ? 11 : 8);
            cnt_wait((j ? C_OB : C_OA) + pt, 8);
            PROF3(j ? 12 : 9);
            PROF_MARK(26);
            fence_async_all();
          }
          mbar_wait(BAR(B_EMPTY + g), par);
          if (n < 7) { PROF2(20 + n); load_proj(n, g); }
          else {
            mbar_expect_tx(BAR(B_FULL + g), 32768);
            bulk_g2s(sb + OFF_RING + g * 32768, j < 0 ? g_kv_img + ((n - 7) & 7) * 32768 : g_o_img + (size_t)(pt * 7 + j) * 32768, 32768,
                     BAR(B_FULL + g));
          }
          if (++g == 3) { g = 0; par ^= 1; }
        }
        if (atomicAdd(&g_cnt[C_DONE * 32], 1u) == NCTA - 1) {
#pragma unroll 1
          for (int i = 0; i < C_N; i++) g_cnt[i * 32] = 0;
          g_epoch = epoch ^ 1;
        }
      }
    } else {
      if (warp == 18) {
        if (elect_one()) {
#pragma unroll 1
          for (int i = 0; i < 4; i++) {
            mbar_wait(BAR(B_SIG + i), 0);
            PROF3(2 * i);
            if (i == 1) {
#pragma unroll 1
              for (int j = 0; j < 4; j++)
                asm volatile("cp.reduce.async.bulk.global.shared::cta.bulk_group.add.f32 [%0], [%1], 8192;"
                             ::"l"(g_kvacc[epoch] + hp * 4096 + (j >> 1) * 2048), "r"(sb + OFF_PHIK + j * 8192) : "memory");
              asm volatile("cp.async.bulk.commit_group;\ncp.async.bulk.wait_group 0;" ::: "memory");
            }
            cnt_arrive(i == 0 ? C_KV : i == 1 ? C_PART : (i == 2 ? C_OA : C_OB) + pt);
            PROF3(2 * i + 1);
            if (i == 1 || i == 2) {
              if (i == 2) mbar_wait(BAR(B_X1FREE), 0);
              mbar_expect_tx(BAR(B_WO + i - 1), 7 * 7168);
#pragma unroll 1
              for (int c = 0; c < 7; c++)
                tma_2d(sb + OFF_WO + (i - 1) * 57344 + c * 8192, i == 1 ? &tm_woa : &tm_wob, hp * 56, c * 64, BAR(B_WO + i - 1));
            }
          }
        }
      } else if (warp == 19) {
        if (lane == 0) {
          mbar_wait(BAR(B_SIG + 0), 0);
          cnt_wait(C_KV, NCTA);
        }
        __syncwarp();
        float ksq = 0.f, vsq = 0.f;
#pragma unroll
        for (int sl = 0; sl < 4; sl++) {
          float4 a = ldcg_f4(g_ksq + sl * 128 + lane * 4), b = ldcg_f4(g_vsq + sl * 128 + lane * 4);
          float m = fmaxf(fmaxf(a.x, a.y), fmaxf(a.z, a.w));
          m = __uint_as_float(__reduce_max_sync(~0u, __float_as_uint(m)));
          ksq += m;
          vsq = fmaxf(vsq, fmaxf(fmaxf(b.x, b.y), fmaxf(b.z, b.w)));
        }
        mbar_wait(BAR(B_QSQ), 0);
        const float4 qa4 = ((const float4*)(sgen + OFF_QSQ))[lane], qb4 = ((const float4*)(sgen + OFF_QSQ))[32 + lane];
        const float qmax = fmaxf(fmaxf(fmaxf(qa4.x, qa4.y), fmaxf(qa4.z, qa4.w)), fmaxf(fmaxf(qb4.x, qb4.y), fmaxf(qb4.z, qb4.w)));
        const bool slow = __any_sync(~0u, !(qmax * ksq <= 98.f * 98.f) || !(vsq <= 2.0e8f));
        if (lane == 0) {
          *(volatile int*)(sgen + OFF_RED) = slow;
          mbar_arrive(BAR(B_SLOW), 1);
        }
      } else {
        float4* z = (float4*)(g_kvacc[epoch ^ 1] + blockIdx.x * 256) + lane;
        z[0] = make_float4(0.f, 0.f, 0.f, 0.f);
        z[32] = make_float4(0.f, 0.f, 0.f, 0.f);
        bar_sync(3, 64);
        if (lane == 0) {
          mbar_wait(BAR(B_SIG + 0), 0);
          cnt_wait(C_KV, NCTA);
        }
        __syncwarp();
        ((float4*)(sgen + OFF_GATE))[lane] = ldcg_f4(g_gate + pt * 128 + lane * 4);
      }
      if (warp != 18) {
        if (lane == 0) {
          mbar_wait(BAR(B_SIG + 1), 0);
          cnt_wait(C_PART, NCTA);
          PROF_MARK(23);
        }
        __syncwarp();
        const int e = warp == 19;
        const float* src = g_kvacc[epoch] + hp * 4096 + e * 2048 + lane * 8;
#pragma unroll 1
        for (int i = 0; i < 8; i += 2) {
          const float4 a = ldcg_f4(src + i * 256), b = ldcg_f4(src + i * 256 + 4), c = ldcg_f4(src + i * 256 + 256), d = ldcg_f4(src + i * 256 + 260);
          const uint32_t ad = sb + OFF_KVR + e * 4096 + sw64_off(i * 8 + (lane >> 2), (lane & 3) * 8);
          sts128(ad, make_uint4(pack_bf16(a.x, a.y), pack_bf16(a.z, a.w), pack_bf16(b.x, b.y), pack_bf16(b.z, b.w)));
          sts128(ad + 512, make_uint4(pack_bf16(c.x, c.y), pack_bf16(c.z, c.w), pack_bf16(d.x, d.y), pack_bf16(d.z, d.w)));
        }
        fence_async_smem();
        __syncwarp();
        if (lane == 0) mbar_arrive(BAR(B_KVR), 1);
        PROF_MARK(24);
      }
    }
  } else {
    asm volatile("setmaxnreg.inc.sync.aligned.u32 112;");
    const int mh = wg & 1, nh = wg >> 1, wq = warp & 3;
    const int lq = lane & 3;
    const int rowl = wq * 16 + (lane >> 2);
    const int row0 = mh * 64 + rowl;
    int slot = 0, prev = 0;
    uint32_t par = 0;
    {
      float acc0[28], acc1[28], accs[4];
      const uint64_t dR = make_desc(sb + OFF_RING + nh * 16384, 1024, 1024, 1);
      const uint64_t dX = make_desc(sb + OFF_X + mh * 8192, 1024, 1024, 1);
#pragma unroll
      for (int i = 0; i < 28; i++) acc0[i] = acc1[i] = 0.f;
#pragma unroll
      for (int i = 0; i < 4; i++) accs[i] = 0.f;
      const uint64_t dSlc = make_desc(sb + OFF_SLC, 128, 128, 0);
#pragma unroll 1
      for (int c = 0; c < 7; c++) {
        if (c == 3 || c == 5) mbar_wait(BAR(B_XL + (c > 4)), 0);
        mbar_wait(BAR(B_FULL + slot), par);
        if (c == 0 && tid == 0) PROF2(17);
        const uint64_t dA = dX + c * 1024, dB = dR + slot * 2048;
        wg_fence();
#pragma unroll
        for (int ks = 0; ks < 4; ks++) {
          wgmma_ss_n56_ta0_tb1<1>(acc0, dA + ks * 2, dB + ks * 128);
          wgmma_ss_n56_ta0_tb1<1>(acc1, dA + ks * 2, dB + 512 + ks * 128);
        }
        if (nh == 1 && c > 0) {
#pragma unroll
          for (int ks = 0; ks < 4; ks++) wgmma_ss_n8_ta0_tb1<1>(accs, dA - 1024 + ks * 2, dSlc + (c - 1) * 64 + ks * 16);
        }
        wg_commit();
        if ((tid & 127) == 0) PROF4(wg * 32 + c * 3);
        if (c == 0) {
          mbar_wait(BAR(B_RAW), 0);
          const int k = tid >> 3, cn = tid & 7;
          const bool data = k < 56 && (cn >> 2) == (k >= DH);
          const uint2* wsrc = (const uint2*)(sgen + OFF_RAW + 25088 + k * 56 + (cn & 3) * 16);
          uint2 w0 = make_uint2(0u, 0u), w1 = w0;
          if (data) w0 = wsrc[0];
          if (data && (cn & 3) != 3) w1 = wsrc[1];
          sts128(sb + OFF_WBD + k * 128 + ((cn ^ (k & 7)) << 4), make_uint4(w0.x, w0.y, w1.x, w1.y));
          if (tid < DM) {
            const uint2* src = (const uint2*)(sgen + OFF_RAW + tid * 56 + (hp & 3) * 16);
            w0 = src[0];
            w1 = make_uint2(hp == 3 ? (uint32_t)((const unsigned short*)(sgen + OFF_RAW + 28224))[tid] : 0u, 0u);
            if ((hp & 3) != 3) w1 = src[1];
            sts128(sb + OFF_SLC + tid * 16, make_uint4(w0.x, w0.y, w1.x, w1.y));
          }
          fence_async_smem();
          __syncwarp();
          if (lane == 0) mbar_arrive(BAR(B_BUILD), 1);
          mbar_wait(BAR(B_BUILD), 0);
        }
        wg_wait<0>();
        if (lane == 0) mbar_arrive(BAR(B_EMPTY + slot), 1);
        if ((tid & 127) == 0) PROF4(wg * 32 + c * 3 + 2);
        if (++slot == 3) { slot = 0; par ^= 1; }
      }
      if (nh == 1) {
        wg_fence();
#pragma unroll
        for (int ks = 0; ks < 4; ks++) wgmma_ss_n8_ta0_tb1<1>(accs, dX + 6 * 1024 + ks * 2, dSlc + 6 * 64 + ks * 16);
        wg_commit();
      }
      wg_wait<0>();
      fence_regs(acc0); fence_regs(acc1); fence_regs(accs);
      if (tid == 0) PROF_MARK(2);
      if (tid == 256) PROF_MARK(3);
      if (nh == 0) {
        float sq[4] = {0.f, 0.f, 0.f, 0.f};
#pragma unroll
        for (int i = 0; i < 28; i++) acc0[i] *= 0.18898223650461362f * 1.4426950408889634f;
#pragma unroll
        for (int j = 0; j < 7; j++) {
#pragma unroll
          for (int rr = 0; rr < 2; rr++) {
            const float s2 = acc0[4 * j + 2 * rr] * acc0[4 * j + 2 * rr] + acc0[4 * j + 2 * rr + 1] * acc0[4 * j + 2 * rr + 1];
            if (j < 3) sq[rr] += s2;
            else if (j > 3) sq[2 + rr] += s2;
            else { sq[rr] += (lq < 2) ? s2 : 0.f; sq[2 + rr] += (lq < 2) ? 0.f : s2; }
          }
        }
#pragma unroll
        for (int i = 0; i < 4; i++) sq[i] = quad_sum(sq[i]);
        const float mine = lq == 0 ? sq[0] : lq == 1 ? sq[1] : lq == 2 ? sq[2] : sq[3];
        ((float*)(sgen + OFF_QSQ))[(mh + (lq & 2)) * 64 + rowl + 8 * (lq & 1)] = mine <= 3.0e38f ? mine : __int_as_float(0x7f800000);
        __syncwarp();
        if (lane == 0) mbar_arrive(BAR(B_QSQ), 1);
      } else {
        const int sl = hp & 3;
        const bool isk = hp < 4, real = (sl < 3) || (lq < 2);
        const int pos = pt * 128 + row0, kr = pos & 63;
        uint8_t* dst = g_kv_img + (pos >> 6) * 8192 + (isk ? 0 : 4096) + sw64_off(kr, sl * 8 + 2 * lq);
        const uint32_t pat = isk ? POLY_PAT >> (kr >> 3) : 0u;
        float mxv = 0.f;
#pragma unroll
        for (int rr = 0; rr < 2; rr++) {
          const float v0 = accs[2 * rr], v1 = accs[2 * rr + 1];
          const bool poly = (pat >> rr) & 1;
          const float sc = poly ? 2.f : 1.f;
          const float s2 = quad_sum(real ? v0 * v0 + v1 * v1 : 0.f);
          mxv = fmaxf(mxv, s2 <= 3.0e38f ? s2 : __int_as_float(0x7f800000));
          const uint32_t padv = lq == 2 ? (poly ? 0x443F4000u : 0x00003F80u) : (poly ? 0x3AB03F4Du : 0u);
          *(uint32_t*)(dst + rr * 512) = real ? pack_bf16(sc * v0, sc * v1) : padv;
          if (hp == 3 && lq == 2) g_gate[pos + 8 * rr] = rcpf(1.f + ex2f(-1.4426950408889634f * v0));
        }
        mxv = __uint_as_float(__reduce_max_sync(~0u, __float_as_uint(mxv)));
        if (lane == 0) (isk ? g_ksq : g_vsq)[sl * 128 + pt * 8 + mh * 4 + wq] = mxv;
        __syncwarp();
        if (lane == 0) mbar_arrive(BAR(B_SIG + 0), 1);
      }
      if (tid == 0) PROF_MARK(4);
      if (tid == 256) PROF_MARK(5);
      uint32_t h[14];
      float pp[32];
      {
        uint32_t a[16];
#pragma unroll
        for (int i = 0; i < 14; i++) {
          const uint32_t u0 = pack_bf16(acc0[2 * i], acc0[2 * i + 1]), u1 = pack_bf16(acc1[2 * i], acc1[2 * i + 1]);
          h[i] = nh ? u1 : u0;
          a[i] = nh ? u0 : u1;
        }
        a[14] = a[0] ^ 0x80008000u;
        a[15] = a[1] ^ 0x80008000u;
        const uint64_t dW = make_desc(sb + OFF_WBD, 1024, 1024, 1);
        wg_fence();
        wgmma_rs_n64_tb1<0>(pp, a[0], a[1], a[2], a[3], dW);
#pragma unroll
        for (int ks = 1; ks < 4; ks++) wgmma_rs_n64_tb1<1>(pp, a[4 * ks], a[4 * ks + 1], a[4 * ks + 2], a[4 * ks + 3], dW + ks * 128);
        wg_commit();
        bar_sync(1, 512);
        if (tid == 0) PROF_MARK(6);
        store_heads(sb + (nh ? OFF_VA : OFF_QP), h, nh ? 0x00003F80u : 0x3F800000u, nh ? 0u : 0x3F803F80u, row0, lq);
        wg_wait<0>();
        fence_regs(pp);
      }
      float v[16];
#pragma unroll
      for (int i = 0; i < 16; i++) v[i] = pp[i];
      uint32_t rb = sb + (nh ? OFF_PHIK : OFF_PHIQ) + row0 * 128 + lq * 4 + ((rowl & 7) << 4);
#pragma unroll 1
      for (int e = 0; e < 2; e++) {
        uint32_t ph[16];
        feature_map(v, ph, lq);
#pragma unroll
        for (int ch = 0; ch < 8; ch++) { sts32(rb ^ (ch << 4), ph[2 * ch]); sts32((rb ^ (ch << 4)) + 1024, ph[2 * ch + 1]); }
        rb += 16384;
#pragma unroll
        for (int i = 0; i < 16; i++) v[i] = pp[16 + i];
      }
      fence_async_smem();
      bar_sync(1, 512);
      if (tid == 0) PROF_MARK(7);
      if (nh == 1) {
        float kv0[16], kv1[16];
        const uint64_t dP = make_desc(sb + OFF_PHIK + mh * 8192, 1024, 1024, 1);
        const uint64_t dV = make_desc(sb + OFF_VA + mh * 4096, 512, 512, 2);
        wg_fence();
        wgmma_ss_n32_ta1_tb1<0>(kv0, dP, dV);
        wgmma_ss_n32_ta1_tb1<0>(kv1, dP + 1024, dV + 512);
#pragma unroll
        for (int ks = 1; ks < 4; ks++) {
          wgmma_ss_n32_ta1_tb1<1>(kv0, dP + ks * 128, dV + ks * 64);
          wgmma_ss_n32_ta1_tb1<1>(kv1, dP + 1024 + ks * 128, dV + 512 + ks * 64);
        }
        wg_commit();
        wg_wait<0>();
        fence_regs(kv0); fence_regs(kv1);
        bar_sync(4 + wg, 128);
        const uint32_t sa = sb + OFF_PHIK + mh * 8192 + rowl * 128 + lq * 8;
#pragma unroll
        for (int j = 0; j < 8; j++) {
          sts64(sa + 32 * (j >> 1) + 1024 * (j & 1), __float_as_uint(kv0[2 * j]), __float_as_uint(kv0[2 * j + 1]));
          sts64(sa + 16384 + 32 * (j >> 1) + 1024 * (j & 1), __float_as_uint(kv1[2 * j]), __float_as_uint(kv1[2 * j + 1]));
        }
        fence_async_smem();
        __syncwarp();
        if (lane == 0) mbar_arrive(BAR(B_SIG + 1), 1);
        if (tid == 256) PROF_MARK(28);
      }
    }
    {
      const uint64_t dK = make_desc(sb + OFF_RING, 512, 512, 2);
      const uint64_t dhi = dK & 0xffffffff00000000ull;
      const uint32_t dlo0 = (uint32_t)dK;
      uint32_t ok = 0, q[8];
      float o[16];
#pragma unroll
      for (int i = 0; i < 16; i++) o[i] = 0.f;
      {
        const int r = mh * 64 + wq * 16 + (lane & 7) + ((lane >> 3) & 1) * 8;
        ldsm4(q, sb + OFF_QP + nh * 8192 + sw64_off(r, (lane >> 4) * 8));
        ldsm4(q + 4, sb + OFF_QP + nh * 8192 + sw64_off(r, 16 + (lane >> 4) * 8));
      }
      if (tid == 0) PROF_MARK(10);
      const int qb = QB_AT;
#pragma unroll 1
      for (int it = 0; it <= 8; it++) {
        uint32_t p[16];
        if (it == qb || it == 8) {
          float t[16];
          wg_wait<0>();
          fence_regs(o);
          if (it < 8) {
            if (tid == 0) PROF_MARK(11);
            mbar_wait(BAR(B_KVR), 0);
            const uint64_t dR = make_desc(sb + OFF_KVR + nh * 4096, 512, 512, 2);
            const uint64_t dP = make_desc(sb + OFF_PHIQ + nh * 16384 + mh * 8192, 1024, 1024, 1);
            wg_fence();
            wgmma_ss_n32_ta0_tb1<0>(t, dP, dR);
#pragma unroll
            for (int ks = 1; ks < 4; ks++) wgmma_ss_n32_ta0_tb1<1>(t, dP + ks * 2, dR + ks * 64);
            wg_commit();
            wg_wait<0>();
            fence_regs(t);
            if (lane == 0) mbar_arrive(BAR(B_X1FREE), 1);
          } else {
            if (lane == 0) mbar_arrive(BAR(B_EMPTY + prev), 1);
            if (tid == 0) PROF_MARK(13);
            mbar_wait(BAR(B_SLOW), 0);
            if (__builtin_expect(__any_sync(~0u, *(volatile int*)(sgen + OFF_RED)), 0)) {
              uint32_t qz[8];
#pragma unroll
              for (int i = 0; i < 8; i++) qz[i] = (i >= 6 && lq >= 2) ? 0u : q[i];
              float m0 = -3.0e38f, m1 = -3.0e38f, o2[16];
              int sl2 = slot;
              uint32_t par2 = par;
#pragma unroll 1
              for (int j64 = 0; j64 < 32; j64++) {
                float s[32];
                mbar_wait(BAR(B_FULL + sl2), par2);
                const uint32_t lo = dlo0 + sl2 * 2048 + (j64 & 3) * 512;
                wg_fence();
                wgmma_rs_n64_tb0<0>(s, qz[0], qz[1], qz[2], qz[3], dhi | lo);
                wgmma_rs_n64_tb0<1>(s, qz[4], qz[5], qz[6], qz[7], dhi | (lo + 2));
                wg_commit();
                wg_wait<0>();
                fence_regs(s);
#pragma unroll
                for (int j = 0; j < 8; j++) {
                  const float sc = ((POLY_PAT >> j) & 1) ? 0.5f : 1.f;
                  m0 = fmaxf(m0, fmaxf(s[4 * j], s[4 * j + 1]) * sc);
                  m1 = fmaxf(m1, fmaxf(s[4 * j + 2], s[4 * j + 3]) * sc);
                }
                if ((j64 & 3) == 3) {
                  if (lane == 0) mbar_arrive(BAR(B_EMPTY + sl2), 1);
                  if (++sl2 == 3) { sl2 = 0; par2 ^= 1; }
                }
              }
              m0 = quad_max(m0); m1 = quad_max(m1);
#pragma unroll
              for (int i = 0; i < 16; i++) o2[i] = 0.f;
#pragma unroll 1
              for (int j64 = 0; j64 < 32; j64++) {
                float s[32];
                mbar_wait(BAR(B_FULL + sl2), par2);
                const uint32_t lo = dlo0 + sl2 * 2048 + (j64 & 3) * 512;
                wg_fence();
                wgmma_rs_n64_tb0<0>(s, qz[0], qz[1], qz[2], qz[3], dhi | lo);
                wgmma_rs_n64_tb0<1>(s, qz[4], qz[5], qz[6], qz[7], dhi | (lo + 2));
                wg_commit();
                wg_wait<0>();
                fence_regs(s);
                uint32_t ps[16];
#pragma unroll
                for (int j = 0; j < 8; j++) {
                  const float sc = ((POLY_PAT >> j) & 1) ? 0.5f : 1.f;
                  ps[2 * j] = pack_bf16(ex2f(fmaf(s[4 * j], sc, -m0)), ex2f(fmaf(s[4 * j + 1], sc, -m0)));
                  ps[2 * j + 1] = pack_bf16(ex2f(fmaf(s[4 * j + 2], sc, -m1)), ex2f(fmaf(s[4 * j + 3], sc, -m1)));
                }
                wg_fence();
#pragma unroll
                for (int ks = 0; ks < 4; ks++)
                  wgmma_rs_n32_tb1<1>(o2, ps[4 * ks], ps[4 * ks + 1], ps[4 * ks + 2], ps[4 * ks + 3], dhi | (lo + 256 + ks * 64));
                wg_commit();
                wg_wait<0>();
                fence_regs(o2);
                if ((j64 & 3) == 3) {
                  if (lane == 0) mbar_arrive(BAR(B_EMPTY + sl2), 1);
                  if (++sl2 == 3) { sl2 = 0; par2 ^= 1; }
                }
              }
#pragma unroll 1
              for (int j = 0; j < 2; j++) {
                mbar_wait(BAR(B_FULL + sl2), par2);
                __syncwarp();
                if (lane == 0) mbar_arrive(BAR(B_EMPTY + sl2), 1);
                if (++sl2 == 3) { sl2 = 0; par2 ^= 1; }
              }
#pragma unroll
              for (int i = 0; i < 16; i++) o[i] = o2[i];
            }
#pragma unroll
            for (int i = 0; i < 16; i++) t[i] = o[i];
          }
          const int br = it == 8;
          const float eps = br ? 0.f : 1e-6f;
          const float g0 = ((const float*)(sgen + OFF_GATE))[row0], g1 = ((const float*)(sgen + OFF_GATE))[row0 + 8];
          const float d0 = __shfl_sync(~0u, t[12], (lane & ~3) | 2), d1 = __shfl_sync(~0u, t[14], (lane & ~3) | 2);
          const float r0 = (br ? 1.f - g0 : g0) * rcpf(d0 + eps), r1 = (br ? 1.f - g1 : g1) * rcpf(d1 + eps);
          uint8_t* img = g_o_img + (size_t)((pt * 2 + br) * 14 + mh) * 8192 + rowl * 128;
          const int col0 = (2 * hp + nh) * DH + 2 * lq;
#pragma unroll
          for (int j = 0; j < 4; j++) {
            const int col = col0 + 8 * j;
            uint8_t* gp = img + (uint32_t)((col >> 6) * 16384 + ((((col >> 3) ^ rowl) & 7) << 4) + (col & 7) * 2);
            const uint32_t v0 = pack_bf16(t[4 * j] * r0, t[4 * j + 1] * r0), v1 = pack_bf16(t[4 * j + 2] * r1, t[4 * j + 3] * r1);
            if (j < 3 || lq < 2) { *(uint32_t*)gp = v0; *(uint32_t*)(gp + 1024) = v1; }
          }
          __syncwarp();
          if (lane == 0) mbar_arrive(BAR(B_SIG + 2 + br), 1);
          if (tid == 0) PROF_MARK(12 + 2 * br);
          if (br) break;
        }
        const uint32_t lo = dlo0 + slot * 2048;
        if (!ok) mbar_wait(BAR(B_FULL + slot), par);
        int nslot = slot + 1;
        uint32_t npar = par;
        if (nslot == 3) { nslot = 0; npar ^= 1; }
        {
          float s[32];
          wg_fence();
          wgmma_rs_n64_tb0<0>(s, q[0], q[1], q[2], q[3], dhi | lo);
          wgmma_rs_n64_tb0<1>(s, q[4], q[5], q[6], q[7], dhi | (lo + 2));
          wg_commit();
#pragma unroll
          for (int u = 0; u < 4; u++) {
            wg_wait<0>();
            fence_regs(s);
            if (u == 0 && lane == 0 && it > 0) mbar_arrive(BAR(B_EMPTY + prev), 1);
            if (u == 2) ok = mbar_test(BAR(B_FULL + nslot), npar);
#pragma unroll
            for (int j = 0; j < 8; j++) {
              if ((POLY_PAT >> j) & 1) {
                p[2 * j] = exp2_pair_fma(s[4 * j], s[4 * j + 1], 0x3F003F00u, 0x00030003u);
                p[2 * j + 1] = exp2_pair_fma(s[4 * j + 2], s[4 * j + 3], 0x3F003F00u, 0x00030003u);
              } else {
                p[2 * j] = pack_bf16(ex2f(s[4 * j]), ex2f(s[4 * j + 1]));
                p[2 * j + 1] = pack_bf16(ex2f(s[4 * j + 2]), ex2f(s[4 * j + 3]));
              }
            }
            wg_fence();
#pragma unroll
            for (int ks = 0; ks < 4; ks++)
              wgmma_rs_n32_tb1<1>(o, p[4 * ks], p[4 * ks + 1], p[4 * ks + 2], p[4 * ks + 3], dhi | (lo + u * 512 + 256 + ks * 64));
            if (u < 3) {
              wgmma_rs_n64_tb0<0>(s, q[0], q[1], q[2], q[3], dhi | (lo + (u + 1) * 512));
              wgmma_rs_n64_tb0<1>(s, q[4], q[5], q[6], q[7], dhi | (lo + (u + 1) * 512 + 2));
            }
            wg_commit();
          }
        }
        prev = slot; slot = nslot; par = npar;
      }
      wg_wait<0>();
    }
    if (nh == 1) return;
    {
      float acc0[28], acc1[28];
#pragma unroll
      for (int i = 0; i < 28; i++) acc0[i] = acc1[i] = 0.f;
      const uint64_t dS = make_desc(sb + OFF_WO, 1024, 1024, 1);
      const uint64_t dR = make_desc(sb + OFF_RING + mh * 8192, 1024, 1024, 1);
#pragma unroll 1
      for (int c = 0; c < 7; c++) {
        mbar_wait(BAR(B_WO + (c >= 3)), 0);
        mbar_wait(BAR(B_FULL + slot), par);
        const uint64_t dA = dR + slot * 2048, dB = dS + c * 1024;
        wg_fence();
#pragma unroll
        for (int ks = 0; ks < 4; ks++) {
          wgmma_ss_n56_ta0_tb1<1>(acc0, dA + ks * 2, dB + ks * 128);
          wgmma_ss_n56_ta0_tb1<1>(acc1, dA + 1024 + ks * 2, dB + 512 + ks * 128);
        }
        wg_commit();
        if (c < 4) {
          wg_wait<0>();
          if (lane == 0) mbar_arrive(BAR(B_EMPTY + slot), 2);
        }
        if (++slot == 3) { slot = 0; par ^= 1; }
      }
      wg_wait<0>();
      fence_regs(acc0); fence_regs(acc1);
      if (tid == 0) PROF_MARK(17);
      __nv_bfloat16* op = prm.out + (size_t)(pt * 128 + row0) * DM + hp * 56 + 2 * lq;
#pragma unroll
      for (int j = 0; j < 7; j++) {
        *(uint32_t*)(op + 8 * j) = pack_bf16(acc0[4 * j] + acc1[4 * j], acc0[4 * j + 1] + acc1[4 * j + 1]);
        *(uint32_t*)(op + 8 * DM + 8 * j) = pack_bf16(acc0[4 * j + 2] + acc1[4 * j + 2], acc0[4 * j + 3] + acc1[4 * j + 3]);
      }
      if (tid == 0) { PROF_MARK(18); PROF_CLK(31); }
    }
  }
}

typedef CUresult (*EncodeFn)(CUtensorMap*, CUtensorMapDataType, cuuint32_t, void*, const cuuint64_t*, const cuuint64_t*,
                             const cuuint32_t*, const cuuint32_t*, CUtensorMapInterleave, CUtensorMapSwizzle,
                             CUtensorMapL2promotion, CUtensorMapFloatOOBfill);

void make_map(EncodeFn enc, CUtensorMap* tm, const void* ptr, uint64_t cols, uint64_t rows, uint32_t box_cols, uint32_t box_rows) {
  cuuint64_t dims[2] = {cols, rows};
  cuuint64_t strides[1] = {cols * 2};
  cuuint32_t box[2] = {box_cols, box_rows};
  cuuint32_t es[2] = {1, 1};
  enc(tm, CU_TENSOR_MAP_DATA_TYPE_BFLOAT16, 2, const_cast<void*>(ptr), dims, strides, box, es, CU_TENSOR_MAP_INTERLEAVE_NONE,
      CU_TENSOR_MAP_SWIZZLE_128B, CU_TENSOR_MAP_L2_PROMOTION_L2_128B, CU_TENSOR_MAP_FLOAT_OOB_FILL_NONE);
}

}

extern "C" void kernel_launch(void* const* d_in, const int* in_sizes, int n_in, void* d_out, int out_size) {
  (void)in_sizes; (void)n_in; (void)out_size;
  static EncodeFn enc = nullptr;
  if (!enc) {
    void* fn = nullptr;
    cudaDriverEntryPointQueryResult qr;
    cudaGetDriverEntryPoint("cuTensorMapEncodeTiled", &fn, cudaEnableDefault, &qr);
    enc = (EncodeFn)fn;
    cudaFuncSetAttribute(fused_kernel, cudaFuncAttributeMaxDynamicSharedMemorySize, SMEM_BYTES);
  }
  CUtensorMap tm_x, tm_wqkv, tm_wq, tm_woa, tm_wob;
  make_map(enc, &tm_x, d_in[0], DM, S_LEN, 64, 128);
  make_map(enc, &tm_wqkv, d_in[1], 3 * DM, DM, 56, 64);
  make_map(enc, &tm_wq, d_in[5], DM, DM, 56, 64);
  make_map(enc, &tm_woa, d_in[3], DM, DM, 56, 64);
  make_map(enc, &tm_wob, d_in[8], DM, DM, 56, 64);
  Params prm;
  prm.w_phi = (const __nv_bfloat16*)d_in[2];
  prm.wk = (const __nv_bfloat16*)d_in[6];
  prm.wv = (const __nv_bfloat16*)d_in[7];
  prm.gate_w = (const __nv_bfloat16*)d_in[9];
  prm.out = (__nv_bfloat16*)d_out;
  fused_kernel<<<NCTA, NTHREADS, SMEM_BYTES>>>(tm_x, tm_wqkv, tm_wq, tm_woa, tm_wob, prm);
}
```

```cpp
#include <cuda_runtime.h>
#include <cuda_bf16.h>
#include <cuda.h>
#include <stdint.h>

namespace {

constexpr int S_LEN = 2048, DM = 448, DH = 28;
constexpr int NCTA = 128;
constexpr int NTHREADS = 640;
constexpr uint32_t POLY_PAT = 0x57;

#define QB_AT (4 + nh)

constexpr int OFF_X = 0;
constexpr int OFF_PHIK = 0;
constexpr int OFF_VA = 32768;
constexpr int OFF_PHIQ = 57344;
constexpr int OFF_KVR = 90112;
constexpr int OFF_QP = 98304;
constexpr int OFF_RAW = 81920;
constexpr int OFF_WO = 0;
constexpr int OFF_RING = 114688;
constexpr int OFF_WBD = 212992;
constexpr int OFF_SLC = 221184;
constexpr int OFF_QSQ = 228352;
constexpr int OFF_GATE = 229376;
constexpr int OFF_RED = 229888;
constexpr int OFF_BAR = 229952;
constexpr int SMEM_BYTES = 230400 + 1024;

constexpr int B_FULL = 0, B_EMPTY = 3, B_WO = 6  , B_KVR = 8, B_RAW = 9, B_X1FREE = 10, B_QSQ = 11, B_SLOW = 12,
              B_BUILD = 13, B_SIG = 14  , B_XL = 18  , B_N = 20;

constexpr int C_KV = 0, C_PART = 1, C_DONE = 3, C_OA = 4, C_OB = 20, C_N = 36;

__device__ __align__(1024) uint8_t g_kv_img[32 * 8192];
__device__ __align__(16) float g_ksq[512];
__device__ __align__(16) float g_vsq[512];
__device__ __align__(16) float g_gate[S_LEN];
__device__ __align__(1024) float g_kvacc[2][16 * 64 * 32];
__device__ unsigned g_epoch;
__device__ __align__(1024) uint8_t g_o_img[2 * 16 * 14 * 8192];
__device__ unsigned g_cnt[C_N * 32];

#define PROF4(i) do { } while (0)
#define PROF3(i) do { } while (0)
#define PROF2(i) do { } while (0)
#define PROF_CLK(i) do { } while (0)
#define PROF_MARK(i) do { } while (0)
__device__ __forceinline__ uint32_t smem_u32(const void* p) { return (uint32_t)__cvta_generic_to_shared(p); }
__device__ __forceinline__ void mbar_init(uint32_t a, int cnt) {
  asm volatile("mbarrier.init.shared::cta.b64 [%0], %1;" ::"r"(a), "r"(cnt) : "memory");
}
__device__ __forceinline__ void mbar_expect_tx(uint32_t a, uint32_t bytes) {
  asm volatile("mbarrier.arrive.expect_tx.shared::cta.b64 _, [%0], %1;" ::"r"(a), "r"(bytes) : "memory");
}
__device__ __forceinline__ void mbar_arrive(uint32_t a, uint32_t cnt) {
  asm volatile("mbarrier.arrive.shared::cta.b64 _, [%0], %1;" ::"r"(a), "r"(cnt) : "memory");
}
__device__ __forceinline__ void mbar_wait(uint32_t a, uint32_t parity) {
  asm volatile(
      "{\n.reg .pred p;\n.reg .u32 c;\nmov.u32 c, 0;\n"
      "W_%=:\nmbarrier.try_wait.parity.shared::cta.b64 p, [%0], %1;\n"
      "add.u32 c, c, 1;\nsetp.lt.and.u32 p, c, 0x40000, !p;\n@p bra W_%=;\n}"
      ::"r"(a), "r"(parity) : "memory");
}
__device__ __forceinline__ uint32_t mbar_test(uint32_t a, uint32_t parity) {
  uint32_t ok;
  asm volatile("{\n.reg .pred p;\nmbarrier.test_wait.parity.shared::cta.b64 p, [%1], %2;\nselp.u32 %0, 1, 0, p;\n}"
               : "=r"(ok) : "r"(a), "r"(parity) : "memory");
  return ok;
}
__device__ __forceinline__ bool elect_one() {
  uint32_t r;
  asm volatile("{\n.reg .pred p;\nelect.sync _|p, 0xffffffff;\nselp.u32 %0, 1, 0, p;\n}" : "=r"(r));
  return r != 0;
}
__device__ __forceinline__ void tma_2d(uint32_t dst, const CUtensorMap* tm, int c0, int c1, uint32_t bar) {
  asm volatile("cp.async.bulk.tensor.2d.shared::cluster.global.mbarrier::complete_tx::bytes [%0], [%1, {%3, %4}], [%2];"
               ::"r"(dst), "l"(tm), "r"(bar), "r"(c0), "r"(c1) : "memory");
}
__device__ __forceinline__ void bulk_g2s(uint32_t dst, const void* src, uint32_t bytes, uint32_t bar) {
  asm volatile("cp.async.bulk.shared::cluster.global.mbarrier::complete_tx::bytes [%0], [%1], %2, [%3];"
               ::"r"(dst), "l"(src), "r"(bytes), "r"(bar) : "memory");
}
__device__ __forceinline__ void fence_async_smem() { asm volatile("fence.proxy.async.shared::cta;" ::: "memory"); }
__device__ __forceinline__ void fence_async_all() { asm volatile("fence.proxy.async.global;" ::: "memory"); }

__device__ __forceinline__ void bar_sync(int id, int n) { asm volatile("bar.sync %0, %1;" ::"r"(id), "r"(n) : "memory"); }
__device__ __forceinline__ void cnt_arrive(int idx) {
  asm volatile("red.release.gpu.global.add.u32 [%0], 1;" ::"l"(&g_cnt[idx * 32]) : "memory");
}
__device__ __forceinline__ void cnt_wait(int idx, unsigned target) {
  unsigned v, n = 0;
#pragma unroll 1
  while (true) {
    asm volatile("ld.acquire.gpu.global.u32 %0, [%1];" : "=r"(v) : "l"(&g_cnt[idx * 32]) : "memory");
    if (v >= target || ++n >= (1u << 18)) break;
    __nanosleep(32);
  }
}
__device__ __forceinline__ void wg_fence() { asm volatile("wgmma.fence.sync.aligned;" ::: "memory"); }
__device__ __forceinline__ void wg_commit() { asm volatile("wgmma.commit_group.sync.aligned;" ::: "memory"); }
template <int N> __device__ __forceinline__ void wg_wait() { asm volatile("wgmma.wait_group.sync.aligned %0;" ::"n"(N) : "memory"); }
template <int N> __device__ __forceinline__ void fence_regs(float (&d)[N]) {
#pragma unroll
  for (int i = 0; i < N; i++) asm volatile("" : "+f"(d[i])::"memory");
}
__device__ __forceinline__ uint64_t make_desc(uint32_t saddr, uint32_t lbo, uint32_t sbo, uint32_t swz) {
  return (uint64_t)((saddr & 0x3FFFF) >> 4) | ((uint64_t)(lbo >> 4) << 16) | ((uint64_t)(sbo >> 4) << 32) | ((uint64_t)swz << 62);
}
__device__ __forceinline__ float ex2f(float x) { float y; asm("ex2.approx.ftz.f32 %0, %1;" : "=f"(y) : "f"(x)); return y; }
__device__ __forceinline__ float rcpf(float x) { float y; asm("rcp.approx.ftz.f32 %0, %1;" : "=f"(y) : "f"(x)); return y; }
__device__ __forceinline__ uint32_t pack_bf16(float lo, float hi) {
  uint32_t r; asm("cvt.rn.bf16x2.f32 %0, %1, %2;" : "=r"(r) : "f"(hi), "f"(lo)); return r;
}
__device__ __forceinline__ uint32_t lop_and_or(uint32_t a, uint32_t m, uint32_t c) {
  uint32_t r; asm("lop3.b32 %0, %1, %2, %3, 0xEA;" : "=r"(r) : "r"(a), "r"(m), "r"(c)); return r;
}
__device__ __forceinline__ void sts32(uint32_t a, uint32_t v) { asm volatile("st.shared.b32 [%0], %1;" ::"r"(a), "r"(v) : "memory"); }
__device__ __forceinline__ void st_shared_nv(uint32_t a, uint32_t v) { asm volatile("st.shared.b32 [%0], %1;" ::"r"(a), "r"(v)); }
__device__ __forceinline__ void sts64(uint32_t a, uint32_t v0, uint32_t v1) { asm volatile("st.shared.v2.b32 [%0], {%1, %2};" ::"r"(a), "r"(v0), "r"(v1) : "memory"); }
__device__ __forceinline__ void sts128(uint32_t a, uint4 v) {
  asm volatile("st.shared.v4.b32 [%0], {%1, %2, %3, %4};" ::"r"(a), "r"(v.x), "r"(v.y), "r"(v.z), "r"(v.w) : "memory");
}
__device__ __forceinline__ float4 ldcg_f4(const float* p) {
  float4 v; asm volatile("ld.global.cg.v4.f32 {%0, %1, %2, %3}, [%4];" : "=f"(v.x), "=f"(v.y), "=f"(v.z), "=f"(v.w) : "l"(p) : "memory"); return v;
}
__device__ __forceinline__ void ldsm4(uint32_t* r, uint32_t a) {
  asm volatile("ldmatrix.sync.aligned.m8n8.x4.shared.b16 {%0, %1, %2, %3}, [%4];"
               : "=r"(r[0]), "=r"(r[1]), "=r"(r[2]), "=r"(r[3]) : "r"(a) : "memory");
}
__device__ __forceinline__ float quad_sum(float v) { v += __shfl_xor_sync(~0u, v, 1); v += __shfl_xor_sync(~0u, v, 2); return v; }
__device__ __forceinline__ float quad_max(float v) { v = fmaxf(v, __shfl_xor_sync(~0u, v, 1)); v = fmaxf(v, __shfl_xor_sync(~0u, v, 2)); return v; }

template <int SD> __device__ __forceinline__ void wgmma_ss_n56_ta0_tb1(float (&d)[28], uint64_t da, uint64_t db) {
  if (SD) asm volatile("wgmma.mma_async.sync.aligned.m64n56k16.f32.bf16.bf16 {%0, %1, %2, %3, %4, %5, %6, %7, %8, %9, %10, %11, %12, %13, %14, %15, %16, %17, %18, %19, %20, %21, %22, %23, %24, %25, %26, %27}, %28, %29, 1, 1, 1, 0, 1;\n"
    : "+f"(d[0]), "+f"(d[1]), "+f"(d[2]), "+f"(d[3]), "+f"(d[4]), "+f"(d[5]), "+f"(d[6]), "+f"(d[7]), "+f"(d[8]), "+f"(d[9]), "+f"(d[10]), "+f"(d[11]), "+f"(d[12]), "+f"(d[13]), "+f"(d[14]), "+f"(d[15]), "+f"(d[16]), "+f"(d[17]), "+f"(d[18]), "+f"(d[19]), "+f"(d[20]), "+f"(d[21]), "+f"(d[22]), "+f"(d[23]), "+f"(d[24]), "+f"(d[25]), "+f"(d[26]), "+f"(d[27])
    : "l"(da), "l"(db));
  else asm volatile("wgmma.mma_async.sync.aligned.m64n56k16.f32.bf16.bf16 {%0, %1, %2, %3, %4, %5, %6, %7, %8, %9, %10, %11, %12, %13, %14, %15, %16, %17, %18, %19, %20, %21, %22, %23, %24, %25, %26, %27}, %28, %29, 0, 1, 1, 0, 1;\n"
    : "=f"(d[0]), "=f"(d[1]), "=f"(d[2]), "=f"(d[3]), "=f"(d[4]), "=f"(d[5]), "=f"(d[6]), "=f"(d[7]), "=f"(d[8]), "=f"(d[9]), "=f"(d[10]), "=f"(d[11]), "=f"(d[12]), "=f"(d[13]), "=f"(d[14]), "=f"(d[15]), "=f"(d[16]), "=f"(d[17]), "=f"(d[18]), "=f"(d[19]), "=f"(d[20]), "=f"(d[21]), "=f"(d[22]), "=f"(d[23]), "=f"(d[24]), "=f"(d[25]), "=f"(d[26]), "=f"(d[27])
    : "l"(da), "l"(db));
}
template <int SD> __device__ __forceinline__ void wgmma_ss_n8_ta0_tb1(float (&d)[4], uint64_t da, uint64_t db) {
  if (SD) asm volatile("wgmma.mma_async.sync.aligned.m64n8k16.f32.bf16.bf16 {%0, %1, %2, %3}, %4, %5, 1, 1, 1, 0, 1;\n"
    : "+f"(d[0]), "+f"(d[1]), "+f"(d[2]), "+f"(d[3])
    : "l"(da), "l"(db));
  else asm volatile("wgmma.mma_async.sync.aligned.m64n8k16.f32.bf16.bf16 {%0, %1, %2, %3}, %4, %5, 0, 1, 1, 0, 1;\n"
    : "=f"(d[0]), "=f"(d[1]), "=f"(d[2]), "=f"(d[3])
    : "l"(da), "l"(db));
}
template <int SD> __device__ __forceinline__ void wgmma_rs_n64_tb1(float (&d)[32], uint32_t a0, uint32_t a1, uint32_t a2, uint32_t a3, uint64_t db) {
  if (SD) asm volatile("wgmma.mma_async.sync.aligned.m64n64k16.f32.bf16.bf16 {%0, %1, %2, %3, %4, %5, %6, %7, %8, %9, %10, %11, %12, %13, %14, %15, %16, %17, %18, %19, %20, %21, %22, %23, %24, %25, %26, %27, %28, %29, %30, %31}, {%32, %33, %34, %35}, %36, 1, 1, 1, 1;\n"
    : "+f"(d[0]), "+f"(d[1]), "+f"(d[2]), "+f"(d[3]), "+f"(d[4]), "+f"(d[5]), "+f"(d[6]), "+f"(d[7]), "+f"(d[8]), "+f"(d[9]), "+f"(d[10]), "+f"(d[11]), "+f"(d[12]), "+f"(d[13]), "+f"(d[14]), "+f"(d[15]), "+f"(d[16]), "+f"(d[17]), "+f"(d[18]), "+f"(d[19]), "+f"(d[20]), "+f"(d[21]), "+f"(d[22]), "+f"(d[23]), "+f"(d[24]), "+f"(d[25]), "+f"(d[26]), "+f"(d[27]), "+f"(d[28]), "+f"(d[29]), "+f"(d[30]), "+f"(d[31])
    : "r"(a0), "r"(a1), "r"(a2), "r"(a3), "l"(db));
  else asm volatile("wgmma.mma_async.sync.aligned.m64n64k16.f32.bf16.bf16 {%0, %1, %2, %3, %4, %5, %6, %7, %8, %9, %10, %11, %12, %13, %14, %15, %16, %17, %18, %19, %20, %21, %22, %23, %24, %25, %26, %27, %28, %29, %30, %31}, {%32, %33, %34, %35}, %36, 0, 1, 1, 1;\n"
    : "=f"(d[0]), "=f"(d[1]), "=f"(d[2]), "=f"(d[3]), "=f"(d[4]), "=f"(d[5]), "=f"(d[6]), "=f"(d[7]), "=f"(d[8]), "=f"(d[9]), "=f"(d[10]), "=f"(d[11]), "=f"(d[12]), "=f"(d[13]), "=f"(d[14]), "=f"(d[15]), "=f"(d[16]), "=f"(d[17]), "=f"(d[18]), "=f"(d[19]), "=f"(d[20]), "=f"(d[21]), "=f"(d[22]), "=f"(d[23]), "=f"(d[24]), "=f"(d[25]), "=f"(d[26]), "=f"(d[27]), "=f"(d[28]), "=f"(d[29]), "=f"(d[30]), "=f"(d[31])
    : "r"(a0), "r"(a1), "r"(a2), "r"(a3), "l"(db));
}
template <int SD> __device__ __forceinline__ void wgmma_ss_n32_ta1_tb1(float (&d)[16], uint64_t da, uint64_t db) {
  if (SD) asm volatile("wgmma.mma_async.sync.aligned.m64n32k16.f32.bf16.bf16 {%0, %1, %2, %3, %4, %5, %6, %7, %8, %9, %10, %11, %12, %13, %14, %15}, %16, %17, 1, 1, 1, 1, 1;\n"
    : "+f"(d[0]), "+f"(d[1]), "+f"(d[2]), "+f"(d[3]), "+f"(d[4]), "+f"(d[5]), "+f"(d[6]), "+f"(d[7]), "+f"(d[8]), "+f"(d[9]), "+f"(d[10]), "+f"(d[11]), "+f"(d[12]), "+f"(d[13]), "+f"(d[14]), "+f"(d[15])
    : "l"(da), "l"(db));
  else asm volatile("wgmma.mma_async.sync.aligned.m64n32k16.f32.bf16.bf16 {%0, %1, %2, %3, %4, %5, %6, %7, %8, %9, %10, %11, %12, %13, %14, %15}, %16, %17, 0, 1, 1, 1, 1;\n"
    : "=f"(d[0]), "=f"(d[1]), "=f"(d[2]), "=f"(d[3]), "=f"(d[4]), "=f"(d[5]), "=f"(d[6]), "=f"(d[7]), "=f"(d[8]), "=f"(d[9]), "=f"(d[10]), "=f"(d[11]), "=f"(d[12]), "=f"(d[13]), "=f"(d[14]), "=f"(d[15])
    : "l"(da), "l"(db));
}
template <int SD> __device__ __forceinline__ void wgmma_ss_n32_ta0_tb1(float (&d)[16], uint64_t da, uint64_t db) {
  if (SD) asm volatile("wgmma.mma_async.sync.aligned.m64n32k16.f32.bf16.bf16 {%0, %1, %2, %3, %4, %5, %6, %7, %8, %9, %10, %11, %12, %13, %14, %15}, %16, %17, 1, 1, 1, 0, 1;\n"
    : "+f"(d[0]), "+f"(d[1]), "+f"(d[2]), "+f"(d[3]), "+f"(d[4]), "+f"(d[5]), "+f"(d[6]), "+f"(d[7]), "+f"(d[8]), "+f"(d[9]), "+f"(d[10]), "+f"(d[11]), "+f"(d[12]), "+f"(d[13]), "+f"(d[14]), "+f"(d[15])
    : "l"(da), "l"(db));
  else asm volatile("wgmma.mma_async.sync.aligned.m64n32k16.f32.bf16.bf16 {%0, %1, %2, %3, %4, %5, %6, %7, %8, %9, %10, %11, %12, %13, %14, %15}, %16, %17, 0, 1, 1, 0, 1;\n"
    : "=f"(d[0]), "=f"(d[1]), "=f"(d[2]), "=f"(d[3]), "=f"(d[4]), "=f"(d[5]), "=f"(d[6]), "=f"(d[7]), "=f"(d[8]), "=f"(d[9]), "=f"(d[10]), "=f"(d[11]), "=f"(d[12]), "=f"(d[13]), "=f"(d[14]), "=f"(d[15])
    : "l"(da), "l"(db));
}
template <int SD> __device__ __forceinline__ void wgmma_rs_n64_tb0(float (&d)[32], uint32_t a0, uint32_t a1, uint32_t a2, uint32_t a3, uint64_t db) {
  if (SD) asm volatile("wgmma.mma_async.sync.aligned.m64n64k16.f32.bf16.bf16 {%0, %1, %2, %3, %4, %5, %6, %7, %8, %9, %10, %11, %12, %13, %14, %15, %16, %17, %18, %19, %20, %21, %22, %23, %24, %25, %26, %27, %28, %29, %30, %31}, {%32, %33, %34, %35}, %36, 1, 1, 1, 0;\n"
    : "+f"(d[0]), "+f"(d[1]), "+f"(d[2]), "+f"(d[3]), "+f"(d[4]), "+f"(d[5]), "+f"(d[6]), "+f"(d[7]), "+f"(d[8]), "+f"(d[9]), "+f"(d[10]), "+f"(d[11]), "+f"(d[12]), "+f"(d[13]), "+f"(d[14]), "+f"(d[15]), "+f"(d[16]), "+f"(d[17]), "+f"(d[18]), "+f"(d[19]), "+f"(d[20]), "+f"(d[21]), "+f"(d[22]), "+f"(d[23]), "+f"(d[24]), "+f"(d[25]), "+f"(d[26]), "+f"(d[27]), "+f"(d[28]), "+f"(d[29]), "+f"(d[30]), "+f"(d[31])
    : "r"(a0), "r"(a1), "r"(a2), "r"(a3), "l"(db));
  else asm volatile("wgmma.mma_async.sync.aligned.m64n64k16.f32.bf16.bf16 {%0, %1, %2, %3, %4, %5, %6, %7, %8, %9, %10, %11, %12, %13, %14, %15, %16, %17, %18, %19, %20, %21, %22, %23, %24, %25, %26, %27, %28, %29, %30, %31}, {%32, %33, %34, %35}, %36, 0, 1, 1, 0;\n"
    : "=f"(d[0]), "=f"(d[1]), "=f"(d[2]), "=f"(d[3]), "=f"(d[4]), "=f"(d[5]), "=f"(d[6]), "=f"(d[7]), "=f"(d[8]), "=f"(d[9]), "=f"(d[10]), "=f"(d[11]), "=f"(d[12]), "=f"(d[13]), "=f"(d[14]), "=f"(d[15]), "=f"(d[16]), "=f"(d[17]), "=f"(d[18]), "=f"(d[19]), "=f"(d[20]), "=f"(d[21]), "=f"(d[22]), "=f"(d[23]), "=f"(d[24]), "=f"(d[25]), "=f"(d[26]), "=f"(d[27]), "=f"(d[28]), "=f"(d[29]), "=f"(d[30]), "=f"(d[31])
    : "r"(a0), "r"(a1), "r"(a2), "r"(a3), "l"(db));
}
template <int SD> __device__ __forceinline__ void wgmma_rs_n32_tb1(float (&d)[16], uint32_t a0, uint32_t a1, uint32_t a2, uint32_t a3, uint64_t db) {
  if (SD) asm volatile("wgmma.mma_async.sync.aligned.m64n32k16.f32.bf16.bf16 {%0, %1, %2, %3, %4, %5, %6, %7, %8, %9, %10, %11, %12, %13, %14, %15}, {%16, %17, %18, %19}, %20, 1, 1, 1, 1;\n"
    : "+f"(d[0]), "+f"(d[1]), "+f"(d[2]), "+f"(d[3]), "+f"(d[4]), "+f"(d[5]), "+f"(d[6]), "+f"(d[7]), "+f"(d[8]), "+f"(d[9]), "+f"(d[10]), "+f"(d[11]), "+f"(d[12]), "+f"(d[13]), "+f"(d[14]), "+f"(d[15])
    : "r"(a0), "r"(a1), "r"(a2), "r"(a3), "l"(db));
  else asm volatile("wgmma.mma_async.sync.aligned.m64n32k16.f32.bf16.bf16 {%0, %1, %2, %3, %4, %5, %6, %7, %8, %9, %10, %11, %12, %13, %14, %15}, {%16, %17, %18, %19}, %20, 0, 1, 1, 1;\n"
    : "=f"(d[0]), "=f"(d[1]), "=f"(d[2]), "=f"(d[3]), "=f"(d[4]), "=f"(d[5]), "=f"(d[6]), "=f"(d[7]), "=f"(d[8]), "=f"(d[9]), "=f"(d[10]), "=f"(d[11]), "=f"(d[12]), "=f"(d[13]), "=f"(d[14]), "=f"(d[15])
    : "r"(a0), "r"(a1), "r"(a2), "r"(a3), "l"(db));
}

__device__ __forceinline__ uint32_t sw64_off(int row, int d) { return row * 64 + ((((d >> 3) ^ (row >> 1)) & 3) << 4) + (d & 7) * 2; }

__device__ __forceinline__ uint32_t exp2_pair_fma(float t0, float t1, uint32_t c_half, uint32_t c_3) {
  uint32_t y0, y;
  asm("prmt.b32 %0, %1, %2, 0x6521;" : "=r"(y0) : "r"(__float_as_uint(t0)), "r"(__float_as_uint(t1)));
  uint32_t h = lop_and_or(y0, 0x007F007Fu, c_half);
  uint32_t e = lop_and_or(y0, 0xFF80FF80u, c_3);
  asm("fma.rn.bf16x2 %0, %1, %2, %3;" : "=r"(y) : "r"(y0), "r"(h), "r"(e));
  return y;
}

__device__ __forceinline__ void feature_map(float (&p)[32], uint32_t rb, int lq) {
  const float L2E = 1.4426950408889634f;
  const bool tail_ok = lq < 2;
  float mx[4], mn[4], b[32], sa[4], sn[4];
#pragma unroll
  for (int g = 0; g < 4; g++) {
    const int o = 16 * (g >> 1) + 2 * (g & 1);
    if (!tail_ok) { p[o + 12] = p[o]; p[o + 13] = p[o]; }
    mx[g] = fmaxf(fmaxf(fmaxf(p[o], p[o + 1]), fmaxf(p[o + 4], p[o + 5])), fmaxf(fmaxf(p[o + 8], p[o + 9]), fmaxf(p[o + 12], p[o + 13])));
    mn[g] = fminf(fminf(fminf(p[o], p[o + 1]), fminf(p[o + 4], p[o + 5])), fminf(fminf(p[o + 8], p[o + 9]), fminf(p[o + 12], p[o + 13])));
  }
#pragma unroll
  for (int o = 1; o <= 2; o <<= 1)
#pragma unroll
    for (int g = 0; g < 4; g++) { mx[g] = fmaxf(mx[g], __shfl_xor_sync(~0u, mx[g], o)); mn[g] = fminf(mn[g], __shfl_xor_sync(~0u, mn[g], o)); }
#pragma unroll
  for (int g = 0; g < 4; g++) {
    const int o = 16 * (g >> 1) + 2 * (g & 1);
    const float cx = -mx[g] * L2E, cn = mn[g] * L2E;
#pragma unroll
    for (int i = 0; i < 8; i++) {
      const int k = o + 4 * (i >> 1) + (i & 1);
      b[k] = ex2f(fmaf(p[k], -L2E, cn));
      p[k] = ex2f(fmaf(p[k], L2E, cx));
    }
    if (!tail_ok) { p[o + 12] = p[o + 13] = b[o + 12] = b[o + 13] = 0.f; }
    sa[g] = ((p[o] + p[o + 1]) + (p[o + 4] + p[o + 5])) + ((p[o + 8] + p[o + 9]) + (p[o + 12] + p[o + 13]));
    sn[g] = ((b[o] + b[o + 1]) + (b[o + 4] + b[o + 5])) + ((b[o + 8] + b[o + 9]) + (b[o + 12] + b[o + 13]));
    sa[g] += __shfl_xor_sync(~0u, sa[g], 1); sn[g] += __shfl_xor_sync(~0u, sn[g], 1);
    sa[g] += __shfl_xor_sync(~0u, sa[g], 2); sn[g] += __shfl_xor_sync(~0u, sn[g], 2);
  }
#pragma unroll
  for (int g = 0; g < 4; g++) {
    const int o = 16 * (g >> 1) + 2 * (g & 1);
    const float ra = rcpf(sa[g]), rn = rcpf(sn[g]);
    const uint32_t off = (g >> 1) * 16384 + (g & 1) * 1024;
#pragma unroll
    for (int jj = 0; jj < 4; jj++) {
      st_shared_nv((rb ^ (jj << 4)) + off, pack_bf16(p[o + 4 * jj] * ra, p[o + 4 * jj + 1] * ra));
      st_shared_nv((rb ^ ((4 + jj) << 4)) + off, pack_bf16(b[o + 4 * jj] * rn, b[o + 4 * jj + 1] * rn));
    }
  }
}

__device__ __forceinline__ void store_heads(uint32_t base, const uint32_t (&a)[14], uint32_t pad0, uint32_t pad1, int row0, int lq) {
  const uint32_t rb = base + row0 * 64 + (((row0 >> 1) & 3) << 4);
  const uint32_t b0 = rb + lq * 4;
  const uint32_t b1 = (rb + 8192 + ((lq * 4 + 8) & 15)) ^ ((lq >> 1) << 4);
#pragma unroll
  for (int j = 0; j < 7; j++) {
    uint32_t ad;
    if (j < 3) ad = b0 ^ (j << 4);
    else if (j == 3) ad = (lq < 2) ? (b0 ^ 48u) : (b1 ^ 16u);
    else ad = (lq < 2) ? (b1 ^ ((j - 4) << 4)) : ((b1 ^ 16u) ^ ((j - 3) << 4));
    sts32(ad, a[2 * j]);
    sts32(ad + 512, a[2 * j + 1]);
  }
  sts64((rb ^ 48u) + 8 + (lq & 1) * 8192 + (lq >> 1) * 512, pad0, pad1);
}

struct Params {
  const __nv_bfloat16* w_phi;
  const __nv_bfloat16* wk;
  const __nv_bfloat16* wv;
  const __nv_bfloat16* gate_w;
  __nv_bfloat16* out;
};

__global__ void __launch_bounds__(NTHREADS, 1)
fused_kernel(const __grid_constant__ CUtensorMap tm_x, const __grid_constant__ CUtensorMap tm_wqkv,
             const __grid_constant__ CUtensorMap tm_wq, const __grid_constant__ CUtensorMap tm_woa,
             const __grid_constant__ CUtensorMap tm_wob, const Params prm) {
  extern __shared__ uint8_t smem_raw[];
  uint32_t sb = (smem_u32(smem_raw) + 1023u) & ~1023u;
  uint8_t* sgen = smem_raw + (sb - smem_u32(smem_raw));
  asm volatile("mov.u32 %0, %0;" : "+r"(sb));
  const int tid = threadIdx.x, lane = tid & 31;
  const int warp = __shfl_sync(~0u, tid >> 5, 0), wg = warp >> 2;
  const int pt = blockIdx.x >> 3, hp = blockIdx.x & 7;
  const uint32_t bars = sb + OFF_BAR;
  auto BAR = [&](int i) { return bars + 8u * i; };
  const unsigned epoch = g_epoch & 1;

  if (tid == 0) { PROF_MARK(0); PROF_CLK(30); PROF2(15); }
  auto load_proj = [&](int c, int g) {
    mbar_expect_tx(BAR(B_FULL + g), (c < 3 ? 16384 : 0) + 4 * 7168);
    if (c < 3) tma_2d(sb + OFF_X + c * 16384, &tm_x, c * 64, pt * 128, BAR(B_FULL + g));
    tma_2d(sb + OFF_RING + g * 32768, &tm_wq, hp * 56, c * 64, BAR(B_FULL + g));
#pragma unroll 1
    for (int j = 0; j < 3; j++) tma_2d(sb + OFF_RING + g * 32768 + 8192 + j * 8192, &tm_wqkv, j * DM + hp * 56, c * 64, BAR(B_FULL + g));
  };
  if (warp == 16) {
    if (elect_one()) {
      mbar_init(BAR(B_FULL), 1);
      fence_async_smem();
      load_proj(0, 0);
      mbar_init(BAR(B_RAW), 1); mbar_init(BAR(B_FULL + 1), 1); mbar_init(BAR(B_FULL + 2), 1);
      fence_async_smem();
    }
    __syncwarp();
    asm volatile("bar.arrive 0, %0;" ::"n"(NTHREADS) : "memory");
  } else {
    if (elect_one()) {
      const int i = warp + 3 - (warp > 16);
      if (i < B_N && i != B_RAW) {
        int cnt = i < B_WO || (i > B_SIG && i < B_XL) || i == B_X1FREE ? 16 : 1;
        if (i == B_BUILD) cnt = 16;
        if (i == B_SIG || i == B_SIG + 1 || i == B_QSQ) cnt = 8;
        if (i == B_KVR) cnt = 2;
        mbar_init(BAR(i), cnt);
        fence_async_smem();
      }
    }
    bar_sync(0, NTHREADS);
  }
  if (tid == 0) PROF2(14);

  if (wg == 4) {
    asm volatile("setmaxnreg.dec.sync.aligned.u32 32;");
    if (warp == 16) {
      if (elect_one()) {
        mbar_expect_tx(BAR(B_RAW), 25088 + 3136 + 896);
        bulk_g2s(sb + OFF_RAW, hp < 4 ? prm.wk : prm.wv, 25088, BAR(B_RAW));
        bulk_g2s(sb + OFF_RAW + 25088, prm.w_phi + 2 * hp * DH * DH, 3136, BAR(B_RAW));
        bulk_g2s(sb + OFF_RAW + 28224, prm.gate_w, 896, BAR(B_RAW));
        load_proj(1, 1);
        load_proj(2, 2);
      }
      __syncwarp();
      bar_sync(3, 64);
      if (elect_one()) {
        int g = 0, nkv = 8;
        uint32_t par = 0;
#pragma unroll 1
        for (int c = 3; c < 7; c++) {
          if (c == 5) mbar_wait(BAR(B_BUILD), 0);
          if (c & 1) mbar_expect_tx(BAR(B_XL + (c > 4)), 32768);
          tma_2d(sb + OFF_X + c * 16384, &tm_x, c * 64, pt * 128, BAR(B_XL + (c > 4)));
        }
#pragma unroll 1
        for (int n = 3; n < 14 + nkv; n++) {
          if (n == 7) { PROF_MARK(20); cnt_wait(C_KV, NCTA); PROF_MARK(21); fence_async_all(); }
          if (n == 15) {
            mbar_wait(BAR(B_SLOW), 0);
            if (*(volatile int*)(sgen + OFF_RED)) nkv = 26;
          }
          const int j = n - 7 - nkv;
          if (j == 0 || j == 3) {
            PROF3(j ? 11 : 8);
            cnt_wait((j ? C_OB : C_OA) + pt, 8);
            PROF3(j ? 12 : 9);
            PROF_MARK(26);
            fence_async_all();
          }
          mbar_wait(BAR(B_EMPTY + g), par);
          if (n < 7) { PROF2(20 + n); load_proj(n, g); }
          else {
            mbar_expect_tx(BAR(B_FULL + g), 32768);
            bulk_g2s(sb + OFF_RING + g * 32768, j < 0 ? g_kv_img + ((n - 7) & 7) * 32768 : g_o_img + (size_t)(pt * 7 + j) * 32768, 32768,
                     BAR(B_FULL + g));
          }
          if (++g == 3) { g = 0; par ^= 1; }
        }
        if (atomicAdd(&g_cnt[C_DONE * 32], 1u) == NCTA - 1) {
#pragma unroll 1
          for (int i = 0; i < C_N; i++) g_cnt[i * 32] = 0;
          g_epoch = epoch ^ 1;
        }
      }
    } else {
      if (warp == 18) {
        if (elect_one()) {
#pragma unroll 1
          for (int i = 0; i < 4; i++) {
            mbar_wait(BAR(B_SIG + i), 0);
            PROF3(2 * i);
            if (i == 1) {
#pragma unroll 1
              for (int j = 0; j < 4; j++)
                asm volatile("cp.reduce.async.bulk.global.shared::cta.bulk_group.add.f32 [%0], [%1], 8192;"
                             ::"l"(g_kvacc[epoch] + hp * 4096 + (j >> 1) * 2048), "r"(sb + OFF_PHIK + j * 8192) : "memory");
              asm volatile("cp.async.bulk.commit_group;\ncp.async.bulk.wait_group 0;" ::: "memory");
            }
            cnt_arrive(i == 0 ? C_KV : i == 1 ? C_PART : (i == 2 ? C_OA : C_OB) + pt);
            PROF3(2 * i + 1);
            if (i == 1 || i == 2) {
              if (i == 2) mbar_wait(BAR(B_X1FREE), 0);
              mbar_expect_tx(BAR(B_WO + i - 1), 7 * 7168);
#pragma unroll 1
              for (int c = 0; c < 7; c++)
                tma_2d(sb + OFF_WO + (i - 1) * 57344 + c * 8192, i == 1 ? &tm_woa : &tm_wob, hp * 56, c * 64, BAR(B_WO + i - 1));
            }
          }
        }
      } else if (warp == 19) {
        if (lane == 0) {
          mbar_wait(BAR(B_SIG + 0), 0);
          cnt_wait(C_KV, NCTA);
        }
        __syncwarp();
        float ksq = 0.f, vsq = 0.f;
#pragma unroll
        for (int sl = 0; sl < 4; sl++) {
          float4 a = ldcg_f4(g_ksq + sl * 128 + lane * 4), b = ldcg_f4(g_vsq + sl * 128 + lane * 4);
          float m = fmaxf(fmaxf(a.x, a.y), fmaxf(a.z, a.w));
          m = __uint_as_float(__reduce_max_sync(~0u, __float_as_uint(m)));
          ksq += m;
          vsq = fmaxf(vsq, fmaxf(fmaxf(b.x, b.y), fmaxf(b.z, b.w)));
        }
        mbar_wait(BAR(B_QSQ), 0);
        const float4 qa4 = ((const float4*)(sgen + OFF_QSQ))[lane], qb4 = ((const float4*)(sgen + OFF_QSQ))[32 + lane];
        const float qmax = fmaxf(fmaxf(fmaxf(qa4.x, qa4.y), fmaxf(qa4.z, qa4.w)), fmaxf(fmaxf(qb4.x, qb4.y), fmaxf(qb4.z, qb4.w)));
        const bool slow = __any_sync(~0u, !(qmax * ksq <= 98.f * 98.f) || !(vsq <= 2.0e8f));
        if (lane == 0) {
          *(volatile int*)(sgen + OFF_RED) = slow;
          mbar_arrive(BAR(B_SLOW), 1);
        }
      } else {
        float4* z = (float4*)(g_kvacc[epoch ^ 1] + blockIdx.x * 256) + lane;
        z[0] = make_float4(0.f, 0.f, 0.f, 0.f);
        z[32] = make_float4(0.f, 0.f, 0.f, 0.f);
        bar_sync(3, 64);
        if (lane == 0) {
          mbar_wait(BAR(B_SIG + 0), 0);
          cnt_wait(C_KV, NCTA);
        }
        __syncwarp();
        ((float4*)(sgen + OFF_GATE))[lane] = ldcg_f4(g_gate + pt * 128 + lane * 4);
      }
      if (warp != 18) {
        if (lane == 0) {
          mbar_wait(BAR(B_SIG + 1), 0);
          cnt_wait(C_PART, NCTA);
          PROF_MARK(23);
        }
        __syncwarp();
        const int e = warp == 19;
        const float* src = g_kvacc[epoch] + hp * 4096 + e * 2048 + lane * 8;
#pragma unroll 1
        for (int i = 0; i < 8; i += 2) {
          const float4 a = ldcg_f4(src + i * 256), b = ldcg_f4(src + i * 256 + 4), c = ldcg_f4(src + i * 256 + 256), d = ldcg_f4(src + i * 256 + 260);
          const uint32_t ad = sb + OFF_KVR + e * 4096 + sw64_off(i * 8 + (lane >> 2), (lane & 3) * 8);
          sts128(ad, make_uint4(pack_bf16(a.x, a.y), pack_bf16(a.z, a.w), pack_bf16(b.x, b.y), pack_bf16(b.z, b.w)));
          sts128(ad + 512, make_uint4(pack_bf16(c.x, c.y), pack_bf16(c.z, c.w), pack_bf16(d.x, d.y), pack_bf16(d.z, d.w)));
        }
        fence_async_smem();
        __syncwarp();
        if (lane == 0) mbar_arrive(BAR(B_KVR), 1);
        PROF_MARK(24);
      }
    }
  } else {
    asm volatile("setmaxnreg.inc.sync.aligned.u32 112;");
    const int mh = wg & 1, nh = wg >> 1, wq = warp & 3;
    const int lq = lane & 3;
    const int rowl = wq * 16 + (lane >> 2);
    const int row0 = mh * 64 + rowl;
    int slot = 0, prev = 0;
    uint32_t par = 0;
    {
      float acc0[28], acc1[28], accs[4];
      const uint64_t dR = make_desc(sb + OFF_RING + nh * 16384, 1024, 1024, 1);
      const uint64_t dX = make_desc(sb + OFF_X + mh * 8192, 1024, 1024, 1);
#pragma unroll
      for (int i = 0; i < 28; i++) acc0[i] = acc1[i] = 0.f;
#pragma unroll
      for (int i = 0; i < 4; i++) accs[i] = 0.f;
      const uint64_t dSlc = make_desc(sb + OFF_SLC, 128, 128, 0);
#pragma unroll 1
      for (int c = 0; c < 7; c++) {
        if (c == 3 || c == 5) mbar_wait(BAR(B_XL + (c > 4)), 0);
        mbar_wait(BAR(B_FULL + slot), par);
        if (c == 0 && tid == 0) PROF2(17);
        const uint64_t dA = dX + c * 1024, dB = dR + slot * 2048;
        wg_fence();
#pragma unroll
        for (int ks = 0; ks < 4; ks++) {
          wgmma_ss_n56_ta0_tb1<1>(acc0, dA + ks * 2, dB + ks * 128);
          wgmma_ss_n56_ta0_tb1<1>(acc1, dA + ks * 2, dB + 512 + ks * 128);
        }
        if (nh == 1 && c > 0) {
#pragma unroll
          for (int ks = 0; ks < 4; ks++) wgmma_ss_n8_ta0_tb1<1>(accs, dA - 1024 + ks * 2, dSlc + (c - 1) * 64 + ks * 16);
        }
        wg_commit();
        if ((tid & 127) == 0) PROF4(wg * 32 + c * 3);
        if (c == 0) {
          mbar_wait(BAR(B_RAW), 0);
          const int k = tid >> 3, cn = tid & 7;
          const bool data = k < 56 && (cn >> 2) == (k >= DH);
          const uint2* wsrc = (const uint2*)(sgen + OFF_RAW + 25088 + k * 56 + (cn & 3) * 16);
          uint2 w0 = make_uint2(0u, 0u), w1 = w0;
          if (data) w0 = wsrc[0];
          if (data && (cn & 3) != 3) w1 = wsrc[1];
          sts128(sb + OFF_WBD + k * 128 + ((cn ^ (k & 7)) << 4), make_uint4(w0.x, w0.y, w1.x, w1.y));
          if (tid < DM) {
            const uint2* src = (const uint2*)(sgen + OFF_RAW + tid * 56 + (hp & 3) * 16);
            w0 = src[0];
            w1 = make_uint2(hp == 3 ? (uint32_t)((const unsigned short*)(sgen + OFF_RAW + 28224))[tid] : 0u, 0u);
            if ((hp & 3) != 3) w1 = src[1];
            sts128(sb + OFF_SLC + tid * 16, make_uint4(w0.x, w0.y, w1.x, w1.y));
          }
          fence_async_smem();
          __syncwarp();
          if (lane == 0) mbar_arrive(BAR(B_BUILD), 1);
          mbar_wait(BAR(B_BUILD), 0);
        }
        wg_wait<0>();
        if (lane == 0) mbar_arrive(BAR(B_EMPTY + slot), 1);
        if ((tid & 127) == 0) PROF4(wg * 32 + c * 3 + 2);
        if (++slot == 3) { slot = 0; par ^= 1; }
      }
      if (nh == 1) {
        wg_fence();
#pragma unroll
        for (int ks = 0; ks < 4; ks++) wgmma_ss_n8_ta0_tb1<1>(accs, dX + 6 * 1024 + ks * 2, dSlc + 6 * 64 + ks * 16);
        wg_commit();
      }
      wg_wait<0>();
      fence_regs(acc0); fence_regs(acc1); fence_regs(accs);
      if (tid == 0) PROF_MARK(2);
      if (tid == 256) PROF_MARK(3);
      if (nh == 0) {
        float sq[4] = {0.f, 0.f, 0.f, 0.f};
#pragma unroll
        for (int i = 0; i < 28; i++) acc0[i] *= 0.18898223650461362f * 1.4426950408889634f;
#pragma unroll
        for (int j = 0; j < 7; j++) {
#pragma unroll
          for (int rr = 0; rr < 2; rr++) {
            const float s2 = acc0[4 * j + 2 * rr] * acc0[4 * j + 2 * rr] + acc0[4 * j + 2 * rr + 1] * acc0[4 * j + 2 * rr + 1];
            if (j < 3) sq[rr] += s2;
            else if (j > 3) sq[2 + rr] += s2;
            else { sq[rr] += (lq < 2) ? s2 : 0.f; sq[2 + rr] += (lq < 2) ? 0.f : s2; }
          }
        }
#pragma unroll
        for (int i = 0; i < 4; i++) sq[i] = quad_sum(sq[i]);
        const float mine = lq == 0 ? sq[0] : lq == 1 ? sq[1] : lq == 2 ? sq[2] : sq[3];
        ((float*)(sgen + OFF_QSQ))[(mh + (lq & 2)) * 64 + rowl + 8 * (lq & 1)] = mine <= 3.0e38f ? mine : __int_as_float(0x7f800000);
        __syncwarp();
        if (lane == 0) mbar_arrive(BAR(B_QSQ), 1);
      } else {
        const int sl = hp & 3;
        const bool isk = hp < 4, real = (sl < 3) || (lq < 2);
        const int pos = pt * 128 + row0, kr = pos & 63;
        uint8_t* dst = g_kv_img + (pos >> 6) * 8192 + (isk ? 0 : 4096) + sw64_off(kr, sl * 8 + 2 * lq);
        const uint32_t pat = isk ? POLY_PAT >> (kr >> 3) : 0u;
        float mxv = 0.f;
#pragma unroll
        for (int rr = 0; rr < 2; rr++) {
          const float v0 = accs[2 * rr], v1 = accs[2 * rr + 1];
          const bool poly = (pat >> rr) & 1;
          const float sc = poly ? 2.f : 1.f;
          const float s2 = quad_sum(real ? v0 * v0 + v1 * v1 : 0.f);
          mxv = fmaxf(mxv, s2 <= 3.0e38f ? s2 : __int_as_float(0x7f800000));
          const uint32_t padv = lq == 2 ? (poly ? 0x443F4000u : 0x00003F80u) : (poly ? 0x3AB03F4Du : 0u);
          *(uint32_t*)(dst + rr * 512) = real ? pack_bf16(sc * v0, sc * v1) : padv;
          if (hp == 3 && lq == 2) g_gate[pos + 8 * rr] = rcpf(1.f + ex2f(-1.4426950408889634f * v0));
        }
        mxv = __uint_as_float(__reduce_max_sync(~0u, __float_as_uint(mxv)));
        if (lane == 0) (isk ? g_ksq : g_vsq)[sl * 128 + pt * 8 + mh * 4 + wq] = mxv;
        __syncwarp();
        if (lane == 0) mbar_arrive(BAR(B_SIG + 0), 1);
      }
      if (tid == 0) PROF_MARK(4);
      if (tid == 256) PROF_MARK(5);
      uint32_t h[14];
      float pp[32];
      {
        uint32_t a[16];
#pragma unroll
        for (int i = 0; i < 14; i++) {
          const uint32_t u0 = pack_bf16(acc0[2 * i], acc0[2 * i + 1]), u1 = pack_bf16(acc1[2 * i], acc1[2 * i + 1]);
          h[i] = nh ? u1 : u0;
          a[i] = nh ? u0 : u1;
        }
        a[14] = a[0] ^ 0x80008000u;
        a[15] = a[1] ^ 0x80008000u;
        const uint64_t dW = make_desc(sb + OFF_WBD, 1024, 1024, 1);
        wg_fence();
        wgmma_rs_n64_tb1<0>(pp, a[0], a[1], a[2], a[3], dW);
#pragma unroll
        for (int ks = 1; ks < 4; ks++) wgmma_rs_n64_tb1<1>(pp, a[4 * ks], a[4 * ks + 1], a[4 * ks + 2], a[4 * ks + 3], dW + ks * 128);
        wg_commit();
        bar_sync(1, 512);
        if (tid == 0) PROF_MARK(6);
        store_heads(sb + (nh ? OFF_VA : OFF_QP), h, nh ? 0x00003F80u : 0x3F800000u, nh ? 0u : 0x3F803F80u, row0, lq);
        wg_wait<0>();
        fence_regs(pp);
      }
      feature_map(pp, sb + (nh ? OFF_PHIK : OFF_PHIQ) + row0 * 128 + lq * 4 + ((rowl & 7) << 4), lq);
      fence_async_smem();
      bar_sync(1, 512);
      if (tid == 0) PROF_MARK(7);
      if (nh == 1) {
        float kv0[16], kv1[16];
        const uint64_t dP = make_desc(sb + OFF_PHIK + mh * 8192, 1024, 1024, 1);
        const uint64_t dV = make_desc(sb + OFF_VA + mh * 4096, 512, 512, 2);
        wg_fence();
        wgmma_ss_n32_ta1_tb1<0>(kv0, dP, dV);
        wgmma_ss_n32_ta1_tb1<0>(kv1, dP + 1024, dV + 512);
#pragma unroll
        for (int ks = 1; ks < 4; ks++) {
          wgmma_ss_n32_ta1_tb1<1>(kv0, dP + ks * 128, dV + ks * 64);
          wgmma_ss_n32_ta1_tb1<1>(kv1, dP + 1024 + ks * 128, dV + 512 + ks * 64);
        }
        wg_commit();
        wg_wait<0>();
        fence_regs(kv0); fence_regs(kv1);
        bar_sync(4 + wg, 128);
        const uint32_t sa = sb + OFF_PHIK + mh * 8192 + rowl * 128 + lq * 8;
#pragma unroll
        for (int j = 0; j < 8; j++) {
          sts64(sa + 32 * (j >> 1) + 1024 * (j & 1), __float_as_uint(kv0[2 * j]), __float_as_uint(kv0[2 * j + 1]));
          sts64(sa + 16384 + 32 * (j >> 1) + 1024 * (j & 1), __float_as_uint(kv1[2 * j]), __float_as_uint(kv1[2 * j + 1]));
        }
        fence_async_smem();
        __syncwarp();
        if (lane == 0) mbar_arrive(BAR(B_SIG + 1), 1);
        if (tid == 256) PROF_MARK(28);
      }
    }
    {
      const uint64_t dK = make_desc(sb + OFF_RING, 512, 512, 2);
      const uint64_t dhi = dK & 0xffffffff00000000ull;
      const uint32_t dlo0 = (uint32_t)dK;
      uint32_t ok = 0, q[8];
      float o[16];
#pragma unroll
      for (int i = 0; i < 16; i++) o[i] = 0.f;
      {
        const int r = mh * 64 + wq * 16 + (lane & 7) + ((lane >> 3) & 1) * 8;
        ldsm4(q, sb + OFF_QP + nh * 8192 + sw64_off(r, (lane >> 4) * 8));
        ldsm4(q + 4, sb + OFF_QP + nh * 8192 + sw64_off(r, 16 + (lane >> 4) * 8));
      }
      if (tid == 0) PROF_MARK(10);
      const int qb = QB_AT;
#pragma unroll 1
      for (int it = 0; it <= 8; it++) {
        uint32_t p[16];
        if (it == qb || it == 8) {
          float t[16];
          wg_wait<0>();
          fence_regs(o);
          if (it < 8) {
            if (tid == 0) PROF_MARK(11);
            mbar_wait(BAR(B_KVR), 0);
            const uint64_t dR = make_desc(sb + OFF_KVR + nh * 4096, 512, 512, 2);
            const uint64_t dP = make_desc(sb + OFF_PHIQ + nh * 16384 + mh * 8192, 1024, 1024, 1);
            wg_fence();
            wgmma_ss_n32_ta0_tb1<0>(t, dP, dR);
#pragma unroll
            for (int ks = 1; ks < 4; ks++) wgmma_ss_n32_ta0_tb1<1>(t, dP + ks * 2, dR + ks * 64);
            wg_commit();
            wg_wait<0>();
            fence_regs(t);
            if (lane == 0) mbar_arrive(BAR(B_X1FREE), 1);
          } else {
            if (lane == 0) mbar_arrive(BAR(B_EMPTY + prev), 1);
            if (tid == 0) PROF_MARK(13);
            mbar_wait(BAR(B_SLOW), 0);
            if (__builtin_expect(__any_sync(~0u, *(volatile int*)(sgen + OFF_RED)), 0)) {
              uint32_t qz[8];
#pragma unroll
              for (int i = 0; i < 8; i++) qz[i] = (i >= 6 && lq >= 2) ? 0u : q[i];
              float m0 = -3.0e38f, m1 = -3.0e38f, o2[16];
              int sl2 = slot;
              uint32_t par2 = par;
#pragma unroll 1
              for (int j64 = 0; j64 < 32; j64++) {
                float s[32];
                mbar_wait(BAR(B_FULL + sl2), par2);
                const uint32_t lo = dlo0 + sl2 * 2048 + (j64 & 3) * 512;
                wg_fence();
                wgmma_rs_n64_tb0<0>(s, qz[0], qz[1], qz[2], qz[3], dhi | lo);
                wgmma_rs_n64_tb0<1>(s, qz[4], qz[5], qz[6], qz[7], dhi | (lo + 2));
                wg_commit();
                wg_wait<0>();
                fence_regs(s);
#pragma unroll
                for (int j = 0; j < 8; j++) {
                  const float sc = ((POLY_PAT >> j) & 1) ? 0.5f : 1.f;
                  m0 = fmaxf(m0, fmaxf(s[4 * j], s[4 * j + 1]) * sc);
                  m1 = fmaxf(m1, fmaxf(s[4 * j + 2], s[4 * j + 3]) * sc);
                }
                if ((j64 & 3) == 3) {
                  if (lane == 0) mbar_arrive(BAR(B_EMPTY + sl2), 1);
                  if (++sl2 == 3) { sl2 = 0; par2 ^= 1; }
                }
              }
              m0 = quad_max(m0); m1 = quad_max(m1);
#pragma unroll
              for (int i = 0; i < 16; i++) o2[i] = 0.f;
#pragma unroll 1
              for (int j64 = 0; j64 < 32; j64++) {
                float s[32];
                mbar_wait(BAR(B_FULL + sl2), par2);
                const uint32_t lo = dlo0 + sl2 * 2048 + (j64 & 3) * 512;
                wg_fence();
                wgmma_rs_n64_tb0<0>(s, qz[0], qz[1], qz[2], qz[3], dhi | lo);
                wgmma_rs_n64_tb0<1>(s, qz[4], qz[5], qz[6], qz[7], dhi | (lo + 2));
                wg_commit();
                wg_wait<0>();
                fence_regs(s);
                uint32_t ps[16];
#pragma unroll
                for (int j = 0; j < 8; j++) {
                  const float sc = ((POLY_PAT >> j) & 1) ? 0.5f : 1.f;
                  ps[2 * j] = pack_bf16(ex2f(fmaf(s[4 * j], sc, -m0)), ex2f(fmaf(s[4 * j + 1], sc, -m0)));
                  ps[2 * j + 1] = pack_bf16(ex2f(fmaf(s[4 * j + 2], sc, -m1)), ex2f(fmaf(s[4 * j + 3], sc, -m1)));
                }
                wg_fence();
#pragma unroll
                for (int ks = 0; ks < 4; ks++)
                  wgmma_rs_n32_tb1<1>(o2, ps[4 * ks], ps[4 * ks + 1], ps[4 * ks + 2], ps[4 * ks + 3], dhi | (lo + 256 + ks * 64));
                wg_commit();
                wg_wait<0>();
                fence_regs(o2);
                if ((j64 & 3) == 3) {
                  if (lane == 0) mbar_arrive(BAR(B_EMPTY + sl2), 1);
                  if (++sl2 == 3) { sl2 = 0; par2 ^= 1; }
                }
              }
#pragma unroll 1
              for (int j = 0; j < 2; j++) {
                mbar_wait(BAR(B_FULL + sl2), par2);
                __syncwarp();
                if (lane == 0) mbar_arrive(BAR(B_EMPTY + sl2), 1);
                if (++sl2 == 3) { sl2 = 0; par2 ^= 1; }
              }
#pragma unroll
              for (int i = 0; i < 16; i++) o[i] = o2[i];
            }
#pragma unroll
            for (int i = 0; i < 16; i++) t[i] = o[i];
          }
          const int br = it == 8;
          const float eps = br ? 0.f : 1e-6f;
          const float g0 = ((const float*)(sgen + OFF_GATE))[row0], g1 = ((const float*)(sgen + OFF_GATE))[row0 + 8];
          const float d0 = __shfl_sync(~0u, t[12], (lane & ~3) | 2), d1 = __shfl_sync(~0u, t[14], (lane & ~3) | 2);
          const float r0 = (br ? 1.f - g0 : g0) * rcpf(d0 + eps), r1 = (br ? 1.f - g1 : g1) * rcpf(d1 + eps);
          uint8_t* img = g_o_img + (size_t)((pt * 2 + br) * 14 + mh) * 8192 + rowl * 128;
          const int col0 = (2 * hp + nh) * DH + 2 * lq;
#pragma unroll
          for (int j = 0; j < 4; j++) {
            const int col = col0 + 8 * j;
            uint8_t* gp = img + (uint32_t)((col >> 6) * 16384 + ((((col >> 3) ^ rowl) & 7) << 4) + (col & 7) * 2);
            const uint32_t v0 = pack_bf16(t[4 * j] * r0, t[4 * j + 1] * r0), v1 = pack_bf16(t[4 * j + 2] * r1, t[4 * j + 3] * r1);
            if (j < 3 || lq < 2) { *(uint32_t*)gp = v0; *(uint32_t*)(gp + 1024) = v1; }
          }
          __syncwarp();
          if (lane == 0) mbar_arrive(BAR(B_SIG + 2 + br), 1);
          if (tid == 0) PROF_MARK(12 + 2 * br);
          if (br) break;
        }
        const uint32_t lo = dlo0 + slot * 2048;
        if (!ok) mbar_wait(BAR(B_FULL + slot), par);
        int nslot = slot + 1;
        uint32_t npar = par;
        if (nslot == 3) { nslot = 0; npar ^= 1; }
        {
          float s[32];
          wg_fence();
          wgmma_rs_n64_tb0<0>(s, q[0], q[1], q[2], q[3], dhi | lo);
          wgmma_rs_n64_tb0<1>(s, q[4], q[5], q[6], q[7], dhi | (lo + 2));
          wg_commit();
#pragma unroll
          for (int u = 0; u < 4; u++) {
            wg_wait<0>();
            fence_regs(s);
            if (u == 0 && lane == 0 && it > 0) mbar_arrive(BAR(B_EMPTY + prev), 1);
            if (u == 2) ok = mbar_test(BAR(B_FULL + nslot), npar);
#pragma unroll
            for (int j = 0; j < 8; j++) {
              if ((POLY_PAT >> j) & 1) {
                p[2 * j] = exp2_pair_fma(s[4 * j], s[4 * j + 1], 0x3F003F00u, 0x00030003u);
                p[2 * j + 1] = exp2_pair_fma(s[4 * j + 2], s[4 * j + 3], 0x3F003F00u, 0x00030003u);
              } else {
                p[2 * j] = pack_bf16(ex2f(s[4 * j]), ex2f(s[4 * j + 1]));
                p[2 * j + 1] = pack_bf16(ex2f(s[4 * j + 2]), ex2f(s[4 * j + 3]));
              }
            }
            wg_fence();
#pragma unroll
            for (int ks = 0; ks < 4; ks++)
              wgmma_rs_n32_tb1<1>(o, p[4 * ks], p[4 * ks + 1], p[4 * ks + 2], p[4 * ks + 3], dhi | (lo + u * 512 + 256 + ks * 64));
            if (u < 3) {
              wgmma_rs_n64_tb0<0>(s, q[0], q[1], q[2], q[3], dhi | (lo + (u + 1) * 512));
              wgmma_rs_n64_tb0<1>(s, q[4], q[5], q[6], q[7], dhi | (lo + (u + 1) * 512 + 2));
            }
            wg_commit();
          }
        }
        prev = slot; slot = nslot; par = npar;
      }
      wg_wait<0>();
    }
    if (nh == 1) return;
    {
      float acc0[28], acc1[28];
#pragma unroll
      for (int i = 0; i < 28; i++) acc0[i] = acc1[i] = 0.f;
      const uint64_t dS = make_desc(sb + OFF_WO, 1024, 1024, 1);
      const uint64_t dR = make_desc(sb + OFF_RING + mh * 8192, 1024, 1024, 1);
#pragma unroll 1
      for (int c = 0; c < 7; c++) {
        mbar_wait(BAR(B_WO + (c >= 3)), 0);
        mbar_wait(BAR(B_FULL + slot), par);
        const uint64_t dA = dR + slot * 2048, dB = dS + c * 1024;
        wg_fence();
#pragma unroll
        for (int ks = 0; ks < 4; ks++) {
          wgmma_ss_n56_ta0_tb1<1>(acc0, dA + ks * 2, dB + ks * 128);
          wgmma_ss_n56_ta0_tb1<1>(acc1, dA + 1024 + ks * 2, dB + 512 + ks * 128);
        }
        wg_commit();
        if (c < 4) {
          wg_wait<0>();
          if (lane == 0) mbar_arrive(BAR(B_EMPTY + slot), 2);
        }
        if (++slot == 3) { slot = 0; par ^= 1; }
      }
      wg_wait<0>();
      fence_regs(acc0); fence_regs(acc1);
      if (tid == 0) PROF_MARK(17);
      __nv_bfloat16* op = prm.out + (size_t)(pt * 128 + row0) * DM + hp * 56 + 2 * lq;
#pragma unroll
      for (int j = 0; j < 7; j++) {
        *(uint32_t*)(op + 8 * j) = pack_bf16(acc0[4 * j] + acc1[4 * j], acc0[4 * j + 1] + acc1[4 * j + 1]);
        *(uint32_t*)(op + 8 * DM + 8 * j) = pack_bf16(acc0[4 * j + 2] + acc1[4 * j + 2], acc0[4 * j + 3] + acc1[4 * j + 3]);
      }
      if (tid == 0) { PROF_MARK(18); PROF_CLK(31); }
    }
  }
}

typedef CUresult (*EncodeFn)(CUtensorMap*, CUtensorMapDataType, cuuint32_t, void*, const cuuint64_t*, const cuuint64_t*,
                             const cuuint32_t*, const cuuint32_t*, CUtensorMapInterleave, CUtensorMapSwizzle,
                             CUtensorMapL2promotion, CUtensorMapFloatOOBfill);

void make_map(EncodeFn enc, CUtensorMap* tm, const void* ptr, uint64_t cols, uint64_t rows, uint32_t box_cols, uint32_t box_rows) {
  cuuint64_t dims[2] = {cols, rows};
  cuuint64_t strides[1] = {cols * 2};
  cuuint32_t box[2] = {box_cols, box_rows};
  cuuint32_t es[2] = {1, 1};
  enc(tm, CU_TENSOR_MAP_DATA_TYPE_BFLOAT16, 2, const_cast<void*>(ptr), dims, strides, box, es, CU_TENSOR_MAP_INTERLEAVE_NONE,
      CU_TENSOR_MAP_SWIZZLE_128B, CU_TENSOR_MAP_L2_PROMOTION_L2_128B, CU_TENSOR_MAP_FLOAT_OOB_FILL_NONE);
}

}

extern "C" void kernel_launch(void* const* d_in, const int* in_sizes, int n_in, void* d_out, int out_size) {
  (void)in_sizes; (void)n_in; (void)out_size;
  static EncodeFn enc = nullptr;
  if (!enc) {
    void* fn = nullptr;
    cudaDriverEntryPointQueryResult qr;
    cudaGetDriverEntryPoint("cuTensorMapEncodeTiled", &fn, cudaEnableDefault, &qr);
    enc = (EncodeFn)fn;
    cudaFuncSetAttribute(fused_kernel, cudaFuncAttributeMaxDynamicSharedMemorySize, SMEM_BYTES);
  }
  CUtensorMap tm_x, tm_wqkv, tm_wq, tm_woa, tm_wob;
  make_map(enc, &tm_x, d_in[0], DM, S_LEN, 64, 128);
  make_map(enc, &tm_wqkv, d_in[1], 3 * DM, DM, 56, 64);
  make_map(enc, &tm_wq, d_in[5], DM, DM, 56, 64);
  make_map(enc, &tm_woa, d_in[3], DM, DM, 56, 64);
  make_map(enc, &tm_wob, d_in[8], DM, DM, 56, 64);
  Params prm;
  prm.w_phi = (const __nv_bfloat16*)d_in[2];
  prm.wk = (const __nv_bfloat16*)d_in[6];
  prm.wv = (const __nv_bfloat16*)d_in[7];
  prm.gate_w = (const __nv_bfloat16*)d_in[9];
  prm.out = (__nv_bfloat16*)d_out;
  fused_kernel<<<NCTA, NTHREADS, SMEM_BYTES>>>(tm_x, tm_wqkv, tm_wq, tm_woa, tm_wob, prm);
}
```

```cpp
#include <cuda_runtime.h>
#include <cuda_bf16.h>
#include <cuda.h>
#include <stdint.h>

namespace {

constexpr int S_LEN = 2048, DM = 448, DH = 28;
constexpr int NCTA = 128;
constexpr int NTHREADS = 640;
constexpr uint32_t POLY_PAT = 0x57;

#define QB_AT (4 + mh)

constexpr int OFF_X = 0;
constexpr int OFF_PHIK = 0;
constexpr int OFF_VA = 32768;
constexpr int OFF_PHIQ = 57344;
constexpr int OFF_KVR = 90112;
constexpr int OFF_QP = 98304;
constexpr int OFF_RAW = 81920;
constexpr int OFF_WO = 0;
constexpr int OFF_RING = 114688;
constexpr int OFF_WBD = 212992;
constexpr int OFF_SLC = 221184;
constexpr int OFF_QSQ = 228352;
constexpr int OFF_GATE = 229376;
constexpr int OFF_RED = 229888;
constexpr int OFF_BAR = 229952;
constexpr int SMEM_BYTES = 230400 + 1024;

constexpr int B_FULL = 0, B_EMPTY = 3, B_WO = 6  , B_KVR = 8, B_RAW = 9, B_X1FREE = 10, B_QSQ = 11, B_SLOW = 12,
              B_BUILD = 13, B_SIG = 14  , B_XL = 18  , B_N = 20;

constexpr int C_KV = 0, C_PART = 1, C_DONE = 3, C_OA = 4, C_OB = 20, C_N = 36;

__device__ __align__(1024) uint8_t g_kv_img[32 * 8192];
__device__ __align__(16) float g_ksq[512];
__device__ __align__(16) float g_vsq[512];
__device__ __align__(16) float g_gate[S_LEN];
__device__ __align__(1024) float g_kvacc[2][16 * 64 * 32];
__device__ unsigned g_epoch;
__device__ __align__(1024) uint8_t g_o_img[2 * 16 * 14 * 8192];
__device__ unsigned g_cnt[C_N * 32];

#define PROF4(i) do { } while (0)
#define PROF3(i) do { } while (0)
#define PROF2(i) do { } while (0)
#define PROF_CLK(i) do { } while (0)
#define PROF_MARK(i) do { } while (0)
__device__ __forceinline__ uint32_t smem_u32(const void* p) { return (uint32_t)__cvta_generic_to_shared(p); }
__device__ __forceinline__ void mbar_init(uint32_t a, int cnt) {
  asm volatile("mbarrier.init.shared::cta.b64 [%0], %1;" ::"r"(a), "r"(cnt) : "memory");
}
__device__ __forceinline__ void mbar_expect_tx(uint32_t a, uint32_t bytes) {
  asm volatile("mbarrier.arrive.expect_tx.shared::cta.b64 _, [%0], %1;" ::"r"(a), "r"(bytes) : "memory");
}
__device__ __forceinline__ void mbar_arrive(uint32_t a, uint32_t cnt) {
  asm volatile("mbarrier.arrive.shared::cta.b64 _, [%0], %1;" ::"r"(a), "r"(cnt) : "memory");
}
__device__ __forceinline__ void mbar_wait(uint32_t a, uint32_t parity) {
  asm volatile(
      "{\n.reg .pred p;\n.reg .u32 c;\nmov.u32 c, 0;\n"
      "W_%=:\nmbarrier.try_wait.parity.shared::cta.b64 p, [%0], %1;\n"
      "add.u32 c, c, 1;\nsetp.lt.and.u32 p, c, 0x40000, !p;\n@p bra W_%=;\n}"
      ::"r"(a), "r"(parity) : "memory");
}
__device__ __forceinline__ uint32_t mbar_test(uint32_t a, uint32_t parity) {
  uint32_t ok;
  asm volatile("{\n.reg .pred p;\nmbarrier.test_wait.parity.shared::cta.b64 p, [%1], %2;\nselp.u32 %0, 1, 0, p;\n}"
               : "=r"(ok) : "r"(a), "r"(parity) : "memory");
  return ok;
}
__device__ __forceinline__ bool elect_one() {
  uint32_t r;
  asm volatile("{\n.reg .pred p;\nelect.sync _|p, 0xffffffff;\nselp.u32 %0, 1, 0, p;\n}" : "=r"(r));
  return r != 0;
}
__device__ __forceinline__ void tma_2d(uint32_t dst, const CUtensorMap* tm, int c0, int c1, uint32_t bar) {
  asm volatile("cp.async.bulk.tensor.2d.shared::cluster.global.mbarrier::complete_tx::bytes [%0], [%1, {%3, %4}], [%2];"
               ::"r"(dst), "l"(tm), "r"(bar), "r"(c0), "r"(c1) : "memory");
}
__device__ __forceinline__ void bulk_g2s(uint32_t dst, const void* src, uint32_t bytes, uint32_t bar) {
  asm volatile("cp.async.bulk.shared::cluster.global.mbarrier::complete_tx::bytes [%0], [%1], %2, [%3];"
               ::"r"(dst), "l"(src), "r"(bytes), "r"(bar) : "memory");
}
__device__ __forceinline__ void fence_async_smem() { asm volatile("fence.proxy.async.shared::cta;" ::: "memory"); }
__device__ __forceinline__ void fence_async_all() { asm volatile("fence.proxy.async.global;" ::: "memory"); }

__device__ __forceinline__ void bar_sync(int id, int n) { asm volatile("bar.sync %0, %1;" ::"r"(id), "r"(n) : "memory"); }
__device__ __forceinline__ void cnt_arrive(int idx) {
  asm volatile("red.release.gpu.global.add.u32 [%0], 1;" ::"l"(&g_cnt[idx * 32]) : "memory");
}
__device__ __forceinline__ void cnt_wait(int idx, unsigned target) {
  unsigned v, n = 0;
#pragma unroll 1
  while (true) {
    asm volatile("ld.acquire.gpu.global.u32 %0, [%1];" : "=r"(v) : "l"(&g_cnt[idx * 32]) : "memory");
    if (v >= target || ++n >= (1u << 18)) break;
    __nanosleep(32);
  }
}
__device__ __forceinline__ void wg_fence() { asm volatile("wgmma.fence.sync.aligned;" ::: "memory"); }
__device__ __forceinline__ void wg_commit() { asm volatile("wgmma.commit_group.sync.aligned;" ::: "memory"); }
template <int N> __device__ __forceinline__ void wg_wait() { asm volatile("wgmma.wait_group.sync.aligned %0;" ::"n"(N) : "memory"); }
template <int N> __device__ __forceinline__ void fence_regs(float (&d)[N]) {
#pragma unroll
  for (int i = 0; i < N; i++) asm volatile("" : "+f"(d[i])::"memory");
}
__device__ __forceinline__ uint64_t make_desc(uint32_t saddr, uint32_t lbo, uint32_t sbo, uint32_t swz) {
  return (uint64_t)((saddr & 0x3FFFF) >> 4) | ((uint64_t)(lbo >> 4) << 16) | ((uint64_t)(sbo >> 4) << 32) | ((uint64_t)swz << 62);
}
__device__ __forceinline__ float ex2f(float x) { float y; asm("ex2.approx.ftz.f32 %0, %1;" : "=f"(y) : "f"(x)); return y; }
__device__ __forceinline__ float rcpf(float x) { float y; asm("rcp.approx.ftz.f32 %0, %1;" : "=f"(y) : "f"(x)); return y; }
__device__ __forceinline__ uint32_t pack_bf16(float lo, float hi) {
  uint32_t r; asm("cvt.rn.bf16x2.f32 %0, %1, %2;" : "=r"(r) : "f"(hi), "f"(lo)); return r;
}
__device__ __forceinline__ uint32_t lop_and_or(uint32_t a, uint32_t m, uint32_t c) {
  uint32_t r; asm("lop3.b32 %0, %1, %2, %3, 0xEA;" : "=r"(r) : "r"(a), "r"(m), "r"(c)); return r;
}
__device__ __forceinline__ void sts32(uint32_t a, uint32_t v) { asm volatile("st.shared.b32 [%0], %1;" ::"r"(a), "r"(v) : "memory"); }
__device__ __forceinline__ void st_shared_nv(uint32_t a, uint32_t v) { asm volatile("st.shared.b32 [%0], %1;" ::"r"(a), "r"(v)); }
__device__ __forceinline__ void sts64(uint32_t a, uint32_t v0, uint32_t v1) { asm volatile("st.shared.v2.b32 [%0], {%1, %2};" ::"r"(a), "r"(v0), "r"(v1) : "memory"); }
__device__ __forceinline__ void sts128(uint32_t a, uint4 v) {
  asm volatile("st.shared.v4.b32 [%0], {%1, %2, %3, %4};" ::"r"(a), "r"(v.x), "r"(v.y), "r"(v.z), "r"(v.w) : "memory");
}
__device__ __forceinline__ float4 ldcg_f4(const float* p) {
  float4 v; asm volatile("ld.global.cg.v4.f32 {%0, %1, %2, %3}, [%4];" : "=f"(v.x), "=f"(v.y), "=f"(v.z), "=f"(v.w) : "l"(p) : "memory"); return v;
}
__device__ __forceinline__ void ldsm4(uint32_t* r, uint32_t a) {
  asm volatile("ldmatrix.sync.aligned.m8n8.x4.shared.b16 {%0, %1, %2, %3}, [%4];"
               : "=r"(r[0]), "=r"(r[1]), "=r"(r[2]), "=r"(r[3]) : "r"(a) : "memory");
}
__device__ __forceinline__ float quad_sum(float v) { v += __shfl_xor_sync(~0u, v, 1); v += __shfl_xor_sync(~0u, v, 2); return v; }
__device__ __forceinline__ float quad_max(float v) { v = fmaxf(v, __shfl_xor_sync(~0u, v, 1)); v = fmaxf(v, __shfl_xor_sync(~0u, v, 2)); return v; }

template <int SD> __device__ __forceinline__ void wgmma_ss_n56_ta0_tb1(float (&d)[28], uint64_t da, uint64_t db) {
  if (SD) asm volatile("wgmma.mma_async.sync.aligned.m64n56k16.f32.bf16.bf16 {%0, %1, %2, %3, %4, %5, %6, %7, %8, %9, %10, %11, %12, %13, %14, %15, %16, %17, %18, %19, %20, %21, %22, %23, %24, %25, %26, %27}, %28, %29, 1, 1, 1, 0, 1;\n"
    : "+f"(d[0]), "+f"(d[1]), "+f"(d[2]), "+f"(d[3]), "+f"(d[4]), "+f"(d[5]), "+f"(d[6]), "+f"(d[7]), "+f"(d[8]), "+f"(d[9]), "+f"(d[10]), "+f"(d[11]), "+f"(d[12]), "+f"(d[13]), "+f"(d[14]), "+f"(d[15]), "+f"(d[16]), "+f"(d[17]), "+f"(d[18]), "+f"(d[19]), "+f"(d[20]), "+f"(d[21]), "+f"(d[22]), "+f"(d[23]), "+f"(d[24]), "+f"(d[25]), "+f"(d[26]), "+f"(d[27])
    : "l"(da), "l"(db));
  else asm volatile("wgmma.mma_async.sync.aligned.m64n56k16.f32.bf16.bf16 {%0, %1, %2, %3, %4, %5, %6, %7, %8, %9, %10, %11, %12, %13, %14, %15, %16, %17, %18, %19, %20, %21, %22, %23, %24, %25, %26, %27}, %28, %29, 0, 1, 1, 0, 1;\n"
    : "=f"(d[0]), "=f"(d[1]), "=f"(d[2]), "=f"(d[3]), "=f"(d[4]), "=f"(d[5]), "=f"(d[6]), "=f"(d[7]), "=f"(d[8]), "=f"(d[9]), "=f"(d[10]), "=f"(d[11]), "=f"(d[12]), "=f"(d[13]), "=f"(d[14]), "=f"(d[15]), "=f"(d[16]), "=f"(d[17]), "=f"(d[18]), "=f"(d[19]), "=f"(d[20]), "=f"(d[21]), "=f"(d[22]), "=f"(d[23]), "=f"(d[24]), "=f"(d[25]), "=f"(d[26]), "=f"(d[27])
    : "l"(da), "l"(db));
}
template <int SD> __device__ __forceinline__ void wgmma_ss_n8_ta0_tb1(float (&d)[4], uint64_t da, uint64_t db) {
  if (SD) asm volatile("wgmma.mma_async.sync.aligned.m64n8k16.f32.bf16.bf16 {%0, %1, %2, %3}, %4, %5, 1, 1, 1, 0, 1;\n"
    : "+f"(d[0]), "+f"(d[1]), "+f"(d[2]), "+f"(d[3])
    : "l"(da), "l"(db));
  else asm volatile("wgmma.mma_async.sync.aligned.m64n8k16.f32.bf16.bf16 {%0, %1, %2, %3}, %4, %5, 0, 1, 1, 0, 1;\n"
    : "=f"(d[0]), "=f"(d[1]), "=f"(d[2]), "=f"(d[3])
    : "l"(da), "l"(db));
}
template <int SD> __device__ __forceinline__ void wgmma_rs_n64_tb1(float (&d)[32], uint32_t a0, uint32_t a1, uint32_t a2, uint32_t a3, uint64_t db) {
  if (SD) asm volatile("wgmma.mma_async.sync.aligned.m64n64k16.f32.bf16.bf16 {%0, %1, %2, %3, %4, %5, %6, %7, %8, %9, %10, %11, %12, %13, %14, %15, %16, %17, %18, %19, %20, %21, %22, %23, %24, %25, %26, %27, %28, %29, %30, %31}, {%32, %33, %34, %35}, %36, 1, 1, 1, 1;\n"
    : "+f"(d[0]), "+f"(d[1]), "+f"(d[2]), "+f"(d[3]), "+f"(d[4]), "+f"(d[5]), "+f"(d[6]), "+f"(d[7]), "+f"(d[8]), "+f"(d[9]), "+f"(d[10]), "+f"(d[11]), "+f"(d[12]), "+f"(d[13]), "+f"(d[14]), "+f"(d[15]), "+f"(d[16]), "+f"(d[17]), "+f"(d[18]), "+f"(d[19]), "+f"(d[20]), "+f"(d[21]), "+f"(d[22]), "+f"(d[23]), "+f"(d[24]), "+f"(d[25]), "+f"(d[26]), "+f"(d[27]), "+f"(d[28]), "+f"(d[29]), "+f"(d[30]), "+f"(d[31])
    : "r"(a0), "r"(a1), "r"(a2), "r"(a3), "l"(db));
  else asm volatile("wgmma.mma_async.sync.aligned.m64n64k16.f32.bf16.bf16 {%0, %1, %2, %3, %4, %5, %6, %7, %8, %9, %10, %11, %12, %13, %14, %15, %16, %17, %18, %19, %20, %21, %22, %23, %24, %25, %26, %27, %28, %29, %30, %31}, {%32, %33, %34, %35}, %36, 0, 1, 1, 1;\n"
    : "=f"(d[0]), "=f"(d[1]), "=f"(d[2]), "=f"(d[3]), "=f"(d[4]), "=f"(d[5]), "=f"(d[6]), "=f"(d[7]), "=f"(d[8]), "=f"(d[9]), "=f"(d[10]), "=f"(d[11]), "=f"(d[12]), "=f"(d[13]), "=f"(d[14]), "=f"(d[15]), "=f"(d[16]), "=f"(d[17]), "=f"(d[18]), "=f"(d[19]), "=f"(d[20]), "=f"(d[21]), "=f"(d[22]), "=f"(d[23]), "=f"(d[24]), "=f"(d[25]), "=f"(d[26]), "=f"(d[27]), "=f"(d[28]), "=f"(d[29]), "=f"(d[30]), "=f"(d[31])
    : "r"(a0), "r"(a1), "r"(a2), "r"(a3), "l"(db));
}
template <int SD> __device__ __forceinline__ void wgmma_ss_n32_ta1_tb1(float (&d)[16], uint64_t da, uint64_t db) {
  if (SD) asm volatile("wgmma.mma_async.sync.aligned.m64n32k16.f32.bf16.bf16 {%0, %1, %2, %3, %4, %5, %6, %7, %8, %9, %10, %11, %12, %13, %14, %15}, %16, %17, 1, 1, 1, 1, 1;\n"
    : "+f"(d[0]), "+f"(d[1]), "+f"(d[2]), "+f"(d[3]), "+f"(d[4]), "+f"(d[5]), "+f"(d[6]), "+f"(d[7]), "+f"(d[8]), "+f"(d[9]), "+f"(d[10]), "+f"(d[11]), "+f"(d[12]), "+f"(d[13]), "+f"(d[14]), "+f"(d[15])
    : "l"(da), "l"(db));
  else asm volatile("wgmma.mma_async.sync.aligned.m64n32k16.f32.bf16.bf16 {%0, %1, %2, %3, %4, %5, %6, %7, %8, %9, %10, %11, %12, %13, %14, %15}, %16, %17, 0, 1, 1, 1, 1;\n"
    : "=f"(d[0]), "=f"(d[1]), "=f"(d[2]), "=f"(d[3]), "=f"(d[4]), "=f"(d[5]), "=f"(d[6]), "=f"(d[7]), "=f"(d[8]), "=f"(d[9]), "=f"(d[10]), "=f"(d[11]), "=f"(d[12]), "=f"(d[13]), "=f"(d[14]), "=f"(d[15])
    : "l"(da), "l"(db));
}
template <int SD> __device__ __forceinline__ void wgmma_ss_n32_ta0_tb1(float (&d)[16], uint64_t da, uint64_t db) {
  if (SD) asm volatile("wgmma.mma_async.sync.aligned.m64n32k16.f32.bf16.bf16 {%0, %1, %2, %3, %4, %5, %6, %7, %8, %9, %10, %11, %12, %13, %14, %15}, %16, %17, 1, 1, 1, 0, 1;\n"
    : "+f"(d[0]), "+f"(d[1]), "+f"(d[2]), "+f"(d[3]), "+f"(d[4]), "+f"(d[5]), "+f"(d[6]), "+f"(d[7]), "+f"(d[8]), "+f"(d[9]), "+f"(d[10]), "+f"(d[11]), "+f"(d[12]), "+f"(d[13]), "+f"(d[14]), "+f"(d[15])
    : "l"(da), "l"(db));
  else asm volatile("wgmma.mma_async.sync.aligned.m64n32k16.f32.bf16.bf16 {%0, %1, %2, %3, %4, %5, %6, %7, %8, %9, %10, %11, %12, %13, %14, %15}, %16, %17, 0, 1, 1, 0, 1;\n"
    : "=f"(d[0]), "=f"(d[1]), "=f"(d[2]), "=f"(d[3]), "=f"(d[4]), "=f"(d[5]), "=f"(d[6]), "=f"(d[7]), "=f"(d[8]), "=f"(d[9]), "=f"(d[10]), "=f"(d[11]), "=f"(d[12]), "=f"(d[13]), "=f"(d[14]), "=f"(d[15])
    : "l"(da), "l"(db));
}
template <int SD> __device__ __forceinline__ void wgmma_rs_n64_tb0(float (&d)[32], uint32_t a0, uint32_t a1, uint32_t a2, uint32_t a3, uint64_t db) {
  if (SD) asm volatile("wgmma.mma_async.sync.aligned.m64n64k16.f32.bf16.bf16 {%0, %1, %2, %3, %4, %5, %6, %7, %8, %9, %10, %11, %12, %13, %14, %15, %16, %17, %18, %19, %20, %21, %22, %23, %24, %25, %26, %27, %28, %29, %30, %31}, {%32, %33, %34, %35}, %36, 1, 1, 1, 0;\n"
    : "+f"(d[0]), "+f"(d[1]), "+f"(d[2]), "+f"(d[3]), "+f"(d[4]), "+f"(d[5]), "+f"(d[6]), "+f"(d[7]), "+f"(d[8]), "+f"(d[9]), "+f"(d[10]), "+f"(d[11]), "+f"(d[12]), "+f"(d[13]), "+f"(d[14]), "+f"(d[15]), "+f"(d[16]), "+f"(d[17]), "+f"(d[18]), "+f"(d[19]), "+f"(d[20]), "+f"(d[21]), "+f"(d[22]), "+f"(d[23]), "+f"(d[24]), "+f"(d[25]), "+f"(d[26]), "+f"(d[27]), "+f"(d[28]), "+f"(d[29]), "+f"(d[30]), "+f"(d[31])
    : "r"(a0), "r"(a1), "r"(a2), "r"(a3), "l"(db));
  else asm volatile("wgmma.mma_async.sync.aligned.m64n64k16.f32.bf16.bf16 {%0, %1, %2, %3, %4, %5, %6, %7, %8, %9, %10, %11, %12, %13, %14, %15, %16, %17, %18, %19, %20, %21, %22, %23, %24, %25, %26, %27, %28, %29, %30, %31}, {%32, %33, %34, %35}, %36, 0, 1, 1, 0;\n"
    : "=f"(d[0]), "=f"(d[1]), "=f"(d[2]), "=f"(d[3]), "=f"(d[4]), "=f"(d[5]), "=f"(d[6]), "=f"(d[7]), "=f"(d[8]), "=f"(d[9]), "=f"(d[10]), "=f"(d[11]), "=f"(d[12]), "=f"(d[13]), "=f"(d[14]), "=f"(d[15]), "=f"(d[16]), "=f"(d[17]), "=f"(d[18]), "=f"(d[19]), "=f"(d[20]), "=f"(d[21]), "=f"(d[22]), "=f"(d[23]), "=f"(d[24]), "=f"(d[25]), "=f"(d[26]), "=f"(d[27]), "=f"(d[28]), "=f"(d[29]), "=f"(d[30]), "=f"(d[31])
    : "r"(a0), "r"(a1), "r"(a2), "r"(a3), "l"(db));
}
template <int SD> __device__ __forceinline__ void wgmma_rs_n32_tb1(float (&d)[16], uint32_t a0, uint32_t a1, uint32_t a2, uint32_t a3, uint64_t db) {
  if (SD) asm volatile("wgmma.mma_async.sync.aligned.m64n32k16.f32.bf16.bf16 {%0, %1, %2, %3, %4, %5, %6, %7, %8, %9, %10, %11, %12, %13, %14, %15}, {%16, %17, %18, %19}, %20, 1, 1, 1, 1;\n"
    : "+f"(d[0]), "+f"(d[1]), "+f"(d[2]), "+f"(d[3]), "+f"(d[4]), "+f"(d[5]), "+f"(d[6]), "+f"(d[7]), "+f"(d[8]), "+f"(d[9]), "+f"(d[10]), "+f"(d[11]), "+f"(d[12]), "+f"(d[13]), "+f"(d[14]), "+f"(d[15])
    : "r"(a0), "r"(a1), "r"(a2), "r"(a3), "l"(db));
  else asm volatile("wgmma.mma_async.sync.aligned.m64n32k16.f32.bf16.bf16 {%0, %1, %2, %3, %4, %5, %6, %7, %8, %9, %10, %11, %12, %13, %14, %15}, {%16, %17, %18, %19}, %20, 0, 1, 1, 1;\n"
    : "=f"(d[0]), "=f"(d[1]), "=f"(d[2]), "=f"(d[3]), "=f"(d[4]), "=f"(d[5]), "=f"(d[6]), "=f"(d[7]), "=f"(d[8]), "=f"(d[9]), "=f"(d[10]), "=f"(d[11]), "=f"(d[12]), "=f"(d[13]), "=f"(d[14]), "=f"(d[15])
    : "r"(a0), "r"(a1), "r"(a2), "r"(a3), "l"(db));
}

__device__ __forceinline__ uint32_t sw64_off(int row, int d) { return row * 64 + ((((d >> 3) ^ (row >> 1)) & 3) << 4) + (d & 7) * 2; }

__device__ __forceinline__ uint32_t exp2_pair_fma(float t0, float t1, uint32_t c_half, uint32_t c_3) {
  uint32_t y0, y;
  asm("prmt.b32 %0, %1, %2, 0x6521;" : "=r"(y0) : "r"(__float_as_uint(t0)), "r"(__float_as_uint(t1)));
  uint32_t h = lop_and_or(y0, 0x007F007Fu, c_half);
  uint32_t e = lop_and_or(y0, 0xFF80FF80u, c_3);
  asm("fma.rn.bf16x2 %0, %1, %2, %3;" : "=r"(y) : "r"(y0), "r"(h), "r"(e));
  return y;
}

__device__ __forceinline__ void feature_map(float (&p)[32], uint32_t rb, int lq) {
  const float L2E = 1.4426950408889634f;
  const bool tail_ok = lq < 2;
  float mx[4], mn[4], b[32], sa[4], sn[4];
#pragma unroll
  for (int g = 0; g < 4; g++) {
    const int o = 16 * (g >> 1) + 2 * (g & 1);
    if (!tail_ok) { p[o + 12] = p[o]; p[o + 13] = p[o]; }
    mx[g] = fmaxf(fmaxf(fmaxf(p[o], p[o + 1]), fmaxf(p[o + 4], p[o + 5])), fmaxf(fmaxf(p[o + 8], p[o + 9]), fmaxf(p[o + 12], p[o + 13])));
    mn[g] = fminf(fminf(fminf(p[o], p[o + 1]), fminf(p[o + 4], p[o + 5])), fminf(fminf(p[o + 8], p[o + 9]), fminf(p[o + 12], p[o + 13])));
  }
#pragma unroll
  for (int o = 1; o <= 2; o <<= 1)
#pragma unroll
    for (int g = 0; g < 4; g++) { mx[g] = fmaxf(mx[g], __shfl_xor_sync(~0u, mx[g], o)); mn[g] = fminf(mn[g], __shfl_xor_sync(~0u, mn[g], o)); }
#pragma unroll
  for (int g = 0; g < 4; g++) {
    const int o = 16 * (g >> 1) + 2 * (g & 1);
    const float cx = -mx[g] * L2E, cn = mn[g] * L2E;
#pragma unroll
    for (int i = 0; i < 8; i++) {
      const int k = o + 4 * (i >> 1) + (i & 1);
      b[k] = ex2f(fmaf(p[k], -L2E, cn));
      p[k] = ex2f(fmaf(p[k], L2E, cx));
    }
    if (!tail_ok) { p[o + 12] = p[o + 13] = b[o + 12] = b[o + 13] = 0.f; }
    sa[g] = ((p[o] + p[o + 1]) + (p[o + 4] + p[o + 5])) + ((p[o + 8] + p[o + 9]) + (p[o + 12] + p[o + 13]));
    sn[g] = ((b[o] + b[o + 1]) + (b[o + 4] + b[o + 5])) + ((b[o + 8] + b[o + 9]) + (b[o + 12] + b[o + 13]));
    sa[g] += __shfl_xor_sync(~0u, sa[g], 1); sn[g] += __shfl_xor_sync(~0u, sn[g], 1);
    sa[g] += __shfl_xor_sync(~0u, sa[g], 2); sn[g] += __shfl_xor_sync(~0u, sn[g], 2);
  }
#pragma unroll
  for (int g = 0; g < 4; g++) {
    const int o = 16 * (g >> 1) + 2 * (g & 1);
    const float ra = rcpf(sa[g]), rn = rcpf(sn[g]);
    const uint32_t off = (g >> 1) * 16384 + (g & 1) * 1024;
#pragma unroll
    for (int jj = 0; jj < 4; jj++) {
      st_shared_nv((rb ^ (jj << 4)) + off, pack_bf16(p[o + 4 * jj] * ra, p[o + 4 * jj + 1] * ra));
      st_shared_nv((rb ^ ((4 + jj) << 4)) + off, pack_bf16(b[o + 4 * jj] * rn, b[o + 4 * jj + 1] * rn));
    }
  }
}

__device__ __forceinline__ void store_heads(uint32_t base, const uint32_t (&a)[14], uint32_t pad0, uint32_t pad1, int row0, int lq) {
  const uint32_t rb = base + row0 * 64 + (((row0 >> 1) & 3) << 4);
  const uint32_t b0 = rb + lq * 4;
  const uint32_t b1 = (rb + 8192 + ((lq * 4 + 8) & 15)) ^ ((lq >> 1) << 4);
#pragma unroll
  for (int j = 0; j < 7; j++) {
    uint32_t ad;
    if (j < 3) ad = b0 ^ (j << 4);
    else if (j == 3) ad = (lq < 2) ? (b0 ^ 48u) : (b1 ^ 16u);
    else ad = (lq < 2) ? (b1 ^ ((j - 4) << 4)) : ((b1 ^ 16u) ^ ((j - 3) << 4));
    sts32(ad, a[2 * j]);
    sts32(ad + 512, a[2 * j + 1]);
  }
  sts64((rb ^ 48u) + 8 + (lq & 1) * 8192 + (lq >> 1) * 512, pad0, pad1);
}

struct Params {
  const __nv_bfloat16* w_phi;
  const __nv_bfloat16* wk;
  const __nv_bfloat16* wv;
  const __nv_bfloat16* gate_w;
  __nv_bfloat16* out;
};

__global__ void __launch_bounds__(NTHREADS, 1)
fused_kernel(const __grid_constant__ CUtensorMap tm_x, const __grid_constant__ CUtensorMap tm_wqkv,
             const __grid_constant__ CUtensorMap tm_wq, const __grid_constant__ CUtensorMap tm_woa,
             const __grid_constant__ CUtensorMap tm_wob, const Params prm) {
  extern __shared__ uint8_t smem_raw[];
  uint32_t sb = (smem_u32(smem_raw) + 1023u) & ~1023u;
  uint8_t* sgen = smem_raw + (sb - smem_u32(smem_raw));
  asm volatile("mov.u32 %0, %0;" : "+r"(sb));
  const int tid = threadIdx.x, lane = tid & 31;
  const int warp = __shfl_sync(~0u, tid >> 5, 0), wg = warp >> 2;
  const int pt = blockIdx.x >> 3, hp = blockIdx.x & 7;
  const uint32_t bars = sb + OFF_BAR;
  auto BAR = [&](int i) { return bars + 8u * i; };
  const unsigned epoch = g_epoch & 1;

  if (tid == 0) { PROF_MARK(0); PROF_CLK(30); PROF2(15); }
  auto load_proj = [&](int c, int g) {
    mbar_expect_tx(BAR(B_FULL + g), (c < 3 ? 16384 : 0) + 4 * 7168);
    if (c < 3) tma_2d(sb + OFF_X + c * 16384, &tm_x, c * 64, pt * 128, BAR(B_FULL + g));
    tma_2d(sb + OFF_RING + g * 32768, &tm_wq, hp * 56, c * 64, BAR(B_FULL + g));
#pragma unroll 1
    for (int j = 0; j < 3; j++) tma_2d(sb + OFF_RING + g * 32768 + 8192 + j * 8192, &tm_wqkv, j * DM + hp * 56, c * 64, BAR(B_FULL + g));
  };
  if (warp == 16) {
    if (elect_one()) {
      mbar_init(BAR(B_FULL), 1);
      fence_async_smem();
      load_proj(0, 0);
      mbar_init(BAR(B_RAW), 1); mbar_init(BAR(B_FULL + 1), 1); mbar_init(BAR(B_FULL + 2), 1);
      fence_async_smem();
    }
    __syncwarp();
    asm volatile("bar.arrive 0, %0;" ::"n"(NTHREADS) : "memory");
  } else {
    if (elect_one()) {
      const int i = warp + 3 - (warp > 16);
      if (i < B_N && i != B_RAW) {
        int cnt = i < B_WO || (i > B_SIG && i < B_XL) || i == B_X1FREE ? 16 : 1;
        if (i == B_BUILD) cnt = 16;
        if (i == B_SIG || i == B_SIG + 1 || i == B_QSQ) cnt = 8;
        if (i == B_KVR) cnt = 2;
        mbar_init(BAR(i), cnt);
        fence_async_smem();
      }
    }
    bar_sync(0, NTHREADS);
  }
  if (tid == 0) PROF2(14);

  if (wg == 4) {
    asm volatile("setmaxnreg.dec.sync.aligned.u32 32;");
    if (warp == 16) {
      if (elect_one()) {
        mbar_expect_tx(BAR(B_RAW), 25088 + 3136 + 896);
        bulk_g2s(sb + OFF_RAW, hp < 4 ? prm.wk : prm.wv, 25088, BAR(B_RAW));
        bulk_g2s(sb + OFF_RAW + 25088, prm.w_phi + 2 * hp * DH * DH, 3136, BAR(B_RAW));
        bulk_g2s(sb + OFF_RAW + 28224, prm.gate_w, 896, BAR(B_RAW));
        load_proj(1, 1);
        load_proj(2, 2);
      }
      __syncwarp();
      bar_sync(3, 64);
      if (elect_one()) {
        int g = 0, nkv = 8;
        uint32_t par = 0;
#pragma unroll 1
        for (int c = 3; c < 7; c++) {
          if (c == 5) mbar_wait(BAR(B_BUILD), 0);
          if (c & 1) mbar_expect_tx(BAR(B_XL + (c > 4)), 32768);
          tma_2d(sb + OFF_X + c * 16384, &tm_x, c * 64, pt * 128, BAR(B_XL + (c > 4)));
        }
#pragma unroll 1
        for (int n = 3; n < 14 + nkv; n++) {
          if (n == 7) { PROF_MARK(20); cnt_wait(C_KV, NCTA); PROF_MARK(21); fence_async_all(); }
          if (n == 15) {
            mbar_wait(BAR(B_SLOW), 0);
            if (*(volatile int*)(sgen + OFF_RED)) nkv = 26;
          }
          const int j = n - 7 - nkv;
          if (j == 0 || j == 3) {
            PROF3(j ? 11 : 8);
            cnt_wait((j ? C_OB : C_OA) + pt, 8);
            PROF3(j ? 12 : 9);
            PROF_MARK(26);
            fence_async_all();
          }
          mbar_wait(BAR(B_EMPTY + g), par);
          if (n < 7) { PROF2(20 + n); load_proj(n, g); }
          else {
            mbar_expect_tx(BAR(B_FULL + g), 32768);
            bulk_g2s(sb + OFF_RING + g * 32768, j < 0 ? g_kv_img + ((n - 7) & 7) * 32768 : g_o_img + (size_t)(pt * 7 + j) * 32768, 32768,
                     BAR(B_FULL + g));
          }
          if (++g == 3) { g = 0; par ^= 1; }
        }
        if (atomicAdd(&g_cnt[C_DONE * 32], 1u) == NCTA - 1) {
#pragma unroll 1
          for (int i = 0; i < C_N; i++) g_cnt[i * 32] = 0;
          g_epoch = epoch ^ 1;
        }
      }
    } else {
      if (warp == 18) {
        if (elect_one()) {
#pragma unroll 1
          for (int i = 0; i < 4; i++) {
            mbar_wait(BAR(B_SIG + i), 0);
            PROF3(2 * i);
            if (i == 1) {
#pragma unroll 1
              for (int j = 0; j < 4; j++)
                asm volatile("cp.reduce.async.bulk.global.shared::cta.bulk_group.add.f32 [%0], [%1], 8192;"
                             ::"l"(g_kvacc[epoch] + hp * 4096 + (j >> 1) * 2048), "r"(sb + OFF_PHIK + j * 8192) : "memory");
              asm volatile("cp.async.bulk.commit_group;\ncp.async.bulk.wait_group 0;" ::: "memory");
            }
            cnt_arrive(i == 0 ? C_KV : i == 1 ? C_PART : (i == 2 ? C_OA : C_OB) + pt);
            PROF3(2 * i + 1);
            if (i == 1 || i == 2) {
              if (i == 2) mbar_wait(BAR(B_X1FREE), 0);
              mbar_expect_tx(BAR(B_WO + i - 1), 7 * 7168);
#pragma unroll 1
              for (int c = 0; c < 7; c++)
                tma_2d(sb + OFF_WO + (i - 1) * 57344 + c * 8192, i == 1 ? &tm_woa : &tm_wob, hp * 56, c * 64, BAR(B_WO + i - 1));
            }
          }
        }
      } else if (warp == 19) {
        if (lane == 0) {
          mbar_wait(BAR(B_SIG + 0), 0);
          cnt_wait(C_KV, NCTA);
        }
        __syncwarp();
        float ksq = 0.f, vsq = 0.f;
#pragma unroll
        for (int sl = 0; sl < 4; sl++) {
          float4 a = ldcg_f4(g_ksq + sl * 128 + lane * 4), b = ldcg_f4(g_vsq + sl * 128 + lane * 4);
          float m = fmaxf(fmaxf(a.x, a.y), fmaxf(a.z, a.w));
          m = __uint_as_float(__reduce_max_sync(~0u, __float_as_uint(m)));
          ksq += m;
          vsq = fmaxf(vsq, fmaxf(fmaxf(b.x, b.y), fmaxf(b.z, b.w)));
        }
        mbar_wait(BAR(B_QSQ), 0);
        const float4 qa4 = ((const float4*)(sgen + OFF_QSQ))[lane], qb4 = ((const float4*)(sgen + OFF_QSQ))[32 + lane];
        const float qmax = fmaxf(fmaxf(fmaxf(qa4.x, qa4.y), fmaxf(qa4.z, qa4.w)), fmaxf(fmaxf(qb4.x, qb4.y), fmaxf(qb4.z, qb4.w)));
        const bool slow = __any_sync(~0u, !(qmax * ksq <= 98.f * 98.f) || !(vsq <= 2.0e8f));
        if (lane == 0) {
          *(volatile int*)(sgen + OFF_RED) = slow;
          mbar_arrive(BAR(B_SLOW), 1);
        }
      } else {
        float4* z = (float4*)(g_kvacc[epoch ^ 1] + blockIdx.x * 256) + lane;
        z[0] = make_float4(0.f, 0.f, 0.f, 0.f);
        z[32] = make_float4(0.f, 0.f, 0.f, 0.f);
        bar_sync(3, 64);
        if (lane == 0) {
          mbar_wait(BAR(B_SIG + 0), 0);
          cnt_wait(C_KV, NCTA);
        }
        __syncwarp();
        ((float4*)(sgen + OFF_GATE))[lane] = ldcg_f4(g_gate + pt * 128 + lane * 4);
      }
      if (warp != 18) {
        if (lane == 0) {
          mbar_wait(BAR(B_SIG + 1), 0);
          cnt_wait(C_PART, NCTA);
          PROF_MARK(23);
        }
        __syncwarp();
        const int e = warp == 19;
        const float* src = g_kvacc[epoch] + hp * 4096 + e * 2048 + (lane ^ ((lane >> 2) & 3)) * 8;
#pragma unroll 1
        for (int i = 0; i < 8; i += 2) {
          const float4 a = ldcg_f4(src + i * 256), b = ldcg_f4(src + i * 256 + 4), c = ldcg_f4(src + i * 256 + 256), d = ldcg_f4(src + i * 256 + 260);
          const uint32_t ad = sb + OFF_KVR + e * 4096 + sw64_off(i * 8 + (lane >> 2), (lane & 3) * 8);
          sts128(ad, make_uint4(pack_bf16(a.x, a.y), pack_bf16(a.z, a.w), pack_bf16(b.x, b.y), pack_bf16(b.z, b.w)));
          sts128(ad + 512, make_uint4(pack_bf16(c.x, c.y), pack_bf16(c.z, c.w), pack_bf16(d.x, d.y), pack_bf16(d.z, d.w)));
        }
        fence_async_smem();
        __syncwarp();
        if (lane == 0) mbar_arrive(BAR(B_KVR), 1);
        PROF_MARK(24);
      }
    }
  } else {
    asm volatile("setmaxnreg.inc.sync.aligned.u32 112;");
    const int mh = wg & 1, nh = wg >> 1, wq = warp & 3;
    const int lq = lane & 3;
    const int rowl = wq * 16 + (lane >> 2);
    const int row0 = mh * 64 + rowl;
    int slot = 0, prev = 0;
    uint32_t par = 0;
    {
      float acc0[28], acc1[28], accs[4];
      const uint64_t dR = make_desc(sb + OFF_RING + nh * 16384, 1024, 1024, 1);
      const uint64_t dX = make_desc(sb + OFF_X + mh * 8192, 1024, 1024, 1);
#pragma unroll
      for (int i = 0; i < 28; i++) acc0[i] = acc1[i] = 0.f;
#pragma unroll
      for (int i = 0; i < 4; i++) accs[i] = 0.f;
      const uint64_t dSlc = make_desc(sb + OFF_SLC, 128, 128, 0);
#pragma unroll 1
      for (int c = 0; c < 7; c++) {
        if (c == 3 || c == 5) mbar_wait(BAR(B_XL + (c > 4)), 0);
        mbar_wait(BAR(B_FULL + slot), par);
        if (c == 0 && tid == 0) PROF2(17);
        const uint64_t dA = dX + c * 1024, dB = dR + slot * 2048;
        wg_fence();
#pragma unroll
        for (int ks = 0; ks < 4; ks++) {
          wgmma_ss_n56_ta0_tb1<1>(acc0, dA + ks * 2, dB + ks * 128);
          wgmma_ss_n56_ta0_tb1<1>(acc1, dA + ks * 2, dB + 512 + ks * 128);
        }
        if (nh == 1 && c > 0) {
#pragma unroll
          for (int ks = 0; ks < 4; ks++) wgmma_ss_n8_ta0_tb1<1>(accs, dA - 1024 + ks * 2, dSlc + (c - 1) * 64 + ks * 16);
        }
        wg_commit();
        if ((tid & 127) == 0) PROF4(wg * 32 + c * 3);
        if (c == 0) {
          mbar_wait(BAR(B_RAW), 0);
          const int k = tid >> 3, cn = tid & 7;
          const bool data = k < 56 && (cn >> 2) == (k >= DH);
          const uint2* wsrc = (const uint2*)(sgen + OFF_RAW + 25088 + k * 56 + (cn & 3) * 16);
          uint2 w0 = make_uint2(0u, 0u), w1 = w0;
          if (data) w0 = wsrc[0];
          if (data && (cn & 3) != 3) w1 = wsrc[1];
          sts128(sb + OFF_WBD + k * 128 + ((cn ^ (k & 7)) << 4), make_uint4(w0.x, w0.y, w1.x, w1.y));
          if (tid < DM) {
            const uint2* src = (const uint2*)(sgen + OFF_RAW + tid * 56 + (hp & 3) * 16);
            w0 = src[0];
            w1 = make_uint2(hp == 3 ? (uint32_t)((const unsigned short*)(sgen + OFF_RAW + 28224))[tid] : 0u, 0u);
            if ((hp & 3) != 3) w1 = src[1];
            sts128(sb + OFF_SLC + tid * 16, make_uint4(w0.x, w0.y, w1.x, w1.y));
          }
          fence_async_smem();
          __syncwarp();
          if (lane == 0) mbar_arrive(BAR(B_BUILD), 1);
          mbar_wait(BAR(B_BUILD), 0);
        }
        wg_wait<0>();
        if (lane == 0) mbar_arrive(BAR(B_EMPTY + slot), 1);
        if ((tid & 127) == 0) PROF4(wg * 32 + c * 3 + 2);
        if (++slot == 3) { slot = 0; par ^= 1; }
      }
      if (nh == 1) {
        wg_fence();
#pragma unroll
        for (int ks = 0; ks < 4; ks++) wgmma_ss_n8_ta0_tb1<1>(accs, dX + 6 * 1024 + ks * 2, dSlc + 6 * 64 + ks * 16);
        wg_commit();
      }
      wg_wait<0>();
      fence_regs(acc0); fence_regs(acc1); fence_regs(accs);
      if (tid == 0) PROF_MARK(2);
      if (tid == 256) PROF_MARK(3);
      if (nh == 0) {
        float sq[4] = {0.f, 0.f, 0.f, 0.f};
#pragma unroll
        for (int i = 0; i < 28; i++) acc0[i] *= 0.18898223650461362f * 1.4426950408889634f;
#pragma unroll
        for (int j = 0; j < 7; j++) {
#pragma unroll
          for (int rr = 0; rr < 2; rr++) {
            const float s2 = acc0[4 * j + 2 * rr] * acc0[4 * j + 2 * rr] + acc0[4 * j + 2 * rr + 1] * acc0[4 * j + 2 * rr + 1];
            if (j < 3) sq[rr] += s2;
            else if (j > 3) sq[2 + rr] += s2;
            else { sq[rr] += (lq < 2) ? s2 : 0.f; sq[2 + rr] += (lq < 2) ? 0.f : s2; }
          }
        }
#pragma unroll
        for (int i = 0; i < 4; i++) sq[i] = quad_sum(sq[i]);
        const float mine = lq == 0 ? sq[0] : lq == 1 ? sq[1] : lq == 2 ? sq[2] : sq[3];
        ((float*)(sgen + OFF_QSQ))[(mh + (lq & 2)) * 64 + rowl + 8 * (lq & 1)] = mine <= 3.0e38f ? mine : __int_as_float(0x7f800000);
        __syncwarp();
        if (lane == 0) mbar_arrive(BAR(B_QSQ), 1);
      } else {
        const int sl = hp & 3;
        const bool isk = hp < 4, real = (sl < 3) || (lq < 2);
        const int pos = pt * 128 + row0, kr = pos & 63;
        uint8_t* dst = g_kv_img + (pos >> 6) * 8192 + (isk ? 0 : 4096) + sw64_off(kr, sl * 8 + 2 * lq);
        const uint32_t pat = isk ? POLY_PAT >> (kr >> 3) : 0u;
        float mxv = 0.f;
#pragma unroll
        for (int rr = 0; rr < 2; rr++) {
          const float v0 = accs[2 * rr], v1 = accs[2 * rr + 1];
          const bool poly = (pat >> rr) & 1;
          const float sc = poly ? 2.f : 1.f;
          const float s2 = quad_sum(real ? v0 * v0 + v1 * v1 : 0.f);
          mxv = fmaxf(mxv, s2 <= 3.0e38f ? s2 : __int_as_float(0x7f800000));
          const uint32_t padv = lq == 2 ? (poly ? 0x443F4000u : 0x00003F80u) : (poly ? 0x3AB03F4Du : 0u);
          *(uint32_t*)(dst + rr * 512) = real ? pack_bf16(sc * v0, sc * v1) : padv;
          if (hp == 3 && lq == 2) g_gate[pos + 8 * rr] = rcpf(1.f + ex2f(-1.4426950408889634f * v0));
        }
        mxv = __uint_as_float(__reduce_max_sync(~0u, __float_as_uint(mxv)));
        if (lane == 0) (isk ? g_ksq : g_vsq)[sl * 128 + pt * 8 + mh * 4 + wq] = mxv;
        __syncwarp();
        if (lane == 0) mbar_arrive(BAR(B_SIG + 0), 1);
      }
      if (tid == 0) PROF_MARK(4);
      if (tid == 256) PROF_MARK(5);
      uint32_t h[14];
      float pp[32];
      {
        uint32_t a[16];
#pragma unroll
        for (int i = 0; i < 14; i++) {
          const uint32_t u0 = pack_bf16(acc0[2 * i], acc0[2 * i + 1]), u1 = pack_bf16(acc1[2 * i], acc1[2 * i + 1]);
          h[i] = nh ? u1 : u0;
          a[i] = nh ? u0 : u1;
        }
        a[14] = a[0] ^ 0x80008000u;
        a[15] = a[1] ^ 0x80008000u;
        const uint64_t dW = make_desc(sb + OFF_WBD, 1024, 1024, 1);
        wg_fence();
        wgmma_rs_n64_tb1<0>(pp, a[0], a[1], a[2], a[3], dW);
#pragma unroll
        for (int ks = 1; ks < 4; ks++) wgmma_rs_n64_tb1<1>(pp, a[4 * ks], a[4 * ks + 1], a[4 * ks + 2], a[4 * ks + 3], dW + ks * 128);
        wg_commit();
        bar_sync(1, 512);
        if (tid == 0) PROF_MARK(6);
        store_heads(sb + (nh ? OFF_VA : OFF_QP), h, nh ? 0x00003F80u : 0x3F800000u, nh ? 0u : 0x3F803F80u, row0, lq);
        wg_wait<0>();
        fence_regs(pp);
      }
      feature_map(pp, sb + (nh ? OFF_PHIK : OFF_PHIQ) + row0 * 128 + lq * 4 + ((rowl & 7) << 4), lq);
      fence_async_smem();
      bar_sync(1, 512);
      if (tid == 0) PROF_MARK(7);
      if (nh == 1) {
        float kv0[16], kv1[16];
        const uint64_t dP = make_desc(sb + OFF_PHIK + mh * 8192, 1024, 1024, 1);
        const uint64_t dV = make_desc(sb + OFF_VA + mh * 4096, 512, 512, 2);
        wg_fence();
        wgmma_ss_n32_ta1_tb1<0>(kv0, dP, dV);
        wgmma_ss_n32_ta1_tb1<0>(kv1, dP + 1024, dV + 512);
#pragma unroll
        for (int ks = 1; ks < 4; ks++) {
          wgmma_ss_n32_ta1_tb1<1>(kv0, dP + ks * 128, dV + ks * 64);
          wgmma_ss_n32_ta1_tb1<1>(kv1, dP + 1024 + ks * 128, dV + 512 + ks * 64);
        }
        wg_commit();
        wg_wait<0>();
        fence_regs(kv0); fence_regs(kv1);
        bar_sync(4 + wg, 128);
        const uint32_t sa = sb + OFF_PHIK + mh * 8192 + rowl * 128 + lq * 8 + (rowl & 3) * 32;
#pragma unroll
        for (int j = 0; j < 8; j++) {
          sts64((sa ^ (32 * (j >> 1))) + 1024 * (j & 1), __float_as_uint(kv0[2 * j]), __float_as_uint(kv0[2 * j + 1]));
          sts64((sa ^ (32 * (j >> 1))) + 16384 + 1024 * (j & 1), __float_as_uint(kv1[2 * j]), __float_as_uint(kv1[2 * j + 1]));
        }
        fence_async_smem();
        __syncwarp();
        if (lane == 0) mbar_arrive(BAR(B_SIG + 1), 1);
        if (tid == 256) PROF_MARK(28);
      }
    }
    {
      const uint64_t dK = make_desc(sb + OFF_RING, 512, 512, 2);
      const uint64_t dhi = dK & 0xffffffff00000000ull;
      const uint32_t dlo0 = (uint32_t)dK;
      uint32_t ok = 0, q[8];
      float o[16];
#pragma unroll
      for (int i = 0; i < 16; i++) o[i] = 0.f;
      {
        const int r = mh * 64 + wq * 16 + (lane & 7) + ((lane >> 3) & 1) * 8;
        ldsm4(q, sb + OFF_QP + nh * 8192 + sw64_off(r, (lane >> 4) * 8));
        ldsm4(q + 4, sb + OFF_QP + nh * 8192 + sw64_off(r, 16 + (lane >> 4) * 8));
      }
      if (tid == 0) PROF_MARK(10);
      const int qb = QB_AT;
#pragma unroll 1
      for (int it = 0; it <= 8; it++) {
        uint32_t p[16];
        if ((nh == 0 && (unsigned)(it - qb) < 2u) || it == 8) {
          const int e = it == 8 ? nh : it - qb;
          float t[16];
          wg_wait<0>();
          fence_regs(o);
          if (it < 8) {
            if (tid == 0) PROF_MARK(11);
            mbar_wait(BAR(B_KVR), 0);
            const uint64_t dR = make_desc(sb + OFF_KVR + e * 4096, 512, 512, 2);
            const uint64_t dP = make_desc(sb + OFF_PHIQ + e * 16384 + mh * 8192, 1024, 1024, 1);
            wg_fence();
            wgmma_ss_n32_ta0_tb1<0>(t, dP, dR);
#pragma unroll
            for (int ks = 1; ks < 4; ks++) wgmma_ss_n32_ta0_tb1<1>(t, dP + ks * 2, dR + ks * 64);
            wg_commit();
            wg_wait<0>();
            fence_regs(t);
            if (lane == 0) mbar_arrive(BAR(B_X1FREE), 1);
          } else {
            if (lane == 0) mbar_arrive(BAR(B_EMPTY + prev), 1);
            if (tid == 0) PROF_MARK(13);
            mbar_wait(BAR(B_KVR), 0);
            mbar_wait(BAR(B_SLOW), 0);
            if (__builtin_expect(__any_sync(~0u, *(volatile int*)(sgen + OFF_RED)), 0)) {
              uint32_t qz[8];
#pragma unroll
              for (int i = 0; i < 8; i++) qz[i] = (i >= 6 && lq >= 2) ? 0u : q[i];
              float m0 = -3.0e38f, m1 = -3.0e38f, o2[16];
              int sl2 = slot;
              uint32_t par2 = par;
#pragma unroll 1
              for (int j64 = 0; j64 < 32; j64++) {
                float s[32];
                mbar_wait(BAR(B_FULL + sl2), par2);
                const uint32_t lo = dlo0 + sl2 * 2048 + (j64 & 3) * 512;
                wg_fence();
                wgmma_rs_n64_tb0<0>(s, qz[0], qz[1], qz[2], qz[3], dhi | lo);
                wgmma_rs_n64_tb0<1>(s, qz[4], qz[5], qz[6], qz[7], dhi | (lo + 2));
                wg_commit();
                wg_wait<0>();
                fence_regs(s);
#pragma unroll
                for (int j = 0; j < 8; j++) {
                  const float sc = ((POLY_PAT >> j) & 1) ? 0.5f : 1.f;
                  m0 = fmaxf(m0, fmaxf(s[4 * j], s[4 * j + 1]) * sc);
                  m1 = fmaxf(m1, fmaxf(s[4 * j + 2], s[4 * j + 3]) * sc);
                }
                if ((j64 & 3) == 3) {
                  if (lane == 0) mbar_arrive(BAR(B_EMPTY + sl2), 1);
                  if (++sl2 == 3) { sl2 = 0; par2 ^= 1; }
                }
              }
              m0 = quad_max(m0); m1 = quad_max(m1);
#pragma unroll
              for (int i = 0; i < 16; i++) o2[i] = 0.f;
#pragma unroll 1
              for (int j64 = 0; j64 < 32; j64++) {
                float s[32];
                mbar_wait(BAR(B_FULL + sl2), par2);
                const uint32_t lo = dlo0 + sl2 * 2048 + (j64 & 3) * 512;
                wg_fence();
                wgmma_rs_n64_tb0<0>(s, qz[0], qz[1], qz[2], qz[3], dhi | lo);
                wgmma_rs_n64_tb0<1>(s, qz[4], qz[5], qz[6], qz[7], dhi | (lo + 2));
                wg_commit();
                wg_wait<0>();
                fence_regs(s);
                uint32_t ps[16];
#pragma unroll
                for (int j = 0; j < 8; j++) {
                  const float sc = ((POLY_PAT >> j) & 1) ? 0.5f : 1.f;
                  ps[2 * j] = pack_bf16(ex2f(fmaf(s[4 * j], sc, -m0)), ex2f(fmaf(s[4 * j + 1], sc, -m0)));
                  ps[2 * j + 1] = pack_bf16(ex2f(fmaf(s[4 * j + 2], sc, -m1)), ex2f(fmaf(s[4 * j + 3], sc, -m1)));
                }
                wg_fence();
#pragma unroll
                for (int ks = 0; ks < 4; ks++)
                  wgmma_rs_n32_tb1<1>(o2, ps[4 * ks], ps[4 * ks + 1], ps[4 * ks + 2], ps[4 * ks + 3], dhi | (lo + 256 + ks * 64));
                wg_commit();
                wg_wait<0>();
                fence_regs(o2);
                if ((j64 & 3) == 3) {
                  if (lane == 0) mbar_arrive(BAR(B_EMPTY + sl2), 1);
                  if (++sl2 == 3) { sl2 = 0; par2 ^= 1; }
                }
              }
#pragma unroll 1
              for (int j = 0; j < 2; j++) {
                mbar_wait(BAR(B_FULL + sl2), par2);
                __syncwarp();
                if (lane == 0) mbar_arrive(BAR(B_EMPTY + sl2), 1);
                if (++sl2 == 3) { sl2 = 0; par2 ^= 1; }
              }
#pragma unroll
              for (int i = 0; i < 16; i++) o[i] = o2[i];
            }
#pragma unroll
            for (int i = 0; i < 16; i++) t[i] = o[i];
          }
          const int br = it == 8;
          const float eps = br ? 0.f : 1e-6f;
          const float g0 = ((const float*)(sgen + OFF_GATE))[row0], g1 = ((const float*)(sgen + OFF_GATE))[row0 + 8];
          const float d0 = __shfl_sync(~0u, t[12], (lane & ~3) | 2), d1 = __shfl_sync(~0u, t[14], (lane & ~3) | 2);
          const float r0 = (br ? 1.f - g0 : g0) * rcpf(d0 + eps), r1 = (br ? 1.f - g1 : g1) * rcpf(d1 + eps);
          uint8_t* img = g_o_img + (size_t)((pt * 2 + br) * 14 + mh) * 8192 + rowl * 128;
          const int col0 = (2 * hp + e) * DH + 2 * lq;
#pragma unroll
          for (int j = 0; j < 4; j++) {
            const int col = col0 + 8 * j;
            uint8_t* gp = img + (uint32_t)((col >> 6) * 16384 + ((((col >> 3) ^ rowl) & 7) << 4) + (col & 7) * 2);
            const uint32_t v0 = pack_bf16(t[4 * j] * r0, t[4 * j + 1] * r0), v1 = pack_bf16(t[4 * j + 2] * r1, t[4 * j + 3] * r1);
            if (j < 3 || lq < 2) { *(uint32_t*)gp = v0; *(uint32_t*)(gp + 1024) = v1; }
          }
          __syncwarp();
          if (lane == 0) mbar_arrive(BAR(B_SIG + 2 + br), 1);
          if (tid == 0) PROF_MARK(12 + 2 * br);
          if (br) break;
        }
        const uint32_t lo = dlo0 + slot * 2048;
        if (!ok) mbar_wait(BAR(B_FULL + slot), par);
        int nslot = slot + 1;
        uint32_t npar = par;
        if (nslot == 3) { nslot = 0; npar ^= 1; }
        {
          float s[32];
          wg_fence();
          wgmma_rs_n64_tb0<0>(s, q[0], q[1], q[2], q[3], dhi | lo);
          wgmma_rs_n64_tb0<1>(s, q[4], q[5], q[6], q[7], dhi | (lo + 2));
          wg_commit();
#pragma unroll
          for (int u = 0; u < 4; u++) {
            wg_wait<0>();
            fence_regs(s);
            if (u == 0 && lane == 0 && it > 0) mbar_arrive(BAR(B_EMPTY + prev), 1);
            if (u == 2) ok = mbar_test(BAR(B_FULL + nslot), npar);
#pragma unroll
            for (int j = 0; j < 8; j++) {
              if ((POLY_PAT >> j) & 1) {
                p[2 * j] = exp2_pair_fma(s[4 * j], s[4 * j + 1], 0x3F003F00u, 0x00030003u);
                p[2 * j + 1] = exp2_pair_fma(s[4 * j + 2], s[4 * j + 3], 0x3F003F00u, 0x00030003u);
              } else {
                p[2 * j] = pack_bf16(ex2f(s[4 * j]), ex2f(s[4 * j + 1]));
                p[2 * j + 1] = pack_bf16(ex2f(s[4 * j + 2]), ex2f(s[4 * j + 3]));
              }
            }
            wg_fence();
#pragma unroll
            for (int ks = 0; ks < 4; ks++)
              wgmma_rs_n32_tb1<1>(o, p[4 * ks], p[4 * ks + 1], p[4 * ks + 2], p[4 * ks + 3], dhi | (lo + u * 512 + 256 + ks * 64));
            if (u < 3) {
              wgmma_rs_n64_tb0<0>(s, q[0], q[1], q[2], q[3], dhi | (lo + (u + 1) * 512));
              wgmma_rs_n64_tb0<1>(s, q[4], q[5], q[6], q[7], dhi | (lo + (u + 1) * 512 + 2));
            }
            wg_commit();
          }
        }
        prev = slot; slot = nslot; par = npar;
      }
      wg_wait<0>();
    }
    if (nh == 1) return;
    {
      float acc0[28], acc1[28];
#pragma unroll
      for (int i = 0; i < 28; i++) acc0[i] = acc1[i] = 0.f;
      const uint64_t dS = make_desc(sb + OFF_WO, 1024, 1024, 1);
      const uint64_t dR = make_desc(sb + OFF_RING + mh * 8192, 1024, 1024, 1);
#pragma unroll 1
      for (int c = 0; c < 7; c++) {
        mbar_wait(BAR(B_WO + (c >= 3)), 0);
        mbar_wait(BAR(B_FULL + slot), par);
        const uint64_t dA = dR + slot * 2048, dB = dS + c * 1024;
        wg_fence();
#pragma unroll
        for (int ks = 0; ks < 4; ks++) {
          wgmma_ss_n56_ta0_tb1<1>(acc0, dA + ks * 2, dB + ks * 128);
          wgmma_ss_n56_ta0_tb1<1>(acc1, dA + 1024 + ks * 2, dB + 512 + ks * 128);
        }
        wg_commit();
        if (c < 4) {
          wg_wait<0>();
          if (lane == 0) mbar_arrive(BAR(B_EMPTY + slot), 2);
        }
        if (++slot == 3) { slot = 0; par ^= 1; }
      }
      wg_wait<0>();
      fence_regs(acc0); fence_regs(acc1);
      if (tid == 0) PROF_MARK(17);
      __nv_bfloat16* op = prm.out + (size_t)(pt * 128 + row0) * DM + hp * 56 + 2 * lq;
#pragma unroll
      for (int j = 0; j < 7; j++) {
        *(uint32_t*)(op + 8 * j) = pack_bf16(acc0[4 * j] + acc1[4 * j], acc0[4 * j + 1] + acc1[4 * j + 1]);
        *(uint32_t*)(op + 8 * DM + 8 * j) = pack_bf16(acc0[4 * j + 2] + acc1[4 * j + 2], acc0[4 * j + 3] + acc1[4 * j + 3]);
      }
      if (tid == 0) { PROF_MARK(18); PROF_CLK(31); }
    }
  }
}

typedef CUresult (*EncodeFn)(CUtensorMap*, CUtensorMapDataType, cuuint32_t, void*, const cuuint64_t*, const cuuint64_t*,
                             const cuuint32_t*, const cuuint32_t*, CUtensorMapInterleave, CUtensorMapSwizzle,
                             CUtensorMapL2promotion, CUtensorMapFloatOOBfill);

void make_map(EncodeFn enc, CUtensorMap* tm, const void* ptr, uint64_t cols, uint64_t rows, uint32_t box_cols, uint32_t box_rows) {
  cuuint64_t dims[2] = {cols, rows};
  cuuint64_t strides[1] = {cols * 2};
  cuuint32_t box[2] = {box_cols, box_rows};
  cuuint32_t es[2] = {1, 1};
  enc(tm, CU_TENSOR_MAP_DATA_TYPE_BFLOAT16, 2, const_cast<void*>(ptr), dims, strides, box, es, CU_TENSOR_MAP_INTERLEAVE_NONE,
      CU_TENSOR_MAP_SWIZZLE_128B, CU_TENSOR_MAP_L2_PROMOTION_L2_128B, CU_TENSOR_MAP_FLOAT_OOB_FILL_NONE);
}

}

extern "C" void kernel_launch(void* const* d_in, const int* in_sizes, int n_in, void* d_out, int out_size) {
  (void)in_sizes; (void)n_in; (void)out_size;
  static EncodeFn enc = nullptr;
  if (!enc) {
    void* fn = nullptr;
    cudaDriverEntryPointQueryResult qr;
    cudaGetDriverEntryPoint("cuTensorMapEncodeTiled", &fn, cudaEnableDefault, &qr);
    enc = (EncodeFn)fn;
    cudaFuncSetAttribute(fused_kernel, cudaFuncAttributeMaxDynamicSharedMemorySize, SMEM_BYTES);
  }
  CUtensorMap tm_x, tm_wqkv, tm_wq, tm_woa, tm_wob;
  make_map(enc, &tm_x, d_in[0], DM, S_LEN, 64, 128);
  make_map(enc, &tm_wqkv, d_in[1], 3 * DM, DM, 56, 64);
  make_map(enc, &tm_wq, d_in[5], DM, DM, 56, 64);
  make_map(enc, &tm_woa, d_in[3], DM, DM, 56, 64);
  make_map(enc, &tm_wob, d_in[8], DM, DM, 56, 64);
  Params prm;
  prm.w_phi = (const __nv_bfloat16*)d_in[2];
  prm.wk = (const __nv_bfloat16*)d_in[6];
  prm.wv = (const __nv_bfloat16*)d_in[7];
  prm.gate_w = (const __nv_bfloat16*)d_in[9];
  prm.out = (__nv_bfloat16*)d_out;
  fused_kernel<<<NCTA, NTHREADS, SMEM_BYTES>>>(tm_x, tm_wqkv, tm_wq, tm_woa, tm_wob, prm);
}
```

```cpp
#include <cuda_runtime.h>
#include <cuda_bf16.h>
#include <cuda.h>
#include <stdint.h>

namespace {

constexpr int S_LEN = 2048, DM = 448, DH = 28;
constexpr int NCTA = 128;
constexpr int NTHREADS = 640;
constexpr uint32_t POLY_PAT = 0x57;

#define QB_AT (4 + (wg >> 1))

constexpr int OFF_X = 0;
constexpr int OFF_PHIK = 0;
constexpr int OFF_VA = 32768;
constexpr int OFF_PHIQ = 57344;
constexpr int OFF_KVR = 90112;
constexpr int OFF_QP = 98304;
constexpr int OFF_RAW = 81920;
constexpr int OFF_WO = 0;
constexpr int OFF_RING = 114688;
constexpr int OFF_WBD = 212992;
constexpr int OFF_SLC = 221184;
constexpr int OFF_QSQ = 228352;
constexpr int OFF_GATE = 229376;
constexpr int OFF_RED = 229888;
constexpr int OFF_BAR = 229952;
constexpr int SMEM_BYTES = 230400 + 1024;

constexpr int B_FULL = 0, B_EMPTY = 3, B_WO = 6  , B_KVR = 8, B_RAW = 9, B_X1FREE = 10, B_QSQ = 11, B_SLOW = 12,
              B_BUILD = 13, B_SIG = 14  , B_XL = 18  , B_N = 20;

constexpr int C_KV = 0, C_PART = 1, C_DONE = 3, C_OA = 4, C_OB = 20, C_N = 36;

__device__ __align__(1024) uint8_t g_kv_img[32 * 8192];
__device__ __align__(16) float g_ksq[512];
__device__ __align__(16) float g_vsq[512];
__device__ __align__(16) float g_gate[S_LEN];
__device__ __align__(1024) float g_kvacc[2][16 * 64 * 32];
__device__ unsigned g_epoch;
__device__ __align__(1024) uint8_t g_o_img[2 * 16 * 14 * 8192];
__device__ unsigned g_cnt[C_N * 32];

#define PROF4(i) do { } while (0)
#define PROF3(i) do { } while (0)
#define PROF2(i) do { } while (0)
#define PROF_CLK(i) do { } while (0)
#define PROF_MARK(i) do { } while (0)
__device__ __forceinline__ uint32_t smem_u32(const void* p) { return (uint32_t)__cvta_generic_to_shared(p); }
__device__ __forceinline__ void mbar_init(uint32_t a, int cnt) {
  asm volatile("mbarrier.init.shared::cta.b64 [%0], %1;" ::"r"(a), "r"(cnt) : "memory");
}
__device__ __forceinline__ void mbar_expect_tx(uint32_t a, uint32_t bytes) {
  asm volatile("mbarrier.arrive.expect_tx.shared::cta.b64 _, [%0], %1;" ::"r"(a), "r"(bytes) : "memory");
}
__device__ __forceinline__ void mbar_arrive(uint32_t a, uint32_t cnt) {
  asm volatile("mbarrier.arrive.shared::cta.b64 _, [%0], %1;" ::"r"(a), "r"(cnt) : "memory");
}
__device__ __forceinline__ void mbar_wait(uint32_t a, uint32_t parity) {
  asm volatile(
      "{\n.reg .pred p;\n.reg .u32 c;\nmov.u32 c, 0;\n"
      "W_%=:\nmbarrier.try_wait.parity.shared::cta.b64 p, [%0], %1;\n"
      "add.u32 c, c, 1;\nsetp.lt.and.u32 p, c, 0x40000, !p;\n@p bra W_%=;\n}"
      ::"r"(a), "r"(parity) : "memory");
}
__device__ __forceinline__ uint32_t mbar_test(uint32_t a, uint32_t parity) {
  uint32_t ok;
  asm volatile("{\n.reg .pred p;\nmbarrier.test_wait.parity.shared::cta.b64 p, [%1], %2;\nselp.u32 %0, 1, 0, p;\n}"
               : "=r"(ok) : "r"(a), "r"(parity) : "memory");
  return ok;
}
__device__ __forceinline__ bool elect_one() {
  uint32_t r;
  asm volatile("{\n.reg .pred p;\nelect.sync _|p, 0xffffffff;\nselp.u32 %0, 1, 0, p;\n}" : "=r"(r));
  return r != 0;
}
__device__ __forceinline__ void tma_2d(uint32_t dst, const CUtensorMap* tm, int c0, int c1, uint32_t bar) {
  asm volatile("cp.async.bulk.tensor.2d.shared::cluster.global.mbarrier::complete_tx::bytes [%0], [%1, {%3, %4}], [%2];"
               ::"r"(dst), "l"(tm), "r"(bar), "r"(c0), "r"(c1) : "memory");
}
__device__ __forceinline__ void bulk_g2s(uint32_t dst, const void* src, uint32_t bytes, uint32_t bar) {
  asm volatile("cp.async.bulk.shared::cluster.global.mbarrier::complete_tx::bytes [%0], [%1], %2, [%3];"
               ::"r"(dst), "l"(src), "r"(bytes), "r"(bar) : "memory");
}
__device__ __forceinline__ void fence_async_smem() { asm volatile("fence.proxy.async.shared::cta;" ::: "memory"); }
__device__ __forceinline__ void fence_async_all() { asm volatile("fence.proxy.async.global;" ::: "memory"); }

__device__ __forceinline__ void bar_sync(int id, int n) { asm volatile("bar.sync %0, %1;" ::"r"(id), "r"(n) : "memory"); }
__device__ __forceinline__ void cnt_arrive(int idx) {
  asm volatile("red.release.gpu.global.add.u32 [%0], 1;" ::"l"(&g_cnt[idx * 32]) : "memory");
}
__device__ __forceinline__ void cnt_wait(int idx, unsigned target) {
  unsigned v, n = 0;
#pragma unroll 1
  while (true) {
    asm volatile("ld.acquire.gpu.global.u32 %0, [%1];" : "=r"(v) : "l"(&g_cnt[idx * 32]) : "memory");
    if (v >= target || ++n >= (1u << 18)) break;
    __nanosleep(32);
  }
}
__device__ __forceinline__ void wg_fence() { asm volatile("wgmma.fence.sync.aligned;" ::: "memory"); }
__device__ __forceinline__ void wg_commit() { asm volatile("wgmma.commit_group.sync.aligned;" ::: "memory"); }
template <int N> __device__ __forceinline__ void wg_wait() { asm volatile("wgmma.wait_group.sync.aligned %0;" ::"n"(N) : "memory"); }
template <int N> __device__ __forceinline__ void fence_regs(float (&d)[N]) {
#pragma unroll
  for (int i = 0; i < N; i++) asm volatile("" : "+f"(d[i])::"memory");
}
__device__ __forceinline__ uint64_t make_desc(uint32_t saddr, uint32_t lbo, uint32_t sbo, uint32_t swz) {
  return (uint64_t)((saddr & 0x3FFFF) >> 4) | ((uint64_t)(lbo >> 4) << 16) | ((uint64_t)(sbo >> 4) << 32) | ((uint64_t)swz << 62);
}
__device__ __forceinline__ float ex2f(float x) { float y; asm("ex2.approx.ftz.f32 %0, %1;" : "=f"(y) : "f"(x)); return y; }
__device__ __forceinline__ float rcpf(float x) { float y; asm("rcp.approx.ftz.f32 %0, %1;" : "=f"(y) : "f"(x)); return y; }
__device__ __forceinline__ uint32_t pack_bf16(float lo, float hi) {
  uint32_t r; asm("cvt.rn.bf16x2.f32 %0, %1, %2;" : "=r"(r) : "f"(hi), "f"(lo)); return r;
}
__device__ __forceinline__ uint32_t lop_and_or(uint32_t a, uint32_t m, uint32_t c) {
  uint32_t r; asm("lop3.b32 %0, %1, %2, %3, 0xEA;" : "=r"(r) : "r"(a), "r"(m), "r"(c)); return r;
}
__device__ __forceinline__ void sts32(uint32_t a, uint32_t v) { asm volatile("st.shared.b32 [%0], %1;" ::"r"(a), "r"(v) : "memory"); }
__device__ __forceinline__ void st_shared_nv(uint32_t a, uint32_t v) { asm volatile("st.shared.b32 [%0], %1;" ::"r"(a), "r"(v)); }
__device__ __forceinline__ void sts64(uint32_t a, uint32_t v0, uint32_t v1) { asm volatile("st.shared.v2.b32 [%0], {%1, %2};" ::"r"(a), "r"(v0), "r"(v1) : "memory"); }
__device__ __forceinline__ void sts128(uint32_t a, uint4 v) {
  asm volatile("st.shared.v4.b32 [%0], {%1, %2, %3, %4};" ::"r"(a), "r"(v.x), "r"(v.y), "r"(v.z), "r"(v.w) : "memory");
}
__device__ __forceinline__ float4 ldcg_f4(const float* p) {
  float4 v; asm volatile("ld.global.cg.v4.f32 {%0, %1, %2, %3}, [%4];" : "=f"(v.x), "=f"(v.y), "=f"(v.z), "=f"(v.w) : "l"(p) : "memory"); return v;
}
__device__ __forceinline__ void ldsm4(uint32_t* r, uint32_t a) {
  asm volatile("ldmatrix.sync.aligned.m8n8.x4.shared.b16 {%0, %1, %2, %3}, [%4];"
               : "=r"(r[0]), "=r"(r[1]), "=r"(r[2]), "=r"(r[3]) : "r"(a) : "memory");
}
__device__ __forceinline__ float quad_sum(float v) { v += __shfl_xor_sync(~0u, v, 1); v += __shfl_xor_sync(~0u, v, 2); return v; }
__device__ __forceinline__ float quad_max(float v) { v = fmaxf(v, __shfl_xor_sync(~0u, v, 1)); v = fmaxf(v, __shfl_xor_sync(~0u, v, 2)); return v; }

template <int SD> __device__ __forceinline__ void wgmma_ss_n56_ta0_tb1(float (&d)[28], uint64_t da, uint64_t db) {
  if (SD) asm volatile("wgmma.mma_async.sync.aligned.m64n56k16.f32.bf16.bf16 {%0, %1, %2, %3, %4, %5, %6, %7, %8, %9, %10, %11, %12, %13, %14, %15, %16, %17, %18, %19, %20, %21, %22, %23, %24, %25, %26, %27}, %28, %29, 1, 1, 1, 0, 1;\n"
    : "+f"(d[0]), "+f"(d[1]), "+f"(d[2]), "+f"(d[3]), "+f"(d[4]), "+f"(d[5]), "+f"(d[6]), "+f"(d[7]), "+f"(d[8]), "+f"(d[9]), "+f"(d[10]), "+f"(d[11]), "+f"(d[12]), "+f"(d[13]), "+f"(d[14]), "+f"(d[15]), "+f"(d[16]), "+f"(d[17]), "+f"(d[18]), "+f"(d[19]), "+f"(d[20]), "+f"(d[21]), "+f"(d[22]), "+f"(d[23]), "+f"(d[24]), "+f"(d[25]), "+f"(d[26]), "+f"(d[27])
    : "l"(da), "l"(db));
  else asm volatile("wgmma.mma_async.sync.aligned.m64n56k16.f32.bf16.bf16 {%0, %1, %2, %3, %4, %5, %6, %7, %8, %9, %10, %11, %12, %13, %14, %15, %16, %17, %18, %19, %20, %21, %22, %23, %24, %25, %26, %27}, %28, %29, 0, 1, 1, 0, 1;\n"
    : "=f"(d[0]), "=f"(d[1]), "=f"(d[2]), "=f"(d[3]), "=f"(d[4]), "=f"(d[5]), "=f"(d[6]), "=f"(d[7]), "=f"(d[8]), "=f"(d[9]), "=f"(d[10]), "=f"(d[11]), "=f"(d[12]), "=f"(d[13]), "=f"(d[14]), "=f"(d[15]), "=f"(d[16]), "=f"(d[17]), "=f"(d[18]), "=f"(d[19]), "=f"(d[20]), "=f"(d[21]), "=f"(d[22]), "=f"(d[23]), "=f"(d[24]), "=f"(d[25]), "=f"(d[26]), "=f"(d[27])
    : "l"(da), "l"(db));
}
template <int SD> __device__ __forceinline__ void wgmma_ss_n8_ta0_tb1(float (&d)[4], uint64_t da, uint64_t db) {
  if (SD) asm volatile("wgmma.mma_async.sync.aligned.m64n8k16.f32.bf16.bf16 {%0, %1, %2, %3}, %4, %5, 1, 1, 1, 0, 1;\n"
    : "+f"(d[0]), "+f"(d[1]), "+f"(d[2]), "+f"(d[3])
    : "l"(da), "l"(db));
  else asm volatile("wgmma.mma_async.sync.aligned.m64n8k16.f32.bf16.bf16 {%0, %1, %2, %3}, %4, %5, 0, 1, 1, 0, 1;\n"
    : "=f"(d[0]), "=f"(d[1]), "=f"(d[2]), "=f"(d[3])
    : "l"(da), "l"(db));
}
template <int SD> __device__ __forceinline__ void wgmma_rs_n64_tb1(float (&d)[32], uint32_t a0, uint32_t a1, uint32_t a2, uint32_t a3, uint64_t db) {
  if (SD) asm volatile("wgmma.mma_async.sync.aligned.m64n64k16.f32.bf16.bf16 {%0, %1, %2, %3, %4, %5, %6, %7, %8, %9, %10, %11, %12, %13, %14, %15, %16, %17, %18, %19, %20, %21, %22, %23, %24, %25, %26, %27, %28, %29, %30, %31}, {%32, %33, %34, %35}, %36, 1, 1, 1, 1;\n"
    : "+f"(d[0]), "+f"(d[1]), "+f"(d[2]), "+f"(d[3]), "+f"(d[4]), "+f"(d[5]), "+f"(d[6]), "+f"(d[7]), "+f"(d[8]), "+f"(d[9]), "+f"(d[10]), "+f"(d[11]), "+f"(d[12]), "+f"(d[13]), "+f"(d[14]), "+f"(d[15]), "+f"(d[16]), "+f"(d[17]), "+f"(d[18]), "+f"(d[19]), "+f"(d[20]), "+f"(d[21]), "+f"(d[22]), "+f"(d[23]), "+f"(d[24]), "+f"(d[25]), "+f"(d[26]), "+f"(d[27]), "+f"(d[28]), "+f"(d[29]), "+f"(d[30]), "+f"(d[31])
    : "r"(a0), "r"(a1), "r"(a2), "r"(a3), "l"(db));
  else asm volatile("wgmma.mma_async.sync.aligned.m64n64k16.f32.bf16.bf16 {%0, %1, %2, %3, %4, %5, %6, %7, %8, %9, %10, %11, %12, %13, %14, %15, %16, %17, %18, %19, %20, %21, %22, %23, %24, %25, %26, %27, %28, %29, %30, %31}, {%32, %33, %34, %35}, %36, 0, 1, 1, 1;\n"
    : "=f"(d[0]), "=f"(d[1]), "=f"(d[2]), "=f"(d[3]), "=f"(d[4]), "=f"(d[5]), "=f"(d[6]), "=f"(d[7]), "=f"(d[8]), "=f"(d[9]), "=f"(d[10]), "=f"(d[11]), "=f"(d[12]), "=f"(d[13]), "=f"(d[14]), "=f"(d[15]), "=f"(d[16]), "=f"(d[17]), "=f"(d[18]), "=f"(d[19]), "=f"(d[20]), "=f"(d[21]), "=f"(d[22]), "=f"(d[23]), "=f"(d[24]), "=f"(d[25]), "=f"(d[26]), "=f"(d[27]), "=f"(d[28]), "=f"(d[29]), "=f"(d[30]), "=f"(d[31])
    : "r"(a0), "r"(a1), "r"(a2), "r"(a3), "l"(db));
}
template <int SD> __device__ __forceinline__ void wgmma_ss_n32_ta1_tb1(float (&d)[16], uint64_t da, uint64_t db) {
  if (SD) asm volatile("wgmma.mma_async.sync.aligned.m64n32k16.f32.bf16.bf16 {%0, %1, %2, %3, %4, %5, %6, %7, %8, %9, %10, %11, %12, %13, %14, %15}, %16, %17, 1, 1, 1, 1, 1;\n"
    : "+f"(d[0]), "+f"(d[1]), "+f"(d[2]), "+f"(d[3]), "+f"(d[4]), "+f"(d[5]), "+f"(d[6]), "+f"(d[7]), "+f"(d[8]), "+f"(d[9]), "+f"(d[10]), "+f"(d[11]), "+f"(d[12]), "+f"(d[13]), "+f"(d[14]), "+f"(d[15])
    : "l"(da), "l"(db));
  else asm volatile("wgmma.mma_async.sync.aligned.m64n32k16.f32.bf16.bf16 {%0, %1, %2, %3, %4, %5, %6, %7, %8, %9, %10, %11, %12, %13, %14, %15}, %16, %17, 0, 1, 1, 1, 1;\n"
    : "=f"(d[0]), "=f"(d[1]), "=f"(d[2]), "=f"(d[3]), "=f"(d[4]), "=f"(d[5]), "=f"(d[6]), "=f"(d[7]), "=f"(d[8]), "=f"(d[9]), "=f"(d[10]), "=f"(d[11]), "=f"(d[12]), "=f"(d[13]), "=f"(d[14]), "=f"(d[15])
    : "l"(da), "l"(db));
}
template <int SD> __device__ __forceinline__ void wgmma_ss_n32_ta0_tb1(float (&d)[16], uint64_t da, uint64_t db) {
  if (SD) asm volatile("wgmma.mma_async.sync.aligned.m64n32k16.f32.bf16.bf16 {%0, %1, %2, %3, %4, %5, %6, %7, %8, %9, %10, %11, %12, %13, %14, %15}, %16, %17, 1, 1, 1, 0, 1;\n"
    : "+f"(d[0]), "+f"(d[1]), "+f"(d[2]), "+f"(d[3]), "+f"(d[4]), "+f"(d[5]), "+f"(d[6]), "+f"(d[7]), "+f"(d[8]), "+f"(d[9]), "+f"(d[10]), "+f"(d[11]), "+f"(d[12]), "+f"(d[13]), "+f"(d[14]), "+f"(d[15])
    : "l"(da), "l"(db));
  else asm volatile("wgmma.mma_async.sync.aligned.m64n32k16.f32.bf16.bf16 {%0, %1, %2, %3, %4, %5, %6, %7, %8, %9, %10, %11, %12, %13, %14, %15}, %16, %17, 0, 1, 1, 0, 1;\n"
    : "=f"(d[0]), "=f"(d[1]), "=f"(d[2]), "=f"(d[3]), "=f"(d[4]), "=f"(d[5]), "=f"(d[6]), "=f"(d[7]), "=f"(d[8]), "=f"(d[9]), "=f"(d[10]), "=f"(d[11]), "=f"(d[12]), "=f"(d[13]), "=f"(d[14]), "=f"(d[15])
    : "l"(da), "l"(db));
}
template <int SD> __device__ __forceinline__ void wgmma_rs_n64_tb0(float (&d)[32], uint32_t a0, uint32_t a1, uint32_t a2, uint32_t a3, uint64_t db) {
  if (SD) asm volatile("wgmma.mma_async.sync.aligned.m64n64k16.f32.bf16.bf16 {%0, %1, %2, %3, %4, %5, %6, %7, %8, %9, %10, %11, %12, %13, %14, %15, %16, %17, %18, %19, %20, %21, %22, %23, %24, %25, %26, %27, %28, %29, %30, %31}, {%32, %33, %34, %35}, %36, 1, 1, 1, 0;\n"
    : "+f"(d[0]), "+f"(d[1]), "+f"(d[2]), "+f"(d[3]), "+f"(d[4]), "+f"(d[5]), "+f"(d[6]), "+f"(d[7]), "+f"(d[8]), "+f"(d[9]), "+f"(d[10]), "+f"(d[11]), "+f"(d[12]), "+f"(d[13]), "+f"(d[14]), "+f"(d[15]), "+f"(d[16]), "+f"(d[17]), "+f"(d[18]), "+f"(d[19]), "+f"(d[20]), "+f"(d[21]), "+f"(d[22]), "+f"(d[23]), "+f"(d[24]), "+f"(d[25]), "+f"(d[26]), "+f"(d[27]), "+f"(d[28]), "+f"(d[29]), "+f"(d[30]), "+f"(d[31])
    : "r"(a0), "r"(a1), "r"(a2), "r"(a3), "l"(db));
  else asm volatile("wgmma.mma_async.sync.aligned.m64n64k16.f32.bf16.bf16 {%0, %1, %2, %3, %4, %5, %6, %7, %8, %9, %10, %11, %12, %13, %14, %15, %16, %17, %18, %19, %20, %21, %22, %23, %24, %25, %26, %27, %28, %29, %30, %31}, {%32, %33, %34, %35}, %36, 0, 1, 1, 0;\n"
    : "=f"(d[0]), "=f"(d[1]), "=f"(d[2]), "=f"(d[3]), "=f"(d[4]), "=f"(d[5]), "=f"(d[6]), "=f"(d[7]), "=f"(d[8]), "=f"(d[9]), "=f"(d[10]), "=f"(d[11]), "=f"(d[12]), "=f"(d[13]), "=f"(d[14]), "=f"(d[15]), "=f"(d[16]), "=f"(d[17]), "=f"(d[18]), "=f"(d[19]), "=f"(d[20]), "=f"(d[21]), "=f"(d[22]), "=f"(d[23]), "=f"(d[24]), "=f"(d[25]), "=f"(d[26]), "=f"(d[27]), "=f"(d[28]), "=f"(d[29]), "=f"(d[30]), "=f"(d[31])
    : "r"(a0), "r"(a1), "r"(a2), "r"(a3), "l"(db));
}
template <int SD> __device__ __forceinline__ void wgmma_rs_n32_tb1(float (&d)[16], uint32_t a0, uint32_t a1, uint32_t a2, uint32_t a3, uint64_t db) {
  if (SD) asm volatile("wgmma.mma_async.sync.aligned.m64n32k16.f32.bf16.bf16 {%0, %1, %2, %3, %4, %5, %6, %7, %8, %9, %10, %11, %12, %13, %14, %15}, {%16, %17, %18, %19}, %20, 1, 1, 1, 1;\n"
    : "+f"(d[0]), "+f"(d[1]), "+f"(d[2]), "+f"(d[3]), "+f"(d[4]), "+f"(d[5]), "+f"(d[6]), "+f"(d[7]), "+f"(d[8]), "+f"(d[9]), "+f"(d[10]), "+f"(d[11]), "+f"(d[12]), "+f"(d[13]), "+f"(d[14]), "+f"(d[15])
    : "r"(a0), "r"(a1), "r"(a2), "r"(a3), "l"(db));
  else asm volatile("wgmma.mma_async.sync.aligned.m64n32k16.f32.bf16.bf16 {%0, %1, %2, %3, %4, %5, %6, %7, %8, %9, %10, %11, %12, %13, %14, %15}, {%16, %17, %18, %19}, %20, 0, 1, 1, 1;\n"
    : "=f"(d[0]), "=f"(d[1]), "=f"(d[2]), "=f"(d[3]), "=f"(d[4]), "=f"(d[5]), "=f"(d[6]), "=f"(d[7]), "=f"(d[8]), "=f"(d[9]), "=f"(d[10]), "=f"(d[11]), "=f"(d[12]), "=f"(d[13]), "=f"(d[14]), "=f"(d[15])
    : "r"(a0), "r"(a1), "r"(a2), "r"(a3), "l"(db));
}

__device__ __forceinline__ uint32_t sw64_off(int row, int d) { return row * 64 + ((((d >> 3) ^ (row >> 1)) & 3) << 4) + (d & 7) * 2; }

__device__ __forceinline__ uint32_t exp2_pair_fma(float t0, float t1, uint32_t c_half, uint32_t c_3) {
  uint32_t y0, y;
  asm("prmt.b32 %0, %1, %2, 0x6521;" : "=r"(y0) : "r"(__float_as_uint(t0)), "r"(__float_as_uint(t1)));
  uint32_t h = lop_and_or(y0, 0x007F007Fu, c_half);
  uint32_t e = lop_and_or(y0, 0xFF80FF80u, c_3);
  asm("fma.rn.bf16x2 %0, %1, %2, %3;" : "=r"(y) : "r"(y0), "r"(h), "r"(e));
  return y;
}

__device__ __forceinline__ void feature_map(float (&p)[32], uint32_t rb, int lq) {
  const float L2E = 1.4426950408889634f;
  const bool tail_ok = lq < 2;
  float mx[4], mn[4], b[32], sa[4], sn[4];
#pragma unroll
  for (int g = 0; g < 4; g++) {
    const int o = 16 * (g >> 1) + 2 * (g & 1);
    if (!tail_ok) { p[o + 12] = p[o]; p[o + 13] = p[o]; }
    mx[g] = fmaxf(fmaxf(fmaxf(p[o], p[o + 1]), fmaxf(p[o + 4], p[o + 5])), fmaxf(fmaxf(p[o + 8], p[o + 9]), fmaxf(p[o + 12], p[o + 13])));
    mn[g] = fminf(fminf(fminf(p[o], p[o + 1]), fminf(p[o + 4], p[o + 5])), fminf(fminf(p[o + 8], p[o + 9]), fminf(p[o + 12], p[o + 13])));
  }
#pragma unroll
  for (int o = 1; o <= 2; o <<= 1)
#pragma unroll
    for (int g = 0; g < 4; g++) { mx[g] = fmaxf(mx[g], __shfl_xor_sync(~0u, mx[g], o)); mn[g] = fminf(mn[g], __shfl_xor_sync(~0u, mn[g], o)); }
#pragma unroll
  for (int g = 0; g < 4; g++) {
    const int o = 16 * (g >> 1) + 2 * (g & 1);
    const float cx = -mx[g] * L2E, cn = mn[g] * L2E;
#pragma unroll
    for (int i = 0; i < 8; i++) {
      const int k = o + 4 * (i >> 1) + (i & 1);
      b[k] = ex2f(fmaf(p[k], -L2E, cn));
      p[k] = ex2f(fmaf(p[k], L2E, cx));
    }
    if (!tail_ok) { p[o + 12] = p[o + 13] = b[o + 12] = b[o + 13] = 0.f; }
    sa[g] = ((p[o] + p[o + 1]) + (p[o + 4] + p[o + 5])) + ((p[o + 8] + p[o + 9]) + (p[o + 12] + p[o + 13]));
    sn[g] = ((b[o] + b[o + 1]) + (b[o + 4] + b[o + 5])) + ((b[o + 8] + b[o + 9]) + (b[o + 12] + b[o + 13]));
    sa[g] += __shfl_xor_sync(~0u, sa[g], 1); sn[g] += __shfl_xor_sync(~0u, sn[g], 1);
    sa[g] += __shfl_xor_sync(~0u, sa[g], 2); sn[g] += __shfl_xor_sync(~0u, sn[g], 2);
  }
#pragma unroll
  for (int g = 0; g < 4; g++) {
    const int o = 16 * (g >> 1) + 2 * (g & 1);
    const float ra = rcpf(sa[g]), rn = rcpf(sn[g]);
    const uint32_t off = (g >> 1) * 16384 + (g & 1) * 1024;
#pragma unroll
    for (int jj = 0; jj < 4; jj++) {
      st_shared_nv((rb ^ (jj << 4)) + off, pack_bf16(p[o + 4 * jj] * ra, p[o + 4 * jj + 1] * ra));
      st_shared_nv((rb ^ ((4 + jj) << 4)) + off, pack_bf16(b[o + 4 * jj] * rn, b[o + 4 * jj + 1] * rn));
    }
  }
}

__device__ __forceinline__ void store_heads(uint32_t base, const uint32_t (&a)[14], uint32_t pad0, uint32_t pad1, int row0, int lq) {
  const uint32_t rb = base + row0 * 64 + (((row0 >> 1) & 3) << 4);
  const uint32_t b0 = rb + lq * 4;
  const uint32_t b1 = (rb + 8192 + ((lq * 4 + 8) & 15)) ^ ((lq >> 1) << 4);
#pragma unroll
  for (int j = 0; j < 7; j++) {
    uint32_t ad;
    if (j < 3) ad = b0 ^ (j << 4);
    else if (j == 3) ad = (lq < 2) ? (b0 ^ 48u) : (b1 ^ 16u);
    else ad = (lq < 2) ? (b1 ^ ((j - 4) << 4)) : ((b1 ^ 16u) ^ ((j - 3) << 4));
    sts32(ad, a[2 * j]);
    sts32(ad + 512, a[2 * j + 1]);
  }
  sts64((rb ^ 48u) + 8 + (lq & 1) * 8192 + (lq >> 1) * 512, pad0, pad1);
}

struct Params {
  const __nv_bfloat16* w_phi;
  const __nv_bfloat16* wk;
  const __nv_bfloat16* wv;
  const __nv_bfloat16* gate_w;
  __nv_bfloat16* out;
};

__global__ void __launch_bounds__(NTHREADS, 1)
fused_kernel(const __grid_constant__ CUtensorMap tm_x, const __grid_constant__ CUtensorMap tm_wqkv,
             const __grid_constant__ CUtensorMap tm_wq, const __grid_constant__ CUtensorMap tm_woa,
             const __grid_constant__ CUtensorMap tm_wob, const Params prm) {
  extern __shared__ uint8_t smem_raw[];
  uint32_t sb = (smem_u32(smem_raw) + 1023u) & ~1023u;
  uint8_t* sgen = smem_raw + (sb - smem_u32(smem_raw));
  asm volatile("mov.u32 %0, %0;" : "+r"(sb));
  const int tid = threadIdx.x, lane = tid & 31;
  const int warp = __shfl_sync(~0u, tid >> 5, 0), wg = warp >> 2;
  const int pt = blockIdx.x >> 3, hp = blockIdx.x & 7;
  const uint32_t bars = sb + OFF_BAR;
  auto BAR = [&](int i) { return bars + 8u * i; };
  const unsigned epoch = g_epoch & 1;

  if (tid == 0) { PROF_MARK(0); PROF_CLK(30); PROF2(15); }
  auto load_proj = [&](int c, int g) {
    mbar_expect_tx(BAR(B_FULL + g), (c < 3 ? 16384 : 0) + 4 * 7168);
    if (c < 3) tma_2d(sb + OFF_X + c * 16384, &tm_x, c * 64, pt * 128, BAR(B_FULL + g));
    tma_2d(sb + OFF_RING + g * 32768, &tm_wq, hp * 56, c * 64, BAR(B_FULL + g));
#pragma unroll 1
    for (int j = 0; j < 3; j++) tma_2d(sb + OFF_RING + g * 32768 + 8192 + j * 8192, &tm_wqkv, j * DM + hp * 56, c * 64, BAR(B_FULL + g));
  };
  if (warp == 16) {
    if (elect_one()) {
      mbar_init(BAR(B_FULL), 1);
      fence_async_smem();
      load_proj(0, 0);
      mbar_init(BAR(B_RAW), 1); mbar_init(BAR(B_FULL + 1), 1); mbar_init(BAR(B_FULL + 2), 1);
      fence_async_smem();
    }
    __syncwarp();
    asm volatile("bar.arrive 0, %0;" ::"n"(NTHREADS) : "memory");
  } else {
    if (elect_one()) {
      const int i = warp + 3 - (warp > 16);
      if (i < B_N && i != B_RAW) {
        int cnt = i < B_WO || (i > B_SIG && i < B_XL) || i == B_X1FREE ? 16 : 1;
        if (i == B_BUILD) cnt = 16;
        if (i == B_SIG || i == B_SIG + 1 || i == B_QSQ) cnt = 8;
        if (i == B_KVR) cnt = 2;
        mbar_init(BAR(i), cnt);
        fence_async_smem();
      }
    }
    bar_sync(0, NTHREADS);
  }
  if (tid == 0) PROF2(14);

  if (wg == 4) {
    asm volatile("setmaxnreg.dec.sync.aligned.u32 32;");
    if (warp == 16) {
      if (elect_one()) {
        mbar_expect_tx(BAR(B_RAW), 25088 + 3136 + 896);
        bulk_g2s(sb + OFF_RAW, hp < 4 ? prm.wk : prm.wv, 25088, BAR(B_RAW));
        bulk_g2s(sb + OFF_RAW + 25088, prm.w_phi + 2 * hp * DH * DH, 3136, BAR(B_RAW));
        bulk_g2s(sb + OFF_RAW + 28224, prm.gate_w, 896, BAR(B_RAW));
        load_proj(1, 1);
        load_proj(2, 2);
      }
      __syncwarp();
      bar_sync(3, 64);
      if (elect_one()) {
        int g = 0, nkv = 8;
        uint32_t par = 0;
#pragma unroll 1
        for (int c = 3; c < 7; c++) {
          if (c == 5) mbar_wait(BAR(B_BUILD), 0);
          if (c & 1) mbar_expect_tx(BAR(B_XL + (c > 4)), 32768);
          tma_2d(sb + OFF_X + c * 16384, &tm_x, c * 64, pt * 128, BAR(B_XL + (c > 4)));
        }
#pragma unroll 1
        for (int n = 3; n < 14 + nkv; n++) {
          if (n == 7) { PROF_MARK(20); cnt_wait(C_KV, NCTA); PROF_MARK(21); fence_async_all(); }
          if (n == 15) {
            mbar_wait(BAR(B_SLOW), 0);
            if (*(volatile int*)(sgen + OFF_RED)) nkv = 26;
          }
          const int j = n - 7 - nkv;
          if (j == 0 || j == 3) {
            PROF3(j ? 11 : 8);
            cnt_wait((j ? C_OB : C_OA) + pt, 8);
            PROF3(j ? 12 : 9);
            PROF_MARK(26);
            fence_async_all();
          }
          mbar_wait(BAR(B_EMPTY + g), par);
          if (n < 7) { PROF2(20 + n); load_proj(n, g); }
          else {
            mbar_expect_tx(BAR(B_FULL + g), 32768);
            bulk_g2s(sb + OFF_RING + g * 32768, j < 0 ? g_kv_img + ((n - 7) & 7) * 32768 : g_o_img + (size_t)(pt * 7 + j) * 32768, 32768,
                     BAR(B_FULL + g));
          }
          if (++g == 3) { g = 0; par ^= 1; }
        }
        if (atomicAdd(&g_cnt[C_DONE * 32], 1u) == NCTA - 1) {
#pragma unroll 1
          for (int i = 0; i < C_N; i++) g_cnt[i * 32] = 0;
          g_epoch = epoch ^ 1;
        }
      }
    } else {
      if (warp == 18) {
        if (elect_one()) {
#pragma unroll 1
          for (int i = 0; i < 4; i++) {
            mbar_wait(BAR(B_SIG + i), 0);
            PROF3(2 * i);
            if (i == 1) {
#pragma unroll 1
              for (int j = 0; j < 4; j++)
                asm volatile("cp.reduce.async.bulk.global.shared::cta.bulk_group.add.f32 [%0], [%1], 8192;"
                             ::"l"(g_kvacc[epoch] + hp * 4096 + (j >> 1) * 2048), "r"(sb + OFF_PHIK + j * 8192) : "memory");
              asm volatile("cp.async.bulk.commit_group;\ncp.async.bulk.wait_group 0;" ::: "memory");
            }
            cnt_arrive(i == 0 ? C_KV : i == 1 ? C_PART : (i == 2 ? C_OA : C_OB) + pt);
            PROF3(2 * i + 1);
            if (i == 1 || i == 2) {
              if (i == 2) mbar_wait(BAR(B_X1FREE), 0);
              mbar_expect_tx(BAR(B_WO + i - 1), 7 * 7168);
#pragma unroll 1
              for (int c = 0; c < 7; c++)
                tma_2d(sb + OFF_WO + (i - 1) * 57344 + c * 8192, i == 1 ? &tm_woa : &tm_wob, hp * 56, c * 64, BAR(B_WO + i - 1));
            }
          }
        }
      } else if (warp == 19) {
        if (lane == 0) {
          mbar_wait(BAR(B_SIG + 0), 0);
          cnt_wait(C_KV, NCTA);
        }
        __syncwarp();
        float ksq = 0.f, vsq = 0.f;
#pragma unroll
        for (int sl = 0; sl < 4; sl++) {
          float4 a = ldcg_f4(g_ksq + sl * 128 + lane * 4), b = ldcg_f4(g_vsq + sl * 128 + lane * 4);
          float m = fmaxf(fmaxf(a.x, a.y), fmaxf(a.z, a.w));
          m = __uint_as_float(__reduce_max_sync(~0u, __float_as_uint(m)));
          ksq += m;
          vsq = fmaxf(vsq, fmaxf(fmaxf(b.x, b.y), fmaxf(b.z, b.w)));
        }
        mbar_wait(BAR(B_QSQ), 0);
        const float4 qa4 = ((const float4*)(sgen + OFF_QSQ))[lane], qb4 = ((const float4*)(sgen + OFF_QSQ))[32 + lane];
        const float qmax = fmaxf(fmaxf(fmaxf(qa4.x, qa4.y), fmaxf(qa4.z, qa4.w)), fmaxf(fmaxf(qb4.x, qb4.y), fmaxf(qb4.z, qb4.w)));
        const bool slow = __any_sync(~0u, !(qmax * ksq <= 98.f * 98.f) || !(vsq <= 2.0e8f));
        if (lane == 0) {
          *(volatile int*)(sgen + OFF_RED) = slow;
          mbar_arrive(BAR(B_SLOW), 1);
        }
      } else {
        float4* z = (float4*)(g_kvacc[epoch ^ 1] + blockIdx.x * 256) + lane;
        z[0] = make_float4(0.f, 0.f, 0.f, 0.f);
        z[32] = make_float4(0.f, 0.f, 0.f, 0.f);
        bar_sync(3, 64);
        if (lane == 0) {
          mbar_wait(BAR(B_SIG + 0), 0);
          cnt_wait(C_KV, NCTA);
        }
        __syncwarp();
        ((float4*)(sgen + OFF_GATE))[lane] = ldcg_f4(g_gate + pt * 128 + lane * 4);
      }
      if (warp != 18) {
        if (lane == 0) {
          mbar_wait(BAR(B_SIG + 1), 0);
          cnt_wait(C_PART, NCTA);
          PROF_MARK(23);
        }
        __syncwarp();
        const int e = warp == 19;
        const float* src = g_kvacc[epoch] + hp * 4096 + e * 2048 + (lane ^ ((lane >> 2) & 3)) * 8;
#pragma unroll 1
        for (int i = 0; i < 8; i += 2) {
          const float4 a = ldcg_f4(src + i * 256), b = ldcg_f4(src + i * 256 + 4), c = ldcg_f4(src + i * 256 + 256), d = ldcg_f4(src + i * 256 + 260);
          const uint32_t ad = sb + OFF_KVR + e * 4096 + sw64_off(i * 8 + (lane >> 2), (lane & 3) * 8);
          sts128(ad, make_uint4(pack_bf16(a.x, a.y), pack_bf16(a.z, a.w), pack_bf16(b.x, b.y), pack_bf16(b.z, b.w)));
          sts128(ad + 512, make_uint4(pack_bf16(c.x, c.y), pack_bf16(c.z, c.w), pack_bf16(d.x, d.y), pack_bf16(d.z, d.w)));
        }
        fence_async_smem();
        __syncwarp();
        if (lane == 0) mbar_arrive(BAR(B_KVR), 1);
        PROF_MARK(24);
      }
    }
  } else {
    asm volatile("setmaxnreg.inc.sync.aligned.u32 112;");
    const int mh = wg & 1, nh = wg >> 1, wq = warp & 3;
    const int lq = lane & 3;
    const int rowl = wq * 16 + (lane >> 2);
    const int row0 = mh * 64 + rowl;
    int slot = 0;
    uint32_t par = 0;
    {
      float acc0[28], acc1[28], accs[4];
      const uint64_t dR = make_desc(sb + OFF_RING + nh * 16384, 1024, 1024, 1);
      const uint64_t dX = make_desc(sb + OFF_X + mh * 8192, 1024, 1024, 1);
#pragma unroll
      for (int i = 0; i < 28; i++) acc0[i] = acc1[i] = 0.f;
#pragma unroll
      for (int i = 0; i < 4; i++) accs[i] = 0.f;
      const uint64_t dSlc = make_desc(sb + OFF_SLC, 128, 128, 0);
#pragma unroll 1
      for (int c = 0; c < 7; c++) {
        if (c == 3 || c == 5) mbar_wait(BAR(B_XL + (c > 4)), 0);
        mbar_wait(BAR(B_FULL + slot), par);
        if (c == 0 && tid == 0) PROF2(17);
        const uint64_t dA = dX + c * 1024, dB = dR + slot * 2048;
        wg_fence();
#pragma unroll
        for (int ks = 0; ks < 4; ks++) {
          wgmma_ss_n56_ta0_tb1<1>(acc0, dA + ks * 2, dB + ks * 128);
          wgmma_ss_n56_ta0_tb1<1>(acc1, dA + ks * 2, dB + 512 + ks * 128);
        }
        if (nh == 1 && c > 0) {
#pragma unroll
          for (int ks = 0; ks < 4; ks++) wgmma_ss_n8_ta0_tb1<1>(accs, dA - 1024 + ks * 2, dSlc + (c - 1) * 64 + ks * 16);
        }
        wg_commit();
        if (c == 0) {
          mbar_wait(BAR(B_RAW), 0);
          const int k = tid >> 3, cn = tid & 7;
          const bool data = k < 56 && (cn >> 2) == (k >= DH);
          const uint2* wsrc = (const uint2*)(sgen + OFF_RAW + 25088 + k * 56 + (cn & 3) * 16);
          uint2 w0 = make_uint2(0u, 0u), w1 = w0;
          if (data) w0 = wsrc[0];
          if (data && (cn & 3) != 3) w1 = wsrc[1];
          sts128(sb + OFF_WBD + k * 128 + ((cn ^ (k & 7)) << 4), make_uint4(w0.x, w0.y, w1.x, w1.y));
          if (tid < DM) {
            const uint2* src = (const uint2*)(sgen + OFF_RAW + tid * 56 + (hp & 3) * 16);
            w0 = src[0];
            w1 = make_uint2(hp == 3 ? (uint32_t)((const unsigned short*)(sgen + OFF_RAW + 28224))[tid] : 0u, 0u);
            if ((hp & 3) != 3) w1 = src[1];
            sts128(sb + OFF_SLC + tid * 16, make_uint4(w0.x, w0.y, w1.x, w1.y));
          }
          fence_async_smem();
          __syncwarp();
          if (lane == 0) mbar_arrive(BAR(B_BUILD), 1);
          mbar_wait(BAR(B_BUILD), 0);
        }
        wg_wait<0>();
        if (lane == 0) mbar_arrive(BAR(B_EMPTY + slot), 1);
        if (++slot == 3) { slot = 0; par ^= 1; }
      }
      if (nh == 1) {
        wg_fence();
#pragma unroll
        for (int ks = 0; ks < 4; ks++) wgmma_ss_n8_ta0_tb1<1>(accs, dX + 6 * 1024 + ks * 2, dSlc + 6 * 64 + ks * 16);
        wg_commit();
      }
      wg_wait<0>();
      fence_regs(acc0); fence_regs(acc1); fence_regs(accs);
      if (tid == 0) PROF_MARK(2);
      if (tid == 256) PROF_MARK(3);
      if (nh == 0) {
        float sq[4] = {0.f, 0.f, 0.f, 0.f};
#pragma unroll
        for (int i = 0; i < 28; i++) acc0[i] *= 0.18898223650461362f * 1.4426950408889634f;
#pragma unroll
        for (int j = 0; j < 7; j++) {
#pragma unroll
          for (int rr = 0; rr < 2; rr++) {
            const float s2 = acc0[4 * j + 2 * rr] * acc0[4 * j + 2 * rr] + acc0[4 * j + 2 * rr + 1] * acc0[4 * j + 2 * rr + 1];
            if (j < 3) sq[rr] += s2;
            else if (j > 3) sq[2 + rr] += s2;
            else { sq[rr] += (lq < 2) ? s2 : 0.f; sq[2 + rr] += (lq < 2) ? 0.f : s2; }
          }
        }
#pragma unroll
        for (int i = 0; i < 4; i++) sq[i] = quad_sum(sq[i]);
        const float mine = lq == 0 ? sq[0] : lq == 1 ? sq[1] : lq == 2 ? sq[2] : sq[3];
        ((float*)(sgen + OFF_QSQ))[(mh + (lq & 2)) * 64 + rowl + 8 * (lq & 1)] = mine <= 3.0e38f ? mine : __int_as_float(0x7f800000);
        __syncwarp();
        if (lane == 0) mbar_arrive(BAR(B_QSQ), 1);
      } else {
        const int sl = hp & 3;
        const bool isk = hp < 4, real = (sl < 3) || (lq < 2);
        const int pos = pt * 128 + row0, kr = pos & 63;
        uint8_t* dst = g_kv_img + (pos >> 6) * 8192 + (isk ? 0 : 4096) + sw64_off(kr, sl * 8 + 2 * lq);
        const uint32_t pat = isk ? POLY_PAT >> (kr >> 3) : 0u;
        float mxv = 0.f;
#pragma unroll
        for (int rr = 0; rr < 2; rr++) {
          const float v0 = accs[2 * rr], v1 = accs[2 * rr + 1];
          const bool poly = (pat >> rr) & 1;
          const float sc = poly ? 2.f : 1.f;
          const float s2 = quad_sum(real ? v0 * v0 + v1 * v1 : 0.f);
          mxv = fmaxf(mxv, s2 <= 3.0e38f ? s2 : __int_as_float(0x7f800000));
          const uint32_t padv = lq == 2 ? (poly ? 0x443F4000u : 0x00003F80u) : (poly ? 0x3AB03F4Du : 0u);
          *(uint32_t*)(dst + rr * 512) = real ? pack_bf16(sc * v0, sc * v1) : padv;
          if (hp == 3 && lq == 2) g_gate[pos + 8 * rr] = rcpf(1.f + ex2f(-1.4426950408889634f * v0));
        }
        mxv = __uint_as_float(__reduce_max_sync(~0u, __float_as_uint(mxv)));
        if (lane == 0) (isk ? g_ksq : g_vsq)[sl * 128 + pt * 8 + mh * 4 + wq] = mxv;
        __syncwarp();
        if (lane == 0) mbar_arrive(BAR(B_SIG + 0), 1);
      }
      if (tid == 0) PROF_MARK(4);
      if (tid == 256) PROF_MARK(5);
      uint32_t h[14];
      float pp[32];
      {
        uint32_t a[16];
#pragma unroll
        for (int i = 0; i < 14; i++) {
          const uint32_t u0 = pack_bf16(acc0[2 * i], acc0[2 * i + 1]), u1 = pack_bf16(acc1[2 * i], acc1[2 * i + 1]);
          h[i] = nh ? u1 : u0;
          a[i] = nh ? u0 : u1;
        }
        a[14] = a[0] ^ 0x80008000u;
        a[15] = a[1] ^ 0x80008000u;
        const uint64_t dW = make_desc(sb + OFF_WBD, 1024, 1024, 1);
        wg_fence();
        wgmma_rs_n64_tb1<0>(pp, a[0], a[1], a[2], a[3], dW);
#pragma unroll
        for (int ks = 1; ks < 4; ks++) wgmma_rs_n64_tb1<1>(pp, a[4 * ks], a[4 * ks + 1], a[4 * ks + 2], a[4 * ks + 3], dW + ks * 128);
        wg_commit();
        bar_sync(1, 512);
        if (tid == 0) PROF_MARK(6);
        store_heads(sb + (nh ? OFF_VA : OFF_QP), h, nh ? 0x00003F80u : 0x3F800000u, nh ? 0u : 0x3F803F80u, row0, lq);
        wg_wait<0>();
        fence_regs(pp);
      }
      feature_map(pp, sb + (nh ? OFF_PHIK : OFF_PHIQ) + row0 * 128 + lq * 4 + ((rowl & 7) << 4), lq);
      fence_async_smem();
      bar_sync(1, 512);
      if (tid == 0) PROF_MARK(7);
      if (nh == 1) {
        float kv0[16], kv1[16];
        const uint64_t dP = make_desc(sb + OFF_PHIK + mh * 8192, 1024, 1024, 1);
        const uint64_t dV = make_desc(sb + OFF_VA + mh * 4096, 512, 512, 2);
        wg_fence();
        wgmma_ss_n32_ta1_tb1<0>(kv0, dP, dV);
        wgmma_ss_n32_ta1_tb1<0>(kv1, dP + 1024, dV + 512);
#pragma unroll
        for (int ks = 1; ks < 4; ks++) {
          wgmma_ss_n32_ta1_tb1<1>(kv0, dP + ks * 128, dV + ks * 64);
          wgmma_ss_n32_ta1_tb1<1>(kv1, dP + 1024 + ks * 128, dV + 512 + ks * 64);
        }
        wg_commit();
        wg_wait<0>();
        fence_regs(kv0); fence_regs(kv1);
        bar_sync(4 + wg, 128);
        const uint32_t sa = sb + OFF_PHIK + mh * 8192 + rowl * 128 + lq * 8 + (rowl & 3) * 32;
#pragma unroll
        for (int j = 0; j < 8; j++) {
          sts64((sa ^ (32 * (j >> 1))) + 1024 * (j & 1), __float_as_uint(kv0[2 * j]), __float_as_uint(kv0[2 * j + 1]));
          sts64((sa ^ (32 * (j >> 1))) + 16384 + 1024 * (j & 1), __float_as_uint(kv1[2 * j]), __float_as_uint(kv1[2 * j + 1]));
        }
        fence_async_smem();
        __syncwarp();
        if (lane == 0) mbar_arrive(BAR(B_SIG + 1), 1);
        if (tid == 256) PROF_MARK(28);
      }
    }
    {
      const uint64_t dK = make_desc(sb + OFF_RING, 512, 512, 2);
      const uint64_t dhi = dK & 0xffffffff00000000ull;
      const uint32_t dlo0 = (uint32_t)dK;
      uint32_t ok = 0, q[8];
      float o[16];
#pragma unroll
      for (int i = 0; i < 16; i++) o[i] = 0.f;
      {
        const int r = mh * 64 + wq * 16 + (lane & 7) + ((lane >> 3) & 1) * 8;
        ldsm4(q, sb + OFF_QP + nh * 8192 + sw64_off(r, (lane >> 4) * 8));
        ldsm4(q + 4, sb + OFF_QP + nh * 8192 + sw64_off(r, 16 + (lane >> 4) * 8));
      }
      if (tid == 0) PROF_MARK(10);
      const int qb = QB_AT;
      float s[32];
      mbar_wait(BAR(B_FULL + slot), par);
      wg_fence();
      wgmma_rs_n64_tb0<0>(s, q[0], q[1], q[2], q[3], dhi | (dlo0 + slot * 2048));
      wgmma_rs_n64_tb0<1>(s, q[4], q[5], q[6], q[7], dhi | (dlo0 + slot * 2048 + 2));
      wg_commit();
      wg_wait<0>();
      fence_regs(s);
#pragma unroll 1
      for (int it = 0; it <= 8; it++) {
        uint32_t p[16];
        if ((tid & 127) == 0) PROF4(wg * 32 + it);
        if (it == qb || it == 8) {
          const int e = nh;
          float t[16];
          if (it < 8) {
            if (tid == 0) PROF_MARK(11);
            mbar_wait(BAR(B_KVR), 0);
            const uint64_t dR = make_desc(sb + OFF_KVR + e * 4096, 512, 512, 2);
            const uint64_t dP = make_desc(sb + OFF_PHIQ + e * 16384 + mh * 8192, 1024, 1024, 1);
            wg_fence();
            wgmma_ss_n32_ta0_tb1<0>(t, dP, dR);
#pragma unroll
            for (int ks = 1; ks < 4; ks++) wgmma_ss_n32_ta0_tb1<1>(t, dP + ks * 2, dR + ks * 64);
            wg_commit();
            wg_wait<0>();
            fence_regs(t);
            if (lane == 0) mbar_arrive(BAR(B_X1FREE), 1);
          } else {
            if (tid == 0) PROF_MARK(13);
            mbar_wait(BAR(B_SLOW), 0);
            if (__builtin_expect(__any_sync(~0u, *(volatile int*)(sgen + OFF_RED)), 0)) {
              uint32_t qz[8];
#pragma unroll
              for (int i = 0; i < 8; i++) qz[i] = (i >= 6 && lq >= 2) ? 0u : q[i];
              float m0 = -3.0e38f, m1 = -3.0e38f, o2[16];
              int sl2 = slot;
              uint32_t par2 = par;
#pragma unroll 1
              for (int j64 = 0; j64 < 32; j64++) {
                float s[32];
                mbar_wait(BAR(B_FULL + sl2), par2);
                const uint32_t lo = dlo0 + sl2 * 2048 + (j64 & 3) * 512;
                wg_fence();
                wgmma_rs_n64_tb0<0>(s, qz[0], qz[1], qz[2], qz[3], dhi | lo);
                wgmma_rs_n64_tb0<1>(s, qz[4], qz[5], qz[6], qz[7], dhi | (lo + 2));
                wg_commit();
                wg_wait<0>();
                fence_regs(s);
#pragma unroll
                for (int j = 0; j < 8; j++) {
                  const float sc = ((POLY_PAT >> j) & 1) ? 0.5f : 1.f;
                  m0 = fmaxf(m0, fmaxf(s[4 * j], s[4 * j + 1]) * sc);
                  m1 = fmaxf(m1, fmaxf(s[4 * j + 2], s[4 * j + 3]) * sc);
                }
                if ((j64 & 3) == 3) {
                  if (lane == 0) mbar_arrive(BAR(B_EMPTY + sl2), 1);
                  if (++sl2 == 3) { sl2 = 0; par2 ^= 1; }
                }
              }
              m0 = quad_max(m0); m1 = quad_max(m1);
#pragma unroll
              for (int i = 0; i < 16; i++) o2[i] = 0.f;
#pragma unroll 1
              for (int j64 = 0; j64 < 32; j64++) {
                float s[32];
                mbar_wait(BAR(B_FULL + sl2), par2);
                const uint32_t lo = dlo0 + sl2 * 2048 + (j64 & 3) * 512;
                wg_fence();
                wgmma_rs_n64_tb0<0>(s, qz[0], qz[1], qz[2], qz[3], dhi | lo);
                wgmma_rs_n64_tb0<1>(s, qz[4], qz[5], qz[6], qz[7], dhi | (lo + 2));
                wg_commit();
                wg_wait<0>();
                fence_regs(s);
                uint32_t ps[16];
#pragma unroll
                for (int j = 0; j < 8; j++) {
                  const float sc = ((POLY_PAT >> j) & 1) ? 0.5f : 1.f;
                  ps[2 * j] = pack_bf16(ex2f(fmaf(s[4 * j], sc, -m0)), ex2f(fmaf(s[4 * j + 1], sc, -m0)));
                  ps[2 * j + 1] = pack_bf16(ex2f(fmaf(s[4 * j + 2], sc, -m1)), ex2f(fmaf(s[4 * j + 3], sc, -m1)));
                }
                wg_fence();
#pragma unroll
                for (int ks = 0; ks < 4; ks++)
                  wgmma_rs_n32_tb1<1>(o2, ps[4 * ks], ps[4 * ks + 1], ps[4 * ks + 2], ps[4 * ks + 3], dhi | (lo + 256 + ks * 64));
                wg_commit();
                wg_wait<0>();
                fence_regs(o2);
                if ((j64 & 3) == 3) {
                  if (lane == 0) mbar_arrive(BAR(B_EMPTY + sl2), 1);
                  if (++sl2 == 3) { sl2 = 0; par2 ^= 1; }
                }
              }
#pragma unroll 1
              for (int j = 0; j < 2; j++) {
                mbar_wait(BAR(B_FULL + sl2), par2);
                __syncwarp();
                if (lane == 0) mbar_arrive(BAR(B_EMPTY + sl2), 1);
                if (++sl2 == 3) { sl2 = 0; par2 ^= 1; }
              }
#pragma unroll
              for (int i = 0; i < 16; i++) o[i] = o2[i];
            }
#pragma unroll
            for (int i = 0; i < 16; i++) t[i] = o[i];
#pragma unroll
            for (int i = 0; i < 32; i++) s[i] = 0.f;
          }
          const int br = it == 8;
          const float eps = br ? 0.f : 1e-6f;
          const float g0 = ((const float*)(sgen + OFF_GATE))[row0], g1 = ((const float*)(sgen + OFF_GATE))[row0 + 8];
          const float d0 = __shfl_sync(~0u, t[12], (lane & ~3) | 2), d1 = __shfl_sync(~0u, t[14], (lane & ~3) | 2);
          const float r0 = (br ? 1.f - g0 : g0) * rcpf(d0 + eps), r1 = (br ? 1.f - g1 : g1) * rcpf(d1 + eps);
          uint8_t* img = g_o_img + (size_t)((pt * 2 + br) * 14 + mh) * 8192 + rowl * 128;
          const int col0 = (2 * hp + e) * DH + 2 * lq;
#pragma unroll
          for (int j = 0; j < 4; j++) {
            const int col = col0 + 8 * j;
            uint8_t* gp = img + (uint32_t)((col >> 6) * 16384 + ((((col >> 3) ^ rowl) & 7) << 4) + (col & 7) * 2);
            const uint32_t v0 = pack_bf16(t[4 * j] * r0, t[4 * j + 1] * r0), v1 = pack_bf16(t[4 * j + 2] * r1, t[4 * j + 3] * r1);
            if (j < 3 || lq < 2) { *(uint32_t*)gp = v0; *(uint32_t*)(gp + 1024) = v1; }
          }
          __syncwarp();
          if (lane == 0) mbar_arrive(BAR(B_SIG + 2 + br), 1);
          if (tid == 0) PROF_MARK(12 + 2 * br);
          if (br) { if ((tid & 127) == 0) PROF4(wg * 32 + 9); break; }
        }
        const uint32_t lo = dlo0 + slot * 2048;
        int nslot = slot + 1;
        uint32_t npar = par;
        if (nslot == 3) { nslot = 0; npar ^= 1; }
#pragma unroll
        for (int u = 0; u < 4; u++) {
          if (u == 2) ok = mbar_test(BAR(B_FULL + nslot), npar);
#pragma unroll
          for (int j = 0; j < 8; j++) {
            if ((POLY_PAT >> j) & 1) {
              p[2 * j] = exp2_pair_fma(s[4 * j], s[4 * j + 1], 0x3F003F00u, 0x00030003u);
              p[2 * j + 1] = exp2_pair_fma(s[4 * j + 2], s[4 * j + 3], 0x3F003F00u, 0x00030003u);
            } else {
              p[2 * j] = pack_bf16(ex2f(s[4 * j]), ex2f(s[4 * j + 1]));
              p[2 * j + 1] = pack_bf16(ex2f(s[4 * j + 2]), ex2f(s[4 * j + 3]));
            }
          }
          if (u == 3 && !ok && it < 7) mbar_wait(BAR(B_FULL + nslot), npar);
          const uint32_t ln = u < 3 ? lo + (u + 1) * 512 : dlo0 + nslot * 2048;
          wg_fence();
#pragma unroll
          for (int ks = 0; ks < 4; ks++)
            wgmma_rs_n32_tb1<1>(o, p[4 * ks], p[4 * ks + 1], p[4 * ks + 2], p[4 * ks + 3], dhi | (lo + u * 512 + 256 + ks * 64));
          wgmma_rs_n64_tb0<0>(s, q[0], q[1], q[2], q[3], dhi | ln);
          wgmma_rs_n64_tb0<1>(s, q[4], q[5], q[6], q[7], dhi | (ln + 2));
          wg_commit();
          wg_wait<0>();
          fence_regs(s);
          fence_regs(o);
        }
        if (lane == 0) mbar_arrive(BAR(B_EMPTY + slot), 1);
        slot = nslot; par = npar;
      }
      wg_wait<0>();
    }
    if (nh == 1) return;
    {
      float acc0[28], acc1[28];
#pragma unroll
      for (int i = 0; i < 28; i++) acc0[i] = acc1[i] = 0.f;
      const uint64_t dS = make_desc(sb + OFF_WO, 1024, 1024, 1);
      const uint64_t dR = make_desc(sb + OFF_RING + mh * 8192, 1024, 1024, 1);
#pragma unroll 1
      for (int c = 0; c < 7; c++) {
        mbar_wait(BAR(B_WO + (c >= 3)), 0);
        mbar_wait(BAR(B_FULL + slot), par);
        const uint64_t dA = dR + slot * 2048, dB = dS + c * 1024;
        wg_fence();
#pragma unroll
        for (int ks = 0; ks < 4; ks++) {
          wgmma_ss_n56_ta0_tb1<1>(acc0, dA + ks * 2, dB + ks * 128);
          wgmma_ss_n56_ta0_tb1<1>(acc1, dA + 1024 + ks * 2, dB + 512 + ks * 128);
        }
        wg_commit();
        if (c < 4) {
          wg_wait<0>();
          if (lane == 0) mbar_arrive(BAR(B_EMPTY + slot), 2);
        }
        if (++slot == 3) { slot = 0; par ^= 1; }
      }
      wg_wait<0>();
      fence_regs(acc0); fence_regs(acc1);
      if (tid == 0) PROF_MARK(17);
      __nv_bfloat16* op = prm.out + (size_t)(pt * 128 + row0) * DM + hp * 56 + 2 * lq;
#pragma unroll
      for (int j = 0; j < 7; j++) {
        *(uint32_t*)(op + 8 * j) = pack_bf16(acc0[4 * j] + acc1[4 * j], acc0[4 * j + 1] + acc1[4 * j + 1]);
        *(uint32_t*)(op + 8 * DM + 8 * j) = pack_bf16(acc0[4 * j + 2] + acc1[4 * j + 2], acc0[4 * j + 3] + acc1[4 * j + 3]);
      }
      if (tid == 0) { PROF_MARK(18); PROF_CLK(31); }
    }
  }
}

typedef CUresult (*EncodeFn)(CUtensorMap*, CUtensorMapDataType, cuuint32_t, void*, const cuuint64_t*, const cuuint64_t*,
                             const cuuint32_t*, const cuuint32_t*, CUtensorMapInterleave, CUtensorMapSwizzle,
                             CUtensorMapL2promotion, CUtensorMapFloatOOBfill);

void make_map(EncodeFn enc, CUtensorMap* tm, const void* ptr, uint64_t cols, uint64_t rows, uint32_t box_cols, uint32_t box_rows) {
  cuuint64_t dims[2] = {cols, rows};
  cuuint64_t strides[1] = {cols * 2};
  cuuint32_t box[2] = {box_cols, box_rows};
  cuuint32_t es[2] = {1, 1};
  enc(tm, CU_TENSOR_MAP_DATA_TYPE_BFLOAT16, 2, const_cast<void*>(ptr), dims, strides, box, es, CU_TENSOR_MAP_INTERLEAVE_NONE,
      CU_TENSOR_MAP_SWIZZLE_128B, CU_TENSOR_MAP_L2_PROMOTION_L2_128B, CU_TENSOR_MAP_FLOAT_OOB_FILL_NONE);
}

}

extern "C" void kernel_launch(void* const* d_in, const int* in_sizes, int n_in, void* d_out, int out_size) {
  (void)in_sizes; (void)n_in; (void)out_size;
  static EncodeFn enc = nullptr;
  if (!enc) {
    void* fn = nullptr;
    cudaDriverEntryPointQueryResult qr;
    cudaGetDriverEntryPoint("cuTensorMapEncodeTiled", &fn, cudaEnableDefault, &qr);
    enc = (EncodeFn)fn;
    cudaFuncSetAttribute(fused_kernel, cudaFuncAttributeMaxDynamicSharedMemorySize, SMEM_BYTES);
  }
  CUtensorMap tm_x, tm_wqkv, tm_wq, tm_woa, tm_wob;
  make_map(enc, &tm_x, d_in[0], DM, S_LEN, 64, 128);
  make_map(enc, &tm_wqkv, d_in[1], 3 * DM, DM, 56, 64);
  make_map(enc, &tm_wq, d_in[5], DM, DM, 56, 64);
  make_map(enc, &tm_woa, d_in[3], DM, DM, 56, 64);
  make_map(enc, &tm_wob, d_in[8], DM, DM, 56, 64);
  Params prm;
  prm.w_phi = (const __nv_bfloat16*)d_in[2];
  prm.wk = (const __nv_bfloat16*)d_in[6];
  prm.wv = (const __nv_bfloat16*)d_in[7];
  prm.gate_w = (const __nv_bfloat16*)d_in[9];
  prm.out = (__nv_bfloat16*)d_out;
  fused_kernel<<<NCTA, NTHREADS, SMEM_BYTES>>>(tm_x, tm_wqkv, tm_wq, tm_woa, tm_wob, prm);
}
```

```cpp
#include <cuda_runtime.h>
#include <cuda_bf16.h>
#include <cuda.h>
#include <stdint.h>

namespace {

constexpr int S_LEN = 2048, DM = 448, DH = 28;
constexpr int NCTA = 128;
constexpr int NTHREADS = 640;
constexpr uint32_t POLY_PAT = 0x57;

#define QB_AT (4 + (wg >> 1))

constexpr int OFF_X = 0;
constexpr int OFF_PHIK = 0;
constexpr int OFF_VA = 32768;
constexpr int OFF_PHIQ = 57344;
constexpr int OFF_KVR = 90112;
constexpr int OFF_QP = 98304;
constexpr int OFF_RAW = 81920;
constexpr int OFF_WO = 0;
constexpr int OFF_RING = 114688;
constexpr int OFF_WBD = 212992;
constexpr int OFF_SLC = 221184;
constexpr int OFF_QSQ = 228352;
constexpr int OFF_OSTG = 212992;
constexpr int OFF_GATE = 229376;
constexpr int OFF_RED = 229888;
constexpr int OFF_BAR = 229952;
constexpr int SMEM_BYTES = 230400 + 1024;

constexpr int B_FULL = 0, B_EMPTY = 3, B_WO = 6  , B_KVR = 8, B_RAW = 9, B_X1FREE = 10, B_QSQ = 11, B_SLOW = 12,
              B_BUILD = 13, B_SIG = 14  , B_XL = 18  , B_N = 20;

constexpr int C_KV = 0, C_PART = 1, C_DONE = 3, C_OA = 4, C_OB = 20, C_N = 36;

__device__ __align__(1024) uint8_t g_kv_img[32 * 8192];
__device__ __align__(16) float g_ksq[512];
__device__ __align__(16) float g_vsq[512];
__device__ __align__(16) float g_gate[S_LEN];
__device__ __align__(1024) float g_kvacc[2][16 * 64 * 32];
__device__ unsigned g_epoch;
__device__ __align__(1024) uint8_t g_o_img[16 * 2 * 16 * 2 * 4096];
__device__ __align__(128) unsigned g_cnt[C_N * 32];

#define PROF4(i) do { } while (0)
#define PROF3(i) do { } while (0)
#define PROF2(i) do { } while (0)
#define PROF_CLK(i) do { } while (0)
#define PROF_MARK(i) do { } while (0)
__device__ __forceinline__ uint32_t smem_u32(const void* p) { return (uint32_t)__cvta_generic_to_shared(p); }
__device__ __forceinline__ void mbar_init(uint32_t a, int cnt) {
  asm volatile("mbarrier.init.shared::cta.b64 [%0], %1;" ::"r"(a), "r"(cnt) : "memory");
}
__device__ __forceinline__ void mbar_expect_tx(uint32_t a, uint32_t bytes) {
  asm volatile("mbarrier.arrive.expect_tx.shared::cta.b64 _, [%0], %1;" ::"r"(a), "r"(bytes) : "memory");
}
__device__ __forceinline__ void mbar_arrive(uint32_t a, uint32_t cnt) {
  asm volatile("mbarrier.arrive.shared::cta.b64 _, [%0], %1;" ::"r"(a), "r"(cnt) : "memory");
}
__device__ __forceinline__ void mbar_wait(uint32_t a, uint32_t parity) {
  asm volatile(
      "{\n.reg .pred p;\n.reg .u32 c;\nmov.u32 c, 0;\n"
      "W_%=:\nmbarrier.try_wait.parity.shared::cta.b64 p, [%0], %1;\n"
      "add.u32 c, c, 1;\nsetp.lt.and.u32 p, c, 0x40000, !p;\n@p bra W_%=;\n}"
      ::"r"(a), "r"(parity) : "memory");
}
__device__ __forceinline__ uint32_t mbar_test(uint32_t a, uint32_t parity) {
  uint32_t ok;
  asm volatile("{\n.reg .pred p;\nmbarrier.test_wait.parity.shared::cta.b64 p, [%1], %2;\nselp.u32 %0, 1, 0, p;\n}"
               : "=r"(ok) : "r"(a), "r"(parity) : "memory");
  return ok;
}
__device__ __forceinline__ bool elect_one() {
  uint32_t r;
  asm volatile("{\n.reg .pred p;\nelect.sync _|p, 0xffffffff;\nselp.u32 %0, 1, 0, p;\n}" : "=r"(r));
  return r != 0;
}
__device__ __forceinline__ void tma_2d(uint32_t dst, const CUtensorMap* tm, int c0, int c1, uint32_t bar) {
  asm volatile("cp.async.bulk.tensor.2d.shared::cluster.global.mbarrier::complete_tx::bytes [%0], [%1, {%3, %4}], [%2];"
               ::"r"(dst), "l"(tm), "r"(bar), "r"(c0), "r"(c1) : "memory");
}
__device__ __forceinline__ void bulk_g2s(uint32_t dst, const void* src, uint32_t bytes, uint32_t bar) {
  asm volatile("cp.async.bulk.shared::cluster.global.mbarrier::complete_tx::bytes [%0], [%1], %2, [%3];"
               ::"r"(dst), "l"(src), "r"(bytes), "r"(bar) : "memory");
}
__device__ __forceinline__ void fence_async_smem() { asm volatile("fence.proxy.async.shared::cta;" ::: "memory"); }
__device__ __forceinline__ void fence_async_all() { asm volatile("fence.proxy.async.global;" ::: "memory"); }

__device__ __forceinline__ void bar_sync(int id, int n) { asm volatile("bar.sync %0, %1;" ::"r"(id), "r"(n) : "memory"); }
__device__ __forceinline__ void cnt_wait(int idx, unsigned target) {
  unsigned v, n = 0;
#pragma unroll 1
  while (true) {
    asm volatile("ld.acquire.gpu.global.u32 %0, [%1];" : "=r"(v) : "l"(&g_cnt[idx * 32]) : "memory");
    if (v >= target || ++n >= (1u << 18)) break;
    __nanosleep(32);
  }
}
__device__ __forceinline__ void wg_fence() { asm volatile("wgmma.fence.sync.aligned;" ::: "memory"); }
__device__ __forceinline__ void wg_commit() { asm volatile("wgmma.commit_group.sync.aligned;" ::: "memory"); }
template <int N> __device__ __forceinline__ void wg_wait() { asm volatile("wgmma.wait_group.sync.aligned %0;" ::"n"(N) : "memory"); }
template <int N> __device__ __forceinline__ void fence_regs(float (&d)[N]) {
#pragma unroll
  for (int i = 0; i < N; i++) asm volatile("" : "+f"(d[i])::"memory");
}
__device__ __forceinline__ uint64_t make_desc(uint32_t saddr, uint32_t lbo, uint32_t sbo, uint32_t swz) {
  return (uint64_t)((saddr & 0x3FFFF) >> 4) | ((uint64_t)(lbo >> 4) << 16) | ((uint64_t)(sbo >> 4) << 32) | ((uint64_t)swz << 62);
}
__device__ __forceinline__ float ex2f(float x) { float y; asm("ex2.approx.ftz.f32 %0, %1;" : "=f"(y) : "f"(x)); return y; }
__device__ __forceinline__ float rcpf(float x) { float y; asm("rcp.approx.ftz.f32 %0, %1;" : "=f"(y) : "f"(x)); return y; }
__device__ __forceinline__ uint32_t pack_bf16(float lo, float hi) {
  uint32_t r; asm("cvt.rn.bf16x2.f32 %0, %1, %2;" : "=r"(r) : "f"(hi), "f"(lo)); return r;
}
__device__ __forceinline__ uint32_t lop_and_or(uint32_t a, uint32_t m, uint32_t c) {
  uint32_t r; asm("lop3.b32 %0, %1, %2, %3, 0xEA;" : "=r"(r) : "r"(a), "r"(m), "r"(c)); return r;
}
__device__ __forceinline__ void sts32(uint32_t a, uint32_t v) { asm volatile("st.shared.b32 [%0], %1;" ::"r"(a), "r"(v) : "memory"); }
__device__ __forceinline__ void st_shared_nv(uint32_t a, uint32_t v) { asm volatile("st.shared.b32 [%0], %1;" ::"r"(a), "r"(v)); }
__device__ __forceinline__ void sts64(uint32_t a, uint32_t v0, uint32_t v1) { asm volatile("st.shared.v2.b32 [%0], {%1, %2};" ::"r"(a), "r"(v0), "r"(v1) : "memory"); }
__device__ __forceinline__ void sts128(uint32_t a, uint4 v) {
  asm volatile("st.shared.v4.b32 [%0], {%1, %2, %3, %4};" ::"r"(a), "r"(v.x), "r"(v.y), "r"(v.z), "r"(v.w) : "memory");
}
__device__ __forceinline__ float4 ldcg_f4(const float* p) {
  float4 v; asm volatile("ld.global.cg.v4.f32 {%0, %1, %2, %3}, [%4];" : "=f"(v.x), "=f"(v.y), "=f"(v.z), "=f"(v.w) : "l"(p) : "memory"); return v;
}
__device__ __forceinline__ void ldsm4(uint32_t* r, uint32_t a) {
  asm volatile("ldmatrix.sync.aligned.m8n8.x4.shared.b16 {%0, %1, %2, %3}, [%4];"
               : "=r"(r[0]), "=r"(r[1]), "=r"(r[2]), "=r"(r[3]) : "r"(a) : "memory");
}
__device__ __forceinline__ float quad_sum(float v) { v += __shfl_xor_sync(~0u, v, 1); v += __shfl_xor_sync(~0u, v, 2); return v; }
__device__ __forceinline__ float quad_max(float v) { v = fmaxf(v, __shfl_xor_sync(~0u, v, 1)); v = fmaxf(v, __shfl_xor_sync(~0u, v, 2)); return v; }

template <int SD> __device__ __forceinline__ void wgmma_ss_n56_ta0_tb1(float (&d)[28], uint64_t da, uint64_t db) {
  if (SD) asm volatile("wgmma.mma_async.sync.aligned.m64n56k16.f32.bf16.bf16 {%0, %1, %2, %3, %4, %5, %6, %7, %8, %9, %10, %11, %12, %13, %14, %15, %16, %17, %18, %19, %20, %21, %22, %23, %24, %25, %26, %27}, %28, %29, 1, 1, 1, 0, 1;\n"
    : "+f"(d[0]), "+f"(d[1]), "+f"(d[2]), "+f"(d[3]), "+f"(d[4]), "+f"(d[5]), "+f"(d[6]), "+f"(d[7]), "+f"(d[8]), "+f"(d[9]), "+f"(d[10]), "+f"(d[11]), "+f"(d[12]), "+f"(d[13]), "+f"(d[14]), "+f"(d[15]), "+f"(d[16]), "+f"(d[17]), "+f"(d[18]), "+f"(d[19]), "+f"(d[20]), "+f"(d[21]), "+f"(d[22]), "+f"(d[23]), "+f"(d[24]), "+f"(d[25]), "+f"(d[26]), "+f"(d[27])
    : "l"(da), "l"(db));
  else asm volatile("wgmma.mma_async.sync.aligned.m64n56k16.f32.bf16.bf16 {%0, %1, %2, %3, %4, %5, %6, %7, %8, %9, %10, %11, %12, %13, %14, %15, %16, %17, %18, %19, %20, %21, %22, %23, %24, %25, %26, %27}, %28, %29, 0, 1, 1, 0, 1;\n"
    : "=f"(d[0]), "=f"(d[1]), "=f"(d[2]), "=f"(d[3]), "=f"(d[4]), "=f"(d[5]), "=f"(d[6]), "=f"(d[7]), "=f"(d[8]), "=f"(d[9]), "=f"(d[10]), "=f"(d[11]), "=f"(d[12]), "=f"(d[13]), "=f"(d[14]), "=f"(d[15]), "=f"(d[16]), "=f"(d[17]), "=f"(d[18]), "=f"(d[19]), "=f"(d[20]), "=f"(d[21]), "=f"(d[22]), "=f"(d[23]), "=f"(d[24]), "=f"(d[25]), "=f"(d[26]), "=f"(d[27])
    : "l"(da), "l"(db));
}
template <int SD> __device__ __forceinline__ void wgmma_ss_n8_ta0_tb1(float (&d)[4], uint64_t da, uint64_t db) {
  if (SD) asm volatile("wgmma.mma_async.sync.aligned.m64n8k16.f32.bf16.bf16 {%0, %1, %2, %3}, %4, %5, 1, 1, 1, 0, 1;\n"
    : "+f"(d[0]), "+f"(d[1]), "+f"(d[2]), "+f"(d[3])
    : "l"(da), "l"(db));
  else asm volatile("wgmma.mma_async.sync.aligned.m64n8k16.f32.bf16.bf16 {%0, %1, %2, %3}, %4, %5, 0, 1, 1, 0, 1;\n"
    : "=f"(d[0]), "=f"(d[1]), "=f"(d[2]), "=f"(d[3])
    : "l"(da), "l"(db));
}
template <int SD> __device__ __forceinline__ void wgmma_rs_n64_tb1(float (&d)[32], uint32_t a0, uint32_t a1, uint32_t a2, uint32_t a3, uint64_t db) {
  if (SD) asm volatile("wgmma.mma_async.sync.aligned.m64n64k16.f32.bf16.bf16 {%0, %1, %2, %3, %4, %5, %6, %7, %8, %9, %10, %11, %12, %13, %14, %15, %16, %17, %18, %19, %20, %21, %22, %23, %24, %25, %26, %27, %28, %29, %30, %31}, {%32, %33, %34, %35}, %36, 1, 1, 1, 1;\n"
    : "+f"(d[0]), "+f"(d[1]), "+f"(d[2]), "+f"(d[3]), "+f"(d[4]), "+f"(d[5]), "+f"(d[6]), "+f"(d[7]), "+f"(d[8]), "+f"(d[9]), "+f"(d[10]), "+f"(d[11]), "+f"(d[12]), "+f"(d[13]), "+f"(d[14]), "+f"(d[15]), "+f"(d[16]), "+f"(d[17]), "+f"(d[18]), "+f"(d[19]), "+f"(d[20]), "+f"(d[21]), "+f"(d[22]), "+f"(d[23]), "+f"(d[24]), "+f"(d[25]), "+f"(d[26]), "+f"(d[27]), "+f"(d[28]), "+f"(d[29]), "+f"(d[30]), "+f"(d[31])
    : "r"(a0), "r"(a1), "r"(a2), "r"(a3), "l"(db));
  else asm volatile("wgmma.mma_async.sync.aligned.m64n64k16.f32.bf16.bf16 {%0, %1, %2, %3, %4, %5, %6, %7, %8, %9, %10, %11, %12, %13, %14, %15, %16, %17, %18, %19, %20, %21, %22, %23, %24, %25, %26, %27, %28, %29, %30, %31}, {%32, %33, %34, %35}, %36, 0, 1, 1, 1;\n"
    : "=f"(d[0]), "=f"(d[1]), "=f"(d[2]), "=f"(d[3]), "=f"(d[4]), "=f"(d[5]), "=f"(d[6]), "=f"(d[7]), "=f"(d[8]), "=f"(d[9]), "=f"(d[10]), "=f"(d[11]), "=f"(d[12]), "=f"(d[13]), "=f"(d[14]), "=f"(d[15]), "=f"(d[16]), "=f"(d[17]), "=f"(d[18]), "=f"(d[19]), "=f"(d[20]), "=f"(d[21]), "=f"(d[22]), "=f"(d[23]), "=f"(d[24]), "=f"(d[25]), "=f"(d[26]), "=f"(d[27]), "=f"(d[28]), "=f"(d[29]), "=f"(d[30]), "=f"(d[31])
    : "r"(a0), "r"(a1), "r"(a2), "r"(a3), "l"(db));
}
template <int SD> __device__ __forceinline__ void wgmma_ss_n32_ta1_tb1(float (&d)[16], uint64_t da, uint64_t db) {
  if (SD) asm volatile("wgmma.mma_async.sync.aligned.m64n32k16.f32.bf16.bf16 {%0, %1, %2, %3, %4, %5, %6, %7, %8, %9, %10, %11, %12, %13, %14, %15}, %16, %17, 1, 1, 1, 1, 1;\n"
    : "+f"(d[0]), "+f"(d[1]), "+f"(d[2]), "+f"(d[3]), "+f"(d[4]), "+f"(d[5]), "+f"(d[6]), "+f"(d[7]), "+f"(d[8]), "+f"(d[9]), "+f"(d[10]), "+f"(d[11]), "+f"(d[12]), "+f"(d[13]), "+f"(d[14]), "+f"(d[15])
    : "l"(da), "l"(db));
  else asm volatile("wgmma.mma_async.sync.aligned.m64n32k16.f32.bf16.bf16 {%0, %1, %2, %3, %4, %5, %6, %7, %8, %9, %10, %11, %12, %13, %14, %15}, %16, %17, 0, 1, 1, 1, 1;\n"
    : "=f"(d[0]), "=f"(d[1]), "=f"(d[2]), "=f"(d[3]), "=f"(d[4]), "=f"(d[5]), "=f"(d[6]), "=f"(d[7]), "=f"(d[8]), "=f"(d[9]), "=f"(d[10]), "=f"(d[11]), "=f"(d[12]), "=f"(d[13]), "=f"(d[14]), "=f"(d[15])
    : "l"(da), "l"(db));
}
template <int SD> __device__ __forceinline__ void wgmma_ss_n32_ta0_tb1(float (&d)[16], uint64_t da, uint64_t db) {
  if (SD) asm volatile("wgmma.mma_async.sync.aligned.m64n32k16.f32.bf16.bf16 {%0, %1, %2, %3, %4, %5, %6, %7, %8, %9, %10, %11, %12, %13, %14, %15}, %16, %17, 1, 1, 1, 0, 1;\n"
    : "+f"(d[0]), "+f"(d[1]), "+f"(d[2]), "+f"(d[3]), "+f"(d[4]), "+f"(d[5]), "+f"(d[6]), "+f"(d[7]), "+f"(d[8]), "+f"(d[9]), "+f"(d[10]), "+f"(d[11]), "+f"(d[12]), "+f"(d[13]), "+f"(d[14]), "+f"(d[15])
    : "l"(da), "l"(db));
  else asm volatile("wgmma.mma_async.sync.aligned.m64n32k16.f32.bf16.bf16 {%0, %1, %2, %3, %4, %5, %6, %7, %8, %9, %10, %11, %12, %13, %14, %15}, %16, %17, 0, 1, 1, 0, 1;\n"
    : "=f"(d[0]), "=f"(d[1]), "=f"(d[2]), "=f"(d[3]), "=f"(d[4]), "=f"(d[5]), "=f"(d[6]), "=f"(d[7]), "=f"(d[8]), "=f"(d[9]), "=f"(d[10]), "=f"(d[11]), "=f"(d[12]), "=f"(d[13]), "=f"(d[14]), "=f"(d[15])
    : "l"(da), "l"(db));
}
template <int SD> __device__ __forceinline__ void wgmma_rs_n64_tb0(float (&d)[32], uint32_t a0, uint32_t a1, uint32_t a2, uint32_t a3, uint64_t db) {
  if (SD) asm volatile("wgmma.mma_async.sync.aligned.m64n64k16.f32.bf16.bf16 {%0, %1, %2, %3, %4, %5, %6, %7, %8, %9, %10, %11, %12, %13, %14, %15, %16, %17, %18, %19, %20, %21, %22, %23, %24, %25, %26, %27, %28, %29, %30, %31}, {%32, %33, %34, %35}, %36, 1, 1, 1, 0;\n"
    : "+f"(d[0]), "+f"(d[1]), "+f"(d[2]), "+f"(d[3]), "+f"(d[4]), "+f"(d[5]), "+f"(d[6]), "+f"(d[7]), "+f"(d[8]), "+f"(d[9]), "+f"(d[10]), "+f"(d[11]), "+f"(d[12]), "+f"(d[13]), "+f"(d[14]), "+f"(d[15]), "+f"(d[16]), "+f"(d[17]), "+f"(d[18]), "+f"(d[19]), "+f"(d[20]), "+f"(d[21]), "+f"(d[22]), "+f"(d[23]), "+f"(d[24]), "+f"(d[25]), "+f"(d[26]), "+f"(d[27]), "+f"(d[28]), "+f"(d[29]), "+f"(d[30]), "+f"(d[31])
    : "r"(a0), "r"(a1), "r"(a2), "r"(a3), "l"(db));
  else asm volatile("wgmma.mma_async.sync.aligned.m64n64k16.f32.bf16.bf16 {%0, %1, %2, %3, %4, %5, %6, %7, %8, %9, %10, %11, %12, %13, %14, %15, %16, %17, %18, %19, %20, %21, %22, %23, %24, %25, %26, %27, %28, %29, %30, %31}, {%32, %33, %34, %35}, %36, 0, 1, 1, 0;\n"
    : "=f"(d[0]), "=f"(d[1]), "=f"(d[2]), "=f"(d[3]), "=f"(d[4]), "=f"(d[5]), "=f"(d[6]), "=f"(d[7]), "=f"(d[8]), "=f"(d[9]), "=f"(d[10]), "=f"(d[11]), "=f"(d[12]), "=f"(d[13]), "=f"(d[14]), "=f"(d[15]), "=f"(d[16]), "=f"(d[17]), "=f"(d[18]), "=f"(d[19]), "=f"(d[20]), "=f"(d[21]), "=f"(d[22]), "=f"(d[23]), "=f"(d[24]), "=f"(d[25]), "=f"(d[26]), "=f"(d[27]), "=f"(d[28]), "=f"(d[29]), "=f"(d[30]), "=f"(d[31])
    : "r"(a0), "r"(a1), "r"(a2), "r"(a3), "l"(db));
}
template <int SD> __device__ __forceinline__ void wgmma_rs_n32_tb1(float (&d)[16], uint32_t a0, uint32_t a1, uint32_t a2, uint32_t a3, uint64_t db) {
  if (SD) asm volatile("wgmma.mma_async.sync.aligned.m64n32k16.f32.bf16.bf16 {%0, %1, %2, %3, %4, %5, %6, %7, %8, %9, %10, %11, %12, %13, %14, %15}, {%16, %17, %18, %19}, %20, 1, 1, 1, 1;\n"
    : "+f"(d[0]), "+f"(d[1]), "+f"(d[2]), "+f"(d[3]), "+f"(d[4]), "+f"(d[5]), "+f"(d[6]), "+f"(d[7]), "+f"(d[8]), "+f"(d[9]), "+f"(d[10]), "+f"(d[11]), "+f"(d[12]), "+f"(d[13]), "+f"(d[14]), "+f"(d[15])
    : "r"(a0), "r"(a1), "r"(a2), "r"(a3), "l"(db));
  else asm volatile("wgmma.mma_async.sync.aligned.m64n32k16.f32.bf16.bf16 {%0, %1, %2, %3, %4, %5, %6, %7, %8, %9, %10, %11, %12, %13, %14, %15}, {%16, %17, %18, %19}, %20, 0, 1, 1, 1;\n"
    : "=f"(d[0]), "=f"(d[1]), "=f"(d[2]), "=f"(d[3]), "=f"(d[4]), "=f"(d[5]), "=f"(d[6]), "=f"(d[7]), "=f"(d[8]), "=f"(d[9]), "=f"(d[10]), "=f"(d[11]), "=f"(d[12]), "=f"(d[13]), "=f"(d[14]), "=f"(d[15])
    : "r"(a0), "r"(a1), "r"(a2), "r"(a3), "l"(db));
}

__device__ __forceinline__ uint32_t sw64_off(int row, int d) { return row * 64 + ((((d >> 3) ^ (row >> 1)) & 3) << 4) + (d & 7) * 2; }

__device__ __forceinline__ uint32_t exp2_pair_fma(float t0, float t1, uint32_t c_half, uint32_t c_3) {
  uint32_t y0, y;
  asm("prmt.b32 %0, %1, %2, 0x6521;" : "=r"(y0) : "r"(__float_as_uint(t0)), "r"(__float_as_uint(t1)));
  uint32_t h = lop_and_or(y0, 0x007F007Fu, c_half);
  uint32_t e = lop_and_or(y0, 0xFF80FF80u, c_3);
  asm("fma.rn.bf16x2 %0, %1, %2, %3;" : "=r"(y) : "r"(y0), "r"(h), "r"(e));
  return y;
}

__device__ __forceinline__ void feature_map(float (&p)[32], uint32_t rb, int lq) {
  const float L2E = 1.4426950408889634f;
  const bool tail_ok = lq < 2;
  float mx[4], mn[4], b[32], sa[4], sn[4];
#pragma unroll
  for (int g = 0; g < 4; g++) {
    const int o = 16 * (g >> 1) + 2 * (g & 1);
    if (!tail_ok) { p[o + 12] = p[o]; p[o + 13] = p[o]; }
    mx[g] = fmaxf(fmaxf(fmaxf(p[o], p[o + 1]), fmaxf(p[o + 4], p[o + 5])), fmaxf(fmaxf(p[o + 8], p[o + 9]), fmaxf(p[o + 12], p[o + 13])));
    mn[g] = fminf(fminf(fminf(p[o], p[o + 1]), fminf(p[o + 4], p[o + 5])), fminf(fminf(p[o + 8], p[o + 9]), fminf(p[o + 12], p[o + 13])));
  }
#pragma unroll
  for (int o = 1; o <= 2; o <<= 1)
#pragma unroll
    for (int g = 0; g < 4; g++) { mx[g] = fmaxf(mx[g], __shfl_xor_sync(~0u, mx[g], o)); mn[g] = fminf(mn[g], __shfl_xor_sync(~0u, mn[g], o)); }
#pragma unroll
  for (int g = 0; g < 4; g++) {
    const int o = 16 * (g >> 1) + 2 * (g & 1);
    const float cx = -mx[g] * L2E, cn = mn[g] * L2E;
#pragma unroll
    for (int i = 0; i < 8; i++) {
      const int k = o + 4 * (i >> 1) + (i & 1);
      b[k] = ex2f(fmaf(p[k], -L2E, cn));
      p[k] = ex2f(fmaf(p[k], L2E, cx));
    }
    if (!tail_ok) { p[o + 12] = p[o + 13] = b[o + 12] = b[o + 13] = 0.f; }
    sa[g] = ((p[o] + p[o + 1]) + (p[o + 4] + p[o + 5])) + ((p[o + 8] + p[o + 9]) + (p[o + 12] + p[o + 13]));
    sn[g] = ((b[o] + b[o + 1]) + (b[o + 4] + b[o + 5])) + ((b[o + 8] + b[o + 9]) + (b[o + 12] + b[o + 13]));
    sa[g] += __shfl_xor_sync(~0u, sa[g], 1); sn[g] += __shfl_xor_sync(~0u, sn[g], 1);
    sa[g] += __shfl_xor_sync(~0u, sa[g], 2); sn[g] += __shfl_xor_sync(~0u, sn[g], 2);
  }
#pragma unroll
  for (int g = 0; g < 4; g++) {
    const int o = 16 * (g >> 1) + 2 * (g & 1);
    const float ra = rcpf(sa[g]), rn = rcpf(sn[g]);
    const uint32_t off = (g >> 1) * 16384 + (g & 1) * 1024;
#pragma unroll
    for (int jj = 0; jj < 4; jj++) {
      st_shared_nv((rb ^ (jj << 4)) + off, pack_bf16(p[o + 4 * jj] * ra, p[o + 4 * jj + 1] * ra));
      st_shared_nv((rb ^ ((4 + jj) << 4)) + off, pack_bf16(b[o + 4 * jj] * rn, b[o + 4 * jj + 1] * rn));
    }
  }
}

__device__ __forceinline__ void store_heads(uint32_t base, const uint32_t (&a)[14], uint32_t pad0, uint32_t pad1, int row0, int lq) {
  const uint32_t rb = base + row0 * 64 + (((row0 >> 1) & 3) << 4);
  const uint32_t b0 = rb + lq * 4;
  const uint32_t b1 = (rb + 8192 + ((lq * 4 + 8) & 15)) ^ ((lq >> 1) << 4);
#pragma unroll
  for (int j = 0; j < 7; j++) {
    uint32_t ad;
    if (j < 3) ad = b0 ^ (j << 4);
    else if (j == 3) ad = (lq < 2) ? (b0 ^ 48u) : (b1 ^ 16u);
    else ad = (lq < 2) ? (b1 ^ ((j - 4) << 4)) : ((b1 ^ 16u) ^ ((j - 3) << 4));
    sts32(ad, a[2 * j]);
    sts32(ad + 512, a[2 * j + 1]);
  }
  sts64((rb ^ 48u) + 8 + (lq & 1) * 8192 + (lq >> 1) * 512, pad0, pad1);
}

struct Params {
  const __nv_bfloat16* w_phi;
  const __nv_bfloat16* wk;
  const __nv_bfloat16* wv;
  const __nv_bfloat16* gate_w;
  __nv_bfloat16* out;
};

__global__ void __launch_bounds__(NTHREADS, 1)
fused_kernel(const __grid_constant__ CUtensorMap tm_x, const __grid_constant__ CUtensorMap tm_wqkv,
             const __grid_constant__ CUtensorMap tm_wq, const __grid_constant__ CUtensorMap tm_woa,
             const __grid_constant__ CUtensorMap tm_wob, const Params prm) {
  extern __shared__ uint8_t smem_raw[];
  uint32_t sb = (smem_u32(smem_raw) + 1023u) & ~1023u;
  uint8_t* sgen = smem_raw + (sb - smem_u32(smem_raw));
  asm volatile("mov.u32 %0, %0;" : "+r"(sb));
  const int tid = threadIdx.x, lane = tid & 31;
  const int warp = __shfl_sync(~0u, tid >> 5, 0), wg = warp >> 2;
  const int pt = blockIdx.x >> 3, hp = blockIdx.x & 7;
  const uint32_t bars = sb + OFF_BAR;
  auto BAR = [&](int i) { return bars + 8u * i; };
  const unsigned epoch = g_epoch & 1;

  if (tid == 0) { PROF_MARK(0); PROF_CLK(30); PROF2(15); }
  auto load_proj = [&](int c, int g) {
    mbar_expect_tx(BAR(B_FULL + g), (c < 3 ? 16384 : 0) + 4 * 7168);
    if (c < 3) tma_2d(sb + OFF_X + c * 16384, &tm_x, c * 64, pt * 128, BAR(B_FULL + g));
    tma_2d(sb + OFF_RING + g * 32768, &tm_wq, hp * 56, c * 64, BAR(B_FULL + g));
#pragma unroll 1
    for (int j = 0; j < 3; j++) tma_2d(sb + OFF_RING + g * 32768 + 8192 + j * 8192, &tm_wqkv, j * DM + hp * 56, c * 64, BAR(B_FULL + g));
  };
  if (warp == 16) {
    if (elect_one()) {
      mbar_init(BAR(B_FULL), 1);
      fence_async_smem();
      load_proj(0, 0);
      mbar_init(BAR(B_RAW), 1); mbar_init(BAR(B_FULL + 1), 1); mbar_init(BAR(B_FULL + 2), 1);
      fence_async_smem();
    }
    __syncwarp();
    asm volatile("bar.arrive 0, %0;" ::"n"(NTHREADS) : "memory");
  } else {
    if (elect_one()) {
      const int i = warp + 3 - (warp > 16);
      if (i < B_N && i != B_RAW) {
        int cnt = i < B_WO || (i > B_SIG && i < B_XL) || i == B_X1FREE ? 16 : 1;
        if (i == B_BUILD) cnt = 16;
        if (i == B_SIG || i == B_SIG + 1 || i == B_QSQ) cnt = 8;
        if (i == B_KVR) cnt = 2;
        mbar_init(BAR(i), cnt);
        fence_async_smem();
      }
    }
    bar_sync(0, NTHREADS);
  }
  if (tid == 0) PROF2(14);

  if (wg == 4) {
    asm volatile("setmaxnreg.dec.sync.aligned.u32 32;");
    if (warp == 16) {
      if (elect_one()) {
        mbar_expect_tx(BAR(B_RAW), 25088 + 3136 + 896);
        bulk_g2s(sb + OFF_RAW, hp < 4 ? prm.wk : prm.wv, 25088, BAR(B_RAW));
        bulk_g2s(sb + OFF_RAW + 25088, prm.w_phi + 2 * hp * DH * DH, 3136, BAR(B_RAW));
        bulk_g2s(sb + OFF_RAW + 28224, prm.gate_w, 896, BAR(B_RAW));
        load_proj(1, 1);
        load_proj(2, 2);
      }
      __syncwarp();
      bar_sync(3, 64);
      if (elect_one()) {
        int g = 0, nkv = 8;
        uint32_t par = 0;
#pragma unroll 1
        for (int c = 3; c < 7; c++) {
          if (c == 5) mbar_wait(BAR(B_BUILD), 0);
          if (c & 1) mbar_expect_tx(BAR(B_XL + (c > 4)), 32768);
          tma_2d(sb + OFF_X + c * 16384, &tm_x, c * 64, pt * 128, BAR(B_XL + (c > 4)));
        }
        uint32_t todo = 15;
#pragma unroll 1
        for (int n = 3; n < 15 + nkv; n++) {
          if (n == 7) { PROF_MARK(20); cnt_wait(C_KV, NCTA); PROF_MARK(21); fence_async_all(); }
          if (n == 15) {
            mbar_wait(BAR(B_SLOW), 0);
            if (*(volatile int*)(sgen + OFF_RED)) nkv = 26;
          }
          int j = n - 7 - nkv;
          if (j == 0) { PROF3(8); cnt_wait(C_OA + pt, 8); PROF3(9); fence_async_all(); }
          mbar_wait(BAR(B_EMPTY + g), par);
          if (j >= 4) {
            uint32_t rdy, spin = 0;
            if (j == 4) PROF3(11);
#pragma unroll 1
            while (true) {
              uint4 v;
              asm volatile("ld.acquire.gpu.global.v4.u32 {%0, %1, %2, %3}, [%4];"
                           : "=r"(v.x), "=r"(v.y), "=r"(v.z), "=r"(v.w) : "l"(&g_cnt[(C_OB + pt) * 32]) : "memory");
              rdy = ((v.x >= 2) | (v.y >= 2) << 1 | (v.z >= 2) << 2 | (v.w >= 2) << 3) & todo;
              if (rdy || ++spin >= (1u << 18)) break;
            }
            const int pick = __ffs(rdy ? rdy : todo) - 1;
            todo &= ~(1u << pick);
            ((volatile int*)(sgen + OFF_RED + 16))[j - 4] = pick;
            j = 4 + pick;
            PROF3(12);
            PROF_MARK(26);
            fence_async_all();
          }
          if (n < 7) { PROF2(20 + n); load_proj(n, g); }
          else {
            mbar_expect_tx(BAR(B_FULL + g), 32768);
            bulk_g2s(sb + OFF_RING + g * 32768, j < 0 ? g_kv_img + ((n - 7) & 7) * 32768 : g_o_img + (size_t)(pt * 8 + j) * 32768, 32768,
                     BAR(B_FULL + g));
          }
          if (++g == 3) { g = 0; par ^= 1; }
        }
        if (atomicAdd(&g_cnt[C_DONE * 32], 1u) == NCTA - 1) {
#pragma unroll 1
          for (int i = 0; i < C_N; i++) *(uint4*)&g_cnt[i * 32] = make_uint4(0u, 0u, 0u, 0u);
          g_epoch = epoch ^ 1;
        }
      }
    } else {
      if (warp == 18) {
        if (elect_one()) {
#pragma unroll 1
          for (int i = 0; i < 4; i++) {
            mbar_wait(BAR(B_SIG + i), 0);
            PROF3(2 * i);
            if (i == 1) {
#pragma unroll 1
              for (int j = 0; j < 4; j++)
                asm volatile("cp.reduce.async.bulk.global.shared::cta.bulk_group.add.f32 [%0], [%1], 8192;"
                             ::"l"(g_kvacc[epoch] + hp * 4096 + (j >> 1) * 2048), "r"(sb + OFF_PHIK + j * 8192) : "memory");
            }
            if (i >= 2)
              asm volatile("cp.async.bulk.global.shared::cta.bulk_group [%0], [%1], 16384;"
                           ::"l"(g_o_img + (size_t)(pt * 2 + i - 2) * 131072 + hp * 16384), "r"(sb + OFF_OSTG) : "memory");
            if (i >= 1) asm volatile("cp.async.bulk.commit_group;\ncp.async.bulk.wait_group 0;" ::: "memory");
            asm volatile("red.release.gpu.global.add.u32 [%0], 1;"
                         ::"l"(&g_cnt[(i == 0 ? C_KV : i == 1 ? C_PART : (i == 2 ? C_OA : C_OB) + pt) * 32 + (i == 3 ? hp >> 1 : 0)]) : "memory");
            PROF3(2 * i + 1);
            if (i == 1 || i == 2) {
              if (i == 2) mbar_wait(BAR(B_X1FREE), 0);
              mbar_expect_tx(BAR(B_WO + i - 1), 7 * 7168);
#pragma unroll 1
              for (int c = 0; c < 7; c++)
                tma_2d(sb + OFF_WO + (i - 1) * 57344 + c * 8192, i == 1 ? &tm_woa : &tm_wob, hp * 56, c * 64, BAR(B_WO + i - 1));
            }
          }
        }
      } else if (warp == 19) {
        if (lane == 0) {
          mbar_wait(BAR(B_SIG + 0), 0);
          cnt_wait(C_KV, NCTA);
        }
        __syncwarp();
        float ksq = 0.f, vsq = 0.f;
#pragma unroll
        for (int sl = 0; sl < 4; sl++) {
          float4 a = ldcg_f4(g_ksq + sl * 128 + lane * 4), b = ldcg_f4(g_vsq + sl * 128 + lane * 4);
          float m = fmaxf(fmaxf(a.x, a.y), fmaxf(a.z, a.w));
          m = __uint_as_float(__reduce_max_sync(~0u, __float_as_uint(m)));
          ksq += m;
          vsq = fmaxf(vsq, fmaxf(fmaxf(b.x, b.y), fmaxf(b.z, b.w)));
        }
        mbar_wait(BAR(B_QSQ), 0);
        const float4 qa4 = ((const float4*)(sgen + OFF_QSQ))[lane], qb4 = ((const float4*)(sgen + OFF_QSQ))[32 + lane];
        const float qmax = fmaxf(fmaxf(fmaxf(qa4.x, qa4.y), fmaxf(qa4.z, qa4.w)), fmaxf(fmaxf(qb4.x, qb4.y), fmaxf(qb4.z, qb4.w)));
        const bool slow = __any_sync(~0u, !(qmax * ksq <= 98.f * 98.f) || !(vsq <= 2.0e8f));
        if (lane == 0) {
          *(volatile int*)(sgen + OFF_RED) = slow;
          mbar_arrive(BAR(B_SLOW), 1);
        }
      } else {
        float4* z = (float4*)(g_kvacc[epoch ^ 1] + blockIdx.x * 256) + lane;
        z[0] = make_float4(0.f, 0.f, 0.f, 0.f);
        z[32] = make_float4(0.f, 0.f, 0.f, 0.f);
        bar_sync(3, 64);
        if (lane == 0) {
          mbar_wait(BAR(B_SIG + 0), 0);
          cnt_wait(C_KV, NCTA);
        }
        __syncwarp();
        ((float4*)(sgen + OFF_GATE))[lane] = ldcg_f4(g_gate + pt * 128 + lane * 4);
      }
      if (warp != 18) {
        if (lane == 0) {
          mbar_wait(BAR(B_SIG + 1), 0);
          cnt_wait(C_PART, NCTA);
          PROF_MARK(23);
        }
        __syncwarp();
        const int e = warp == 19;
        const float* src = g_kvacc[epoch] + hp * 4096 + e * 2048 + (lane ^ ((lane >> 2) & 3)) * 8;
#pragma unroll 1
        for (int i = 0; i < 8; i += 2) {
          const float4 a = ldcg_f4(src + i * 256), b = ldcg_f4(src + i * 256 + 4), c = ldcg_f4(src + i * 256 + 256), d = ldcg_f4(src + i * 256 + 260);
          const uint32_t ad = sb + OFF_KVR + e * 4096 + sw64_off(i * 8 + (lane >> 2), (lane & 3) * 8);
          sts128(ad, make_uint4(pack_bf16(a.x, a.y), pack_bf16(a.z, a.w), pack_bf16(b.x, b.y), pack_bf16(b.z, b.w)));
          sts128(ad + 512, make_uint4(pack_bf16(c.x, c.y), pack_bf16(c.z, c.w), pack_bf16(d.x, d.y), pack_bf16(d.z, d.w)));
        }
        fence_async_smem();
        __syncwarp();
        if (lane == 0) mbar_arrive(BAR(B_KVR), 1);
        PROF_MARK(24);
      }
    }
  } else {
    asm volatile("setmaxnreg.inc.sync.aligned.u32 112;");
    const int mh = wg & 1, nh = wg >> 1, wq = warp & 3;
    const int lq = lane & 3;
    const int rowl = wq * 16 + (lane >> 2);
    const int row0 = mh * 64 + rowl;
    int slot = 0;
    uint32_t par = 0;
    {
      float acc0[28], acc1[28], accs[4];
      const uint64_t dR = make_desc(sb + OFF_RING + nh * 16384, 1024, 1024, 1);
      const uint64_t dX = make_desc(sb + OFF_X + mh * 8192, 1024, 1024, 1);
#pragma unroll
      for (int i = 0; i < 28; i++) acc0[i] = acc1[i] = 0.f;
#pragma unroll
      for (int i = 0; i < 4; i++) accs[i] = 0.f;
      const uint64_t dSlc = make_desc(sb + OFF_SLC, 128, 128, 0);
#pragma unroll 1
      for (int c = 0; c < 7; c++) {
        if (c == 3 || c == 5) mbar_wait(BAR(B_XL + (c > 4)), 0);
        mbar_wait(BAR(B_FULL + slot), par);
        if (c == 0 && tid == 0) PROF2(17);
        const uint64_t dA = dX + c * 1024, dB = dR + slot * 2048;
        wg_fence();
#pragma unroll
        for (int ks = 0; ks < 4; ks++) {
          wgmma_ss_n56_ta0_tb1<1>(acc0, dA + ks * 2, dB + ks * 128);
          wgmma_ss_n56_ta0_tb1<1>(acc1, dA + ks * 2, dB + 512 + ks * 128);
        }
        if (nh == 1 && c > 0) {
#pragma unroll
          for (int ks = 0; ks < 4; ks++) wgmma_ss_n8_ta0_tb1<1>(accs, dA - 1024 + ks * 2, dSlc + (c - 1) * 64 + ks * 16);
        }
        wg_commit();
        if (c == 0) {
          mbar_wait(BAR(B_RAW), 0);
          const int k = tid >> 3, cn = tid & 7;
          const bool data = k < 56 && (cn >> 2) == (k >= DH);
          const uint2* wsrc = (const uint2*)(sgen + OFF_RAW + 25088 + k * 56 + (cn & 3) * 16);
          uint2 w0 = make_uint2(0u, 0u), w1 = w0;
          if (data) w0 = wsrc[0];
          if (data && (cn & 3) != 3) w1 = wsrc[1];
          sts128(sb + OFF_WBD + k * 128 + ((cn ^ (k & 7)) << 4), make_uint4(w0.x, w0.y, w1.x, w1.y));
          if (tid < DM) {
            const uint2* src = (const uint2*)(sgen + OFF_RAW + tid * 56 + (hp & 3) * 16);
            w0 = src[0];
            w1 = make_uint2(hp == 3 ? (uint32_t)((const unsigned short*)(sgen + OFF_RAW + 28224))[tid] : 0u, 0u);
            if ((hp & 3) != 3) w1 = src[1];
            sts128(sb + OFF_SLC + tid * 16, make_uint4(w0.x, w0.y, w1.x, w1.y));
          }
          fence_async_smem();
          __syncwarp();
          if (lane == 0) mbar_arrive(BAR(B_BUILD), 1);
          mbar_wait(BAR(B_BUILD), 0);
        }
        wg_wait<0>();
        if (lane == 0) mbar_arrive(BAR(B_EMPTY + slot), 1);
        if (++slot == 3) { slot = 0; par ^= 1; }
      }
      if (nh == 1) {
        wg_fence();
#pragma unroll
        for (int ks = 0; ks < 4; ks++) wgmma_ss_n8_ta0_tb1<1>(accs, dX + 6 * 1024 + ks * 2, dSlc + 6 * 64 + ks * 16);
        wg_commit();
      }
      wg_wait<0>();
      fence_regs(acc0); fence_regs(acc1); fence_regs(accs);
      if (tid == 0) PROF_MARK(2);
      if (tid == 256) PROF_MARK(3);
      if (nh == 0) {
        float sq[4] = {0.f, 0.f, 0.f, 0.f};
#pragma unroll
        for (int i = 0; i < 28; i++) acc0[i] *= 0.18898223650461362f * 1.4426950408889634f;
#pragma unroll
        for (int j = 0; j < 7; j++) {
#pragma unroll
          for (int rr = 0; rr < 2; rr++) {
            const float s2 = acc0[4 * j + 2 * rr] * acc0[4 * j + 2 * rr] + acc0[4 * j + 2 * rr + 1] * acc0[4 * j + 2 * rr + 1];
            if (j < 3) sq[rr] += s2;
            else if (j > 3) sq[2 + rr] += s2;
            else { sq[rr] += (lq < 2) ? s2 : 0.f; sq[2 + rr] += (lq < 2) ? 0.f : s2; }
          }
        }
#pragma unroll
        for (int i = 0; i < 4; i++) sq[i] = quad_sum(sq[i]);
        const float mine = lq == 0 ? sq[0] : lq == 1 ? sq[1] : lq == 2 ? sq[2] : sq[3];
        ((float*)(sgen + OFF_QSQ))[(mh + (lq & 2)) * 64 + rowl + 8 * (lq & 1)] = mine <= 3.0e38f ? mine : __int_as_float(0x7f800000);
        __syncwarp();
        if (lane == 0) mbar_arrive(BAR(B_QSQ), 1);
      } else {
        const int sl = hp & 3;
        const bool isk = hp < 4, real = (sl < 3) || (lq < 2);
        const int pos = pt * 128 + row0, kr = pos & 63;
        uint8_t* dst = g_kv_img + (pos >> 6) * 8192 + (isk ? 0 : 4096) + sw64_off(kr, sl * 8 + 2 * lq);
        const uint32_t pat = isk ? POLY_PAT >> (kr >> 3) : 0u;
        float mxv = 0.f;
#pragma unroll
        for (int rr = 0; rr < 2; rr++) {
          const float v0 = accs[2 * rr], v1 = accs[2 * rr + 1];
          const bool poly = (pat >> rr) & 1;
          const float sc = poly ? 2.f : 1.f;
          const float s2 = quad_sum(real ? v0 * v0 + v1 * v1 : 0.f);
          mxv = fmaxf(mxv, s2 <= 3.0e38f ? s2 : __int_as_float(0x7f800000));
          const uint32_t padv = lq == 2 ? (poly ? 0x443F4000u : 0x00003F80u) : (poly ? 0x3AB03F4Du : 0u);
          *(uint32_t*)(dst + rr * 512) = real ? pack_bf16(sc * v0, sc * v1) : padv;
          if (hp == 3 && lq == 2) g_gate[pos + 8 * rr] = rcpf(1.f + ex2f(-1.4426950408889634f * v0));
        }
        mxv = __uint_as_float(__reduce_max_sync(~0u, __float_as_uint(mxv)));
        if (lane == 0) (isk ? g_ksq : g_vsq)[sl * 128 + pt * 8 + mh * 4 + wq] = mxv;
        __syncwarp();
        if (lane == 0) mbar_arrive(BAR(B_SIG + 0), 1);
      }
      if (tid == 0) PROF_MARK(4);
      if (tid == 256) PROF_MARK(5);
      uint32_t h[14];
      float pp[32];
      {
        uint32_t a[16];
#pragma unroll
        for (int i = 0; i < 14; i++) {
          const uint32_t u0 = pack_bf16(acc0[2 * i], acc0[2 * i + 1]), u1 = pack_bf16(acc1[2 * i], acc1[2 * i + 1]);
          h[i] = nh ? u1 : u0;
          a[i] = nh ? u0 : u1;
        }
        a[14] = a[0] ^ 0x80008000u;
        a[15] = a[1] ^ 0x80008000u;
        const uint64_t dW = make_desc(sb + OFF_WBD, 1024, 1024, 1);
        wg_fence();
        wgmma_rs_n64_tb1<0>(pp, a[0], a[1], a[2], a[3], dW);
#pragma unroll
        for (int ks = 1; ks < 4; ks++) wgmma_rs_n64_tb1<1>(pp, a[4 * ks], a[4 * ks + 1], a[4 * ks + 2], a[4 * ks + 3], dW + ks * 128);
        wg_commit();
        bar_sync(1, 512);
        if (tid == 0) PROF_MARK(6);
        store_heads(sb + (nh ? OFF_VA : OFF_QP), h, nh ? 0x00003F80u : 0x3F800000u, nh ? 0u : 0x3F803F80u, row0, lq);
        wg_wait<0>();
        fence_regs(pp);
      }
      feature_map(pp, sb + (nh ? OFF_PHIK : OFF_PHIQ) + row0 * 128 + lq * 4 + ((rowl & 7) << 4), lq);
      fence_async_smem();
      bar_sync(1, 512);
      if (tid == 0) PROF_MARK(7);
      if (nh == 1) {
        float kv0[16], kv1[16];
        const uint64_t dP = make_desc(sb + OFF_PHIK + mh * 8192, 1024, 1024, 1);
        const uint64_t dV = make_desc(sb + OFF_VA + mh * 4096, 512, 512, 2);
        wg_fence();
        wgmma_ss_n32_ta1_tb1<0>(kv0, dP, dV);
        wgmma_ss_n32_ta1_tb1<0>(kv1, dP + 1024, dV + 512);
#pragma unroll
        for (int ks = 1; ks < 4; ks++) {
          wgmma_ss_n32_ta1_tb1<1>(kv0, dP + ks * 128, dV + ks * 64);
          wgmma_ss_n32_ta1_tb1<1>(kv1, dP + 1024 + ks * 128, dV + 512 + ks * 64);
        }
        wg_commit();
        wg_wait<0>();
        fence_regs(kv0); fence_regs(kv1);
        bar_sync(4 + wg, 128);
        const uint32_t sa = sb + OFF_PHIK + mh * 8192 + rowl * 128 + lq * 8 + (rowl & 3) * 32;
#pragma unroll
        for (int j = 0; j < 8; j++) {
          sts64((sa ^ (32 * (j >> 1))) + 1024 * (j & 1), __float_as_uint(kv0[2 * j]), __float_as_uint(kv0[2 * j + 1]));
          sts64((sa ^ (32 * (j >> 1))) + 16384 + 1024 * (j & 1), __float_as_uint(kv1[2 * j]), __float_as_uint(kv1[2 * j + 1]));
        }
        fence_async_smem();
        __syncwarp();
        if (lane == 0) mbar_arrive(BAR(B_SIG + 1), 1);
        if (tid == 256) PROF_MARK(28);
      }
    }
    {
      const uint64_t dK = make_desc(sb + OFF_RING, 512, 512, 2);
      const uint64_t dhi = dK & 0xffffffff00000000ull;
      const uint32_t dlo0 = (uint32_t)dK;
      uint32_t ok = 0, q[8];
      float o[16];
#pragma unroll
      for (int i = 0; i < 16; i++) o[i] = 0.f;
      {
        const int r = mh * 64 + wq * 16 + (lane & 7) + ((lane >> 3) & 1) * 8;
        ldsm4(q, sb + OFF_QP + nh * 8192 + sw64_off(r, (lane >> 4) * 8));
        ldsm4(q + 4, sb + OFF_QP + nh * 8192 + sw64_off(r, 16 + (lane >> 4) * 8));
      }
      if (tid == 0) PROF_MARK(10);
      const int qb = QB_AT;
      float s[32];
      mbar_wait(BAR(B_FULL + slot), par);
      wg_fence();
      wgmma_rs_n64_tb0<0>(s, q[0], q[1], q[2], q[3], dhi | (dlo0 + slot * 2048));
      wgmma_rs_n64_tb0<1>(s, q[4], q[5], q[6], q[7], dhi | (dlo0 + slot * 2048 + 2));
      wg_commit();
      wg_wait<0>();
      fence_regs(s);
#pragma unroll 1
      for (int it = 0; it <= 8; it++) {
        uint32_t p[16];
        if ((tid & 127) == 0) PROF4(wg * 32 + it);
        if (it == qb || it == 8) {
          float t[16];
          if (it < 8) {
            if (tid == 0) PROF_MARK(11);
            mbar_wait(BAR(B_KVR), 0);
            const uint64_t dR = make_desc(sb + OFF_KVR + nh * 4096, 512, 512, 2);
            const uint64_t dP = make_desc(sb + OFF_PHIQ + nh * 16384 + mh * 8192, 1024, 1024, 1);
            wg_fence();
            wgmma_ss_n32_ta0_tb1<0>(t, dP, dR);
#pragma unroll
            for (int ks = 1; ks < 4; ks++) wgmma_ss_n32_ta0_tb1<1>(t, dP + ks * 2, dR + ks * 64);
            wg_commit();
            wg_wait<0>();
            fence_regs(t);
            if (lane == 0) mbar_arrive(BAR(B_X1FREE), 1);
          } else {
            if (tid == 0) PROF_MARK(13);
            mbar_wait(BAR(B_SLOW), 0);
            if (__builtin_expect(__any_sync(~0u, *(volatile int*)(sgen + OFF_RED)), 0)) {
              uint32_t qz[8];
#pragma unroll
              for (int i = 0; i < 8; i++) qz[i] = (i >= 6 && lq >= 2) ? 0u : q[i];
              float m0 = -3.0e38f, m1 = -3.0e38f, o2[16];
              int sl2 = slot;
              uint32_t par2 = par;
#pragma unroll 1
              for (int j64 = 0; j64 < 32; j64++) {
                float s[32];
                mbar_wait(BAR(B_FULL + sl2), par2);
                const uint32_t lo = dlo0 + sl2 * 2048 + (j64 & 3) * 512;
                wg_fence();
                wgmma_rs_n64_tb0<0>(s, qz[0], qz[1], qz[2], qz[3], dhi | lo);
                wgmma_rs_n64_tb0<1>(s, qz[4], qz[5], qz[6], qz[7], dhi | (lo + 2));
                wg_commit();
                wg_wait<0>();
                fence_regs(s);
#pragma unroll
                for (int j = 0; j < 8; j++) {
                  const float sc = ((POLY_PAT >> j) & 1) ? 0.5f : 1.f;
                  m0 = fmaxf(m0, fmaxf(s[4 * j], s[4 * j + 1]) * sc);
                  m1 = fmaxf(m1, fmaxf(s[4 * j + 2], s[4 * j + 3]) * sc);
                }
                if ((j64 & 3) == 3) {
                  if (lane == 0) mbar_arrive(BAR(B_EMPTY + sl2), 1);
                  if (++sl2 == 3) { sl2 = 0; par2 ^= 1; }
                }
              }
              m0 = quad_max(m0); m1 = quad_max(m1);
#pragma unroll
              for (int i = 0; i < 16; i++) o2[i] = 0.f;
#pragma unroll 1
              for (int j64 = 0; j64 < 32; j64++) {
                float s[32];
                mbar_wait(BAR(B_FULL + sl2), par2);
                const uint32_t lo = dlo0 + sl2 * 2048 + (j64 & 3) * 512;
                wg_fence();
                wgmma_rs_n64_tb0<0>(s, qz[0], qz[1], qz[2], qz[3], dhi | lo);
                wgmma_rs_n64_tb0<1>(s, qz[4], qz[5], qz[6], qz[7], dhi | (lo + 2));
                wg_commit();
                wg_wait<0>();
                fence_regs(s);
                uint32_t ps[16];
#pragma unroll
                for (int j = 0; j < 8; j++) {
                  const float sc = ((POLY_PAT >> j) & 1) ? 0.5f : 1.f;
                  ps[2 * j] = pack_bf16(ex2f(fmaf(s[4 * j], sc, -m0)), ex2f(fmaf(s[4 * j + 1], sc, -m0)));
                  ps[2 * j + 1] = pack_bf16(ex2f(fmaf(s[4 * j + 2], sc, -m1)), ex2f(fmaf(s[4 * j + 3], sc, -m1)));
                }
                wg_fence();
#pragma unroll
                for (int ks = 0; ks < 4; ks++)
                  wgmma_rs_n32_tb1<1>(o2, ps[4 * ks], ps[4 * ks + 1], ps[4 * ks + 2], ps[4 * ks + 3], dhi | (lo + 256 + ks * 64));
                wg_commit();
                wg_wait<0>();
                fence_regs(o2);
                if ((j64 & 3) == 3) {
                  if (lane == 0) mbar_arrive(BAR(B_EMPTY + sl2), 1);
                  if (++sl2 == 3) { sl2 = 0; par2 ^= 1; }
                }
              }
#pragma unroll 1
              for (int j = 0; j < 2; j++) {
                mbar_wait(BAR(B_FULL + sl2), par2);
                __syncwarp();
                if (lane == 0) mbar_arrive(BAR(B_EMPTY + sl2), 1);
                if (++sl2 == 3) { sl2 = 0; par2 ^= 1; }
              }
#pragma unroll
              for (int i = 0; i < 16; i++) o[i] = o2[i];
            }
#pragma unroll
            for (int i = 0; i < 16; i++) t[i] = o[i];
#pragma unroll
            for (int i = 0; i < 32; i++) s[i] = 0.f;
          }
          const int br = it == 8;
          const float eps = br ? 0.f : 1e-6f;
          const float g0 = ((const float*)(sgen + OFF_GATE))[row0], g1 = ((const float*)(sgen + OFF_GATE))[row0 + 8];
          const float d0 = __shfl_sync(~0u, t[12], (lane & ~3) | 2), d1 = __shfl_sync(~0u, t[14], (lane & ~3) | 2);
          const float r0 = (br ? 1.f - g0 : g0) * rcpf(d0 + eps), r1 = (br ? 1.f - g1 : g1) * rcpf(d1 + eps);
          const uint32_t oa = sb + OFF_OSTG + (nh * 2 + mh) * 4096 + sw64_off(rowl, 2 * lq);
#pragma unroll
          for (int j = 0; j < 4; j++) {
            const bool real = j < 3 || lq < 2;
            sts32(oa ^ (j << 4), real ? pack_bf16(t[4 * j] * r0, t[4 * j + 1] * r0) : 0u);
            sts32((oa ^ (j << 4)) + 512, real ? pack_bf16(t[4 * j + 2] * r1, t[4 * j + 3] * r1) : 0u);
          }
          fence_async_smem();
          __syncwarp();
          if (lane == 0) mbar_arrive(BAR(B_SIG + 2 + br), 1);
          if (tid == 0) PROF_MARK(12 + 2 * br);
          if (br) { if ((tid & 127) == 0) PROF4(wg * 32 + 9); break; }
        }
        const uint32_t lo = dlo0 + slot * 2048;
        int nslot = slot + 1;
        uint32_t npar = par;
        if (nslot == 3) { nslot = 0; npar ^= 1; }
#pragma unroll
        for (int u = 0; u < 4; u++) {
          if (u == 2) ok = mbar_test(BAR(B_FULL + nslot), npar);
#pragma unroll
          for (int j = 0; j < 8; j++) {
            if ((POLY_PAT >> j) & 1) {
              p[2 * j] = exp2_pair_fma(s[4 * j], s[4 * j + 1], 0x3F003F00u, 0x00030003u);
              p[2 * j + 1] = exp2_pair_fma(s[4 * j + 2], s[4 * j + 3], 0x3F003F00u, 0x00030003u);
            } else {
              p[2 * j] = pack_bf16(ex2f(s[4 * j]), ex2f(s[4 * j + 1]));
              p[2 * j + 1] = pack_bf16(ex2f(s[4 * j + 2]), ex2f(s[4 * j + 3]));
            }
          }
          if (u == 3 && !ok && it < 7) mbar_wait(BAR(B_FULL + nslot), npar);
          const uint32_t ln = u < 3 ? lo + (u + 1) * 512 : dlo0 + nslot * 2048;
          wg_fence();
#pragma unroll
          for (int ks = 0; ks < 4; ks++)
            wgmma_rs_n32_tb1<1>(o, p[4 * ks], p[4 * ks + 1], p[4 * ks + 2], p[4 * ks + 3], dhi | (lo + u * 512 + 256 + ks * 64));
          wgmma_rs_n64_tb0<0>(s, q[0], q[1], q[2], q[3], dhi | ln);
          wgmma_rs_n64_tb0<1>(s, q[4], q[5], q[6], q[7], dhi | (ln + 2));
          wg_commit();
          wg_wait<0>();
          fence_regs(s);
          fence_regs(o);
        }
        if (lane == 0) mbar_arrive(BAR(B_EMPTY + slot), 1);
        slot = nslot; par = npar;
      }
      wg_wait<0>();
    }
    if (nh == 1) return;
    {
      float acc[28];
#pragma unroll
      for (int i = 0; i < 28; i++) acc[i] = 0.f;
      const uint64_t dS = make_desc(sb + OFF_WO, 1024, 1024, 1);
      const uint64_t dR = make_desc(sb + OFF_RING + mh * 4096, 512, 512, 2);
#pragma unroll 1
      for (int c = 0; c < 8; c++) {
        mbar_wait(BAR(B_WO + (c >> 2)), 0);
        mbar_wait(BAR(B_FULL + slot), par);
        const int id = c < 4 ? c : 4 + __shfl_sync(~0u, ((volatile int*)(sgen + OFF_RED + 16))[c & 3], 0);
        const uint64_t dA = dR + slot * 2048, dB = dS + id * 896;
        wg_fence();
#pragma unroll
        for (int h = 0; h < 4; h++) {
          wgmma_ss_n56_ta0_tb1<1>(acc, dA + h * 512, dB + h * 224);
          wgmma_ss_n56_ta0_tb1<1>(acc, dA + h * 512 + 2, dB + h * 224 + 128);
        }
        wg_commit();
        if (c < 5) {
          wg_wait<0>();
          if (lane == 0) mbar_arrive(BAR(B_EMPTY + slot), 2);
        }
        if (++slot == 3) { slot = 0; par ^= 1; }
      }
      wg_wait<0>();
      fence_regs(acc);
      if (tid == 0) PROF_MARK(17);
      __nv_bfloat16* op = prm.out + (size_t)(pt * 128 + row0) * DM + hp * 56 + 2 * lq;
#pragma unroll
      for (int j = 0; j < 7; j++) {
        *(uint32_t*)(op + 8 * j) = pack_bf16(acc[4 * j], acc[4 * j + 1]);
        *(uint32_t*)(op + 8 * DM + 8 * j) = pack_bf16(acc[4 * j + 2], acc[4 * j + 3]);
      }
      if (tid == 0) { PROF_MARK(18); PROF_CLK(31); }
    }
  }
}

typedef CUresult (*EncodeFn)(CUtensorMap*, CUtensorMapDataType, cuuint32_t, void*, const cuuint64_t*, const cuuint64_t*,
                             const cuuint32_t*, const cuuint32_t*, CUtensorMapInterleave, CUtensorMapSwizzle,
                             CUtensorMapL2promotion, CUtensorMapFloatOOBfill);

void make_map(EncodeFn enc, CUtensorMap* tm, const void* ptr, uint64_t cols, uint64_t rows, uint32_t box_cols, uint32_t box_rows) {
  cuuint64_t dims[2] = {cols, rows};
  cuuint64_t strides[1] = {cols * 2};
  cuuint32_t box[2] = {box_cols, box_rows};
  cuuint32_t es[2] = {1, 1};
  enc(tm, CU_TENSOR_MAP_DATA_TYPE_BFLOAT16, 2, const_cast<void*>(ptr), dims, strides, box, es, CU_TENSOR_MAP_INTERLEAVE_NONE,
      CU_TENSOR_MAP_SWIZZLE_128B, CU_TENSOR_MAP_L2_PROMOTION_L2_128B, CU_TENSOR_MAP_FLOAT_OOB_FILL_NONE);
}

}

extern "C" void kernel_launch(void* const* d_in, const int* in_sizes, int n_in, void* d_out, int out_size) {
  (void)in_sizes; (void)n_in; (void)out_size;
  static EncodeFn enc = nullptr;
  if (!enc) {
    void* fn = nullptr;
    cudaDriverEntryPointQueryResult qr;
    cudaGetDriverEntryPoint("cuTensorMapEncodeTiled", &fn, cudaEnableDefault, &qr);
    enc = (EncodeFn)fn;
    cudaFuncSetAttribute(fused_kernel, cudaFuncAttributeMaxDynamicSharedMemorySize, SMEM_BYTES);
  }
  CUtensorMap tm_x, tm_wqkv, tm_wq, tm_woa, tm_wob;
  make_map(enc, &tm_x, d_in[0], DM, S_LEN, 64, 128);
  make_map(enc, &tm_wqkv, d_in[1], 3 * DM, DM, 56, 64);
  make_map(enc, &tm_wq, d_in[5], DM, DM, 56, 64);
  make_map(enc, &tm_woa, d_in[3], DM, DM, 56, 64);
  make_map(enc, &tm_wob, d_in[8], DM, DM, 56, 64);
  Params prm;
  prm.w_phi = (const __nv_bfloat16*)d_in[2];
  prm.wk = (const __nv_bfloat16*)d_in[6];
  prm.wv = (const __nv_bfloat16*)d_in[7];
  prm.gate_w = (const __nv_bfloat16*)d_in[9];
  prm.out = (__nv_bfloat16*)d_out;
  fused_kernel<<<NCTA, NTHREADS, SMEM_BYTES>>>(tm_x, tm_wqkv, tm_wq, tm_woa, tm_wob, prm);
}
```

```cpp
#include <cuda_runtime.h>
#include <cuda_bf16.h>
#include <cuda.h>
#include <stdint.h>

namespace {

constexpr int S_LEN = 2048, DM = 448, DH = 28;
constexpr int NCTA = 128;
constexpr int NTHREADS = 640;
constexpr uint32_t POLY_PAT = 0x57;

#define QB_AT (4 + (wg >> 1))

constexpr int OFF_X = 0;
constexpr int OFF_PHIK = 0;
constexpr int OFF_VA = 32768;
constexpr int OFF_PHIQ = 57344;
constexpr int OFF_KVR = 90112;
constexpr int OFF_QP = 98304;
constexpr int OFF_RAW = 81920;
constexpr int OFF_WO = 0;
constexpr int OFF_RING = 114688;
constexpr int OFF_WBD = 212992;
constexpr int OFF_SLC = 221184;
constexpr int OFF_QSQ = 228352;
constexpr int OFF_OSTG = 212992;
constexpr int OFF_GATE = 229376;
constexpr int OFF_RED = 229888;
constexpr int OFF_BAR = 229952;
constexpr int SMEM_BYTES = 230400 + 1024;

constexpr int B_FULL = 0, B_EMPTY = 3, B_WO = 6  , B_KVR = 8, B_RAW = 9, B_X1FREE = 10, B_QSQ = 11, B_SLOW = 12,
              B_BUILD = 13, B_SIG = 14  , B_XL = 18  , B_N = 20;

constexpr int C_KV = 0, C_PART = 1, C_DONE = 3, C_OA = 4, C_OB = 20, C_N = 36;

__device__ __align__(1024) uint8_t g_kv_img[32 * 8192];
__device__ __align__(16) float g_ksq[512];
__device__ __align__(16) float g_vsq[512];
__device__ __align__(16) float g_gate[S_LEN];
__device__ __align__(1024) float g_kvacc[2][16 * 64 * 32];
__device__ unsigned g_epoch;
__device__ __align__(1024) uint8_t g_o_img[16 * 2 * 16 * 2 * 4096];
__device__ __align__(128) unsigned g_cnt[C_N * 32];

#define PROF4(i) do { } while (0)
#define PROF3(i) do { } while (0)
#define PROF2(i) do { } while (0)
#define PROF_CLK(i) do { } while (0)
#define PROF_MARK(i) do { } while (0)
__device__ __forceinline__ uint32_t smem_u32(const void* p) { return (uint32_t)__cvta_generic_to_shared(p); }
__device__ __forceinline__ void mbar_init(uint32_t a, int cnt) {
  asm volatile("mbarrier.init.shared::cta.b64 [%0], %1;" ::"r"(a), "r"(cnt) : "memory");
}
__device__ __forceinline__ void mbar_expect_tx(uint32_t a, uint32_t bytes) {
  asm volatile("mbarrier.arrive.expect_tx.shared::cta.b64 _, [%0], %1;" ::"r"(a), "r"(bytes) : "memory");
}
__device__ __forceinline__ void mbar_arrive(uint32_t a, uint32_t cnt) {
  asm volatile("mbarrier.arrive.shared::cta.b64 _, [%0], %1;" ::"r"(a), "r"(cnt) : "memory");
}
__device__ __forceinline__ void mbar_wait(uint32_t a, uint32_t parity) {
  asm volatile(
      "{\n.reg .pred p;\n.reg .u32 c;\nmov.u32 c, 0;\n"
      "W_%=:\nmbarrier.try_wait.parity.shared::cta.b64 p, [%0], %1;\n"
      "add.u32 c, c, 1;\nsetp.lt.and.u32 p, c, 0x40000, !p;\n@p bra W_%=;\n}"
      ::"r"(a), "r"(parity) : "memory");
}
__device__ __forceinline__ uint32_t mbar_test(uint32_t a, uint32_t parity) {
  uint32_t ok;
  asm volatile("{\n.reg .pred p;\nmbarrier.test_wait.parity.shared::cta.b64 p, [%1], %2;\nselp.u32 %0, 1, 0, p;\n}"
               : "=r"(ok) : "r"(a), "r"(parity) : "memory");
  return ok;
}
__device__ __forceinline__ bool elect_one() {
  uint32_t r;
  asm volatile("{\n.reg .pred p;\nelect.sync _|p, 0xffffffff;\nselp.u32 %0, 1, 0, p;\n}" : "=r"(r));
  return r != 0;
}
__device__ __forceinline__ void tma_2d(uint32_t dst, const CUtensorMap* tm, int c0, int c1, uint32_t bar) {
  asm volatile("cp.async.bulk.tensor.2d.shared::cluster.global.mbarrier::complete_tx::bytes [%0], [%1, {%3, %4}], [%2];"
               ::"r"(dst), "l"(tm), "r"(bar), "r"(c0), "r"(c1) : "memory");
}
__device__ __forceinline__ void bulk_g2s(uint32_t dst, const void* src, uint32_t bytes, uint32_t bar) {
  asm volatile("cp.async.bulk.shared::cluster.global.mbarrier::complete_tx::bytes [%0], [%1], %2, [%3];"
               ::"r"(dst), "l"(src), "r"(bytes), "r"(bar) : "memory");
}
__device__ __forceinline__ void fence_async_smem() { asm volatile("fence.proxy.async.shared::cta;" ::: "memory"); }
__device__ __forceinline__ void fence_async_all() { asm volatile("fence.proxy.async.global;" ::: "memory"); }

__device__ __forceinline__ void bar_sync(int id, int n) { asm volatile("bar.sync %0, %1;" ::"r"(id), "r"(n) : "memory"); }
__device__ __forceinline__ void cnt_wait(int idx, unsigned target) {
  unsigned v, n = 0;
#pragma unroll 1
  while (true) {
    asm volatile("ld.acquire.gpu.global.u32 %0, [%1];" : "=r"(v) : "l"(&g_cnt[idx * 32]) : "memory");
    if (v >= target || ++n >= (1u << 18)) break;
    __nanosleep(32);
  }
}
__device__ __forceinline__ void wg_fence() { asm volatile("wgmma.fence.sync.aligned;" ::: "memory"); }
__device__ __forceinline__ void wg_commit() { asm volatile("wgmma.commit_group.sync.aligned;" ::: "memory"); }
template <int N> __device__ __forceinline__ void wg_wait() { asm volatile("wgmma.wait_group.sync.aligned %0;" ::"n"(N) : "memory"); }
template <int N> __device__ __forceinline__ void fence_regs(float (&d)[N]) {
#pragma unroll
  for (int i = 0; i < N; i++) asm volatile("" : "+f"(d[i])::"memory");
}
__device__ __forceinline__ uint64_t make_desc(uint32_t saddr, uint32_t lbo, uint32_t sbo, uint32_t swz) {
  return (uint64_t)((saddr & 0x3FFFF) >> 4) | ((uint64_t)(lbo >> 4) << 16) | ((uint64_t)(sbo >> 4) << 32) | ((uint64_t)swz << 62);
}
__device__ __forceinline__ float ex2f(float x) { float y; asm("ex2.approx.ftz.f32 %0, %1;" : "=f"(y) : "f"(x)); return y; }
__device__ __forceinline__ float rcpf(float x) { float y; asm("rcp.approx.ftz.f32 %0, %1;" : "=f"(y) : "f"(x)); return y; }
__device__ __forceinline__ uint32_t pack_bf16(float lo, float hi) {
  uint32_t r; asm("cvt.rn.bf16x2.f32 %0, %1, %2;" : "=r"(r) : "f"(hi), "f"(lo)); return r;
}
__device__ __forceinline__ uint32_t lop_and_or(uint32_t a, uint32_t m, uint32_t c) {
  uint32_t r; asm("lop3.b32 %0, %1, %2, %3, 0xEA;" : "=r"(r) : "r"(a), "r"(m), "r"(c)); return r;
}
__device__ __forceinline__ void sts32(uint32_t a, uint32_t v) { asm volatile("st.shared.b32 [%0], %1;" ::"r"(a), "r"(v) : "memory"); }
__device__ __forceinline__ void st_shared_nv(uint32_t a, uint32_t v) { asm volatile("st.shared.b32 [%0], %1;" ::"r"(a), "r"(v)); }
__device__ __forceinline__ void sts64(uint32_t a, uint32_t v0, uint32_t v1) { asm volatile("st.shared.v2.b32 [%0], {%1, %2};" ::"r"(a), "r"(v0), "r"(v1) : "memory"); }
__device__ __forceinline__ void sts128(uint32_t a, uint4 v) {
  asm volatile("st.shared.v4.b32 [%0], {%1, %2, %3, %4};" ::"r"(a), "r"(v.x), "r"(v.y), "r"(v.z), "r"(v.w) : "memory");
}
__device__ __forceinline__ float4 ldcg_f4(const float* p) {
  float4 v; asm volatile("ld.global.cg.v4.f32 {%0, %1, %2, %3}, [%4];" : "=f"(v.x), "=f"(v.y), "=f"(v.z), "=f"(v.w) : "l"(p) : "memory"); return v;
}
__device__ __forceinline__ void ldsm4(uint32_t* r, uint32_t a) {
  asm volatile("ldmatrix.sync.aligned.m8n8.x4.shared.b16 {%0, %1, %2, %3}, [%4];"
               : "=r"(r[0]), "=r"(r[1]), "=r"(r[2]), "=r"(r[3]) : "r"(a) : "memory");
}
__device__ __forceinline__ float quad_sum(float v) { v += __shfl_xor_sync(~0u, v, 1); v += __shfl_xor_sync(~0u, v, 2); return v; }
__device__ __forceinline__ float quad_max(float v) { v = fmaxf(v, __shfl_xor_sync(~0u, v, 1)); v = fmaxf(v, __shfl_xor_sync(~0u, v, 2)); return v; }

template <int SD> __device__ __forceinline__ void wgmma_ss_n56_ta0_tb1(float (&d)[28], uint64_t da, uint64_t db) {
  if (SD) asm volatile("wgmma.mma_async.sync.aligned.m64n56k16.f32.bf16.bf16 {%0, %1, %2, %3, %4, %5, %6, %7, %8, %9, %10, %11, %12, %13, %14, %15, %16, %17, %18, %19, %20, %21, %22, %23, %24, %25, %26, %27}, %28, %29, 1, 1, 1, 0, 1;\n"
    : "+f"(d[0]), "+f"(d[1]), "+f"(d[2]), "+f"(d[3]), "+f"(d[4]), "+f"(d[5]), "+f"(d[6]), "+f"(d[7]), "+f"(d[8]), "+f"(d[9]), "+f"(d[10]), "+f"(d[11]), "+f"(d[12]), "+f"(d[13]), "+f"(d[14]), "+f"(d[15]), "+f"(d[16]), "+f"(d[17]), "+f"(d[18]), "+f"(d[19]), "+f"(d[20]), "+f"(d[21]), "+f"(d[22]), "+f"(d[23]), "+f"(d[24]), "+f"(d[25]), "+f"(d[26]), "+f"(d[27])
    : "l"(da), "l"(db));
  else asm volatile("wgmma.mma_async.sync.aligned.m64n56k16.f32.bf16.bf16 {%0, %1, %2, %3, %4, %5, %6, %7, %8, %9, %10, %11, %12, %13, %14, %15, %16, %17, %18, %19, %20, %21, %22, %23, %24, %25, %26, %27}, %28, %29, 0, 1, 1, 0, 1;\n"
    : "=f"(d[0]), "=f"(d[1]), "=f"(d[2]), "=f"(d[3]), "=f"(d[4]), "=f"(d[5]), "=f"(d[6]), "=f"(d[7]), "=f"(d[8]), "=f"(d[9]), "=f"(d[10]), "=f"(d[11]), "=f"(d[12]), "=f"(d[13]), "=f"(d[14]), "=f"(d[15]), "=f"(d[16]), "=f"(d[17]), "=f"(d[18]), "=f"(d[19]), "=f"(d[20]), "=f"(d[21]), "=f"(d[22]), "=f"(d[23]), "=f"(d[24]), "=f"(d[25]), "=f"(d[26]), "=f"(d[27])
    : "l"(da), "l"(db));
}
template <int SD> __device__ __forceinline__ void wgmma_ss_n8_ta0_tb1(float (&d)[4], uint64_t da, uint64_t db) {
  if (SD) asm volatile("wgmma.mma_async.sync.aligned.m64n8k16.f32.bf16.bf16 {%0, %1, %2, %3}, %4, %5, 1, 1, 1, 0, 1;\n"
    : "+f"(d[0]), "+f"(d[1]), "+f"(d[2]), "+f"(d[3])
    : "l"(da), "l"(db));
  else asm volatile("wgmma.mma_async.sync.aligned.m64n8k16.f32.bf16.bf16 {%0, %1, %2, %3}, %4, %5, 0, 1, 1, 0, 1;\n"
    : "=f"(d[0]), "=f"(d[1]), "=f"(d[2]), "=f"(d[3])
    : "l"(da), "l"(db));
}
template <int SD> __device__ __forceinline__ void wgmma_rs_n64_tb1(float (&d)[32], uint32_t a0, uint32_t a1, uint32_t a2, uint32_t a3, uint64_t db) {
  if (SD) asm volatile("wgmma.mma_async.sync.aligned.m64n64k16.f32.bf16.bf16 {%0, %1, %2, %3, %4, %5, %6, %7, %8, %9, %10, %11, %12, %13, %14, %15, %16, %17, %18, %19, %20, %21, %22, %23, %24, %25, %26, %27, %28, %29, %30, %31}, {%32, %33, %34, %35}, %36, 1, 1, 1, 1;\n"
    : "+f"(d[0]), "+f"(d[1]), "+f"(d[2]), "+f"(d[3]), "+f"(d[4]), "+f"(d[5]), "+f"(d[6]), "+f"(d[7]), "+f"(d[8]), "+f"(d[9]), "+f"(d[10]), "+f"(d[11]), "+f"(d[12]), "+f"(d[13]), "+f"(d[14]), "+f"(d[15]), "+f"(d[16]), "+f"(d[17]), "+f"(d[18]), "+f"(d[19]), "+f"(d[20]), "+f"(d[21]), "+f"(d[22]), "+f"(d[23]), "+f"(d[24]), "+f"(d[25]), "+f"(d[26]), "+f"(d[27]), "+f"(d[28]), "+f"(d[29]), "+f"(d[30]), "+f"(d[31])
    : "r"(a0), "r"(a1), "r"(a2), "r"(a3), "l"(db));
  else asm volatile("wgmma.mma_async.sync.aligned.m64n64k16.f32.bf16.bf16 {%0, %1, %2, %3, %4, %5, %6, %7, %8, %9, %10, %11, %12, %13, %14, %15, %16, %17, %18, %19, %20, %21, %22, %23, %24, %25, %26, %27, %28, %29, %30, %31}, {%32, %33, %34, %35}, %36, 0, 1, 1, 1;\n"
    : "=f"(d[0]), "=f"(d[1]), "=f"(d[2]), "=f"(d[3]), "=f"(d[4]), "=f"(d[5]), "=f"(d[6]), "=f"(d[7]), "=f"(d[8]), "=f"(d[9]), "=f"(d[10]), "=f"(d[11]), "=f"(d[12]), "=f"(d[13]), "=f"(d[14]), "=f"(d[15]), "=f"(d[16]), "=f"(d[17]), "=f"(d[18]), "=f"(d[19]), "=f"(d[20]), "=f"(d[21]), "=f"(d[22]), "=f"(d[23]), "=f"(d[24]), "=f"(d[25]), "=f"(d[26]), "=f"(d[27]), "=f"(d[28]), "=f"(d[29]), "=f"(d[30]), "=f"(d[31])
    : "r"(a0), "r"(a1), "r"(a2), "r"(a3), "l"(db));
}
template <int SD> __device__ __forceinline__ void wgmma_ss_n32_ta1_tb1(float (&d)[16], uint64_t da, uint64_t db) {
  if (SD) asm volatile("wgmma.mma_async.sync.aligned.m64n32k16.f32.bf16.bf16 {%0, %1, %2, %3, %4, %5, %6, %7, %8, %9, %10, %11, %12, %13, %14, %15}, %16, %17, 1, 1, 1, 1, 1;\n"
    : "+f"(d[0]), "+f"(d[1]), "+f"(d[2]), "+f"(d[3]), "+f"(d[4]), "+f"(d[5]), "+f"(d[6]), "+f"(d[7]), "+f"(d[8]), "+f"(d[9]), "+f"(d[10]), "+f"(d[11]), "+f"(d[12]), "+f"(d[13]), "+f"(d[14]), "+f"(d[15])
    : "l"(da), "l"(db));
  else asm volatile("wgmma.mma_async.sync.aligned.m64n32k16.f32.bf16.bf16 {%0, %1, %2, %3, %4, %5, %6, %7, %8, %9, %10, %11, %12, %13, %14, %15}, %16, %17, 0, 1, 1, 1, 1;\n"
    : "=f"(d[0]), "=f"(d[1]), "=f"(d[2]), "=f"(d[3]), "=f"(d[4]), "=f"(d[5]), "=f"(d[6]), "=f"(d[7]), "=f"(d[8]), "=f"(d[9]), "=f"(d[10]), "=f"(d[11]), "=f"(d[12]), "=f"(d[13]), "=f"(d[14]), "=f"(d[15])
    : "l"(da), "l"(db));
}
template <int SD> __device__ __forceinline__ void wgmma_ss_n32_ta0_tb1(float (&d)[16], uint64_t da, uint64_t db) {
  if (SD) asm volatile("wgmma.mma_async.sync.aligned.m64n32k16.f32.bf16.bf16 {%0, %1, %2, %3, %4, %5, %6, %7, %8, %9, %10, %11, %12, %13, %14, %15}, %16, %17, 1, 1, 1, 0, 1;\n"
    : "+f"(d[0]), "+f"(d[1]), "+f"(d[2]), "+f"(d[3]), "+f"(d[4]), "+f"(d[5]), "+f"(d[6]), "+f"(d[7]), "+f"(d[8]), "+f"(d[9]), "+f"(d[10]), "+f"(d[11]), "+f"(d[12]), "+f"(d[13]), "+f"(d[14]), "+f"(d[15])
    : "l"(da), "l"(db));
  else asm volatile("wgmma.mma_async.sync.aligned.m64n32k16.f32.bf16.bf16 {%0, %1, %2, %3, %4, %5, %6, %7, %8, %9, %10, %11, %12, %13, %14, %15}, %16, %17, 0, 1, 1, 0, 1;\n"
    : "=f"(d[0]), "=f"(d[1]), "=f"(d[2]), "=f"(d[3]), "=f"(d[4]), "=f"(d[5]), "=f"(d[6]), "=f"(d[7]), "=f"(d[8]), "=f"(d[9]), "=f"(d[10]), "=f"(d[11]), "=f"(d[12]), "=f"(d[13]), "=f"(d[14]), "=f"(d[15])
    : "l"(da), "l"(db));
}
template <int SD> __device__ __forceinline__ void wgmma_rs_n64_tb0(float (&d)[32], uint32_t a0, uint32_t a1, uint32_t a2, uint32_t a3, uint64_t db) {
  if (SD) asm volatile("wgmma.mma_async.sync.aligned.m64n64k16.f32.bf16.bf16 {%0, %1, %2, %3, %4, %5, %6, %7, %8, %9, %10, %11, %12, %13, %14, %15, %16, %17, %18, %19, %20, %21, %22, %23, %24, %25, %26, %27, %28, %29, %30, %31}, {%32, %33, %34, %35}, %36, 1, 1, 1, 0;\n"
    : "+f"(d[0]), "+f"(d[1]), "+f"(d[2]), "+f"(d[3]), "+f"(d[4]), "+f"(d[5]), "+f"(d[6]), "+f"(d[7]), "+f"(d[8]), "+f"(d[9]), "+f"(d[10]), "+f"(d[11]), "+f"(d[12]), "+f"(d[13]), "+f"(d[14]), "+f"(d[15]), "+f"(d[16]), "+f"(d[17]), "+f"(d[18]), "+f"(d[19]), "+f"(d[20]), "+f"(d[21]), "+f"(d[22]), "+f"(d[23]), "+f"(d[24]), "+f"(d[25]), "+f"(d[26]), "+f"(d[27]), "+f"(d[28]), "+f"(d[29]), "+f"(d[30]), "+f"(d[31])
    : "r"(a0), "r"(a1), "r"(a2), "r"(a3), "l"(db));
  else asm volatile("wgmma.mma_async.sync.aligned.m64n64k16.f32.bf16.bf16 {%0, %1, %2, %3, %4, %5, %6, %7, %8, %9, %10, %11, %12, %13, %14, %15, %16, %17, %18, %19, %20, %21, %22, %23, %24, %25, %26, %27, %28, %29, %30, %31}, {%32, %33, %34, %35}, %36, 0, 1, 1, 0;\n"
    : "=f"(d[0]), "=f"(d[1]), "=f"(d[2]), "=f"(d[3]), "=f"(d[4]), "=f"(d[5]), "=f"(d[6]), "=f"(d[7]), "=f"(d[8]), "=f"(d[9]), "=f"(d[10]), "=f"(d[11]), "=f"(d[12]), "=f"(d[13]), "=f"(d[14]), "=f"(d[15]), "=f"(d[16]), "=f"(d[17]), "=f"(d[18]), "=f"(d[19]), "=f"(d[20]), "=f"(d[21]), "=f"(d[22]), "=f"(d[23]), "=f"(d[24]), "=f"(d[25]), "=f"(d[26]), "=f"(d[27]), "=f"(d[28]), "=f"(d[29]), "=f"(d[30]), "=f"(d[31])
    : "r"(a0), "r"(a1), "r"(a2), "r"(a3), "l"(db));
}
template <int SD> __device__ __forceinline__ void wgmma_rs_n32_tb1(float (&d)[16], uint32_t a0, uint32_t a1, uint32_t a2, uint32_t a3, uint64_t db) {
  if (SD) asm volatile("wgmma.mma_async.sync.aligned.m64n32k16.f32.bf16.bf16 {%0, %1, %2, %3, %4, %5, %6, %7, %8, %9, %10, %11, %12, %13, %14, %15}, {%16, %17, %18, %19}, %20, 1, 1, 1, 1;\n"
    : "+f"(d[0]), "+f"(d[1]), "+f"(d[2]), "+f"(d[3]), "+f"(d[4]), "+f"(d[5]), "+f"(d[6]), "+f"(d[7]), "+f"(d[8]), "+f"(d[9]), "+f"(d[10]), "+f"(d[11]), "+f"(d[12]), "+f"(d[13]), "+f"(d[14]), "+f"(d[15])
    : "r"(a0), "r"(a1), "r"(a2), "r"(a3), "l"(db));
  else asm volatile("wgmma.mma_async.sync.aligned.m64n32k16.f32.bf16.bf16 {%0, %1, %2, %3, %4, %5, %6, %7, %8, %9, %10, %11, %12, %13, %14, %15}, {%16, %17, %18, %19}, %20, 0, 1, 1, 1;\n"
    : "=f"(d[0]), "=f"(d[1]), "=f"(d[2]), "=f"(d[3]), "=f"(d[4]), "=f"(d[5]), "=f"(d[6]), "=f"(d[7]), "=f"(d[8]), "=f"(d[9]), "=f"(d[10]), "=f"(d[11]), "=f"(d[12]), "=f"(d[13]), "=f"(d[14]), "=f"(d[15])
    : "r"(a0), "r"(a1), "r"(a2), "r"(a3), "l"(db));
}

__device__ __forceinline__ uint32_t sw64_off(int row, int d) { return row * 64 + ((((d >> 3) ^ (row >> 1)) & 3) << 4) + (d & 7) * 2; }

__device__ __forceinline__ uint32_t exp2_pair_fma(float t0, float t1, uint32_t c_half, uint32_t c_3) {
  uint32_t y0, y;
  asm("prmt.b32 %0, %1, %2, 0x6521;" : "=r"(y0) : "r"(__float_as_uint(t0)), "r"(__float_as_uint(t1)));
  uint32_t h = lop_and_or(y0, 0x007F007Fu, c_half);
  uint32_t e = lop_and_or(y0, 0xFF80FF80u, c_3);
  asm("fma.rn.bf16x2 %0, %1, %2, %3;" : "=r"(y) : "r"(y0), "r"(h), "r"(e));
  return y;
}

__device__ __forceinline__ void feature_map(float (&p)[32], uint32_t rb, int lq) {
  const float L2E = 1.4426950408889634f;
  const bool tail_ok = lq < 2;
  float mx[4], mn[4], b[32], sa[4], sn[4];
#pragma unroll
  for (int g = 0; g < 4; g++) {
    const int o = 16 * (g >> 1) + 2 * (g & 1);
    if (!tail_ok) { p[o + 12] = p[o]; p[o + 13] = p[o]; }
    mx[g] = fmaxf(fmaxf(fmaxf(p[o], p[o + 1]), fmaxf(p[o + 4], p[o + 5])), fmaxf(fmaxf(p[o + 8], p[o + 9]), fmaxf(p[o + 12], p[o + 13])));
    mn[g] = fminf(fminf(fminf(p[o], p[o + 1]), fminf(p[o + 4], p[o + 5])), fminf(fminf(p[o + 8], p[o + 9]), fminf(p[o + 12], p[o + 13])));
  }
#pragma unroll
  for (int o = 1; o <= 2; o <<= 1)
#pragma unroll
    for (int g = 0; g < 4; g++) { mx[g] = fmaxf(mx[g], __shfl_xor_sync(~0u, mx[g], o)); mn[g] = fminf(mn[g], __shfl_xor_sync(~0u, mn[g], o)); }
#pragma unroll
  for (int g = 0; g < 4; g++) {
    const int o = 16 * (g >> 1) + 2 * (g & 1);
    const float cx = -mx[g] * L2E, cn = mn[g] * L2E;
#pragma unroll
    for (int i = 0; i < 8; i++) {
      const int k = o + 4 * (i >> 1) + (i & 1);
      b[k] = ex2f(fmaf(p[k], -L2E, cn));
      p[k] = ex2f(fmaf(p[k], L2E, cx));
    }
    if (!tail_ok) { p[o + 12] = p[o + 13] = b[o + 12] = b[o + 13] = 0.f; }
    sa[g] = ((p[o] + p[o + 1]) + (p[o + 4] + p[o + 5])) + ((p[o + 8] + p[o + 9]) + (p[o + 12] + p[o + 13]));
    sn[g] = ((b[o] + b[o + 1]) + (b[o + 4] + b[o + 5])) + ((b[o + 8] + b[o + 9]) + (b[o + 12] + b[o + 13]));
    sa[g] += __shfl_xor_sync(~0u, sa[g], 1); sn[g] += __shfl_xor_sync(~0u, sn[g], 1);
    sa[g] += __shfl_xor_sync(~0u, sa[g], 2); sn[g] += __shfl_xor_sync(~0u, sn[g], 2);
  }
#pragma unroll
  for (int g = 0; g < 4; g++) {
    const int o = 16 * (g >> 1) + 2 * (g & 1);
    const float ra = rcpf(sa[g]), rn = rcpf(sn[g]);
    const uint32_t off = (g >> 1) * 16384 + (g & 1) * 1024;
#pragma unroll
    for (int jj = 0; jj < 4; jj++) {
      st_shared_nv((rb ^ (jj << 4)) + off, pack_bf16(p[o + 4 * jj] * ra, p[o + 4 * jj + 1] * ra));
      st_shared_nv((rb ^ ((4 + jj) << 4)) + off, pack_bf16(b[o + 4 * jj] * rn, b[o + 4 * jj + 1] * rn));
    }
  }
}

__device__ __forceinline__ void store_heads(uint32_t base, const uint32_t (&a)[14], uint32_t pad0, uint32_t pad1, int row0, int lq) {
  const uint32_t rb = base + row0 * 64 + (((row0 >> 1) & 3) << 4);
  const uint32_t b0 = rb + lq * 4;
  const uint32_t b1 = (rb + 8192 + ((lq * 4 + 8) & 15)) ^ ((lq >> 1) << 4);
#pragma unroll
  for (int j = 0; j < 7; j++) {
    uint32_t ad;
    if (j < 3) ad = b0 ^ (j << 4);
    else if (j == 3) ad = (lq < 2) ? (b0 ^ 48u) : (b1 ^ 16u);
    else ad = (lq < 2) ? (b1 ^ ((j - 4) << 4)) : ((b1 ^ 16u) ^ ((j - 3) << 4));
    sts32(ad, a[2 * j]);
    sts32(ad + 512, a[2 * j + 1]);
  }
  sts64((rb ^ 48u) + 8 + (lq & 1) * 8192 + (lq >> 1) * 512, pad0, pad1);
}

struct Params {
  const __nv_bfloat16* w_phi;
  const __nv_bfloat16* wk;
  const __nv_bfloat16* wv;
  const __nv_bfloat16* gate_w;
  __nv_bfloat16* out;
};

__global__ void __launch_bounds__(NTHREADS, 1)
fused_kernel(const __grid_constant__ CUtensorMap tm_x, const __grid_constant__ CUtensorMap tm_wqkv,
             const __grid_constant__ CUtensorMap tm_wq, const __grid_constant__ CUtensorMap tm_woa,
             const __grid_constant__ CUtensorMap tm_wob, const Params prm) {
  extern __shared__ uint8_t smem_raw[];
  uint32_t sb = (smem_u32(smem_raw) + 1023u) & ~1023u;
  uint8_t* sgen = smem_raw + (sb - smem_u32(smem_raw));
  asm volatile("mov.u32 %0, %0;" : "+r"(sb));
  const int tid = threadIdx.x, lane = tid & 31;
  const int warp = __shfl_sync(~0u, tid >> 5, 0), wg = warp >> 2;
  const int pt = blockIdx.x >> 3, hp = blockIdx.x & 7;
  const uint32_t bars = sb + OFF_BAR;
  auto BAR = [&](int i) { return bars + 8u * i; };
  const unsigned epoch = g_epoch & 1;

  if (tid == 0) { PROF_MARK(0); PROF_CLK(30); PROF2(15); }
  auto load_proj = [&](int c, int g) {
    mbar_expect_tx(BAR(B_FULL + g), (c < 3 ? 16384 : 0) + 4 * 7168);
    if (c < 3) tma_2d(sb + OFF_X + c * 16384, &tm_x, c * 64, pt * 128, BAR(B_FULL + g));
    tma_2d(sb + OFF_RING + g * 32768, &tm_wq, hp * 56, c * 64, BAR(B_FULL + g));
#pragma unroll 1
    for (int j = 0; j < 3; j++) tma_2d(sb + OFF_RING + g * 32768 + 8192 + j * 8192, &tm_wqkv, j * DM + hp * 56, c * 64, BAR(B_FULL + g));
  };
  if (warp == 16) {
    if (elect_one()) {
      mbar_init(BAR(B_FULL), 1);
      fence_async_smem();
      load_proj(0, 0);
      mbar_init(BAR(B_RAW), 1); mbar_init(BAR(B_FULL + 1), 1); mbar_init(BAR(B_FULL + 2), 1);
      fence_async_smem();
    }
    __syncwarp();
    asm volatile("bar.arrive 0, %0;" ::"n"(NTHREADS) : "memory");
  } else {
    if (elect_one()) {
      const int i = warp + 3 - (warp > 16);
      if (i < B_N && i != B_RAW) {
        int cnt = i < B_WO || (i > B_SIG && i < B_XL) || i == B_X1FREE ? 16 : 1;
        if (i == B_BUILD) cnt = 16;
        if (i == B_SIG || i == B_SIG + 1 || i == B_QSQ) cnt = 8;
        if (i == B_KVR) cnt = 2;
        mbar_init(BAR(i), cnt);
        fence_async_smem();
      }
    }
    bar_sync(0, NTHREADS);
  }
  if (tid == 0) PROF2(14);

  if (wg == 4) {
    asm volatile("setmaxnreg.dec.sync.aligned.u32 32;");
    if (warp == 16) {
      if (elect_one()) {
        mbar_expect_tx(BAR(B_RAW), 25088 + 3136 + 896);
        bulk_g2s(sb + OFF_RAW, hp < 4 ? prm.wk : prm.wv, 25088, BAR(B_RAW));
        bulk_g2s(sb + OFF_RAW + 25088, prm.w_phi + 2 * hp * DH * DH, 3136, BAR(B_RAW));
        bulk_g2s(sb + OFF_RAW + 28224, prm.gate_w, 896, BAR(B_RAW));
        load_proj(1, 1);
        load_proj(2, 2);
      }
      __syncwarp();
      bar_sync(3, 64);
      if (elect_one()) {
        int g = 0, nkv = 8;
        uint32_t par = 0;
#pragma unroll 1
        for (int c = 3; c < 7; c++) {
          if (c == 5) mbar_wait(BAR(B_BUILD), 0);
          if (c & 1) mbar_expect_tx(BAR(B_XL + (c > 4)), 32768);
          tma_2d(sb + OFF_X + c * 16384, &tm_x, c * 64, pt * 128, BAR(B_XL + (c > 4)));
        }
        uint32_t todo = 15;
#pragma unroll 1
        for (int n = 3; n < 15 + nkv; n++) {
          if (n == 7) { PROF_MARK(20); cnt_wait(C_KV, NCTA); PROF_MARK(21); fence_async_all(); }
          if (n == 15) {
            mbar_wait(BAR(B_SLOW), 0);
            if (*(volatile int*)(sgen + OFF_RED)) nkv = 26;
          }
          int j = n - 7 - nkv;
          if (j == 0) { PROF3(8); cnt_wait(C_OA + pt, 8); PROF3(9); fence_async_all(); }
          const bool last = j == 7;
          if (!last) mbar_wait(BAR(B_EMPTY + g), par);
          if (j >= 4) {
            uint32_t rdy, spin = 0;
            if (j == 4) PROF3(11);
#pragma unroll 1
            while (true) {
              uint4 v;
              asm volatile("ld.acquire.gpu.global.v4.u32 {%0, %1, %2, %3}, [%4];"
                           : "=r"(v.x), "=r"(v.y), "=r"(v.z), "=r"(v.w) : "l"(&g_cnt[(C_OB + pt) * 32]) : "memory");
              rdy = ((v.x >= 2) | (v.y >= 2) << 1 | (v.z >= 2) << 2 | (v.w >= 2) << 3) & todo;
              if (rdy || ++spin >= (1u << 18)) break;
            }
            const int pick = __ffs(rdy ? rdy : todo) - 1;
            todo &= ~(1u << pick);
            ((volatile int*)(sgen + OFF_RED + 16))[j - 4] = pick;
            j = 4 + pick;
            PROF3(12);
            PROF_MARK(26);
            fence_async_all();
          }
          if (n < 7) { PROF2(20 + n); load_proj(n, g); }
          else {
            const uint32_t fb = BAR(last ? B_RAW : B_FULL + g);
            mbar_expect_tx(fb, 32768);
            bulk_g2s(last ? sb + OFF_WO : sb + OFF_RING + g * 32768,
                     j < 0 ? g_kv_img + ((n - 7) & 7) * 32768 : g_o_img + (size_t)(pt * 8 + j) * 32768, 32768, fb);
          }
          if (++g == 3) { g = 0; par ^= 1; }
        }
        if (atomicAdd(&g_cnt[C_DONE * 32], 1u) == NCTA - 1) {
#pragma unroll 1
          for (int i = 0; i < C_N; i++) *(uint4*)&g_cnt[i * 32] = make_uint4(0u, 0u, 0u, 0u);
          g_epoch = epoch ^ 1;
        }
      }
    } else {
      if (warp == 18) {
        if (elect_one()) {
#pragma unroll 1
          for (int i = 0; i < 4; i++) {
            mbar_wait(BAR(B_SIG + i), 0);
            PROF3(2 * i);
            if (i == 1) {
#pragma unroll 1
              for (int j = 0; j < 4; j++)
                asm volatile("cp.reduce.async.bulk.global.shared::cta.bulk_group.add.f32 [%0], [%1], 8192;"
                             ::"l"(g_kvacc[epoch] + hp * 4096 + (j >> 1) * 2048), "r"(sb + OFF_PHIK + j * 8192) : "memory");
            }
            if (i >= 2)
              asm volatile("cp.async.bulk.global.shared::cta.bulk_group [%0], [%1], 16384;"
                           ::"l"(g_o_img + (size_t)(pt * 2 + i - 2) * 131072 + hp * 16384), "r"(sb + OFF_OSTG) : "memory");
            if (i >= 1) asm volatile("cp.async.bulk.commit_group;\ncp.async.bulk.wait_group 0;" ::: "memory");
            asm volatile("red.release.gpu.global.add.u32 [%0], 1;"
                         ::"l"(&g_cnt[(i == 0 ? C_KV : i == 1 ? C_PART : (i == 2 ? C_OA : C_OB) + pt) * 32 + (i == 3 ? hp >> 1 : 0)]) : "memory");
            PROF3(2 * i + 1);
            if (i == 1 || i == 2) {
              if (i == 2) mbar_wait(BAR(B_X1FREE), 0);
              mbar_expect_tx(BAR(B_WO + i - 1), 7 * 7168);
#pragma unroll 1
              for (int c = 0; c < 7; c++)
                tma_2d(sb + OFF_WO + (i - 1) * 57344 + c * 8192, i == 1 ? &tm_woa : &tm_wob, hp * 56, c * 64, BAR(B_WO + i - 1));
            }
          }
        }
      } else if (warp == 19) {
        if (lane == 0) {
          mbar_wait(BAR(B_SIG + 0), 0);
          cnt_wait(C_KV, NCTA);
        }
        __syncwarp();
        float ksq = 0.f, vsq = 0.f;
#pragma unroll
        for (int sl = 0; sl < 4; sl++) {
          float4 a = ldcg_f4(g_ksq + sl * 128 + lane * 4), b = ldcg_f4(g_vsq + sl * 128 + lane * 4);
          float m = fmaxf(fmaxf(a.x, a.y), fmaxf(a.z, a.w));
          m = __uint_as_float(__reduce_max_sync(~0u, __float_as_uint(m)));
          ksq += m;
          vsq = fmaxf(vsq, fmaxf(fmaxf(b.x, b.y), fmaxf(b.z, b.w)));
        }
        mbar_wait(BAR(B_QSQ), 0);
        const float4 qa4 = ((const float4*)(sgen + OFF_QSQ))[lane], qb4 = ((const float4*)(sgen + OFF_QSQ))[32 + lane];
        const float qmax = fmaxf(fmaxf(fmaxf(qa4.x, qa4.y), fmaxf(qa4.z, qa4.w)), fmaxf(fmaxf(qb4.x, qb4.y), fmaxf(qb4.z, qb4.w)));
        const bool slow = __any_sync(~0u, !(qmax * ksq <= 98.f * 98.f) || !(vsq <= 2.0e8f));
        if (lane == 0) {
          *(volatile int*)(sgen + OFF_RED) = slow;
          mbar_arrive(BAR(B_SLOW), 1);
        }
      } else {
        float4* z = (float4*)(g_kvacc[epoch ^ 1] + blockIdx.x * 256) + lane;
        z[0] = make_float4(0.f, 0.f, 0.f, 0.f);
        z[32] = make_float4(0.f, 0.f, 0.f, 0.f);
        bar_sync(3, 64);
        if (lane == 0) {
          mbar_wait(BAR(B_SIG + 0), 0);
          cnt_wait(C_KV, NCTA);
        }
        __syncwarp();
        ((float4*)(sgen + OFF_GATE))[lane] = ldcg_f4(g_gate + pt * 128 + lane * 4);
      }
      if (warp != 18) {
        if (lane == 0) {
          mbar_wait(BAR(B_SIG + 1), 0);
          cnt_wait(C_PART, NCTA);
          PROF_MARK(23);
        }
        __syncwarp();
        const int e = warp == 19;
        const float* src = g_kvacc[epoch] + hp * 4096 + e * 2048 + (lane ^ ((lane >> 2) & 3)) * 8;
#pragma unroll 1
        for (int i = 0; i < 8; i += 2) {
          const float4 a = ldcg_f4(src + i * 256), b = ldcg_f4(src + i * 256 + 4), c = ldcg_f4(src + i * 256 + 256), d = ldcg_f4(src + i * 256 + 260);
          const uint32_t ad = sb + OFF_KVR + e * 4096 + sw64_off(i * 8 + (lane >> 2), (lane & 3) * 8);
          sts128(ad, make_uint4(pack_bf16(a.x, a.y), pack_bf16(a.z, a.w), pack_bf16(b.x, b.y), pack_bf16(b.z, b.w)));
          sts128(ad + 512, make_uint4(pack_bf16(c.x, c.y), pack_bf16(c.z, c.w), pack_bf16(d.x, d.y), pack_bf16(d.z, d.w)));
        }
        fence_async_smem();
        __syncwarp();
        if (lane == 0) mbar_arrive(BAR(B_KVR), 1);
        PROF_MARK(24);
      }
    }
  } else {
    asm volatile("setmaxnreg.inc.sync.aligned.u32 112;");
    const int mh = wg & 1, nh = wg >> 1, wq = warp & 3;
    const int lq = lane & 3;
    const int rowl = wq * 16 + (lane >> 2);
    const int row0 = mh * 64 + rowl;
    int slot = 0;
    uint32_t par = 0;
    {
      float acc0[28], acc1[28], accs[4];
      const uint64_t dR = make_desc(sb + OFF_RING + nh * 16384, 1024, 1024, 1);
      const uint64_t dX = make_desc(sb + OFF_X + mh * 8192, 1024, 1024, 1);
#pragma unroll
      for (int i = 0; i < 28; i++) acc0[i] = acc1[i] = 0.f;
#pragma unroll
      for (int i = 0; i < 4; i++) accs[i] = 0.f;
      const uint64_t dSlc = make_desc(sb + OFF_SLC, 128, 128, 0);
#pragma unroll 1
      for (int c = 0; c < 7; c++) {
        if (c == 3 || c == 5) mbar_wait(BAR(B_XL + (c > 4)), 0);
        mbar_wait(BAR(B_FULL + slot), par);
        if (c == 0 && tid == 0) PROF2(17);
        const uint64_t dA = dX + c * 1024, dB = dR + slot * 2048;
        wg_fence();
#pragma unroll
        for (int ks = 0; ks < 4; ks++) {
          wgmma_ss_n56_ta0_tb1<1>(acc0, dA + ks * 2, dB + ks * 128);
          wgmma_ss_n56_ta0_tb1<1>(acc1, dA + ks * 2, dB + 512 + ks * 128);
        }
        if (nh == 1 && c > 0) {
#pragma unroll
          for (int ks = 0; ks < 4; ks++) wgmma_ss_n8_ta0_tb1<1>(accs, dA - 1024 + ks * 2, dSlc + (c - 1) * 64 + ks * 16);
        }
        wg_commit();
        if (c == 0) {
          mbar_wait(BAR(B_RAW), 0);
          const int k = tid >> 3, cn = tid & 7;
          const bool data = k < 56 && (cn >> 2) == (k >= DH);
          const uint2* wsrc = (const uint2*)(sgen + OFF_RAW + 25088 + k * 56 + (cn & 3) * 16);
          uint2 w0 = make_uint2(0u, 0u), w1 = w0;
          if (data) w0 = wsrc[0];
          if (data && (cn & 3) != 3) w1 = wsrc[1];
          sts128(sb + OFF_WBD + k * 128 + ((cn ^ (k & 7)) << 4), make_uint4(w0.x, w0.y, w1.x, w1.y));
          if (tid < DM) {
            const uint2* src = (const uint2*)(sgen + OFF_RAW + tid * 56 + (hp & 3) * 16);
            w0 = src[0];
            w1 = make_uint2(hp == 3 ? (uint32_t)((const unsigned short*)(sgen + OFF_RAW + 28224))[tid] : 0u, 0u);
            if ((hp & 3) != 3) w1 = src[1];
            sts128(sb + OFF_SLC + tid * 16, make_uint4(w0.x, w0.y, w1.x, w1.y));
          }
          fence_async_smem();
          __syncwarp();
          if (lane == 0) mbar_arrive(BAR(B_BUILD), 1);
          mbar_wait(BAR(B_BUILD), 0);
        }
        wg_wait<0>();
        if (lane == 0) mbar_arrive(BAR(B_EMPTY + slot), 1);
        if (++slot == 3) { slot = 0; par ^= 1; }
      }
      if (nh == 1) {
        wg_fence();
#pragma unroll
        for (int ks = 0; ks < 4; ks++) wgmma_ss_n8_ta0_tb1<1>(accs, dX + 6 * 1024 + ks * 2, dSlc + 6 * 64 + ks * 16);
        wg_commit();
      }
      wg_wait<0>();
      fence_regs(acc0); fence_regs(acc1); fence_regs(accs);
      if (tid == 0) PROF_MARK(2);
      if (tid == 256) PROF_MARK(3);
      if (nh == 0) {
        float sq[4] = {0.f, 0.f, 0.f, 0.f};
#pragma unroll
        for (int i = 0; i < 28; i++) acc0[i] *= 0.18898223650461362f * 1.4426950408889634f;
#pragma unroll
        for (int j = 0; j < 7; j++) {
#pragma unroll
          for (int rr = 0; rr < 2; rr++) {
            const float s2 = acc0[4 * j + 2 * rr] * acc0[4 * j + 2 * rr] + acc0[4 * j + 2 * rr + 1] * acc0[4 * j + 2 * rr + 1];
            if (j < 3) sq[rr] += s2;
            else if (j > 3) sq[2 + rr] += s2;
            else { sq[rr] += (lq < 2) ? s2 : 0.f; sq[2 + rr] += (lq < 2) ? 0.f : s2; }
          }
        }
#pragma unroll
        for (int i = 0; i < 4; i++) sq[i] = quad_sum(sq[i]);
        const float mine = lq == 0 ? sq[0] : lq == 1 ? sq[1] : lq == 2 ? sq[2] : sq[3];
        ((float*)(sgen + OFF_QSQ))[(mh + (lq & 2)) * 64 + rowl + 8 * (lq & 1)] = mine <= 3.0e38f ? mine : __int_as_float(0x7f800000);
        __syncwarp();
        if (lane == 0) mbar_arrive(BAR(B_QSQ), 1);
      } else {
        const int sl = hp & 3;
        const bool isk = hp < 4, real = (sl < 3) || (lq < 2);
        const int pos = pt * 128 + row0, kr = pos & 63;
        uint8_t* dst = g_kv_img + (pos >> 6) * 8192 + (isk ? 0 : 4096) + sw64_off(kr, sl * 8 + 2 * lq);
        const uint32_t pat = isk ? POLY_PAT >> (kr >> 3) : 0u;
        float mxv = 0.f;
#pragma unroll
        for (int rr = 0; rr < 2; rr++) {
          const float v0 = accs[2 * rr], v1 = accs[2 * rr + 1];
          const bool poly = (pat >> rr) & 1;
          const float sc = poly ? 2.f : 1.f;
          const float s2 = quad_sum(real ? v0 * v0 + v1 * v1 : 0.f);
          mxv = fmaxf(mxv, s2 <= 3.0e38f ? s2 : __int_as_float(0x7f800000));
          const uint32_t padv = lq == 2 ? (poly ? 0x443F4000u : 0x00003F80u) : (poly ? 0x3AB03F4Du : 0u);
          *(uint32_t*)(dst + rr * 512) = real ? pack_bf16(sc * v0, sc * v1) : padv;
          if (hp == 3 && lq == 2) g_gate[pos + 8 * rr] = rcpf(1.f + ex2f(-1.4426950408889634f * v0));
        }
        mxv = __uint_as_float(__reduce_max_sync(~0u, __float_as_uint(mxv)));
        if (lane == 0) (isk ? g_ksq : g_vsq)[sl * 128 + pt * 8 + mh * 4 + wq] = mxv;
        __syncwarp();
        if (lane == 0) mbar_arrive(BAR(B_SIG + 0), 1);
      }
      if (tid == 0) PROF_MARK(4);
      if (tid == 256) PROF_MARK(5);
      uint32_t h[14];
      float pp[32];
      {
        uint32_t a[16];
#pragma unroll
        for (int i = 0; i < 14; i++) {
          const uint32_t u0 = pack_bf16(acc0[2 * i], acc0[2 * i + 1]), u1 = pack_bf16(acc1[2 * i], acc1[2 * i + 1]);
          h[i] = nh ? u1 : u0;
          a[i] = nh ? u0 : u1;
        }
        a[14] = a[0] ^ 0x80008000u;
        a[15] = a[1] ^ 0x80008000u;
        const uint64_t dW = make_desc(sb + OFF_WBD, 1024, 1024, 1);
        wg_fence();
        wgmma_rs_n64_tb1<0>(pp, a[0], a[1], a[2], a[3], dW);
#pragma unroll
        for (int ks = 1; ks < 4; ks++) wgmma_rs_n64_tb1<1>(pp, a[4 * ks], a[4 * ks + 1], a[4 * ks + 2], a[4 * ks + 3], dW + ks * 128);
        wg_commit();
        bar_sync(1, 512);
        if (tid == 0) PROF_MARK(6);
        store_heads(sb + (nh ? OFF_VA : OFF_QP), h, nh ? 0x00003F80u : 0x3F800000u, nh ? 0u : 0x3F803F80u, row0, lq);
        wg_wait<0>();
        fence_regs(pp);
      }
      feature_map(pp, sb + (nh ? OFF_PHIK : OFF_PHIQ) + row0 * 128 + lq * 4 + ((rowl & 7) << 4), lq);
      fence_async_smem();
      bar_sync(1, 512);
      if (tid == 0) PROF_MARK(7);
      if (nh == 1) {
        float kv0[16], kv1[16];
        const uint64_t dP = make_desc(sb + OFF_PHIK + mh * 8192, 1024, 1024, 1);
        const uint64_t dV = make_desc(sb + OFF_VA + mh * 4096, 512, 512, 2);
        wg_fence();
        wgmma_ss_n32_ta1_tb1<0>(kv0, dP, dV);
        wgmma_ss_n32_ta1_tb1<0>(kv1, dP + 1024, dV + 512);
#pragma unroll
        for (int ks = 1; ks < 4; ks++) {
          wgmma_ss_n32_ta1_tb1<1>(kv0, dP + ks * 128, dV + ks * 64);
          wgmma_ss_n32_ta1_tb1<1>(kv1, dP + 1024 + ks * 128, dV + 512 + ks * 64);
        }
        wg_commit();
        wg_wait<0>();
        fence_regs(kv0); fence_regs(kv1);
        bar_sync(4 + wg, 128);
        const uint32_t sa = sb + OFF_PHIK + mh * 8192 + rowl * 128 + lq * 8 + (rowl & 3) * 32;
#pragma unroll
        for (int j = 0; j < 8; j++) {
          sts64((sa ^ (32 * (j >> 1))) + 1024 * (j & 1), __float_as_uint(kv0[2 * j]), __float_as_uint(kv0[2 * j + 1]));
          sts64((sa ^ (32 * (j >> 1))) + 16384 + 1024 * (j & 1), __float_as_uint(kv1[2 * j]), __float_as_uint(kv1[2 * j + 1]));
        }
        fence_async_smem();
        __syncwarp();
        if (lane == 0) mbar_arrive(BAR(B_SIG + 1), 1);
        if (tid == 256) PROF_MARK(28);
      }
    }
    {
      const uint64_t dK = make_desc(sb + OFF_RING, 512, 512, 2);
      const uint64_t dhi = dK & 0xffffffff00000000ull;
      const uint32_t dlo0 = (uint32_t)dK;
      uint32_t ok = 0, q[8];
      float o[16];
#pragma unroll
      for (int i = 0; i < 16; i++) o[i] = 0.f;
      {
        const int r = mh * 64 + wq * 16 + (lane & 7) + ((lane >> 3) & 1) * 8;
        ldsm4(q, sb + OFF_QP + nh * 8192 + sw64_off(r, (lane >> 4) * 8));
        ldsm4(q + 4, sb + OFF_QP + nh * 8192 + sw64_off(r, 16 + (lane >> 4) * 8));
      }
      if (tid == 0) PROF_MARK(10);
      const int qb = QB_AT;
      float s[32];
      mbar_wait(BAR(B_FULL + slot), par);
      wg_fence();
      wgmma_rs_n64_tb0<0>(s, q[0], q[1], q[2], q[3], dhi | (dlo0 + slot * 2048));
      wgmma_rs_n64_tb0<1>(s, q[4], q[5], q[6], q[7], dhi | (dlo0 + slot * 2048 + 2));
      wg_commit();
      wg_wait<0>();
      fence_regs(s);
#pragma unroll 1
      for (int it = 0; it <= 8; it++) {
        uint32_t p[16];
        if ((tid & 127) == 0) PROF4(wg * 32 + it);
        if (it == qb || it == 8) {
          float t[16];
          if (it < 8) {
            if (tid == 0) PROF_MARK(11);
            mbar_wait(BAR(B_KVR), 0);
            const uint64_t dR = make_desc(sb + OFF_KVR + nh * 4096, 512, 512, 2);
            const uint64_t dP = make_desc(sb + OFF_PHIQ + nh * 16384 + mh * 8192, 1024, 1024, 1);
            wg_fence();
            wgmma_ss_n32_ta0_tb1<0>(t, dP, dR);
#pragma unroll
            for (int ks = 1; ks < 4; ks++) wgmma_ss_n32_ta0_tb1<1>(t, dP + ks * 2, dR + ks * 64);
            wg_commit();
            wg_wait<0>();
            fence_regs(t);
            if (lane == 0) mbar_arrive(BAR(B_X1FREE), 1);
          } else {
            if (tid == 0) PROF_MARK(13);
            mbar_wait(BAR(B_SLOW), 0);
            if (__builtin_expect(__any_sync(~0u, *(volatile int*)(sgen + OFF_RED)), 0)) {
              uint32_t qz[8];
#pragma unroll
              for (int i = 0; i < 8; i++) qz[i] = (i >= 6 && lq >= 2) ? 0u : q[i];
              float m0 = -3.0e38f, m1 = -3.0e38f, o2[16];
              int sl2 = slot;
              uint32_t par2 = par;
#pragma unroll 1
              for (int j64 = 0; j64 < 32; j64++) {
                float s[32];
                mbar_wait(BAR(B_FULL + sl2), par2);
                const uint32_t lo = dlo0 + sl2 * 2048 + (j64 & 3) * 512;
                wg_fence();
                wgmma_rs_n64_tb0<0>(s, qz[0], qz[1], qz[2], qz[3], dhi | lo);
                wgmma_rs_n64_tb0<1>(s, qz[4], qz[5], qz[6], qz[7], dhi | (lo + 2));
                wg_commit();
                wg_wait<0>();
                fence_regs(s);
#pragma unroll
                for (int j = 0; j < 8; j++) {
                  const float sc = ((POLY_PAT >> j) & 1) ? 0.5f : 1.f;
                  m0 = fmaxf(m0, fmaxf(s[4 * j], s[4 * j + 1]) * sc);
                  m1 = fmaxf(m1, fmaxf(s[4 * j + 2], s[4 * j + 3]) * sc);
                }
                if ((j64 & 3) == 3) {
                  if (lane == 0) mbar_arrive(BAR(B_EMPTY + sl2), 1);
                  if (++sl2 == 3) { sl2 = 0; par2 ^= 1; }
                }
              }
              m0 = quad_max(m0); m1 = quad_max(m1);
#pragma unroll
              for (int i = 0; i < 16; i++) o2[i] = 0.f;
#pragma unroll 1
              for (int j64 = 0; j64 < 32; j64++) {
                float s[32];
                mbar_wait(BAR(B_FULL + sl2), par2);
                const uint32_t lo = dlo0 + sl2 * 2048 + (j64 & 3) * 512;
                wg_fence();
                wgmma_rs_n64_tb0<0>(s, qz[0], qz[1], qz[2], qz[3], dhi | lo);
                wgmma_rs_n64_tb0<1>(s, qz[4], qz[5], qz[6], qz[7], dhi | (lo + 2));
                wg_commit();
                wg_wait<0>();
                fence_regs(s);
                uint32_t ps[16];
#pragma unroll
                for (int j = 0; j < 8; j++) {
                  const float sc = ((POLY_PAT >> j) & 1) ? 0.5f : 1.f;
                  ps[2 * j] = pack_bf16(ex2f(fmaf(s[4 * j], sc, -m0)), ex2f(fmaf(s[4 * j + 1], sc, -m0)));
                  ps[2 * j + 1] = pack_bf16(ex2f(fmaf(s[4 * j + 2], sc, -m1)), ex2f(fmaf(s[4 * j + 3], sc, -m1)));
                }
                wg_fence();
#pragma unroll
                for (int ks = 0; ks < 4; ks++)
                  wgmma_rs_n32_tb1<1>(o2, ps[4 * ks], ps[4 * ks + 1], ps[4 * ks + 2], ps[4 * ks + 3], dhi | (lo + 256 + ks * 64));
                wg_commit();
                wg_wait<0>();
                fence_regs(o2);
                if ((j64 & 3) == 3) {
                  if (lane == 0) mbar_arrive(BAR(B_EMPTY + sl2), 1);
                  if (++sl2 == 3) { sl2 = 0; par2 ^= 1; }
                }
              }
#pragma unroll 1
              for (int j = 0; j < 2; j++) {
                mbar_wait(BAR(B_FULL + sl2), par2);
                __syncwarp();
                if (lane == 0) mbar_arrive(BAR(B_EMPTY + sl2), 1);
                if (++sl2 == 3) { sl2 = 0; par2 ^= 1; }
              }
#pragma unroll
              for (int i = 0; i < 16; i++) o[i] = o2[i];
            }
#pragma unroll
            for (int i = 0; i < 16; i++) t[i] = o[i];
#pragma unroll
            for (int i = 0; i < 32; i++) s[i] = 0.f;
          }
          const int br = it == 8;
          const float eps = br ? 0.f : 1e-6f;
          const float g0 = ((const float*)(sgen + OFF_GATE))[row0], g1 = ((const float*)(sgen + OFF_GATE))[row0 + 8];
          const float d0 = __shfl_sync(~0u, t[12], (lane & ~3) | 2), d1 = __shfl_sync(~0u, t[14], (lane & ~3) | 2);
          const float r0 = (br ? 1.f - g0 : g0) * rcpf(d0 + eps), r1 = (br ? 1.f - g1 : g1) * rcpf(d1 + eps);
          const uint32_t oa = sb + OFF_OSTG + (nh * 2 + mh) * 4096 + sw64_off(rowl, 2 * lq);
#pragma unroll
          for (int j = 0; j < 4; j++) {
            const bool real = j < 3 || lq < 2;
            sts32(oa ^ (j << 4), real ? pack_bf16(t[4 * j] * r0, t[4 * j + 1] * r0) : 0u);
            sts32((oa ^ (j << 4)) + 512, real ? pack_bf16(t[4 * j + 2] * r1, t[4 * j + 3] * r1) : 0u);
          }
          fence_async_smem();
          __syncwarp();
          if (lane == 0) mbar_arrive(BAR(B_SIG + 2 + br), 1);
          if (tid == 0) PROF_MARK(12 + 2 * br);
          if (br) { if ((tid & 127) == 0) PROF4(wg * 32 + 9); break; }
        }
        const uint32_t lo = dlo0 + slot * 2048;
        int nslot = slot + 1;
        uint32_t npar = par;
        if (nslot == 3) { nslot = 0; npar ^= 1; }
#pragma unroll
        for (int u = 0; u < 4; u++) {
          if (u == 2) ok = mbar_test(BAR(B_FULL + nslot), npar);
#pragma unroll
          for (int j = 0; j < 8; j++) {
            if ((POLY_PAT >> j) & 1) {
              p[2 * j] = exp2_pair_fma(s[4 * j], s[4 * j + 1], 0x3F003F00u, 0x00030003u);
              p[2 * j + 1] = exp2_pair_fma(s[4 * j + 2], s[4 * j + 3], 0x3F003F00u, 0x00030003u);
            } else {
              p[2 * j] = pack_bf16(ex2f(s[4 * j]), ex2f(s[4 * j + 1]));
              p[2 * j + 1] = pack_bf16(ex2f(s[4 * j + 2]), ex2f(s[4 * j + 3]));
            }
          }
          if (u == 3 && !ok && it < 7) mbar_wait(BAR(B_FULL + nslot), npar);
          const uint32_t ln = u < 3 ? lo + (u + 1) * 512 : dlo0 + nslot * 2048;
          wg_fence();
#pragma unroll
          for (int ks = 0; ks < 4; ks++)
            wgmma_rs_n32_tb1<1>(o, p[4 * ks], p[4 * ks + 1], p[4 * ks + 2], p[4 * ks + 3], dhi | (lo + u * 512 + 256 + ks * 64));
          wgmma_rs_n64_tb0<0>(s, q[0], q[1], q[2], q[3], dhi | ln);
          wgmma_rs_n64_tb0<1>(s, q[4], q[5], q[6], q[7], dhi | (ln + 2));
          wg_commit();
          wg_wait<0>();
          fence_regs(s);
          fence_regs(o);
        }
        if (lane == 0) mbar_arrive(BAR(B_EMPTY + slot), 1);
        slot = nslot; par = npar;
      }
      wg_wait<0>();
    }
    if (nh == 1) return;
    {
      float acc[28];
#pragma unroll
      for (int i = 0; i < 28; i++) acc[i] = 0.f;
      const uint64_t dS = make_desc(sb + OFF_WO, 1024, 1024, 1);
      const uint64_t dR = make_desc(sb + OFF_RING + mh * 4096, 512, 512, 2);
#pragma unroll 1
      for (int c = 0; c < 8; c++) {
        mbar_wait(BAR(B_WO + (c >> 2)), 0);
        mbar_wait(BAR(c == 7 ? B_RAW : B_FULL + slot), c == 7 ? 1 : par);
        const int id = c < 4 ? c : 4 + __shfl_sync(~0u, ((volatile int*)(sgen + OFF_RED + 16))[c & 3], 0);
        const uint64_t dA = c == 7 ? dR - (OFF_RING - OFF_WO) / 16 : dR + slot * 2048, dB = dS + id * 896;
        wg_fence();
#pragma unroll
        for (int h = 0; h < 4; h++) {
          wgmma_ss_n56_ta0_tb1<1>(acc, dA + h * 512, dB + h * 224);
          wgmma_ss_n56_ta0_tb1<1>(acc, dA + h * 512 + 2, dB + h * 224 + 128);
        }
        wg_commit();
        if (c < 4) {
          wg_wait<0>();
          if (lane == 0) mbar_arrive(BAR(B_EMPTY + slot), 2);
        }
        if (++slot == 3) { slot = 0; par ^= 1; }
      }
      wg_wait<0>();
      fence_regs(acc);
      if (tid == 0) PROF_MARK(17);
      __nv_bfloat16* op = prm.out + (size_t)(pt * 128 + row0) * DM + hp * 56 + 2 * lq;
#pragma unroll
      for (int j = 0; j < 7; j++) {
        *(uint32_t*)(op + 8 * j) = pack_bf16(acc[4 * j], acc[4 * j + 1]);
        *(uint32_t*)(op + 8 * DM + 8 * j) = pack_bf16(acc[4 * j + 2], acc[4 * j + 3]);
      }
      if (tid == 0) { PROF_MARK(18); PROF_CLK(31); }
    }
  }
}

typedef CUresult (*EncodeFn)(CUtensorMap*, CUtensorMapDataType, cuuint32_t, void*, const cuuint64_t*, const cuuint64_t*,
                             const cuuint32_t*, const cuuint32_t*, CUtensorMapInterleave, CUtensorMapSwizzle,
                             CUtensorMapL2promotion, CUtensorMapFloatOOBfill);

void make_map(EncodeFn enc, CUtensorMap* tm, const void* ptr, uint64_t cols, uint64_t rows, uint32_t box_cols, uint32_t box_rows) {
  cuuint64_t dims[2] = {cols, rows};
  cuuint64_t strides[1] = {cols * 2};
  cuuint32_t box[2] = {box_cols, box_rows};
  cuuint32_t es[2] = {1, 1};
  enc(tm, CU_TENSOR_MAP_DATA_TYPE_BFLOAT16, 2, const_cast<void*>(ptr), dims, strides, box, es, CU_TENSOR_MAP_INTERLEAVE_NONE,
      CU_TENSOR_MAP_SWIZZLE_128B, CU_TENSOR_MAP_L2_PROMOTION_L2_128B, CU_TENSOR_MAP_FLOAT_OOB_FILL_NONE);
}

}

extern "C" void kernel_launch(void* const* d_in, const int* in_sizes, int n_in, void* d_out, int out_size) {
  (void)in_sizes; (void)n_in; (void)out_size;
  static EncodeFn enc = nullptr;
  if (!enc) {
    void* fn = nullptr;
    cudaDriverEntryPointQueryResult qr;
    cudaGetDriverEntryPoint("cuTensorMapEncodeTiled", &fn, cudaEnableDefault, &qr);
    enc = (EncodeFn)fn;
    cudaFuncSetAttribute(fused_kernel, cudaFuncAttributeMaxDynamicSharedMemorySize, SMEM_BYTES);
  }
  CUtensorMap tm_x, tm_wqkv, tm_wq, tm_woa, tm_wob;
  make_map(enc, &tm_x, d_in[0], DM, S_LEN, 64, 128);
  make_map(enc, &tm_wqkv, d_in[1], 3 * DM, DM, 56, 64);
  make_map(enc, &tm_wq, d_in[5], DM, DM, 56, 64);
  make_map(enc, &tm_woa, d_in[3], DM, DM, 56, 64);
  make_map(enc, &tm_wob, d_in[8], DM, DM, 56, 64);
  Params prm;
  prm.w_phi = (const __nv_bfloat16*)d_in[2];
  prm.wk = (const __nv_bfloat16*)d_in[6];
  prm.wv = (const __nv_bfloat16*)d_in[7];
  prm.gate_w = (const __nv_bfloat16*)d_in[9];
  prm.out = (__nv_bfloat16*)d_out;
  fused_kernel<<<NCTA, NTHREADS, SMEM_BYTES>>>(tm_x, tm_wqkv, tm_wq, tm_woa, tm_wob, prm);
}
```

```cpp
#include <cuda_runtime.h>
#include <cuda_bf16.h>
#include <cuda.h>
#include <stdint.h>

namespace {

constexpr int S_LEN = 2048, DM = 448, DH = 28;
constexpr int NCTA = 128;
constexpr int NTHREADS = 640;
constexpr uint32_t POLY_PAT = 0x57;

#define QB_AT (4 + (wg >> 1))

constexpr int OFF_X = 0;
constexpr int OFF_PHIK = 0;
constexpr int OFF_VA = 32768;
constexpr int OFF_PHIQ = 57344;
constexpr int OFF_KVR = 90112;
constexpr int OFF_QP = 98304;
constexpr int OFF_RAW = 81920;
constexpr int OFF_WO = 0;
constexpr int OFF_RING = 114688;
constexpr int OFF_WBD = 212992;
constexpr int OFF_SLC = 221184;
constexpr int OFF_QSQ = 228352;
constexpr int OFF_OSTG = 212992;
constexpr int OFF_GATE = 229376;
constexpr int OFF_RED = 229888;
constexpr int OFF_BAR = 229952;
constexpr int SMEM_BYTES = 230400 + 1024;

constexpr int B_FULL = 0, B_EMPTY = 3, B_WO = 6  , B_KVR = 8, B_RAW = 9, B_X1FREE = 10, B_QSQ = 11, B_SLOW = 12,
              B_BUILD = 13, B_SIG = 14  , B_XL = 18  , B_N = 20;

constexpr int C_KV = 0, C_PART = 1, C_DONE = 3, C_OA = 4, C_OB = 20, C_N = 36;

__device__ __align__(1024) uint8_t g_kv_img[32 * 8192];
__device__ __align__(16) float g_ksq[512];
__device__ __align__(16) float g_vsq[512];
__device__ __align__(16) float g_gate[S_LEN];
__device__ __align__(1024) float g_kvacc[2][16 * 64 * 32];
__device__ unsigned g_epoch;
__device__ __align__(1024) uint8_t g_o_img[16 * 2 * 16 * 2 * 4096];
__device__ __align__(128) unsigned g_cnt[C_N * 32];

#define PROF4(i) do { } while (0)
#define PROF3(i) do { } while (0)
#define PROF2(i) do { } while (0)
#define PROF_CLK(i) do { } while (0)
#define PROF_MARK(i) do { } while (0)
__device__ __forceinline__ uint32_t smem_u32(const void* p) { return (uint32_t)__cvta_generic_to_shared(p); }
__device__ __forceinline__ void mbar_init(uint32_t a, int cnt) {
  asm volatile("mbarrier.init.shared::cta.b64 [%0], %1;" ::"r"(a), "r"(cnt) : "memory");
}
__device__ __forceinline__ void mbar_expect_tx(uint32_t a, uint32_t bytes) {
  asm volatile("mbarrier.arrive.expect_tx.shared::cta.b64 _, [%0], %1;" ::"r"(a), "r"(bytes) : "memory");
}
__device__ __forceinline__ void mbar_arrive(uint32_t a, uint32_t cnt) {
  asm volatile("mbarrier.arrive.shared::cta.b64 _, [%0], %1;" ::"r"(a), "r"(cnt) : "memory");
}
__device__ __forceinline__ void mbar_wait(uint32_t a, uint32_t parity) {
  asm volatile(
      "{\n.reg .pred p;\n.reg .u32 c;\nmov.u32 c, 0;\n"
      "W_%=:\nmbarrier.try_wait.parity.shared::cta.b64 p, [%0], %1;\n"
      "add.u32 c, c, 1;\nsetp.lt.and.u32 p, c, 0x40000, !p;\n@p bra W_%=;\n}"
      ::"r"(a), "r"(parity) : "memory");
}
__device__ __forceinline__ uint32_t mbar_test(uint32_t a, uint32_t parity) {
  uint32_t ok;
  asm volatile("{\n.reg .pred p;\nmbarrier.test_wait.parity.shared::cta.b64 p, [%1], %2;\nselp.u32 %0, 1, 0, p;\n}"
               : "=r"(ok) : "r"(a), "r"(parity) : "memory");
  return ok;
}
__device__ __forceinline__ bool elect_one() {
  uint32_t r;
  asm volatile("{\n.reg .pred p;\nelect.sync _|p, 0xffffffff;\nselp.u32 %0, 1, 0, p;\n}" : "=r"(r));
  return r != 0;
}
__device__ __forceinline__ void tma_2d(uint32_t dst, const CUtensorMap* tm, int c0, int c1, uint32_t bar) {
  asm volatile("cp.async.bulk.tensor.2d.shared::cluster.global.mbarrier::complete_tx::bytes [%0], [%1, {%3, %4}], [%2];"
               ::"r"(dst), "l"(tm), "r"(bar), "r"(c0), "r"(c1) : "memory");
}
__device__ __forceinline__ void bulk_g2s(uint32_t dst, const void* src, uint32_t bytes, uint32_t bar) {
  asm volatile("cp.async.bulk.shared::cluster.global.mbarrier::complete_tx::bytes [%0], [%1], %2, [%3];"
               ::"r"(dst), "l"(src), "r"(bytes), "r"(bar) : "memory");
}
__device__ __forceinline__ void fence_async_smem() { asm volatile("fence.proxy.async.shared::cta;" ::: "memory"); }
__device__ __forceinline__ void fence_async_all() { asm volatile("fence.proxy.async.global;" ::: "memory"); }

__device__ __forceinline__ void bar_sync(int id, int n) { asm volatile("bar.sync %0, %1;" ::"r"(id), "r"(n) : "memory"); }
__device__ __forceinline__ void cnt_wait(int idx, unsigned target) {
  unsigned v, n = 0;
#pragma unroll 1
  while (true) {
    asm volatile("ld.acquire.gpu.global.u32 %0, [%1];" : "=r"(v) : "l"(&g_cnt[idx * 32]) : "memory");
    if (v >= target || ++n >= (1u << 18)) break;
    __nanosleep(32);
  }
}
__device__ __forceinline__ void wg_fence() { asm volatile("wgmma.fence.sync.aligned;" ::: "memory"); }
__device__ __forceinline__ void wg_commit() { asm volatile("wgmma.commit_group.sync.aligned;" ::: "memory"); }
template <int N> __device__ __forceinline__ void wg_wait() { asm volatile("wgmma.wait_group.sync.aligned %0;" ::"n"(N) : "memory"); }
template <int N> __device__ __forceinline__ void fence_regs(float (&d)[N]) {
#pragma unroll
  for (int i = 0; i < N; i++) asm volatile("" : "+f"(d[i])::"memory");
}
__device__ __forceinline__ uint64_t make_desc(uint32_t saddr, uint32_t lbo, uint32_t sbo, uint32_t swz) {
  return (uint64_t)((saddr & 0x3FFFF) >> 4) | ((uint64_t)(lbo >> 4) << 16) | ((uint64_t)(sbo >> 4) << 32) | ((uint64_t)swz << 62);
}
__device__ __forceinline__ float ex2f(float x) { float y; asm("ex2.approx.ftz.f32 %0, %1;" : "=f"(y) : "f"(x)); return y; }
__device__ __forceinline__ float rcpf(float x) { float y; asm("rcp.approx.ftz.f32 %0, %1;" : "=f"(y) : "f"(x)); return y; }
__device__ __forceinline__ uint32_t pack_bf16(float lo, float hi) {
  uint32_t r; asm("cvt.rn.bf16x2.f32 %0, %1, %2;" : "=r"(r) : "f"(hi), "f"(lo)); return r;
}
__device__ __forceinline__ uint32_t lop_and_or(uint32_t a, uint32_t m, uint32_t c) {
  uint32_t r; asm("lop3.b32 %0, %1, %2, %3, 0xEA;" : "=r"(r) : "r"(a), "r"(m), "r"(c)); return r;
}
__device__ __forceinline__ void sts32(uint32_t a, uint32_t v) { asm volatile("st.shared.b32 [%0], %1;" ::"r"(a), "r"(v) : "memory"); }
__device__ __forceinline__ void st_shared_nv(uint32_t a, uint32_t v) { asm volatile("st.shared.b32 [%0], %1;" ::"r"(a), "r"(v)); }
__device__ __forceinline__ void sts64(uint32_t a, uint32_t v0, uint32_t v1) { asm volatile("st.shared.v2.b32 [%0], {%1, %2};" ::"r"(a), "r"(v0), "r"(v1) : "memory"); }
__device__ __forceinline__ void sts128(uint32_t a, uint4 v) {
  asm volatile("st.shared.v4.b32 [%0], {%1, %2, %3, %4};" ::"r"(a), "r"(v.x), "r"(v.y), "r"(v.z), "r"(v.w) : "memory");
}
__device__ __forceinline__ float4 ldcg_f4(const float* p) {
  float4 v; asm volatile("ld.global.cg.v4.f32 {%0, %1, %2, %3}, [%4];" : "=f"(v.x), "=f"(v.y), "=f"(v.z), "=f"(v.w) : "l"(p) : "memory"); return v;
}
__device__ __forceinline__ void ldsm4(uint32_t* r, uint32_t a) {
  asm volatile("ldmatrix.sync.aligned.m8n8.x4.shared.b16 {%0, %1, %2, %3}, [%4];"
               : "=r"(r[0]), "=r"(r[1]), "=r"(r[2]), "=r"(r[3]) : "r"(a) : "memory");
}
__device__ __forceinline__ float quad_sum(float v) { v += __shfl_xor_sync(~0u, v, 1); v += __shfl_xor_sync(~0u, v, 2); return v; }
__device__ __forceinline__ float quad_max(float v) { v = fmaxf(v, __shfl_xor_sync(~0u, v, 1)); v = fmaxf(v, __shfl_xor_sync(~0u, v, 2)); return v; }

template <int SD> __device__ __forceinline__ void wgmma_ss_n56_ta0_tb1(float (&d)[28], uint64_t da, uint64_t db) {
  if (SD) asm volatile("wgmma.mma_async.sync.aligned.m64n56k16.f32.bf16.bf16 {%0, %1, %2, %3, %4, %5, %6, %7, %8, %9, %10, %11, %12, %13, %14, %15, %16, %17, %18, %19, %20, %21, %22, %23, %24, %25, %26, %27}, %28, %29, 1, 1, 1, 0, 1;\n"
    : "+f"(d[0]), "+f"(d[1]), "+f"(d[2]), "+f"(d[3]), "+f"(d[4]), "+f"(d[5]), "+f"(d[6]), "+f"(d[7]), "+f"(d[8]), "+f"(d[9]), "+f"(d[10]), "+f"(d[11]), "+f"(d[12]), "+f"(d[13]), "+f"(d[14]), "+f"(d[15]), "+f"(d[16]), "+f"(d[17]), "+f"(d[18]), "+f"(d[19]), "+f"(d[20]), "+f"(d[21]), "+f"(d[22]), "+f"(d[23]), "+f"(d[24]), "+f"(d[25]), "+f"(d[26]), "+f"(d[27])
    : "l"(da), "l"(db));
  else asm volatile("wgmma.mma_async.sync.aligned.m64n56k16.f32.bf16.bf16 {%0, %1, %2, %3, %4, %5, %6, %7, %8, %9, %10, %11, %12, %13, %14, %15, %16, %17, %18, %19, %20, %21, %22, %23, %24, %25, %26, %27}, %28, %29, 0, 1, 1, 0, 1;\n"
    : "=f"(d[0]), "=f"(d[1]), "=f"(d[2]), "=f"(d[3]), "=f"(d[4]), "=f"(d[5]), "=f"(d[6]), "=f"(d[7]), "=f"(d[8]), "=f"(d[9]), "=f"(d[10]), "=f"(d[11]), "=f"(d[12]), "=f"(d[13]), "=f"(d[14]), "=f"(d[15]), "=f"(d[16]), "=f"(d[17]), "=f"(d[18]), "=f"(d[19]), "=f"(d[20]), "=f"(d[21]), "=f"(d[22]), "=f"(d[23]), "=f"(d[24]), "=f"(d[25]), "=f"(d[26]), "=f"(d[27])
    : "l"(da), "l"(db));
}
template <int SD> __device__ __forceinline__ void wgmma_ss_n8_ta0_tb1(float (&d)[4], uint64_t da, uint64_t db) {
  if (SD) asm volatile("wgmma.mma_async.sync.aligned.m64n8k16.f32.bf16.bf16 {%0, %1, %2, %3}, %4, %5, 1, 1, 1, 0, 1;\n"
    : "+f"(d[0]), "+f"(d[1]), "+f"(d[2]), "+f"(d[3])
    : "l"(da), "l"(db));
  else asm volatile("wgmma.mma_async.sync.aligned.m64n8k16.f32.bf16.bf16 {%0, %1, %2, %3}, %4, %5, 0, 1, 1, 0, 1;\n"
    : "=f"(d[0]), "=f"(d[1]), "=f"(d[2]), "=f"(d[3])
    : "l"(da), "l"(db));
}
template <int SD> __device__ __forceinline__ void wgmma_rs_n64_tb1(float (&d)[32], uint32_t a0, uint32_t a1, uint32_t a2, uint32_t a3, uint64_t db) {
  if (SD) asm volatile("wgmma.mma_async.sync.aligned.m64n64k16.f32.bf16.bf16 {%0, %1, %2, %3, %4, %5, %6, %7, %8, %9, %10, %11, %12, %13, %14, %15, %16, %17, %18, %19, %20, %21, %22, %23, %24, %25, %26, %27, %28, %29, %30, %31}, {%32, %33, %34, %35}, %36, 1, 1, 1, 1;\n"
    : "+f"(d[0]), "+f"(d[1]), "+f"(d[2]), "+f"(d[3]), "+f"(d[4]), "+f"(d[5]), "+f"(d[6]), "+f"(d[7]), "+f"(d[8]), "+f"(d[9]), "+f"(d[10]), "+f"(d[11]), "+f"(d[12]), "+f"(d[13]), "+f"(d[14]), "+f"(d[15]), "+f"(d[16]), "+f"(d[17]), "+f"(d[18]), "+f"(d[19]), "+f"(d[20]), "+f"(d[21]), "+f"(d[22]), "+f"(d[23]), "+f"(d[24]), "+f"(d[25]), "+f"(d[26]), "+f"(d[27]), "+f"(d[28]), "+f"(d[29]), "+f"(d[30]), "+f"(d[31])
    : "r"(a0), "r"(a1), "r"(a2), "r"(a3), "l"(db));
  else asm volatile("wgmma.mma_async.sync.aligned.m64n64k16.f32.bf16.bf16 {%0, %1, %2, %3, %4, %5, %6, %7, %8, %9, %10, %11, %12, %13, %14, %15, %16, %17, %18, %19, %20, %21, %22, %23, %24, %25, %26, %27, %28, %29, %30, %31}, {%32, %33, %34, %35}, %36, 0, 1, 1, 1;\n"
    : "=f"(d[0]), "=f"(d[1]), "=f"(d[2]), "=f"(d[3]), "=f"(d[4]), "=f"(d[5]), "=f"(d[6]), "=f"(d[7]), "=f"(d[8]), "=f"(d[9]), "=f"(d[10]), "=f"(d[11]), "=f"(d[12]), "=f"(d[13]), "=f"(d[14]), "=f"(d[15]), "=f"(d[16]), "=f"(d[17]), "=f"(d[18]), "=f"(d[19]), "=f"(d[20]), "=f"(d[21]), "=f"(d[22]), "=f"(d[23]), "=f"(d[24]), "=f"(d[25]), "=f"(d[26]), "=f"(d[27]), "=f"(d[28]), "=f"(d[29]), "=f"(d[30]), "=f"(d[31])
    : "r"(a0), "r"(a1), "r"(a2), "r"(a3), "l"(db));
}
template <int SD> __device__ __forceinline__ void wgmma_ss_n32_ta1_tb1(float (&d)[16], uint64_t da, uint64_t db) {
  if (SD) asm volatile("wgmma.mma_async.sync.aligned.m64n32k16.f32.bf16.bf16 {%0, %1, %2, %3, %4, %5, %6, %7, %8, %9, %10, %11, %12, %13, %14, %15}, %16, %17, 1, 1, 1, 1, 1;\n"
    : "+f"(d[0]), "+f"(d[1]), "+f"(d[2]), "+f"(d[3]), "+f"(d[4]), "+f"(d[5]), "+f"(d[6]), "+f"(d[7]), "+f"(d[8]), "+f"(d[9]), "+f"(d[10]), "+f"(d[11]), "+f"(d[12]), "+f"(d[13]), "+f"(d[14]), "+f"(d[15])
    : "l"(da), "l"(db));
  else asm volatile("wgmma.mma_async.sync.aligned.m64n32k16.f32.bf16.bf16 {%0, %1, %2, %3, %4, %5, %6, %7, %8, %9, %10, %11, %12, %13, %14, %15}, %16, %17, 0, 1, 1, 1, 1;\n"
    : "=f"(d[0]), "=f"(d[1]), "=f"(d[2]), "=f"(d[3]), "=f"(d[4]), "=f"(d[5]), "=f"(d[6]), "=f"(d[7]), "=f"(d[8]), "=f"(d[9]), "=f"(d[10]), "=f"(d[11]), "=f"(d[12]), "=f"(d[13]), "=f"(d[14]), "=f"(d[15])
    : "l"(da), "l"(db));
}
template <int SD> __device__ __forceinline__ void wgmma_ss_n32_ta0_tb1(float (&d)[16], uint64_t da, uint64_t db) {
  if (SD) asm volatile("wgmma.mma_async.sync.aligned.m64n32k16.f32.bf16.bf16 {%0, %1, %2, %3, %4, %5, %6, %7, %8, %9, %10, %11, %12, %13, %14, %15}, %16, %17, 1, 1, 1, 0, 1;\n"
    : "+f"(d[0]), "+f"(d[1]), "+f"(d[2]), "+f"(d[3]), "+f"(d[4]), "+f"(d[5]), "+f"(d[6]), "+f"(d[7]), "+f"(d[8]), "+f"(d[9]), "+f"(d[10]), "+f"(d[11]), "+f"(d[12]), "+f"(d[13]), "+f"(d[14]), "+f"(d[15])
    : "l"(da), "l"(db));
  else asm volatile("wgmma.mma_async.sync.aligned.m64n32k16.f32.bf16.bf16 {%0, %1, %2, %3, %4, %5, %6, %7, %8, %9, %10, %11, %12, %13, %14, %15}, %16, %17, 0, 1, 1, 0, 1;\n"
    : "=f"(d[0]), "=f"(d[1]), "=f"(d[2]), "=f"(d[3]), "=f"(d[4]), "=f"(d[5]), "=f"(d[6]), "=f"(d[7]), "=f"(d[8]), "=f"(d[9]), "=f"(d[10]), "=f"(d[11]), "=f"(d[12]), "=f"(d[13]), "=f"(d[14]), "=f"(d[15])
    : "l"(da), "l"(db));
}
template <int SD> __device__ __forceinline__ void wgmma_rs_n64_tb0(float (&d)[32], uint32_t a0, uint32_t a1, uint32_t a2, uint32_t a3, uint64_t db) {
  if (SD) asm volatile("wgmma.mma_async.sync.aligned.m64n64k16.f32.bf16.bf16 {%0, %1, %2, %3, %4, %5, %6, %7, %8, %9, %10, %11, %12, %13, %14, %15, %16, %17, %18, %19, %20, %21, %22, %23, %24, %25, %26, %27, %28, %29, %30, %31}, {%32, %33, %34, %35}, %36, 1, 1, 1, 0;\n"
    : "+f"(d[0]), "+f"(d[1]), "+f"(d[2]), "+f"(d[3]), "+f"(d[4]), "+f"(d[5]), "+f"(d[6]), "+f"(d[7]), "+f"(d[8]), "+f"(d[9]), "+f"(d[10]), "+f"(d[11]), "+f"(d[12]), "+f"(d[13]), "+f"(d[14]), "+f"(d[15]), "+f"(d[16]), "+f"(d[17]), "+f"(d[18]), "+f"(d[19]), "+f"(d[20]), "+f"(d[21]), "+f"(d[22]), "+f"(d[23]), "+f"(d[24]), "+f"(d[25]), "+f"(d[26]), "+f"(d[27]), "+f"(d[28]), "+f"(d[29]), "+f"(d[30]), "+f"(d[31])
    : "r"(a0), "r"(a1), "r"(a2), "r"(a3), "l"(db));
  else asm volatile("wgmma.mma_async.sync.aligned.m64n64k16.f32.bf16.bf16 {%0, %1, %2, %3, %4, %5, %6, %7, %8, %9, %10, %11, %12, %13, %14, %15, %16, %17, %18, %19, %20, %21, %22, %23, %24, %25, %26, %27, %28, %29, %30, %31}, {%32, %33, %34, %35}, %36, 0, 1, 1, 0;\n"
    : "=f"(d[0]), "=f"(d[1]), "=f"(d[2]), "=f"(d[3]), "=f"(d[4]), "=f"(d[5]), "=f"(d[6]), "=f"(d[7]), "=f"(d[8]), "=f"(d[9]), "=f"(d[10]), "=f"(d[11]), "=f"(d[12]), "=f"(d[13]), "=f"(d[14]), "=f"(d[15]), "=f"(d[16]), "=f"(d[17]), "=f"(d[18]), "=f"(d[19]), "=f"(d[20]), "=f"(d[21]), "=f"(d[22]), "=f"(d[23]), "=f"(d[24]), "=f"(d[25]), "=f"(d[26]), "=f"(d[27]), "=f"(d[28]), "=f"(d[29]), "=f"(d[30]), "=f"(d[31])
    : "r"(a0), "r"(a1), "r"(a2), "r"(a3), "l"(db));
}
template <int SD> __device__ __forceinline__ void wgmma_rs_n32_tb1(float (&d)[16], uint32_t a0, uint32_t a1, uint32_t a2, uint32_t a3, uint64_t db) {
  if (SD) asm volatile("wgmma.mma_async.sync.aligned.m64n32k16.f32.bf16.bf16 {%0, %1, %2, %3, %4, %5, %6, %7, %8, %9, %10, %11, %12, %13, %14, %15}, {%16, %17, %18, %19}, %20, 1, 1, 1, 1;\n"
    : "+f"(d[0]), "+f"(d[1]), "+f"(d[2]), "+f"(d[3]), "+f"(d[4]), "+f"(d[5]), "+f"(d[6]), "+f"(d[7]), "+f"(d[8]), "+f"(d[9]), "+f"(d[10]), "+f"(d[11]), "+f"(d[12]), "+f"(d[13]), "+f"(d[14]), "+f"(d[15])
    : "r"(a0), "r"(a1), "r"(a2), "r"(a3), "l"(db));
  else asm volatile("wgmma.mma_async.sync.aligned.m64n32k16.f32.bf16.bf16 {%0, %1, %2, %3, %4, %5, %6, %7, %8, %9, %10, %11, %12, %13, %14, %15}, {%16, %17, %18, %19}, %20, 0, 1, 1, 1;\n"
    : "=f"(d[0]), "=f"(d[1]), "=f"(d[2]), "=f"(d[3]), "=f"(d[4]), "=f"(d[5]), "=f"(d[6]), "=f"(d[7]), "=f"(d[8]), "=f"(d[9]), "=f"(d[10]), "=f"(d[11]), "=f"(d[12]), "=f"(d[13]), "=f"(d[14]), "=f"(d[15])
    : "r"(a0), "r"(a1), "r"(a2), "r"(a3), "l"(db));
}

__device__ __forceinline__ uint32_t sw64_off(int row, int d) { return row * 64 + ((((d >> 3) ^ (row >> 1)) & 3) << 4) + (d & 7) * 2; }

__device__ __forceinline__ uint32_t exp2_pair_fma(float t0, float t1, uint32_t c_half, uint32_t c_3) {
  uint32_t y0, y;
  asm("prmt.b32 %0, %1, %2, 0x6521;" : "=r"(y0) : "r"(__float_as_uint(t0)), "r"(__float_as_uint(t1)));
  uint32_t h = lop_and_or(y0, 0x007F007Fu, c_half);
  uint32_t e = lop_and_or(y0, 0xFF80FF80u, c_3);
  asm("fma.rn.bf16x2 %0, %1, %2, %3;" : "=r"(y) : "r"(y0), "r"(h), "r"(e));
  return y;
}

__device__ __forceinline__ void feature_map(float (&p)[32], uint32_t rb, int lq) {
  const float L2E = 1.4426950408889634f;
  const bool tail_ok = lq < 2;
  float mx[4], mn[4], b[32], sa[4], sn[4];
#pragma unroll
  for (int g = 0; g < 4; g++) {
    const int o = 16 * (g >> 1) + 2 * (g & 1);
    if (!tail_ok) { p[o + 12] = p[o]; p[o + 13] = p[o]; }
    mx[g] = fmaxf(fmaxf(fmaxf(p[o], p[o + 1]), fmaxf(p[o + 4], p[o + 5])), fmaxf(fmaxf(p[o + 8], p[o + 9]), fmaxf(p[o + 12], p[o + 13])));
    mn[g] = fminf(fminf(fminf(p[o], p[o + 1]), fminf(p[o + 4], p[o + 5])), fminf(fminf(p[o + 8], p[o + 9]), fminf(p[o + 12], p[o + 13])));
  }
#pragma unroll
  for (int o = 1; o <= 2; o <<= 1)
#pragma unroll
    for (int g = 0; g < 4; g++) { mx[g] = fmaxf(mx[g], __shfl_xor_sync(~0u, mx[g], o)); mn[g] = fminf(mn[g], __shfl_xor_sync(~0u, mn[g], o)); }
#pragma unroll
  for (int g = 0; g < 4; g++) {
    const int o = 16 * (g >> 1) + 2 * (g & 1);
    const float cx = -mx[g] * L2E, cn = mn[g] * L2E;
#pragma unroll
    for (int i = 0; i < 8; i++) {
      const int k = o + 4 * (i >> 1) + (i & 1);
      b[k] = ex2f(fmaf(p[k], -L2E, cn));
      p[k] = ex2f(fmaf(p[k], L2E, cx));
    }
    if (!tail_ok) { p[o + 12] = p[o + 13] = b[o + 12] = b[o + 13] = 0.f; }
    sa[g] = ((p[o] + p[o + 1]) + (p[o + 4] + p[o + 5])) + ((p[o + 8] + p[o + 9]) + (p[o + 12] + p[o + 13]));
    sn[g] = ((b[o] + b[o + 1]) + (b[o + 4] + b[o + 5])) + ((b[o + 8] + b[o + 9]) + (b[o + 12] + b[o + 13]));
    sa[g] += __shfl_xor_sync(~0u, sa[g], 1); sn[g] += __shfl_xor_sync(~0u, sn[g], 1);
    sa[g] += __shfl_xor_sync(~0u, sa[g], 2); sn[g] += __shfl_xor_sync(~0u, sn[g], 2);
  }
#pragma unroll
  for (int g = 0; g < 4; g++) {
    const int o = 16 * (g >> 1) + 2 * (g & 1);
    const float ra = rcpf(sa[g]), rn = rcpf(sn[g]);
    const uint32_t off = (g >> 1) * 16384 + (g & 1) * 1024;
#pragma unroll
    for (int jj = 0; jj < 4; jj++) {
      st_shared_nv((rb ^ (jj << 4)) + off, pack_bf16(p[o + 4 * jj] * ra, p[o + 4 * jj + 1] * ra));
      st_shared_nv((rb ^ ((4 + jj) << 4)) + off, pack_bf16(b[o + 4 * jj] * rn, b[o + 4 * jj + 1] * rn));
    }
  }
}

__device__ __forceinline__ void store_heads(uint32_t base, const uint32_t (&a)[14], uint32_t pad0, uint32_t pad1, int row0, int lq) {
  const uint32_t rb = base + row0 * 64 + (((row0 >> 1) & 3) << 4);
  const uint32_t b0 = rb + lq * 4;
  const uint32_t b1 = (rb + 8192 + ((lq * 4 + 8) & 15)) ^ ((lq >> 1) << 4);
#pragma unroll
  for (int j = 0; j < 7; j++) {
    uint32_t ad;
    if (j < 3) ad = b0 ^ (j << 4);
    else if (j == 3) ad = (lq < 2) ? (b0 ^ 48u) : (b1 ^ 16u);
    else ad = (lq < 2) ? (b1 ^ ((j - 4) << 4)) : ((b1 ^ 16u) ^ ((j - 3) << 4));
    sts32(ad, a[2 * j]);
    sts32(ad + 512, a[2 * j + 1]);
  }
  sts64((rb ^ 48u) + 8 + (lq & 1) * 8192 + (lq >> 1) * 512, pad0, pad1);
}

struct Params {
  const __nv_bfloat16* w_phi;
  const __nv_bfloat16* wk;
  const __nv_bfloat16* wv;
  const __nv_bfloat16* gate_w;
  __nv_bfloat16* out;
};

__global__ void __launch_bounds__(NTHREADS, 1)
fused_kernel(const __grid_constant__ CUtensorMap tm_x, const __grid_constant__ CUtensorMap tm_wqkv,
             const __grid_constant__ CUtensorMap tm_wq, const __grid_constant__ CUtensorMap tm_woa,
             const __grid_constant__ CUtensorMap tm_wob, const Params prm) {
  extern __shared__ uint8_t smem_raw[];
  uint32_t sb = (smem_u32(smem_raw) + 1023u) & ~1023u;
  uint8_t* sgen = smem_raw + (sb - smem_u32(smem_raw));
  asm volatile("mov.u32 %0, %0;" : "+r"(sb));
  const int tid = threadIdx.x, lane = tid & 31;
  const int warp = __shfl_sync(~0u, tid >> 5, 0), wg = warp >> 2;
  const int pt = blockIdx.x >> 3, hp = blockIdx.x & 7;
  const uint32_t bars = sb + OFF_BAR;
  auto BAR = [&](int i) { return bars + 8u * i; };
  const unsigned epoch = g_epoch & 1;

  if (tid == 0) { PROF_MARK(0); PROF_CLK(30); PROF2(15); }
  auto load_proj = [&](int c, int g) {
    mbar_expect_tx(BAR(B_FULL + g), (c < 3 ? 16384 : 0) + 4 * 7168);
    if (c < 3) tma_2d(sb + OFF_X + c * 16384, &tm_x, c * 64, pt * 128, BAR(B_FULL + g));
    tma_2d(sb + OFF_RING + g * 32768, &tm_wq, hp * 56, c * 64, BAR(B_FULL + g));
#pragma unroll 1
    for (int j = 0; j < 3; j++) tma_2d(sb + OFF_RING + g * 32768 + 8192 + j * 8192, &tm_wqkv, j * DM + hp * 56, c * 64, BAR(B_FULL + g));
  };
  if (warp == 16) {
    if (elect_one()) {
      mbar_init(BAR(B_FULL), 1);
      fence_async_smem();
      load_proj(0, 0);
      mbar_init(BAR(B_RAW), 1); mbar_init(BAR(B_FULL + 1), 1); mbar_init(BAR(B_FULL + 2), 1);
      fence_async_smem();
    }
    __syncwarp();
    asm volatile("bar.arrive 0, %0;" ::"n"(NTHREADS) : "memory");
  } else {
    if (elect_one()) {
      const int i = warp + 3 - (warp > 16);
      if (i < B_N && i != B_RAW) {
        int cnt = i < B_WO || (i > B_SIG && i < B_XL) || i == B_X1FREE ? 16 : 1;
        if (i == B_BUILD) cnt = 16;
        if (i == B_SIG || i == B_SIG + 1 || i == B_QSQ) cnt = 8;
        if (i == B_KVR) cnt = 2;
        mbar_init(BAR(i), cnt);
        fence_async_smem();
      }
    }
    bar_sync(0, NTHREADS);
  }
  if (tid == 0) PROF2(14);

  if (wg == 4) {
    asm volatile("setmaxnreg.dec.sync.aligned.u32 32;");
    if (warp == 16) {
      if (elect_one()) {
        mbar_expect_tx(BAR(B_RAW), 25088 + 3136 + 896);
        bulk_g2s(sb + OFF_RAW, hp < 4 ? prm.wk : prm.wv, 25088, BAR(B_RAW));
        bulk_g2s(sb + OFF_RAW + 25088, prm.w_phi + 2 * hp * DH * DH, 3136, BAR(B_RAW));
        bulk_g2s(sb + OFF_RAW + 28224, prm.gate_w, 896, BAR(B_RAW));
        load_proj(1, 1);
        load_proj(2, 2);
      }
      __syncwarp();
      bar_sync(3, 64);
      if (elect_one()) {
        int g = 0, nkv = 8;
        uint32_t par = 0;
#pragma unroll 1
        for (int c = 3; c < 7; c++) {
          if (c == 5) mbar_wait(BAR(B_BUILD), 0);
          if (c & 1) mbar_expect_tx(BAR(B_XL + (c > 4)), 32768);
          tma_2d(sb + OFF_X + c * 16384, &tm_x, c * 64, pt * 128, BAR(B_XL + (c > 4)));
        }
        uint32_t todo = 15, rdy = 0;
#pragma unroll 1
        for (int n = 3; n < 15 + nkv; n++) {
          if (n == 7) { PROF_MARK(20); cnt_wait(C_KV, NCTA); PROF_MARK(21); fence_async_all(); }
          if (n == 15) {
            mbar_wait(BAR(B_SLOW), 0);
            if (*(volatile int*)(sgen + OFF_RED)) nkv = 26;
          }
          int j = n - 7 - nkv;
          if (j == 0) { PROF3(8); cnt_wait(C_OA + pt, 8); PROF3(9); fence_async_all(); }
          const bool last = j == 7;
          if (!last) mbar_wait(BAR(B_EMPTY + g), par);
          if (j >= 4) {
            uint32_t spin = 0;
            if (j == 4) PROF3(11);
#pragma unroll 1
            while (!rdy) {
              uint4 v;
              asm volatile("ld.acquire.gpu.global.v4.u32 {%0, %1, %2, %3}, [%4];"
                           : "=r"(v.x), "=r"(v.y), "=r"(v.z), "=r"(v.w) : "l"(&g_cnt[(C_OB + pt) * 32]) : "memory");
              rdy = ((v.x >= 2) | (v.y >= 2) << 1 | (v.z >= 2) << 2 | (v.w >= 2) << 3) & todo;
              if (++spin >= (1u << 18)) rdy = todo;
            }
            const int pick = __ffs(rdy) - 1;
            todo &= ~(1u << pick);
            rdy &= todo;
            ((volatile int*)(sgen + OFF_RED + 16))[j - 4] = pick;
            j = 4 + pick;
            PROF3(12);
            PROF_MARK(26);
            fence_async_all();
          }
          if (n < 7) { PROF2(20 + n); load_proj(n, g); }
          else {
            const uint32_t fb = BAR(last ? B_RAW : B_FULL + g);
            mbar_expect_tx(fb, 32768);
            bulk_g2s(last ? sb + OFF_WO : sb + OFF_RING + g * 32768,
                     j < 0 ? g_kv_img + ((n - 7) & 7) * 32768 : g_o_img + (size_t)(pt * 8 + j) * 32768, 32768, fb);
          }
          if (++g == 3) { g = 0; par ^= 1; }
        }
        if (atomicAdd(&g_cnt[C_DONE * 32], 1u) == NCTA - 1) {
#pragma unroll 1
          for (int i = 0; i < C_N; i++) *(uint4*)&g_cnt[i * 32] = make_uint4(0u, 0u, 0u, 0u);
          g_epoch = epoch ^ 1;
        }
      }
    } else {
      if (warp == 18) {
        if (elect_one()) {
#pragma unroll 1
          for (int i = 0; i < 4; i++) {
            mbar_wait(BAR(B_SIG + i), 0);
            PROF3(2 * i);
            if (i == 1) {
#pragma unroll 1
              for (int j = 0; j < 4; j++)
                asm volatile("cp.reduce.async.bulk.global.shared::cta.bulk_group.add.f32 [%0], [%1], 8192;"
                             ::"l"(g_kvacc[epoch] + hp * 4096 + (j >> 1) * 2048), "r"(sb + OFF_PHIK + j * 8192) : "memory");
            }
            if (i >= 2)
              asm volatile("cp.async.bulk.global.shared::cta.bulk_group [%0], [%1], 16384;"
                           ::"l"(g_o_img + (size_t)(pt * 2 + i - 2) * 131072 + hp * 16384), "r"(sb + OFF_OSTG) : "memory");
            if (i >= 1) asm volatile("cp.async.bulk.commit_group;\ncp.async.bulk.wait_group 0;" ::: "memory");
            asm volatile("red.release.gpu.global.add.u32 [%0], 1;"
                         ::"l"(&g_cnt[(i == 0 ? C_KV : i == 1 ? C_PART : (i == 2 ? C_OA : C_OB) + pt) * 32 + (i == 3 ? hp >> 1 : 0)]) : "memory");
            PROF3(2 * i + 1);
            if (i == 1 || i == 2) {
              if (i == 2) mbar_wait(BAR(B_X1FREE), 0);
              mbar_expect_tx(BAR(B_WO + i - 1), 7 * 7168);
#pragma unroll 1
              for (int c = 0; c < 7; c++)
                tma_2d(sb + OFF_WO + (i - 1) * 57344 + c * 8192, i == 1 ? &tm_woa : &tm_wob, hp * 56, c * 64, BAR(B_WO + i - 1));
            }
          }
        }
      } else if (warp == 19) {
        if (lane == 0) {
          mbar_wait(BAR(B_SIG + 0), 0);
          cnt_wait(C_KV, NCTA);
        }
        __syncwarp();
        float ksq = 0.f, vsq = 0.f;
#pragma unroll
        for (int sl = 0; sl < 4; sl++) {
          float4 a = ldcg_f4(g_ksq + sl * 128 + lane * 4), b = ldcg_f4(g_vsq + sl * 128 + lane * 4);
          float m = fmaxf(fmaxf(a.x, a.y), fmaxf(a.z, a.w));
          m = __uint_as_float(__reduce_max_sync(~0u, __float_as_uint(m)));
          ksq += m;
          vsq = fmaxf(vsq, fmaxf(fmaxf(b.x, b.y), fmaxf(b.z, b.w)));
        }
        mbar_wait(BAR(B_QSQ), 0);
        const float4 qa4 = ((const float4*)(sgen + OFF_QSQ))[lane], qb4 = ((const float4*)(sgen + OFF_QSQ))[32 + lane];
        const float qmax = fmaxf(fmaxf(fmaxf(qa4.x, qa4.y), fmaxf(qa4.z, qa4.w)), fmaxf(fmaxf(qb4.x, qb4.y), fmaxf(qb4.z, qb4.w)));
        const bool slow = __any_sync(~0u, !(qmax * ksq <= 98.f * 98.f) || !(vsq <= 2.0e8f));
        if (lane == 0) {
          *(volatile int*)(sgen + OFF_RED) = slow;
          mbar_arrive(BAR(B_SLOW), 1);
        }
      } else {
        float4* z = (float4*)(g_kvacc[epoch ^ 1] + blockIdx.x * 256) + lane;
        z[0] = make_float4(0.f, 0.f, 0.f, 0.f);
        z[32] = make_float4(0.f, 0.f, 0.f, 0.f);
        bar_sync(3, 64);
        if (lane == 0) {
          mbar_wait(BAR(B_SIG + 0), 0);
          cnt_wait(C_KV, NCTA);
        }
        __syncwarp();
        ((float4*)(sgen + OFF_GATE))[lane] = ldcg_f4(g_gate + pt * 128 + lane * 4);
      }
      if (warp != 18) {
        if (lane == 0) {
          mbar_wait(BAR(B_SIG + 1), 0);
          cnt_wait(C_PART, NCTA);
          PROF_MARK(23);
        }
        __syncwarp();
        const int e = warp == 19;
        const float* src = g_kvacc[epoch] + hp * 4096 + e * 2048 + (lane ^ ((lane >> 2) & 3)) * 8;
#pragma unroll 1
        for (int i = 0; i < 8; i += 2) {
          const float4 a = ldcg_f4(src + i * 256), b = ldcg_f4(src + i * 256 + 4), c = ldcg_f4(src + i * 256 + 256), d = ldcg_f4(src + i * 256 + 260);
          const uint32_t ad = sb + OFF_KVR + e * 4096 + sw64_off(i * 8 + (lane >> 2), (lane & 3) * 8);
          sts128(ad, make_uint4(pack_bf16(a.x, a.y), pack_bf16(a.z, a.w), pack_bf16(b.x, b.y), pack_bf16(b.z, b.w)));
          sts128(ad + 512, make_uint4(pack_bf16(c.x, c.y), pack_bf16(c.z, c.w), pack_bf16(d.x, d.y), pack_bf16(d.z, d.w)));
        }
        fence_async_smem();
        __syncwarp();
        if (lane == 0) mbar_arrive(BAR(B_KVR), 1);
        PROF_MARK(24);
      }
    }
  } else {
    asm volatile("setmaxnreg.inc.sync.aligned.u32 112;");
    const int mh = wg & 1, nh = wg >> 1, wq = warp & 3;
    const int lq = lane & 3;
    const int rowl = wq * 16 + (lane >> 2);
    const int row0 = mh * 64 + rowl;
    int slot = 0;
    uint32_t par = 0;
    {
      float acc0[28], acc1[28], accs[4];
      const uint64_t dR = make_desc(sb + OFF_RING + nh * 16384, 1024, 1024, 1);
      const uint64_t dX = make_desc(sb + OFF_X + mh * 8192, 1024, 1024, 1);
#pragma unroll
      for (int i = 0; i < 28; i++) acc0[i] = acc1[i] = 0.f;
#pragma unroll
      for (int i = 0; i < 4; i++) accs[i] = 0.f;
      const uint64_t dSlc = make_desc(sb + OFF_SLC, 128, 128, 0);
#pragma unroll 1
      for (int c = 0; c < 7; c++) {
        if (c == 3 || c == 5) mbar_wait(BAR(B_XL + (c > 4)), 0);
        mbar_wait(BAR(B_FULL + slot), par);
        if (c == 0 && tid == 0) PROF2(17);
        const uint64_t dA = dX + c * 1024, dB = dR + slot * 2048;
        wg_fence();
#pragma unroll
        for (int ks = 0; ks < 4; ks++) {
          wgmma_ss_n56_ta0_tb1<1>(acc0, dA + ks * 2, dB + ks * 128);
          wgmma_ss_n56_ta0_tb1<1>(acc1, dA + ks * 2, dB + 512 + ks * 128);
        }
        if (nh == 1 && c > 0) {
#pragma unroll
          for (int ks = 0; ks < 4; ks++) wgmma_ss_n8_ta0_tb1<1>(accs, dA - 1024 + ks * 2, dSlc + (c - 1) * 64 + ks * 16);
        }
        wg_commit();
        if (c == 0) {
          mbar_wait(BAR(B_RAW), 0);
          const int k = tid >> 3, cn = tid & 7;
          const bool data = k < 56 && (cn >> 2) == (k >= DH);
          const uint2* wsrc = (const uint2*)(sgen + OFF_RAW + 25088 + k * 56 + (cn & 3) * 16);
          uint2 w0 = make_uint2(0u, 0u), w1 = w0;
          if (data) w0 = wsrc[0];
          if (data && (cn & 3) != 3) w1 = wsrc[1];
          sts128(sb + OFF_WBD + k * 128 + ((cn ^ (k & 7)) << 4), make_uint4(w0.x, w0.y, w1.x, w1.y));
          if (tid < DM) {
            const uint2* src = (const uint2*)(sgen + OFF_RAW + tid * 56 + (hp & 3) * 16);
            w0 = src[0];
            w1 = make_uint2(hp == 3 ? (uint32_t)((const unsigned short*)(sgen + OFF_RAW + 28224))[tid] : 0u, 0u);
            if ((hp & 3) != 3) w1 = src[1];
            sts128(sb + OFF_SLC + tid * 16, make_uint4(w0.x, w0.y, w1.x, w1.y));
          }
          fence_async_smem();
          __syncwarp();
          if (lane == 0) mbar_arrive(BAR(B_BUILD), 1);
          mbar_wait(BAR(B_BUILD), 0);
        }
        wg_wait<0>();
        if (lane == 0) mbar_arrive(BAR(B_EMPTY + slot), 1);
        if (++slot == 3) { slot = 0; par ^= 1; }
      }
      if (nh == 1) {
        wg_fence();
#pragma unroll
        for (int ks = 0; ks < 4; ks++) wgmma_ss_n8_ta0_tb1<1>(accs, dX + 6 * 1024 + ks * 2, dSlc + 6 * 64 + ks * 16);
        wg_commit();
      }
      wg_wait<0>();
      fence_regs(acc0); fence_regs(acc1); fence_regs(accs);
      if (tid == 0) PROF_MARK(2);
      if (tid == 256) PROF_MARK(3);
      if (nh == 0) {
        float sq[4] = {0.f, 0.f, 0.f, 0.f};
#pragma unroll
        for (int i = 0; i < 28; i++) acc0[i] *= 0.18898223650461362f * 1.4426950408889634f;
#pragma unroll
        for (int j = 0; j < 7; j++) {
#pragma unroll
          for (int rr = 0; rr < 2; rr++) {
            const float s2 = acc0[4 * j + 2 * rr] * acc0[4 * j + 2 * rr] + acc0[4 * j + 2 * rr + 1] * acc0[4 * j + 2 * rr + 1];
            if (j < 3) sq[rr] += s2;
            else if (j > 3) sq[2 + rr] += s2;
            else { sq[rr] += (lq < 2) ? s2 : 0.f; sq[2 + rr] += (lq < 2) ? 0.f : s2; }
          }
        }
#pragma unroll
        for (int i = 0; i < 4; i++) sq[i] = quad_sum(sq[i]);
        const float mine = lq == 0 ? sq[0] : lq == 1 ? sq[1] : lq == 2 ? sq[2] : sq[3];
        ((float*)(sgen + OFF_QSQ))[(mh + (lq & 2)) * 64 + rowl + 8 * (lq & 1)] = mine <= 3.0e38f ? mine : __int_as_float(0x7f800000);
        __syncwarp();
        if (lane == 0) mbar_arrive(BAR(B_QSQ), 1);
      } else {
        const int sl = hp & 3;
        const bool isk = hp < 4, real = (sl < 3) || (lq < 2);
        const int pos = pt * 128 + row0, kr = pos & 63;
        uint8_t* dst = g_kv_img + (pos >> 6) * 8192 + (isk ? 0 : 4096) + sw64_off(kr, sl * 8 + 2 * lq);
        const uint32_t pat = isk ? POLY_PAT >> (kr >> 3) : 0u;
        float mxv = 0.f;
#pragma unroll
        for (int rr = 0; rr < 2; rr++) {
          const float v0 = accs[2 * rr], v1 = accs[2 * rr + 1];
          const bool poly = (pat >> rr) & 1;
          const float sc = poly ? 2.f : 1.f;
          const float s2 = quad_sum(real ? v0 * v0 + v1 * v1 : 0.f);
          mxv = fmaxf(mxv, s2 <= 3.0e38f ? s2 : __int_as_float(0x7f800000));
          const uint32_t padv = lq == 2 ? (poly ? 0x443F4000u : 0x00003F80u) : (poly ? 0x3AB03F4Du : 0u);
          *(uint32_t*)(dst + rr * 512) = real ? pack_bf16(sc * v0, sc * v1) : padv;
          if (hp == 3 && lq == 2) g_gate[pos + 8 * rr] = rcpf(1.f + ex2f(-1.4426950408889634f * v0));
        }
        mxv = __uint_as_float(__reduce_max_sync(~0u, __float_as_uint(mxv)));
        if (lane == 0) (isk ? g_ksq : g_vsq)[sl * 128 + pt * 8 + mh * 4 + wq] = mxv;
        __syncwarp();
        if (lane == 0) mbar_arrive(BAR(B_SIG + 0), 1);
      }
      if (tid == 0) PROF_MARK(4);
      if (tid == 256) PROF_MARK(5);
      uint32_t h[14];
      float pp[32];
      {
        uint32_t a[16];
#pragma unroll
        for (int i = 0; i < 14; i++) {
          const uint32_t u0 = pack_bf16(acc0[2 * i], acc0[2 * i + 1]), u1 = pack_bf16(acc1[2 * i], acc1[2 * i + 1]);
          h[i] = nh ? u1 : u0;
          a[i] = nh ? u0 : u1;
        }
        a[14] = a[0] ^ 0x80008000u;
        a[15] = a[1] ^ 0x80008000u;
        const uint64_t dW = make_desc(sb + OFF_WBD, 1024, 1024, 1);
        wg_fence();
        wgmma_rs_n64_tb1<0>(pp, a[0], a[1], a[2], a[3], dW);
#pragma unroll
        for (int ks = 1; ks < 4; ks++) wgmma_rs_n64_tb1<1>(pp, a[4 * ks], a[4 * ks + 1], a[4 * ks + 2], a[4 * ks + 3], dW + ks * 128);
        wg_commit();
        bar_sync(1, 512);
        if (tid == 0) PROF_MARK(6);
        store_heads(sb + (nh ? OFF_VA : OFF_QP), h, nh ? 0x00003F80u : 0x3F800000u, nh ? 0u : 0x3F803F80u, row0, lq);
        wg_wait<0>();
        fence_regs(pp);
      }
      feature_map(pp, sb + (nh ? OFF_PHIK : OFF_PHIQ) + row0 * 128 + lq * 4 + ((rowl & 7) << 4), lq);
      fence_async_smem();
      bar_sync(1, 512);
      if (tid == 0) PROF_MARK(7);
      if (nh == 1) {
        float kv0[16], kv1[16];
        const uint64_t dP = make_desc(sb + OFF_PHIK + mh * 8192, 1024, 1024, 1);
        const uint64_t dV = make_desc(sb + OFF_VA + mh * 4096, 512, 512, 2);
        wg_fence();
        wgmma_ss_n32_ta1_tb1<0>(kv0, dP, dV);
        wgmma_ss_n32_ta1_tb1<0>(kv1, dP + 1024, dV + 512);
#pragma unroll
        for (int ks = 1; ks < 4; ks++) {
          wgmma_ss_n32_ta1_tb1<1>(kv0, dP + ks * 128, dV + ks * 64);
          wgmma_ss_n32_ta1_tb1<1>(kv1, dP + 1024 + ks * 128, dV + 512 + ks * 64);
        }
        wg_commit();
        wg_wait<0>();
        fence_regs(kv0); fence_regs(kv1);
        bar_sync(4 + wg, 128);
        const uint32_t sa = sb + OFF_PHIK + mh * 8192 + rowl * 128 + lq * 8 + (rowl & 3) * 32;
#pragma unroll
        for (int j = 0; j < 8; j++) {
          sts64((sa ^ (32 * (j >> 1))) + 1024 * (j & 1), __float_as_uint(kv0[2 * j]), __float_as_uint(kv0[2 * j + 1]));
          sts64((sa ^ (32 * (j >> 1))) + 16384 + 1024 * (j & 1), __float_as_uint(kv1[2 * j]), __float_as_uint(kv1[2 * j + 1]));
        }
        fence_async_smem();
        __syncwarp();
        if (lane == 0) mbar_arrive(BAR(B_SIG + 1), 1);
        if (tid == 256) PROF_MARK(28);
      }
    }
    {
      const uint64_t dK = make_desc(sb + OFF_RING, 512, 512, 2);
      const uint64_t dhi = dK & 0xffffffff00000000ull;
      const uint32_t dlo0 = (uint32_t)dK;
      uint32_t ok = 0, q[8];
      float o[16];
#pragma unroll
      for (int i = 0; i < 16; i++) o[i] = 0.f;
      {
        const int r = mh * 64 + wq * 16 + (lane & 7) + ((lane >> 3) & 1) * 8;
        ldsm4(q, sb + OFF_QP + nh * 8192 + sw64_off(r, (lane >> 4) * 8));
        ldsm4(q + 4, sb + OFF_QP + nh * 8192 + sw64_off(r, 16 + (lane >> 4) * 8));
      }
      if (tid == 0) PROF_MARK(10);
      const int qb = QB_AT;
      float s[32];
      mbar_wait(BAR(B_FULL + slot), par);
      wg_fence();
      wgmma_rs_n64_tb0<0>(s, q[0], q[1], q[2], q[3], dhi | (dlo0 + slot * 2048));
      wgmma_rs_n64_tb0<1>(s, q[4], q[5], q[6], q[7], dhi | (dlo0 + slot * 2048 + 2));
      wg_commit();
      wg_wait<0>();
      fence_regs(s);
#pragma unroll 1
      for (int it = 0; it <= 8; it++) {
        uint32_t p[16];
        if ((tid & 127) == 0) PROF4(wg * 32 + it);
        if (it == qb || it == 8) {
          float t[16];
          if (it < 8) {
            if (tid == 0) PROF_MARK(11);
            mbar_wait(BAR(B_KVR), 0);
            const uint64_t dR = make_desc(sb + OFF_KVR + nh * 4096, 512, 512, 2);
            const uint64_t dP = make_desc(sb + OFF_PHIQ + nh * 16384 + mh * 8192, 1024, 1024, 1);
            wg_fence();
            wgmma_ss_n32_ta0_tb1<0>(t, dP, dR);
#pragma unroll
            for (int ks = 1; ks < 4; ks++) wgmma_ss_n32_ta0_tb1<1>(t, dP + ks * 2, dR + ks * 64);
            wg_commit();
            wg_wait<0>();
            fence_regs(t);
            if (lane == 0) mbar_arrive(BAR(B_X1FREE), 1);
          } else {
            if (tid == 0) PROF_MARK(13);
            mbar_wait(BAR(B_SLOW), 0);
            if (__builtin_expect(__any_sync(~0u, *(volatile int*)(sgen + OFF_RED)), 0)) {
              uint32_t qz[8];
#pragma unroll
              for (int i = 0; i < 8; i++) qz[i] = (i >= 6 && lq >= 2) ? 0u : q[i];
              float m0 = -3.0e38f, m1 = -3.0e38f, o2[16];
              int sl2 = slot;
              uint32_t par2 = par;
#pragma unroll 1
              for (int j64 = 0; j64 < 32; j64++) {
                float s[32];
                mbar_wait(BAR(B_FULL + sl2), par2);
                const uint32_t lo = dlo0 + sl2 * 2048 + (j64 & 3) * 512;
                wg_fence();
                wgmma_rs_n64_tb0<0>(s, qz[0], qz[1], qz[2], qz[3], dhi | lo);
                wgmma_rs_n64_tb0<1>(s, qz[4], qz[5], qz[6], qz[7], dhi | (lo + 2));
                wg_commit();
                wg_wait<0>();
                fence_regs(s);
#pragma unroll
                for (int j = 0; j < 8; j++) {
                  const float sc = ((POLY_PAT >> j) & 1) ? 0.5f : 1.f;
                  m0 = fmaxf(m0, fmaxf(s[4 * j], s[4 * j + 1]) * sc);
                  m1 = fmaxf(m1, fmaxf(s[4 * j + 2], s[4 * j + 3]) * sc);
                }
                if ((j64 & 3) == 3) {
                  if (lane == 0) mbar_arrive(BAR(B_EMPTY + sl2), 1);
                  if (++sl2 == 3) { sl2 = 0; par2 ^= 1; }
                }
              }
              m0 = quad_max(m0); m1 = quad_max(m1);
#pragma unroll
              for (int i = 0; i < 16; i++) o2[i] = 0.f;
#pragma unroll 1
              for (int j64 = 0; j64 < 32; j64++) {
                float s[32];
                mbar_wait(BAR(B_FULL + sl2), par2);
                const uint32_t lo = dlo0 + sl2 * 2048 + (j64 & 3) * 512;
                wg_fence();
                wgmma_rs_n64_tb0<0>(s, qz[0], qz[1], qz[2], qz[3], dhi | lo);
                wgmma_rs_n64_tb0<1>(s, qz[4], qz[5], qz[6], qz[7], dhi | (lo + 2));
                wg_commit();
                wg_wait<0>();
                fence_regs(s);
                uint32_t ps[16];
#pragma unroll
                for (int j = 0; j < 8; j++) {
                  const float sc = ((POLY_PAT >> j) & 1) ? 0.5f : 1.f;
                  ps[2 * j] = pack_bf16(ex2f(fmaf(s[4 * j], sc, -m0)), ex2f(fmaf(s[4 * j + 1], sc, -m0)));
                  ps[2 * j + 1] = pack_bf16(ex2f(fmaf(s[4 * j + 2], sc, -m1)), ex2f(fmaf(s[4 * j + 3], sc, -m1)));
                }
                wg_fence();
#pragma unroll
                for (int ks = 0; ks < 4; ks++)
                  wgmma_rs_n32_tb1<1>(o2, ps[4 * ks], ps[4 * ks + 1], ps[4 * ks + 2], ps[4 * ks + 3], dhi | (lo + 256 + ks * 64));
                wg_commit();
                wg_wait<0>();
                fence_regs(o2);
                if ((j64 & 3) == 3) {
                  if (lane == 0) mbar_arrive(BAR(B_EMPTY + sl2), 1);
                  if (++sl2 == 3) { sl2 = 0; par2 ^= 1; }
                }
              }
#pragma unroll 1
              for (int j = 0; j < 2; j++) {
                mbar_wait(BAR(B_FULL + sl2), par2);
                __syncwarp();
                if (lane == 0) mbar_arrive(BAR(B_EMPTY + sl2), 1);
                if (++sl2 == 3) { sl2 = 0; par2 ^= 1; }
              }
#pragma unroll
              for (int i = 0; i < 16; i++) o[i] = o2[i];
            }
#pragma unroll
            for (int i = 0; i < 16; i++) t[i] = o[i];
#pragma unroll
            for (int i = 0; i < 32; i++) s[i] = 0.f;
          }
          const int br = it == 8;
          const float eps = br ? 0.f : 1e-6f;
          const float g0 = ((const float*)(sgen + OFF_GATE))[row0], g1 = ((const float*)(sgen + OFF_GATE))[row0 + 8];
          const float d0 = __shfl_sync(~0u, t[12], (lane & ~3) | 2), d1 = __shfl_sync(~0u, t[14], (lane & ~3) | 2);
          const float r0 = (br ? 1.f - g0 : g0) * rcpf(d0 + eps), r1 = (br ? 1.f - g1 : g1) * rcpf(d1 + eps);
          const uint32_t oa = sb + OFF_OSTG + (nh * 2 + mh) * 4096 + sw64_off(rowl, 2 * lq);
#pragma unroll
          for (int j = 0; j < 4; j++) {
            const bool real = j < 3 || lq < 2;
            sts32(oa ^ (j << 4), real ? pack_bf16(t[4 * j] * r0, t[4 * j + 1] * r0) : 0u);
            sts32((oa ^ (j << 4)) + 512, real ? pack_bf16(t[4 * j + 2] * r1, t[4 * j + 3] * r1) : 0u);
          }
          fence_async_smem();
          __syncwarp();
          if (lane == 0) mbar_arrive(BAR(B_SIG + 2 + br), 1);
          if (tid == 0) PROF_MARK(12 + 2 * br);
          if (br) { if ((tid & 127) == 0) PROF4(wg * 32 + 9); break; }
        }
        const uint32_t lo = dlo0 + slot * 2048;
        int nslot = slot + 1;
        uint32_t npar = par;
        if (nslot == 3) { nslot = 0; npar ^= 1; }
#pragma unroll
        for (int u = 0; u < 4; u++) {
          if (u == 2) ok = mbar_test(BAR(B_FULL + nslot), npar);
#pragma unroll
          for (int j = 0; j < 8; j++) {
            if ((POLY_PAT >> j) & 1) {
              p[2 * j] = exp2_pair_fma(s[4 * j], s[4 * j + 1], 0x3F003F00u, 0x00030003u);
              p[2 * j + 1] = exp2_pair_fma(s[4 * j + 2], s[4 * j + 3], 0x3F003F00u, 0x00030003u);
            } else {
              p[2 * j] = pack_bf16(ex2f(s[4 * j]), ex2f(s[4 * j + 1]));
              p[2 * j + 1] = pack_bf16(ex2f(s[4 * j + 2]), ex2f(s[4 * j + 3]));
            }
          }
          if (u == 3 && !ok && it < 7) mbar_wait(BAR(B_FULL + nslot), npar);
          const uint32_t ln = u < 3 ? lo + (u + 1) * 512 : dlo0 + nslot * 2048;
          wg_fence();
#pragma unroll
          for (int ks = 0; ks < 4; ks++)
            wgmma_rs_n32_tb1<1>(o, p[4 * ks], p[4 * ks + 1], p[4 * ks + 2], p[4 * ks + 3], dhi | (lo + u * 512 + 256 + ks * 64));
          wgmma_rs_n64_tb0<0>(s, q[0], q[1], q[2], q[3], dhi | ln);
          wgmma_rs_n64_tb0<1>(s, q[4], q[5], q[6], q[7], dhi | (ln + 2));
          wg_commit();
          wg_wait<0>();
          fence_regs(s);
          fence_regs(o);
        }
        if (lane == 0) mbar_arrive(BAR(B_EMPTY + slot), 1);
        slot = nslot; par = npar;
      }
      wg_wait<0>();
    }
    if (nh == 1) return;
    {
      float acc[28];
#pragma unroll
      for (int i = 0; i < 28; i++) acc[i] = 0.f;
      const uint64_t dS = make_desc(sb + OFF_WO, 1024, 1024, 1);
      const uint64_t dR = make_desc(sb + OFF_RING + mh * 4096, 512, 512, 2);
#pragma unroll 1
      for (int c = 0; c < 8; c++) {
        mbar_wait(BAR(B_WO + (c >> 2)), 0);
        mbar_wait(BAR(c == 7 ? B_RAW : B_FULL + slot), c == 7 ? 1 : par);
        const int id = c < 4 ? c : 4 + __shfl_sync(~0u, ((volatile int*)(sgen + OFF_RED + 16))[c & 3], 0);
        const uint64_t dA = c == 7 ? dR - (OFF_RING - OFF_WO) / 16 : dR + slot * 2048, dB = dS + id * 896;
        wg_fence();
#pragma unroll
        for (int h = 0; h < 4; h++) {
          wgmma_ss_n56_ta0_tb1<1>(acc, dA + h * 512, dB + h * 224);
          wgmma_ss_n56_ta0_tb1<1>(acc, dA + h * 512 + 2, dB + h * 224 + 128);
        }
        wg_commit();
        if (c < 4) {
          wg_wait<0>();
          if (lane == 0) mbar_arrive(BAR(B_EMPTY + slot), 2);
        }
        if (++slot == 3) { slot = 0; par ^= 1; }
      }
      wg_wait<0>();
      fence_regs(acc);
      if (tid == 0) PROF_MARK(17);
      __nv_bfloat16* op = prm.out + (size_t)(pt * 128 + row0) * DM + hp * 56 + 2 * lq;
#pragma unroll
      for (int j = 0; j < 7; j++) {
        *(uint32_t*)(op + 8 * j) = pack_bf16(acc[4 * j], acc[4 * j + 1]);
        *(uint32_t*)(op + 8 * DM + 8 * j) = pack_bf16(acc[4 * j + 2], acc[4 * j + 3]);
      }
      if (tid == 0) { PROF_MARK(18); PROF_CLK(31); }
    }
  }
}

typedef CUresult (*EncodeFn)(CUtensorMap*, CUtensorMapDataType, cuuint32_t, void*, const cuuint64_t*, const cuuint64_t*,
                             const cuuint32_t*, const cuuint32_t*, CUtensorMapInterleave, CUtensorMapSwizzle,
                             CUtensorMapL2promotion, CUtensorMapFloatOOBfill);

void make_map(EncodeFn enc, CUtensorMap* tm, const void* ptr, uint64_t cols, uint64_t rows, uint32_t box_cols, uint32_t box_rows) {
  cuuint64_t dims[2] = {cols, rows};
  cuuint64_t strides[1] = {cols * 2};
  cuuint32_t box[2] = {box_cols, box_rows};
  cuuint32_t es[2] = {1, 1};
  enc(tm, CU_TENSOR_MAP_DATA_TYPE_BFLOAT16, 2, const_cast<void*>(ptr), dims, strides, box, es, CU_TENSOR_MAP_INTERLEAVE_NONE,
      CU_TENSOR_MAP_SWIZZLE_128B, CU_TENSOR_MAP_L2_PROMOTION_L2_128B, CU_TENSOR_MAP_FLOAT_OOB_FILL_NONE);
}

}

extern "C" void kernel_launch(void* const* d_in, const int* in_sizes, int n_in, void* d_out, int out_size) {
  (void)in_sizes; (void)n_in; (void)out_size;
  static EncodeFn enc = nullptr;
  if (!enc) {
    void* fn = nullptr;
    cudaDriverEntryPointQueryResult qr;
    cudaGetDriverEntryPoint("cuTensorMapEncodeTiled", &fn, cudaEnableDefault, &qr);
    enc = (EncodeFn)fn;
    cudaFuncSetAttribute(fused_kernel, cudaFuncAttributeMaxDynamicSharedMemorySize, SMEM_BYTES);
  }
  CUtensorMap tm_x, tm_wqkv, tm_wq, tm_woa, tm_wob;
  make_map(enc, &tm_x, d_in[0], DM, S_LEN, 64, 128);
  make_map(enc, &tm_wqkv, d_in[1], 3 * DM, DM, 56, 64);
  make_map(enc, &tm_wq, d_in[5], DM, DM, 56, 64);
  make_map(enc, &tm_woa, d_in[3], DM, DM, 56, 64);
  make_map(enc, &tm_wob, d_in[8], DM, DM, 56, 64);
  Params prm;
  prm.w_phi = (const __nv_bfloat16*)d_in[2];
  prm.wk = (const __nv_bfloat16*)d_in[6];
  prm.wv = (const __nv_bfloat16*)d_in[7];
  prm.gate_w = (const __nv_bfloat16*)d_in[9];
  prm.out = (__nv_bfloat16*)d_out;
  fused_kernel<<<NCTA, NTHREADS, SMEM_BYTES>>>(tm_x, tm_wqkv, tm_wq, tm_woa, tm_wob, prm);
}
```

```cpp
#include <cuda_runtime.h>
#include <cuda_bf16.h>
#include <cuda.h>
#include <stdint.h>

namespace {

constexpr int S_LEN = 2048, DM = 448, DH = 28;
constexpr int NCTA = 128;
constexpr int NTHREADS = 640;
constexpr uint32_t POLY_PAT = 0x57;

#define QB_AT (4 + (wg >> 1))

constexpr int OFF_X = 0;
constexpr int OFF_PHIK = 0;
constexpr int OFF_VA = 32768;
constexpr int OFF_PHIQ = 57344;
constexpr int OFF_KVR = 90112;
constexpr int OFF_QP = 98304;
constexpr int OFF_RAW = 81920;
constexpr int OFF_WO = 0;
constexpr int OFF_RING = 114688;
constexpr int OFF_WBD = 212992;
constexpr int OFF_SLC = 221184;
constexpr int OFF_QSQ = 228352;
constexpr int OFF_OSTG = 212992;
constexpr int OFF_GATE = 229376;
constexpr int OFF_RED = 229888;
constexpr int OFF_BAR = 229952;
constexpr int SMEM_BYTES = 230400 + 1024;

constexpr int B_FULL = 0, B_EMPTY = 3, B_WO = 6  , B_KVR = 8, B_RAW = 9, B_X1FREE = 10, B_QSQ = 11, B_SLOW = 12,
              B_BUILD = 13, B_SIG = 14  , B_XL = 18  , B_N = 21;

constexpr int C_KV = 0, C_PART = 1, C_DONE = 3, C_OA = 4, C_OB = 20, C_N = 36;

__device__ __align__(1024) uint8_t g_kv_img[32 * 8192];
__device__ __align__(16) float g_ksq[256];
__device__ __align__(16) float g_vsq[256];
__device__ __align__(16) float g_gate[S_LEN];
__device__ __align__(1024) float g_kvacc[2][16 * 64 * 32];
__device__ unsigned g_epoch;
__device__ __align__(1024) uint8_t g_o_img[16 * 2 * 16 * 2 * 4096];
__device__ __align__(128) unsigned g_cnt[C_N * 32];

#define PROF4(i) do { } while (0)
#define PROF3(i) do { } while (0)
#define PROF2(i) do { } while (0)
#define PROF_CLK(i) do { } while (0)
#define PROF_MARK(i) do { } while (0)
__device__ __forceinline__ uint32_t smem_u32(const void* p) { return (uint32_t)__cvta_generic_to_shared(p); }
__device__ __forceinline__ void mbar_init(uint32_t a, int cnt) {
  asm volatile("mbarrier.init.shared::cta.b64 [%0], %1;" ::"r"(a), "r"(cnt) : "memory");
}
__device__ __forceinline__ void mbar_expect_tx(uint32_t a, uint32_t bytes) {
  asm volatile("mbarrier.arrive.expect_tx.shared::cta.b64 _, [%0], %1;" ::"r"(a), "r"(bytes) : "memory");
}
__device__ __forceinline__ void mbar_arrive(uint32_t a, uint32_t cnt) {
  asm volatile("mbarrier.arrive.shared::cta.b64 _, [%0], %1;" ::"r"(a), "r"(cnt) : "memory");
}
__device__ __forceinline__ void mbar_wait(uint32_t a, uint32_t parity) {
  asm volatile(
      "{\n.reg .pred p;\n.reg .u32 c;\nmov.u32 c, 0;\n"
      "W_%=:\nmbarrier.try_wait.parity.shared::cta.b64 p, [%0], %1;\n"
      "add.u32 c, c, 1;\nsetp.lt.and.u32 p, c, 0x40000, !p;\n@p bra W_%=;\n}"
      ::"r"(a), "r"(parity) : "memory");
}
__device__ __forceinline__ uint32_t mbar_test(uint32_t a, uint32_t parity) {
  uint32_t ok;
  asm volatile("{\n.reg .pred p;\nmbarrier.test_wait.parity.shared::cta.b64 p, [%1], %2;\nselp.u32 %0, 1, 0, p;\n}"
               : "=r"(ok) : "r"(a), "r"(parity) : "memory");
  return ok;
}
__device__ __forceinline__ bool elect_one() {
  uint32_t r;
  asm volatile("{\n.reg .pred p;\nelect.sync _|p, 0xffffffff;\nselp.u32 %0, 1, 0, p;\n}" : "=r"(r));
  return r != 0;
}
__device__ __forceinline__ void tma_2d(uint32_t dst, const CUtensorMap* tm, int c0, int c1, uint32_t bar) {
  asm volatile("cp.async.bulk.tensor.2d.shared::cluster.global.mbarrier::complete_tx::bytes [%0], [%1, {%3, %4}], [%2];"
               ::"r"(dst), "l"(tm), "r"(bar), "r"(c0), "r"(c1) : "memory");
}
__device__ __forceinline__ void bulk_g2s(uint32_t dst, const void* src, uint32_t bytes, uint32_t bar) {
  asm volatile("cp.async.bulk.shared::cluster.global.mbarrier::complete_tx::bytes [%0], [%1], %2, [%3];"
               ::"r"(dst), "l"(src), "r"(bytes), "r"(bar) : "memory");
}
__device__ __forceinline__ void fence_async_smem() { asm volatile("fence.proxy.async.shared::cta;" ::: "memory"); }
__device__ __forceinline__ void fence_async_all() { asm volatile("fence.proxy.async.global;" ::: "memory"); }

__device__ __forceinline__ void bar_sync(int id, int n) { asm volatile("bar.sync %0, %1;" ::"r"(id), "r"(n) : "memory"); }
__device__ __forceinline__ void cnt_wait(int idx, unsigned target) {
  unsigned v, n = 0;
#pragma unroll 1
  while (true) {
    asm volatile("ld.acquire.gpu.global.u32 %0, [%1];" : "=r"(v) : "l"(&g_cnt[idx * 32]) : "memory");
    if (v >= target || ++n >= (1u << 18)) break;
    __nanosleep(32);
  }
}
__device__ __forceinline__ void wg_fence() { asm volatile("wgmma.fence.sync.aligned;" ::: "memory"); }
__device__ __forceinline__ void wg_commit() { asm volatile("wgmma.commit_group.sync.aligned;" ::: "memory"); }
template <int N> __device__ __forceinline__ void wg_wait() { asm volatile("wgmma.wait_group.sync.aligned %0;" ::"n"(N) : "memory"); }
template <int N> __device__ __forceinline__ void fence_regs(float (&d)[N]) {
#pragma unroll
  for (int i = 0; i < N; i++) asm volatile("" : "+f"(d[i])::"memory");
}
__device__ __forceinline__ uint64_t make_desc(uint32_t saddr, uint32_t lbo, uint32_t sbo, uint32_t swz) {
  return (uint64_t)((saddr & 0x3FFFF) >> 4) | ((uint64_t)(lbo >> 4) << 16) | ((uint64_t)(sbo >> 4) << 32) | ((uint64_t)swz << 62);
}
__device__ __forceinline__ float ex2f(float x) { float y; asm("ex2.approx.ftz.f32 %0, %1;" : "=f"(y) : "f"(x)); return y; }
__device__ __forceinline__ float rcpf(float x) { float y; asm("rcp.approx.ftz.f32 %0, %1;" : "=f"(y) : "f"(x)); return y; }
__device__ __forceinline__ uint32_t pack_bf16(float lo, float hi) {
  uint32_t r; asm("cvt.rn.bf16x2.f32 %0, %1, %2;" : "=r"(r) : "f"(hi), "f"(lo)); return r;
}
__device__ __forceinline__ uint32_t lop_and_or(uint32_t a, uint32_t m, uint32_t c) {
  uint32_t r; asm("lop3.b32 %0, %1, %2, %3, 0xEA;" : "=r"(r) : "r"(a), "r"(m), "r"(c)); return r;
}
__device__ __forceinline__ void sts32(uint32_t a, uint32_t v) { asm volatile("st.shared.b32 [%0], %1;" ::"r"(a), "r"(v) : "memory"); }
__device__ __forceinline__ void st_shared_nv(uint32_t a, uint32_t v) { asm volatile("st.shared.b32 [%0], %1;" ::"r"(a), "r"(v)); }
__device__ __forceinline__ void sts64(uint32_t a, uint32_t v0, uint32_t v1) { asm volatile("st.shared.v2.b32 [%0], {%1, %2};" ::"r"(a), "r"(v0), "r"(v1) : "memory"); }
__device__ __forceinline__ void sts128(uint32_t a, uint4 v) {
  asm volatile("st.shared.v4.b32 [%0], {%1, %2, %3, %4};" ::"r"(a), "r"(v.x), "r"(v.y), "r"(v.z), "r"(v.w) : "memory");
}
__device__ __forceinline__ float4 ldcg_f4(const float* p) {
  float4 v; asm volatile("ld.global.cg.v4.f32 {%0, %1, %2, %3}, [%4];" : "=f"(v.x), "=f"(v.y), "=f"(v.z), "=f"(v.w) : "l"(p) : "memory"); return v;
}
__device__ __forceinline__ void ldsm4(uint32_t* r, uint32_t a) {
  asm volatile("ldmatrix.sync.aligned.m8n8.x4.shared.b16 {%0, %1, %2, %3}, [%4];"
               : "=r"(r[0]), "=r"(r[1]), "=r"(r[2]), "=r"(r[3]) : "r"(a) : "memory");
}
__device__ __forceinline__ float quad_sum(float v) { v += __shfl_xor_sync(~0u, v, 1); v += __shfl_xor_sync(~0u, v, 2); return v; }
__device__ __forceinline__ float quad_max(float v) { v = fmaxf(v, __shfl_xor_sync(~0u, v, 1)); v = fmaxf(v, __shfl_xor_sync(~0u, v, 2)); return v; }

template <int SD> __device__ __forceinline__ void wgmma_ss_n56_ta0_tb1(float (&d)[28], uint64_t da, uint64_t db) {
  if (SD) asm volatile("wgmma.mma_async.sync.aligned.m64n56k16.f32.bf16.bf16 {%0, %1, %2, %3, %4, %5, %6, %7, %8, %9, %10, %11, %12, %13, %14, %15, %16, %17, %18, %19, %20, %21, %22, %23, %24, %25, %26, %27}, %28, %29, 1, 1, 1, 0, 1;\n"
    : "+f"(d[0]), "+f"(d[1]), "+f"(d[2]), "+f"(d[3]), "+f"(d[4]), "+f"(d[5]), "+f"(d[6]), "+f"(d[7]), "+f"(d[8]), "+f"(d[9]), "+f"(d[10]), "+f"(d[11]), "+f"(d[12]), "+f"(d[13]), "+f"(d[14]), "+f"(d[15]), "+f"(d[16]), "+f"(d[17]), "+f"(d[18]), "+f"(d[19]), "+f"(d[20]), "+f"(d[21]), "+f"(d[22]), "+f"(d[23]), "+f"(d[24]), "+f"(d[25]), "+f"(d[26]), "+f"(d[27])
    : "l"(da), "l"(db));
  else asm volatile("wgmma.mma_async.sync.aligned.m64n56k16.f32.bf16.bf16 {%0, %1, %2, %3, %4, %5, %6, %7, %8, %9, %10, %11, %12, %13, %14, %15, %16, %17, %18, %19, %20, %21, %22, %23, %24, %25, %26, %27}, %28, %29, 0, 1, 1, 0, 1;\n"
    : "=f"(d[0]), "=f"(d[1]), "=f"(d[2]), "=f"(d[3]), "=f"(d[4]), "=f"(d[5]), "=f"(d[6]), "=f"(d[7]), "=f"(d[8]), "=f"(d[9]), "=f"(d[10]), "=f"(d[11]), "=f"(d[12]), "=f"(d[13]), "=f"(d[14]), "=f"(d[15]), "=f"(d[16]), "=f"(d[17]), "=f"(d[18]), "=f"(d[19]), "=f"(d[20]), "=f"(d[21]), "=f"(d[22]), "=f"(d[23]), "=f"(d[24]), "=f"(d[25]), "=f"(d[26]), "=f"(d[27])
    : "l"(da), "l"(db));
}
template <int SD> __device__ __forceinline__ void wgmma_rs_n64_tb1(float (&d)[32], uint32_t a0, uint32_t a1, uint32_t a2, uint32_t a3, uint64_t db) {
  if (SD) asm volatile("wgmma.mma_async.sync.aligned.m64n64k16.f32.bf16.bf16 {%0, %1, %2, %3, %4, %5, %6, %7, %8, %9, %10, %11, %12, %13, %14, %15, %16, %17, %18, %19, %20, %21, %22, %23, %24, %25, %26, %27, %28, %29, %30, %31}, {%32, %33, %34, %35}, %36, 1, 1, 1, 1;\n"
    : "+f"(d[0]), "+f"(d[1]), "+f"(d[2]), "+f"(d[3]), "+f"(d[4]), "+f"(d[5]), "+f"(d[6]), "+f"(d[7]), "+f"(d[8]), "+f"(d[9]), "+f"(d[10]), "+f"(d[11]), "+f"(d[12]), "+f"(d[13]), "+f"(d[14]), "+f"(d[15]), "+f"(d[16]), "+f"(d[17]), "+f"(d[18]), "+f"(d[19]), "+f"(d[20]), "+f"(d[21]), "+f"(d[22]), "+f"(d[23]), "+f"(d[24]), "+f"(d[25]), "+f"(d[26]), "+f"(d[27]), "+f"(d[28]), "+f"(d[29]), "+f"(d[30]), "+f"(d[31])
    : "r"(a0), "r"(a1), "r"(a2), "r"(a3), "l"(db));
  else asm volatile("wgmma.mma_async.sync.aligned.m64n64k16.f32.bf16.bf16 {%0, %1, %2, %3, %4, %5, %6, %7, %8, %9, %10, %11, %12, %13, %14, %15, %16, %17, %18, %19, %20, %21, %22, %23, %24, %25, %26, %27, %28, %29, %30, %31}, {%32, %33, %34, %35}, %36, 0, 1, 1, 1;\n"
    : "=f"(d[0]), "=f"(d[1]), "=f"(d[2]), "=f"(d[3]), "=f"(d[4]), "=f"(d[5]), "=f"(d[6]), "=f"(d[7]), "=f"(d[8]), "=f"(d[9]), "=f"(d[10]), "=f"(d[11]), "=f"(d[12]), "=f"(d[13]), "=f"(d[14]), "=f"(d[15]), "=f"(d[16]), "=f"(d[17]), "=f"(d[18]), "=f"(d[19]), "=f"(d[20]), "=f"(d[21]), "=f"(d[22]), "=f"(d[23]), "=f"(d[24]), "=f"(d[25]), "=f"(d[26]), "=f"(d[27]), "=f"(d[28]), "=f"(d[29]), "=f"(d[30]), "=f"(d[31])
    : "r"(a0), "r"(a1), "r"(a2), "r"(a3), "l"(db));
}
template <int SD> __device__ __forceinline__ void wgmma_ss_n32_ta1_tb1(float (&d)[16], uint64_t da, uint64_t db) {
  if (SD) asm volatile("wgmma.mma_async.sync.aligned.m64n32k16.f32.bf16.bf16 {%0, %1, %2, %3, %4, %5, %6, %7, %8, %9, %10, %11, %12, %13, %14, %15}, %16, %17, 1, 1, 1, 1, 1;\n"
    : "+f"(d[0]), "+f"(d[1]), "+f"(d[2]), "+f"(d[3]), "+f"(d[4]), "+f"(d[5]), "+f"(d[6]), "+f"(d[7]), "+f"(d[8]), "+f"(d[9]), "+f"(d[10]), "+f"(d[11]), "+f"(d[12]), "+f"(d[13]), "+f"(d[14]), "+f"(d[15])
    : "l"(da), "l"(db));
  else asm volatile("wgmma.mma_async.sync.aligned.m64n32k16.f32.bf16.bf16 {%0, %1, %2, %3, %4, %5, %6, %7, %8, %9, %10, %11, %12, %13, %14, %15}, %16, %17, 0, 1, 1, 1, 1;\n"
    : "=f"(d[0]), "=f"(d[1]), "=f"(d[2]), "=f"(d[3]), "=f"(d[4]), "=f"(d[5]), "=f"(d[6]), "=f"(d[7]), "=f"(d[8]), "=f"(d[9]), "=f"(d[10]), "=f"(d[11]), "=f"(d[12]), "=f"(d[13]), "=f"(d[14]), "=f"(d[15])
    : "l"(da), "l"(db));
}
template <int SD> __device__ __forceinline__ void wgmma_ss_n32_ta0_tb1(float (&d)[16], uint64_t da, uint64_t db) {
  if (SD) asm volatile("wgmma.mma_async.sync.aligned.m64n32k16.f32.bf16.bf16 {%0, %1, %2, %3, %4, %5, %6, %7, %8, %9, %10, %11, %12, %13, %14, %15}, %16, %17, 1, 1, 1, 0, 1;\n"
    : "+f"(d[0]), "+f"(d[1]), "+f"(d[2]), "+f"(d[3]), "+f"(d[4]), "+f"(d[5]), "+f"(d[6]), "+f"(d[7]), "+f"(d[8]), "+f"(d[9]), "+f"(d[10]), "+f"(d[11]), "+f"(d[12]), "+f"(d[13]), "+f"(d[14]), "+f"(d[15])
    : "l"(da), "l"(db));
  else asm volatile("wgmma.mma_async.sync.aligned.m64n32k16.f32.bf16.bf16 {%0, %1, %2, %3, %4, %5, %6, %7, %8, %9, %10, %11, %12, %13, %14, %15}, %16, %17, 0, 1, 1, 0, 1;\n"
    : "=f"(d[0]), "=f"(d[1]), "=f"(d[2]), "=f"(d[3]), "=f"(d[4]), "=f"(d[5]), "=f"(d[6]), "=f"(d[7]), "=f"(d[8]), "=f"(d[9]), "=f"(d[10]), "=f"(d[11]), "=f"(d[12]), "=f"(d[13]), "=f"(d[14]), "=f"(d[15])
    : "l"(da), "l"(db));
}
template <int SD> __device__ __forceinline__ void wgmma_rs_n64_tb0(float (&d)[32], uint32_t a0, uint32_t a1, uint32_t a2, uint32_t a3, uint64_t db) {
  if (SD) asm volatile("wgmma.mma_async.sync.aligned.m64n64k16.f32.bf16.bf16 {%0, %1, %2, %3, %4, %5, %6, %7, %8, %9, %10, %11, %12, %13, %14, %15, %16, %17, %18, %19, %20, %21, %22, %23, %24, %25, %26, %27, %28, %29, %30, %31}, {%32, %33, %34, %35}, %36, 1, 1, 1, 0;\n"
    : "+f"(d[0]), "+f"(d[1]), "+f"(d[2]), "+f"(d[3]), "+f"(d[4]), "+f"(d[5]), "+f"(d[6]), "+f"(d[7]), "+f"(d[8]), "+f"(d[9]), "+f"(d[10]), "+f"(d[11]), "+f"(d[12]), "+f"(d[13]), "+f"(d[14]), "+f"(d[15]), "+f"(d[16]), "+f"(d[17]), "+f"(d[18]), "+f"(d[19]), "+f"(d[20]), "+f"(d[21]), "+f"(d[22]), "+f"(d[23]), "+f"(d[24]), "+f"(d[25]), "+f"(d[26]), "+f"(d[27]), "+f"(d[28]), "+f"(d[29]), "+f"(d[30]), "+f"(d[31])
    : "r"(a0), "r"(a1), "r"(a2), "r"(a3), "l"(db));
  else asm volatile("wgmma.mma_async.sync.aligned.m64n64k16.f32.bf16.bf16 {%0, %1, %2, %3, %4, %5, %6, %7, %8, %9, %10, %11, %12, %13, %14, %15, %16, %17, %18, %19, %20, %21, %22, %23, %24, %25, %26, %27, %28, %29, %30, %31}, {%32, %33, %34, %35}, %36, 0, 1, 1, 0;\n"
    : "=f"(d[0]), "=f"(d[1]), "=f"(d[2]), "=f"(d[3]), "=f"(d[4]), "=f"(d[5]), "=f"(d[6]), "=f"(d[7]), "=f"(d[8]), "=f"(d[9]), "=f"(d[10]), "=f"(d[11]), "=f"(d[12]), "=f"(d[13]), "=f"(d[14]), "=f"(d[15]), "=f"(d[16]), "=f"(d[17]), "=f"(d[18]), "=f"(d[19]), "=f"(d[20]), "=f"(d[21]), "=f"(d[22]), "=f"(d[23]), "=f"(d[24]), "=f"(d[25]), "=f"(d[26]), "=f"(d[27]), "=f"(d[28]), "=f"(d[29]), "=f"(d[30]), "=f"(d[31])
    : "r"(a0), "r"(a1), "r"(a2), "r"(a3), "l"(db));
}
template <int SD> __device__ __forceinline__ void wgmma_rs_n32_tb1(float (&d)[16], uint32_t a0, uint32_t a1, uint32_t a2, uint32_t a3, uint64_t db) {
  if (SD) asm volatile("wgmma.mma_async.sync.aligned.m64n32k16.f32.bf16.bf16 {%0, %1, %2, %3, %4, %5, %6, %7, %8, %9, %10, %11, %12, %13, %14, %15}, {%16, %17, %18, %19}, %20, 1, 1, 1, 1;\n"
    : "+f"(d[0]), "+f"(d[1]), "+f"(d[2]), "+f"(d[3]), "+f"(d[4]), "+f"(d[5]), "+f"(d[6]), "+f"(d[7]), "+f"(d[8]), "+f"(d[9]), "+f"(d[10]), "+f"(d[11]), "+f"(d[12]), "+f"(d[13]), "+f"(d[14]), "+f"(d[15])
    : "r"(a0), "r"(a1), "r"(a2), "r"(a3), "l"(db));
  else asm volatile("wgmma.mma_async.sync.aligned.m64n32k16.f32.bf16.bf16 {%0, %1, %2, %3, %4, %5, %6, %7, %8, %9, %10, %11, %12, %13, %14, %15}, {%16, %17, %18, %19}, %20, 0, 1, 1, 1;\n"
    : "=f"(d[0]), "=f"(d[1]), "=f"(d[2]), "=f"(d[3]), "=f"(d[4]), "=f"(d[5]), "=f"(d[6]), "=f"(d[7]), "=f"(d[8]), "=f"(d[9]), "=f"(d[10]), "=f"(d[11]), "=f"(d[12]), "=f"(d[13]), "=f"(d[14]), "=f"(d[15])
    : "r"(a0), "r"(a1), "r"(a2), "r"(a3), "l"(db));
}

__device__ __forceinline__ uint32_t sw64_off(int row, int d) { return row * 64 + ((((d >> 3) ^ (row >> 1)) & 3) << 4) + (d & 7) * 2; }

__device__ __forceinline__ uint32_t exp2_pair_fma(float t0, float t1, uint32_t c_half, uint32_t c_3) {
  uint32_t y0, y;
  asm("prmt.b32 %0, %1, %2, 0x6521;" : "=r"(y0) : "r"(__float_as_uint(t0)), "r"(__float_as_uint(t1)));
  uint32_t h = lop_and_or(y0, 0x007F007Fu, c_half);
  uint32_t e = lop_and_or(y0, 0xFF80FF80u, c_3);
  asm("fma.rn.bf16x2 %0, %1, %2, %3;" : "=r"(y) : "r"(y0), "r"(h), "r"(e));
  return y;
}

__device__ __forceinline__ void feature_map(float (&p)[32], uint32_t rb, int lq) {
  const float L2E = 1.4426950408889634f;
  const bool tail_ok = lq < 2;
  float mx[4], mn[4], b[32], sa[4], sn[4];
#pragma unroll
  for (int g = 0; g < 4; g++) {
    const int o = 16 * (g >> 1) + 2 * (g & 1);
    if (!tail_ok) { p[o + 12] = p[o]; p[o + 13] = p[o]; }
    mx[g] = fmaxf(fmaxf(fmaxf(p[o], p[o + 1]), fmaxf(p[o + 4], p[o + 5])), fmaxf(fmaxf(p[o + 8], p[o + 9]), fmaxf(p[o + 12], p[o + 13])));
    mn[g] = fminf(fminf(fminf(p[o], p[o + 1]), fminf(p[o + 4], p[o + 5])), fminf(fminf(p[o + 8], p[o + 9]), fminf(p[o + 12], p[o + 13])));
  }
#pragma unroll
  for (int o = 1; o <= 2; o <<= 1)
#pragma unroll
    for (int g = 0; g < 4; g++) { mx[g] = fmaxf(mx[g], __shfl_xor_sync(~0u, mx[g], o)); mn[g] = fminf(mn[g], __shfl_xor_sync(~0u, mn[g], o)); }
#pragma unroll
  for (int g = 0; g < 4; g++) {
    const int o = 16 * (g >> 1) + 2 * (g & 1);
    const float cx = -mx[g] * L2E, cn = mn[g] * L2E;
#pragma unroll
    for (int i = 0; i < 8; i++) {
      const int k = o + 4 * (i >> 1) + (i & 1);
      b[k] = ex2f(fmaf(p[k], -L2E, cn));
      p[k] = ex2f(fmaf(p[k], L2E, cx));
    }
    if (!tail_ok) { p[o + 12] = p[o + 13] = b[o + 12] = b[o + 13] = 0.f; }
    sa[g] = ((p[o] + p[o + 1]) + (p[o + 4] + p[o + 5])) + ((p[o + 8] + p[o + 9]) + (p[o + 12] + p[o + 13]));
    sn[g] = ((b[o] + b[o + 1]) + (b[o + 4] + b[o + 5])) + ((b[o + 8] + b[o + 9]) + (b[o + 12] + b[o + 13]));
    sa[g] += __shfl_xor_sync(~0u, sa[g], 1); sn[g] += __shfl_xor_sync(~0u, sn[g], 1);
    sa[g] += __shfl_xor_sync(~0u, sa[g], 2); sn[g] += __shfl_xor_sync(~0u, sn[g], 2);
  }
#pragma unroll
  for (int g = 0; g < 4; g++) {
    const int o = 16 * (g >> 1) + 2 * (g & 1);
    const float ra = rcpf(sa[g]), rn = rcpf(sn[g]);
    const uint32_t off = (g >> 1) * 16384 + (g & 1) * 1024;
#pragma unroll
    for (int jj = 0; jj < 4; jj++) {
      st_shared_nv((rb ^ (jj << 4)) + off, pack_bf16(p[o + 4 * jj] * ra, p[o + 4 * jj + 1] * ra));
      st_shared_nv((rb ^ ((4 + jj) << 4)) + off, pack_bf16(b[o + 4 * jj] * rn, b[o + 4 * jj + 1] * rn));
    }
  }
}

__device__ __forceinline__ void store_heads(uint32_t base, const uint32_t (&a)[14], uint32_t pad0, uint32_t pad1, int row0, int lq) {
  const uint32_t rb = base + row0 * 64 + (((row0 >> 1) & 3) << 4);
  const uint32_t b0 = rb + lq * 4;
  const uint32_t b1 = (rb + 8192 + ((lq * 4 + 8) & 15)) ^ ((lq >> 1) << 4);
#pragma unroll
  for (int j = 0; j < 7; j++) {
    uint32_t ad;
    if (j < 3) ad = b0 ^ (j << 4);
    else if (j == 3) ad = (lq < 2) ? (b0 ^ 48u) : (b1 ^ 16u);
    else ad = (lq < 2) ? (b1 ^ ((j - 4) << 4)) : ((b1 ^ 16u) ^ ((j - 3) << 4));
    sts32(ad, a[2 * j]);
    sts32(ad + 512, a[2 * j + 1]);
  }
  sts64((rb ^ 48u) + 8 + (lq & 1) * 8192 + (lq >> 1) * 512, pad0, pad1);
}

struct Params {
  const __nv_bfloat16* w_phi;
  const __nv_bfloat16* wk;
  const __nv_bfloat16* wv;
  const __nv_bfloat16* gate_w;
  __nv_bfloat16* out;
};

__global__ void __launch_bounds__(NTHREADS, 1)
fused_kernel(const __grid_constant__ CUtensorMap tm_x, const __grid_constant__ CUtensorMap tm_wqkv,
             const __grid_constant__ CUtensorMap tm_wq, const __grid_constant__ CUtensorMap tm_woa,
             const __grid_constant__ CUtensorMap tm_wob, const Params prm) {
  extern __shared__ uint8_t smem_raw[];
  uint32_t sb = (smem_u32(smem_raw) + 1023u) & ~1023u;
  uint8_t* sgen = smem_raw + (sb - smem_u32(smem_raw));
  asm volatile("mov.u32 %0, %0;" : "+r"(sb));
  const int tid = threadIdx.x, lane = tid & 31;
  const int warp = __shfl_sync(~0u, tid >> 5, 0), wg = warp >> 2;
  const int pt = blockIdx.x >> 3, hp = blockIdx.x & 7;
  const uint32_t bars = sb + OFF_BAR;
  auto BAR = [&](int i) { return bars + 8u * i; };
  const unsigned epoch = g_epoch & 1;

  if (tid == 0) { PROF_MARK(0); PROF_CLK(30); PROF2(15); }
  auto load_proj = [&](int c, int g) {
    mbar_expect_tx(BAR(B_FULL + g), (c == 0 ? 16384 : 0) + 4 * 7168);
    if (c < 3) tma_2d(sb + OFF_X + c * 16384, &tm_x, c * 64, pt * 128, BAR(c ? B_XL : B_FULL));
    tma_2d(sb + OFF_RING + g * 32768, &tm_wq, hp * 56, c * 64, BAR(B_FULL + g));
#pragma unroll 1
    for (int j = 0; j < 3; j++) tma_2d(sb + OFF_RING + g * 32768 + 8192 + j * 8192, &tm_wqkv, j * DM + hp * 56, c * 64, BAR(B_FULL + g));
  };
  if (warp == 16) {
    if (elect_one()) {
      mbar_init(BAR(B_FULL), 1);
      fence_async_smem();
      load_proj(0, 0);
      mbar_init(BAR(B_RAW), 1); mbar_init(BAR(B_XL), 1); mbar_init(BAR(B_FULL + 1), 1); mbar_init(BAR(B_FULL + 2), 1);
      fence_async_smem();
    }
    __syncwarp();
    asm volatile("bar.arrive 0, %0;" ::"n"(NTHREADS) : "memory");
  } else {
    if (elect_one()) {
      const int i = warp + 3 - (warp > 16);
      if (i < B_N && i != B_RAW && i != B_XL) {
        int cnt = i < B_WO || (i > B_SIG && i < B_XL) || i == B_X1FREE ? 16 : 1;
        if (i == B_BUILD) cnt = 16;
        if (i == B_SIG + 1 || i == B_QSQ) cnt = 8;
        if (i == B_SIG) cnt = 3;
        if (i == B_KVR) cnt = 2;
        mbar_init(BAR(i), cnt);
        fence_async_smem();
      }
    }
    bar_sync(0, NTHREADS);
  }
  if (tid == 0) PROF2(14);

  if (wg == 4) {
    asm volatile("setmaxnreg.dec.sync.aligned.u32 32;");
    if (warp == 16) {
      if (elect_one()) {
        mbar_expect_tx(BAR(B_RAW), 25088 + 3136 + 896);
        bulk_g2s(sb + OFF_RAW, hp < 4 ? prm.wk : prm.wv, 25088, BAR(B_RAW));
        bulk_g2s(sb + OFF_RAW + 25088, prm.w_phi + 2 * hp * DH * DH, 3136, BAR(B_RAW));
        bulk_g2s(sb + OFF_RAW + 28224, prm.gate_w, 896, BAR(B_RAW));
        mbar_expect_tx(BAR(B_XL), 32768);
        load_proj(1, 1);
        load_proj(2, 2);
      }
      __syncwarp();
      bar_sync(3, 64);
      if (elect_one()) {
        int g = 0, nkv = 8;
        uint32_t par = 0;
#pragma unroll 1
        for (int c = 3; c < 7; c++) {
          if (c == 5) mbar_wait(BAR(B_BUILD), 0);
          if (c & 1) mbar_expect_tx(BAR(B_XL + (c >> 1)), 32768);
          tma_2d(sb + OFF_X + c * 16384, &tm_x, c * 64, pt * 128, BAR(B_XL + ((c - 1) >> 1)));
        }
        uint32_t todo = 15, rdy = 0;
#pragma unroll 1
        for (int n = 3; n < 15 + nkv; n++) {
          if (n == 7) { PROF_MARK(20); cnt_wait(C_KV, NCTA); PROF_MARK(21); fence_async_all(); }
          if (n == 15) {
            mbar_wait(BAR(B_SLOW), 0);
            if (*(volatile int*)(sgen + OFF_RED)) nkv = 26;
          }
          int j = n - 7 - nkv;
          if (j == 0) { PROF3(8); cnt_wait(C_OA + pt, 8); PROF3(9); fence_async_all(); }
          const bool last = j == 7;
          if (!last) mbar_wait(BAR(B_EMPTY + g), par);
          if (j >= 4) {
            uint32_t spin = 0;
            if (j == 4) PROF3(11);
#pragma unroll 1
            while (!rdy) {
              uint4 v;
              asm volatile("ld.acquire.gpu.global.v4.u32 {%0, %1, %2, %3}, [%4];"
                           : "=r"(v.x), "=r"(v.y), "=r"(v.z), "=r"(v.w) : "l"(&g_cnt[(C_OB + pt) * 32]) : "memory");
              rdy = ((v.x >= 2) | (v.y >= 2) << 1 | (v.z >= 2) << 2 | (v.w >= 2) << 3) & todo;
              if (++spin >= (1u << 18)) rdy = todo;
            }
            const int pick = __ffs(rdy) - 1;
            todo &= ~(1u << pick);
            rdy &= todo;
            ((volatile int*)(sgen + OFF_RED + 16))[j - 4] = pick;
            j = 4 + pick;
            PROF3(12);
            PROF_MARK(26);
            fence_async_all();
          }
          if (n < 7) { PROF2(20 + n); load_proj(n, g); }
          else {
            const uint32_t fb = BAR(last ? B_RAW : B_FULL + g);
            mbar_expect_tx(fb, 32768);
            bulk_g2s(last ? sb + OFF_WO : sb + OFF_RING + g * 32768,
                     j < 0 ? g_kv_img + ((n - 7) & 7) * 32768 : g_o_img + (size_t)(pt * 8 + j) * 32768, 32768, fb);
          }
          if (++g == 3) { g = 0; par ^= 1; }
        }
        if (atomicAdd(&g_cnt[C_DONE * 32], 1u) == NCTA - 1) {
#pragma unroll 1
          for (int i = 0; i < C_N; i++) *(uint4*)&g_cnt[i * 32] = make_uint4(0u, 0u, 0u, 0u);
          g_epoch = epoch ^ 1;
        }
      }
    } else {
      if (warp == 17) bar_sync(3, 64);
      {
        const int w = warp - 17, lq = lane & 3;
        float ac[3][4];
#pragma unroll
        for (int t = 0; t < 3; t++) ac[t][0] = ac[t][1] = ac[t][2] = ac[t][3] = 0.f;
        const int lr = w * 16 + (lane & 7) + ((lane >> 3) & 1) * 8;
        const uint32_t xa = sb + OFF_X + lr * 128 + (((lane >> 4) ^ (lr & 7)) << 4);
        mbar_wait(BAR(B_BUILD), 0);
#pragma unroll 1
        for (int kk = 0; kk < 28; kk++) {
          if ((kk & 7) == 4) mbar_wait(BAR(B_XL + (kk >> 3)), 0);
          uint32_t b0, b1;
          asm volatile("ldmatrix.sync.aligned.m8n8.x2.trans.shared.b16 {%0, %1}, [%2];" : "=r"(b0), "=r"(b1)
                       : "r"(sb + OFF_SLC + kk * 256 + (lane & 15) * 16) : "memory");
          const uint32_t ad = (xa + (kk >> 2) * 16384) ^ ((kk & 3) << 5);
#pragma unroll
          for (int t = 0; t < 3; t++) {
            if (t < 2 || w < 2) {
              uint32_t a[4];
              ldsm4(a, ad + t * 6144);
              asm volatile("mma.sync.aligned.m16n8k16.row.col.f32.bf16.bf16.f32 {%0, %1, %2, %3}, {%4, %5, %6, %7}, {%8, %9}, {%0, %1, %2, %3};"
                           : "+f"(ac[t][0]), "+f"(ac[t][1]), "+f"(ac[t][2]), "+f"(ac[t][3])
                           : "r"(a[0]), "r"(a[1]), "r"(a[2]), "r"(a[3]), "r"(b0), "r"(b1));
            }
          }
        }
        asm volatile("bar.arrive 2, 608;" ::: "memory");
        const int sl = hp & 3;
        const bool isk = hp < 4, real = (sl < 3) || (lq < 2);
        float mxv = 0.f;
#pragma unroll
        for (int t = 0; t < 3; t++) {
          if (t < 2 || w < 2) {
            const int pos = pt * 128 + (w + 3 * t) * 16 + (lane >> 2), kr = pos & 63;
            uint8_t* dst = g_kv_img + (pos >> 6) * 8192 + (isk ? 0 : 4096) + sw64_off(kr, sl * 8 + 2 * lq);
            const uint32_t pat = isk ? POLY_PAT >> (kr >> 3) : 0u;
#pragma unroll
            for (int rr = 0; rr < 2; rr++) {
              const float v0 = ac[t][2 * rr], v1 = ac[t][2 * rr + 1];
              const bool poly = (pat >> rr) & 1;
              const float sc = poly ? 2.f : 1.f;
              const float s2 = quad_sum(real ? v0 * v0 + v1 * v1 : 0.f);
              mxv = fmaxf(mxv, s2 <= 3.0e38f ? s2 : __int_as_float(0x7f800000));
              const uint32_t padv = lq == 2 ? (poly ? 0x443F4000u : 0x00003F80u) : (poly ? 0x3AB03F4Du : 0u);
              *(uint32_t*)(dst + rr * 512) = real ? pack_bf16(sc * v0, sc * v1) : padv;
              if (hp == 3 && lq == 2) g_gate[pos + 8 * rr] = rcpf(1.f + ex2f(-1.4426950408889634f * v0));
            }
          }
        }
        mxv = __uint_as_float(__reduce_max_sync(~0u, __float_as_uint(mxv)));
        if (lane == 0) (isk ? g_ksq : g_vsq)[sl * 64 + pt * 4 + w] = mxv;
        __syncwarp();
        if (lane == 0) mbar_arrive(BAR(B_SIG + 0), 1);
      }
      if (warp == 18) {
        if (elect_one()) {
#pragma unroll 1
          for (int i = 0; i < 4; i++) {
            mbar_wait(BAR(B_SIG + i), 0);
            PROF3(2 * i);
            if (i == 1) {
#pragma unroll 1
              for (int j = 0; j < 4; j++)
                asm volatile("cp.reduce.async.bulk.global.shared::cta.bulk_group.add.f32 [%0], [%1], 8192;"
                             ::"l"(g_kvacc[epoch] + hp * 4096 + (j >> 1) * 2048), "r"(sb + OFF_PHIK + j * 8192) : "memory");
            }
            if (i >= 2)
              asm volatile("cp.async.bulk.global.shared::cta.bulk_group [%0], [%1], 16384;"
                           ::"l"(g_o_img + (size_t)(pt * 2 + i - 2) * 131072 + hp * 16384), "r"(sb + OFF_OSTG) : "memory");
            if (i >= 1) asm volatile("cp.async.bulk.commit_group;\ncp.async.bulk.wait_group 0;" ::: "memory");
            asm volatile("red.release.gpu.global.add.u32 [%0], 1;"
                         ::"l"(&g_cnt[(i == 0 ? C_KV : i == 1 ? C_PART : (i == 2 ? C_OA : C_OB) + pt) * 32 + (i == 3 ? hp >> 1 : 0)]) : "memory");
            PROF3(2 * i + 1);
            if (i == 1 || i == 2) {
              if (i == 2) mbar_wait(BAR(B_X1FREE), 0);
              mbar_expect_tx(BAR(B_WO + i - 1), 7 * 7168);
#pragma unroll 1
              for (int c = 0; c < 7; c++)
                tma_2d(sb + OFF_WO + (i - 1) * 57344 + c * 8192, i == 1 ? &tm_woa : &tm_wob, hp * 56, c * 64, BAR(B_WO + i - 1));
            }
          }
        }
      } else if (warp == 19) {
        if (lane == 0) {
          mbar_wait(BAR(B_SIG + 0), 0);
          cnt_wait(C_KV, NCTA);
        }
        __syncwarp();
        float ksq = 0.f, vsq = 0.f;
#pragma unroll
        for (int i = 0; i < 2; i++) {
          float4 a = ldcg_f4(g_ksq + i * 128 + lane * 4), b = ldcg_f4(g_vsq + i * 128 + lane * 4);
          const uint32_t m = __float_as_uint(fmaxf(fmaxf(a.x, a.y), a.z));
          ksq += __uint_as_float(__reduce_max_sync(~0u, lane < 16 ? m : 0u)) + __uint_as_float(__reduce_max_sync(~0u, lane < 16 ? 0u : m));
          vsq = fmaxf(vsq, fmaxf(fmaxf(b.x, b.y), b.z));
        }
        mbar_wait(BAR(B_QSQ), 0);
        const float4 qa4 = ((const float4*)(sgen + OFF_QSQ))[lane], qb4 = ((const float4*)(sgen + OFF_QSQ))[32 + lane];
        const float qmax = fmaxf(fmaxf(fmaxf(qa4.x, qa4.y), fmaxf(qa4.z, qa4.w)), fmaxf(fmaxf(qb4.x, qb4.y), fmaxf(qb4.z, qb4.w)));
        const bool slow = __any_sync(~0u, !(qmax * ksq <= 98.f * 98.f) || !(vsq <= 2.0e8f));
        if (lane == 0) {
          *(volatile int*)(sgen + OFF_RED) = slow;
          mbar_arrive(BAR(B_SLOW), 1);
        }
      } else {
        float4* z = (float4*)(g_kvacc[epoch ^ 1] + blockIdx.x * 256) + lane;
        z[0] = make_float4(0.f, 0.f, 0.f, 0.f);
        z[32] = make_float4(0.f, 0.f, 0.f, 0.f);
        if (lane == 0) {
          mbar_wait(BAR(B_SIG + 0), 0);
          cnt_wait(C_KV, NCTA);
        }
        __syncwarp();
        ((float4*)(sgen + OFF_GATE))[lane] = ldcg_f4(g_gate + pt * 128 + lane * 4);
      }
      if (warp != 18) {
        if (lane == 0) {
          mbar_wait(BAR(B_SIG + 1), 0);
          cnt_wait(C_PART, NCTA);
          PROF_MARK(23);
        }
        __syncwarp();
        const int e = warp == 19;
        const float* src = g_kvacc[epoch] + hp * 4096 + e * 2048 + (lane ^ ((lane >> 2) & 3)) * 8;
#pragma unroll 1
        for (int i = 0; i < 8; i += 2) {
          const float4 a = ldcg_f4(src + i * 256), b = ldcg_f4(src + i * 256 + 4), c = ldcg_f4(src + i * 256 + 256), d = ldcg_f4(src + i * 256 + 260);
          const uint32_t ad = sb + OFF_KVR + e * 4096 + sw64_off(i * 8 + (lane >> 2), (lane & 3) * 8);
          sts128(ad, make_uint4(pack_bf16(a.x, a.y), pack_bf16(a.z, a.w), pack_bf16(b.x, b.y), pack_bf16(b.z, b.w)));
          sts128(ad + 512, make_uint4(pack_bf16(c.x, c.y), pack_bf16(c.z, c.w), pack_bf16(d.x, d.y), pack_bf16(d.z, d.w)));
        }
        fence_async_smem();
        __syncwarp();
        if (lane == 0) mbar_arrive(BAR(B_KVR), 1);
        PROF_MARK(24);
      }
    }
  } else {
    asm volatile("setmaxnreg.inc.sync.aligned.u32 112;");
    const int mh = wg & 1, nh = wg >> 1, wq = warp & 3;
    const int lq = lane & 3;
    const int rowl = wq * 16 + (lane >> 2);
    const int row0 = mh * 64 + rowl;
    int slot = 0;
    uint32_t par = 0;
    {
      float acc0[28], acc1[28];
      const uint64_t dR = make_desc(sb + OFF_RING + nh * 16384, 1024, 1024, 1);
      const uint64_t dX = make_desc(sb + OFF_X + mh * 8192, 1024, 1024, 1);
#pragma unroll
      for (int i = 0; i < 28; i++) acc0[i] = acc1[i] = 0.f;
#pragma unroll 1
      for (int c = 0; c < 7; c++) {
        if (c & 1) mbar_wait(BAR(B_XL + (c >> 1)), 0);
        mbar_wait(BAR(B_FULL + slot), par);
        if (c == 0 && tid == 0) PROF2(17);
        const uint64_t dA = dX + c * 1024, dB = dR + slot * 2048;
        wg_fence();
#pragma unroll
        for (int ks = 0; ks < 4; ks++) {
          wgmma_ss_n56_ta0_tb1<1>(acc0, dA + ks * 2, dB + ks * 128);
          wgmma_ss_n56_ta0_tb1<1>(acc1, dA + ks * 2, dB + 512 + ks * 128);
        }
        wg_commit();
        if (c == 0) {
          mbar_wait(BAR(B_RAW), 0);
          const int k = tid >> 3, cn = tid & 7;
          const bool data = k < 56 && (cn >> 2) == (k >= DH);
          const uint2* wsrc = (const uint2*)(sgen + OFF_RAW + 25088 + k * 56 + (cn & 3) * 16);
          uint2 w0 = make_uint2(0u, 0u), w1 = w0;
          if (data) w0 = wsrc[0];
          if (data && (cn & 3) != 3) w1 = wsrc[1];
          sts128(sb + OFF_WBD + k * 128 + ((cn ^ (k & 7)) << 4), make_uint4(w0.x, w0.y, w1.x, w1.y));
          if (tid < DM) {
            const uint2* src = (const uint2*)(sgen + OFF_RAW + tid * 56 + (hp & 3) * 16);
            w0 = src[0];
            w1 = make_uint2(hp == 3 ? (uint32_t)((const unsigned short*)(sgen + OFF_RAW + 28224))[tid] : 0u, 0u);
            if ((hp & 3) != 3) w1 = src[1];
            sts128(sb + OFF_SLC + tid * 16, make_uint4(w0.x, w0.y, w1.x, w1.y));
          }
          fence_async_smem();
          __syncwarp();
          if (lane == 0) mbar_arrive(BAR(B_BUILD), 1);
        }
        wg_wait<0>();
        if (lane == 0) mbar_arrive(BAR(B_EMPTY + slot), 1);
        if (++slot == 3) { slot = 0; par ^= 1; }
      }
      fence_regs(acc0); fence_regs(acc1);
      if (tid == 0) PROF_MARK(2);
      if (tid == 256) PROF_MARK(3);
      if (nh == 0) {
        float sq[4] = {0.f, 0.f, 0.f, 0.f};
#pragma unroll
        for (int i = 0; i < 28; i++) acc0[i] *= 0.18898223650461362f * 1.4426950408889634f;
#pragma unroll
        for (int j = 0; j < 7; j++) {
#pragma unroll
          for (int rr = 0; rr < 2; rr++) {
            const float s2 = acc0[4 * j + 2 * rr] * acc0[4 * j + 2 * rr] + acc0[4 * j + 2 * rr + 1] * acc0[4 * j + 2 * rr + 1];
            if (j < 3) sq[rr] += s2;
            else if (j > 3) sq[2 + rr] += s2;
            else { sq[rr] += (lq < 2) ? s2 : 0.f; sq[2 + rr] += (lq < 2) ? 0.f : s2; }
          }
        }
#pragma unroll
        for (int i = 0; i < 4; i++) sq[i] = quad_sum(sq[i]);
        const float mine = lq == 0 ? sq[0] : lq == 1 ? sq[1] : lq == 2 ? sq[2] : sq[3];
        ((float*)(sgen + OFF_QSQ))[(mh + (lq & 2)) * 64 + rowl + 8 * (lq & 1)] = mine <= 3.0e38f ? mine : __int_as_float(0x7f800000);
        __syncwarp();
        if (lane == 0) mbar_arrive(BAR(B_QSQ), 1);
      }
      if (tid == 0) PROF_MARK(4);
      if (tid == 256) PROF_MARK(5);
      uint32_t h[14];
      float pp[32];
      {
        uint32_t a[16];
#pragma unroll
        for (int i = 0; i < 14; i++) {
          const uint32_t u0 = pack_bf16(acc0[2 * i], acc0[2 * i + 1]), u1 = pack_bf16(acc1[2 * i], acc1[2 * i + 1]);
          h[i] = nh ? u1 : u0;
          a[i] = nh ? u0 : u1;
        }
        a[14] = a[0] ^ 0x80008000u;
        a[15] = a[1] ^ 0x80008000u;
        const uint64_t dW = make_desc(sb + OFF_WBD, 1024, 1024, 1);
        mbar_wait(BAR(B_BUILD), 0);
        wg_fence();
        wgmma_rs_n64_tb1<0>(pp, a[0], a[1], a[2], a[3], dW);
#pragma unroll
        for (int ks = 1; ks < 4; ks++) wgmma_rs_n64_tb1<1>(pp, a[4 * ks], a[4 * ks + 1], a[4 * ks + 2], a[4 * ks + 3], dW + ks * 128);
        wg_commit();
        bar_sync(2, 608);
        if (tid == 0) PROF_MARK(6);
        store_heads(sb + (nh ? OFF_VA : OFF_QP), h, nh ? 0x00003F80u : 0x3F800000u, nh ? 0u : 0x3F803F80u, row0, lq);
        wg_wait<0>();
        fence_regs(pp);
      }
      feature_map(pp, sb + (nh ? OFF_PHIK : OFF_PHIQ) + row0 * 128 + lq * 4 + ((rowl & 7) << 4), lq);
      fence_async_smem();
      bar_sync(1, 512);
      if (tid == 0) PROF_MARK(7);
      if (nh == 1) {
        float kv0[16], kv1[16];
        const uint64_t dP = make_desc(sb + OFF_PHIK + mh * 8192, 1024, 1024, 1);
        const uint64_t dV = make_desc(sb + OFF_VA + mh * 4096, 512, 512, 2);
        wg_fence();
        wgmma_ss_n32_ta1_tb1<0>(kv0, dP, dV);
        wgmma_ss_n32_ta1_tb1<0>(kv1, dP + 1024, dV + 512);
#pragma unroll
        for (int ks = 1; ks < 4; ks++) {
          wgmma_ss_n32_ta1_tb1<1>(kv0, dP + ks * 128, dV + ks * 64);
          wgmma_ss_n32_ta1_tb1<1>(kv1, dP + 1024 + ks * 128, dV + 512 + ks * 64);
        }
        wg_commit();
        wg_wait<0>();
        fence_regs(kv0); fence_regs(kv1);
        bar_sync(4 + wg, 128);
        const uint32_t sa = sb + OFF_PHIK + mh * 8192 + rowl * 128 + lq * 8 + (rowl & 3) * 32;
#pragma unroll
        for (int j = 0; j < 8; j++) {
          sts64((sa ^ (32 * (j >> 1))) + 1024 * (j & 1), __float_as_uint(kv0[2 * j]), __float_as_uint(kv0[2 * j + 1]));
          sts64((sa ^ (32 * (j >> 1))) + 16384 + 1024 * (j & 1), __float_as_uint(kv1[2 * j]), __float_as_uint(kv1[2 * j + 1]));
        }
        fence_async_smem();
        __syncwarp();
        if (lane == 0) mbar_arrive(BAR(B_SIG + 1), 1);
        if (tid == 256) PROF_MARK(28);
      }
    }
    {
      const uint64_t dK = make_desc(sb + OFF_RING, 512, 512, 2);
      const uint64_t dhi = dK & 0xffffffff00000000ull;
      const uint32_t dlo0 = (uint32_t)dK;
      uint32_t ok = 0, q[8];
      float o[16];
#pragma unroll
      for (int i = 0; i < 16; i++) o[i] = 0.f;
      {
        const int r = mh * 64 + wq * 16 + (lane & 7) + ((lane >> 3) & 1) * 8;
        ldsm4(q, sb + OFF_QP + nh * 8192 + sw64_off(r, (lane >> 4) * 8));
        ldsm4(q + 4, sb + OFF_QP + nh * 8192 + sw64_off(r, 16 + (lane >> 4) * 8));
      }
      if (tid == 0) PROF_MARK(10);
      const int qb = QB_AT;
      float s[32];
      mbar_wait(BAR(B_FULL + slot), par);
      wg_fence();
      wgmma_rs_n64_tb0<0>(s, q[0], q[1], q[2], q[3], dhi | (dlo0 + slot * 2048));
      wgmma_rs_n64_tb0<1>(s, q[4], q[5], q[6], q[7], dhi | (dlo0 + slot * 2048 + 2));
      wg_commit();
      wg_wait<0>();
      fence_regs(s);
#pragma unroll 1
      for (int it = 0; it <= 8; it++) {
        uint32_t p[16];
        if ((tid & 127) == 0) PROF4(wg * 32 + it);
        if (it == qb || it == 8) {
          float t[16];
          if (it < 8) {
            if (tid == 0) PROF_MARK(11);
            mbar_wait(BAR(B_KVR), 0);
            const uint64_t dR = make_desc(sb + OFF_KVR + nh * 4096, 512, 512, 2);
            const uint64_t dP = make_desc(sb + OFF_PHIQ + nh * 16384 + mh * 8192, 1024, 1024, 1);
            wg_fence();
            wgmma_ss_n32_ta0_tb1<0>(t, dP, dR);
#pragma unroll
            for (int ks = 1; ks < 4; ks++) wgmma_ss_n32_ta0_tb1<1>(t, dP + ks * 2, dR + ks * 64);
            wg_commit();
            wg_wait<0>();
            fence_regs(t);
            if (lane == 0) mbar_arrive(BAR(B_X1FREE), 1);
          } else {
            if (tid == 0) PROF_MARK(13);
            mbar_wait(BAR(B_SLOW), 0);
            if (__builtin_expect(__any_sync(~0u, *(volatile int*)(sgen + OFF_RED)), 0)) {
              uint32_t qz[8];
#pragma unroll
              for (int i = 0; i < 8; i++) qz[i] = (i >= 6 && lq >= 2) ? 0u : q[i];
              float m0 = -3.0e38f, m1 = -3.0e38f, o2[16];
              int sl2 = slot;
              uint32_t par2 = par;
#pragma unroll 1
              for (int j64 = 0; j64 < 32; j64++) {
                float s[32];
                mbar_wait(BAR(B_FULL + sl2), par2);
                const uint32_t lo = dlo0 + sl2 * 2048 + (j64 & 3) * 512;
                wg_fence();
                wgmma_rs_n64_tb0<0>(s, qz[0], qz[1], qz[2], qz[3], dhi | lo);
                wgmma_rs_n64_tb0<1>(s, qz[4], qz[5], qz[6], qz[7], dhi | (lo + 2));
                wg_commit();
                wg_wait<0>();
                fence_regs(s);
#pragma unroll
                for (int j = 0; j < 8; j++) {
                  const float sc = ((POLY_PAT >> j) & 1) ? 0.5f : 1.f;
                  m0 = fmaxf(m0, fmaxf(s[4 * j], s[4 * j + 1]) * sc);
                  m1 = fmaxf(m1, fmaxf(s[4 * j + 2], s[4 * j + 3]) * sc);
                }
                if ((j64 & 3) == 3) {
                  if (lane == 0) mbar_arrive(BAR(B_EMPTY + sl2), 1);
                  if (++sl2 == 3) { sl2 = 0; par2 ^= 1; }
                }
              }
              m0 = quad_max(m0); m1 = quad_max(m1);
#pragma unroll
              for (int i = 0; i < 16; i++) o2[i] = 0.f;
#pragma unroll 1
              for (int j64 = 0; j64 < 32; j64++) {
                float s[32];
                mbar_wait(BAR(B_FULL + sl2), par2);
                const uint32_t lo = dlo0 + sl2 * 2048 + (j64 & 3) * 512;
                wg_fence();
                wgmma_rs_n64_tb0<0>(s, qz[0], qz[1], qz[2], qz[3], dhi | lo);
                wgmma_rs_n64_tb0<1>(s, qz[4], qz[5], qz[6], qz[7], dhi | (lo + 2));
                wg_commit();
                wg_wait<0>();
                fence_regs(s);
                uint32_t ps[16];
#pragma unroll
                for (int j = 0; j < 8; j++) {
                  const float sc = ((POLY_PAT >> j) & 1) ? 0.5f : 1.f;
                  ps[2 * j] = pack_bf16(ex2f(fmaf(s[4 * j], sc, -m0)), ex2f(fmaf(s[4 * j + 1], sc, -m0)));
                  ps[2 * j + 1] = pack_bf16(ex2f(fmaf(s[4 * j + 2], sc, -m1)), ex2f(fmaf(s[4 * j + 3], sc, -m1)));
                }
                wg_fence();
#pragma unroll
                for (int ks = 0; ks < 4; ks++)
                  wgmma_rs_n32_tb1<1>(o2, ps[4 * ks], ps[4 * ks + 1], ps[4 * ks + 2], ps[4 * ks + 3], dhi | (lo + 256 + ks * 64));
                wg_commit();
                wg_wait<0>();
                fence_regs(o2);
                if ((j64 & 3) == 3) {
                  if (lane == 0) mbar_arrive(BAR(B_EMPTY + sl2), 1);
                  if (++sl2 == 3) { sl2 = 0; par2 ^= 1; }
                }
              }
#pragma unroll 1
              for (int j = 0; j < 2; j++) {
                mbar_wait(BAR(B_FULL + sl2), par2);
                __syncwarp();
                if (lane == 0) mbar_arrive(BAR(B_EMPTY + sl2), 1);
                if (++sl2 == 3) { sl2 = 0; par2 ^= 1; }
              }
#pragma unroll
              for (int i = 0; i < 16; i++) o[i] = o2[i];
            }
#pragma unroll
            for (int i = 0; i < 16; i++) t[i] = o[i];
#pragma unroll
            for (int i = 0; i < 32; i++) s[i] = 0.f;
          }
          const int br = it == 8;
          const float eps = br ? 0.f : 1e-6f;
          const float g0 = ((const float*)(sgen + OFF_GATE))[row0], g1 = ((const float*)(sgen + OFF_GATE))[row0 + 8];
          const float d0 = __shfl_sync(~0u, t[12], (lane & ~3) | 2), d1 = __shfl_sync(~0u, t[14], (lane & ~3) | 2);
          const float r0 = (br ? 1.f - g0 : g0) * rcpf(d0 + eps), r1 = (br ? 1.f - g1 : g1) * rcpf(d1 + eps);
          const uint32_t oa = sb + OFF_OSTG + (nh * 2 + mh) * 4096 + sw64_off(rowl, 2 * lq);
#pragma unroll
          for (int j = 0; j < 4; j++) {
            const bool real = j < 3 || lq < 2;
            sts32(oa ^ (j << 4), real ? pack_bf16(t[4 * j] * r0, t[4 * j + 1] * r0) : 0u);
            sts32((oa ^ (j << 4)) + 512, real ? pack_bf16(t[4 * j + 2] * r1, t[4 * j + 3] * r1) : 0u);
          }
          fence_async_smem();
          __syncwarp();
          if (lane == 0) mbar_arrive(BAR(B_SIG + 2 + br), 1);
          if (tid == 0) PROF_MARK(12 + 2 * br);
          if (br) { if ((tid & 127) == 0) PROF4(wg * 32 + 9); break; }
        }
        const uint32_t lo = dlo0 + slot * 2048;
        int nslot = slot + 1;
        uint32_t npar = par;
        if (nslot == 3) { nslot = 0; npar ^= 1; }
#pragma unroll
        for (int u = 0; u < 4; u++) {
          if (u == 2) ok = mbar_test(BAR(B_FULL + nslot), npar);
#pragma unroll
          for (int j = 0; j < 8; j++) {
            if ((POLY_PAT >> j) & 1) {
              p[2 * j] = exp2_pair_fma(s[4 * j], s[4 * j + 1], 0x3F003F00u, 0x00030003u);
              p[2 * j + 1] = exp2_pair_fma(s[4 * j + 2], s[4 * j + 3], 0x3F003F00u, 0x00030003u);
            } else {
              p[2 * j] = pack_bf16(ex2f(s[4 * j]), ex2f(s[4 * j + 1]));
              p[2 * j + 1] = pack_bf16(ex2f(s[4 * j + 2]), ex2f(s[4 * j + 3]));
            }
          }
          if (u == 3 && !ok && it < 7) mbar_wait(BAR(B_FULL + nslot), npar);
          const uint32_t ln = u < 3 ? lo + (u + 1) * 512 : dlo0 + nslot * 2048;
          wg_fence();
#pragma unroll
          for (int ks = 0; ks < 4; ks++)
            wgmma_rs_n32_tb1<1>(o, p[4 * ks], p[4 * ks + 1], p[4 * ks + 2], p[4 * ks + 3], dhi | (lo + u * 512 + 256 + ks * 64));
          wgmma_rs_n64_tb0<0>(s, q[0], q[1], q[2], q[3], dhi | ln);
          wgmma_rs_n64_tb0<1>(s, q[4], q[5], q[6], q[7], dhi | (ln + 2));
          wg_commit();
          wg_wait<0>();
          fence_regs(s);
          fence_regs(o);
        }
        if (lane == 0) mbar_arrive(BAR(B_EMPTY + slot), 1);
        slot = nslot; par = npar;
      }
      wg_wait<0>();
    }
    if (nh == 1) return;
    {
      float acc[28];
#pragma unroll
      for (int i = 0; i < 28; i++) acc[i] = 0.f;
      const uint64_t dS = make_desc(sb + OFF_WO, 1024, 1024, 1);
      const uint64_t dR = make_desc(sb + OFF_RING + mh * 4096, 512, 512, 2);
#pragma unroll 1
      for (int c = 0; c < 8; c++) {
        mbar_wait(BAR(B_WO + (c >> 2)), 0);
        mbar_wait(BAR(c == 7 ? B_RAW : B_FULL + slot), c == 7 ? 1 : par);
        const int id = c < 4 ? c : 4 + __shfl_sync(~0u, ((volatile int*)(sgen + OFF_RED + 16))[c & 3], 0);
        const uint64_t dA = c == 7 ? dR - (OFF_RING - OFF_WO) / 16 : dR + slot * 2048, dB = dS + id * 896;
        wg_fence();
#pragma unroll
        for (int h = 0; h < 4; h++) {
          wgmma_ss_n56_ta0_tb1<1>(acc, dA + h * 512, dB + h * 224);
          wgmma_ss_n56_ta0_tb1<1>(acc, dA + h * 512 + 2, dB + h * 224 + 128);
        }
        wg_commit();
        if (c < 4) {
          wg_wait<0>();
          if (lane == 0) mbar_arrive(BAR(B_EMPTY + slot), 2);
        }
        if (++slot == 3) { slot = 0; par ^= 1; }
      }
      wg_wait<0>();
      fence_regs(acc);
      if (tid == 0) PROF_MARK(17);
      __nv_bfloat16* op = prm.out + (size_t)(pt * 128 + row0) * DM + hp * 56 + 2 * lq;
#pragma unroll
      for (int j = 0; j < 7; j++) {
        *(uint32_t*)(op + 8 * j) = pack_bf16(acc[4 * j], acc[4 * j + 1]);
        *(uint32_t*)(op + 8 * DM + 8 * j) = pack_bf16(acc[4 * j + 2], acc[4 * j + 3]);
      }
      if (tid == 0) { PROF_MARK(18); PROF_CLK(31); }
    }
  }
}

typedef CUresult (*EncodeFn)(CUtensorMap*, CUtensorMapDataType, cuuint32_t, void*, const cuuint64_t*, const cuuint64_t*,
                             const cuuint32_t*, const cuuint32_t*, CUtensorMapInterleave, CUtensorMapSwizzle,
                             CUtensorMapL2promotion, CUtensorMapFloatOOBfill);

void make_map(EncodeFn enc, CUtensorMap* tm, const void* ptr, uint64_t cols, uint64_t rows, uint32_t box_cols, uint32_t box_rows) {
  cuuint64_t dims[2] = {cols, rows};
  cuuint64_t strides[1] = {cols * 2};
  cuuint32_t box[2] = {box_cols, box_rows};
  cuuint32_t es[2] = {1, 1};
  enc(tm, CU_TENSOR_MAP_DATA_TYPE_BFLOAT16, 2, const_cast<void*>(ptr), dims, strides, box, es, CU_TENSOR_MAP_INTERLEAVE_NONE,
      CU_TENSOR_MAP_SWIZZLE_128B, CU_TENSOR_MAP_L2_PROMOTION_L2_128B, CU_TENSOR_MAP_FLOAT_OOB_FILL_NONE);
}

}

extern "C" void kernel_launch(void* const* d_in, const int* in_sizes, int n_in, void* d_out, int out_size) {
  (void)in_sizes; (void)n_in; (void)out_size;
  static EncodeFn enc = nullptr;
  if (!enc) {
    void* fn = nullptr;
    cudaDriverEntryPointQueryResult qr;
    cudaGetDriverEntryPoint("cuTensorMapEncodeTiled", &fn, cudaEnableDefault, &qr);
    enc = (EncodeFn)fn;
    cudaFuncSetAttribute(fused_kernel, cudaFuncAttributeMaxDynamicSharedMemorySize, SMEM_BYTES);
  }
  CUtensorMap tm_x, tm_wqkv, tm_wq, tm_woa, tm_wob;
  make_map(enc, &tm_x, d_in[0], DM, S_LEN, 64, 128);
  make_map(enc, &tm_wqkv, d_in[1], 3 * DM, DM, 56, 64);
  make_map(enc, &tm_wq, d_in[5], DM, DM, 56, 64);
  make_map(enc, &tm_woa, d_in[3], DM, DM, 56, 64);
  make_map(enc, &tm_wob, d_in[8], DM, DM, 56, 64);
  Params prm;
  prm.w_phi = (const __nv_bfloat16*)d_in[2];
  prm.wk = (const __nv_bfloat16*)d_in[6];
  prm.wv = (const __nv_bfloat16*)d_in[7];
  prm.gate_w = (const __nv_bfloat16*)d_in[9];
  prm.out = (__nv_bfloat16*)d_out;
  fused_kernel<<<NCTA, NTHREADS, SMEM_BYTES>>>(tm_x, tm_wqkv, tm_wq, tm_woa, tm_wob, prm);
}
```

```cpp
#include <cuda_runtime.h>
#include <cuda_bf16.h>
#include <cuda.h>
#include <stdint.h>

namespace {

constexpr int S_LEN = 2048, DM = 448, DH = 28;
constexpr int NCTA = 128;
constexpr int NTHREADS = 640;
constexpr uint32_t POLY_PAT = 0x57;

#define QB_AT (4 + (wg >> 1))

constexpr int OFF_X = 0;
constexpr int OFF_PHIK = 0;
constexpr int OFF_VA = 32768;
constexpr int OFF_PHIQ = 57344;
constexpr int OFF_KVR = 90112;
constexpr int OFF_QP = 98304;
constexpr int OFF_RAW = 81920;
constexpr int OFF_WO = 0;
constexpr int OFF_RING = 114688;
constexpr int OFF_WBD = 212992;
constexpr int OFF_SLC = 221184;
constexpr int OFF_QSQ = 228352;
constexpr int OFF_OSTG = 212992;
constexpr int OFF_GATE = 229376;
constexpr int OFF_RED = 229888;
constexpr int OFF_BAR = 229952;
constexpr int SMEM_BYTES = 230400 + 1024;

constexpr int B_FULL = 0, B_EMPTY = 3, B_WO = 6  , B_KVR = 8, B_RAW = 9, B_X1FREE = 10, B_QSQ = 11, B_SLOW = 12,
              B_BUILD = 13, B_SIG = 14  , B_XL = 18  , B_SLJ = 20  , B_N = 24;

constexpr int C_KV = 0, C_PART = 1, C_DONE = 3, C_OA = 4, C_OB = 20, C_N = 36;

__device__ __align__(1024) uint8_t g_kv_img[32 * 8192];
__device__ __align__(16) float g_ksq[512];
__device__ __align__(16) float g_vsq[512];
__device__ __align__(16) float g_gate[S_LEN];
__device__ __align__(1024) float g_kvacc[2][16 * 64 * 32];
__device__ unsigned g_epoch;
__device__ __align__(1024) uint8_t g_o_img[16 * 2 * 16 * 2 * 4096];
__device__ __align__(128) unsigned g_cnt[C_N * 32];

__device__ __forceinline__ uint32_t smem_u32(const void* p) { return (uint32_t)__cvta_generic_to_shared(p); }
__device__ __forceinline__ void mbar_init(uint32_t a, int cnt) {
  asm volatile("mbarrier.init.shared::cta.b64 [%0], %1;" ::"r"(a), "r"(cnt) : "memory");
}
__device__ __forceinline__ void mbar_expect_tx(uint32_t a, uint32_t bytes) {
  asm volatile("mbarrier.arrive.expect_tx.shared::cta.b64 _, [%0], %1;" ::"r"(a), "r"(bytes) : "memory");
}
__device__ __forceinline__ void mbar_arrive(uint32_t a, uint32_t cnt) {
  asm volatile("mbarrier.arrive.shared::cta.b64 _, [%0], %1;" ::"r"(a), "r"(cnt) : "memory");
}
__device__ __forceinline__ void mbar_wait(uint32_t a, uint32_t parity) {
  asm volatile(
      "{\n.reg .pred p;\n.reg .u32 c;\nmov.u32 c, 0;\n"
      "W_%=:\nmbarrier.try_wait.parity.shared::cta.b64 p, [%0], %1;\n"
      "add.u32 c, c, 1;\nsetp.lt.and.u32 p, c, 0x8000, !p;\n@p bra W_%=;\n}"
      ::"r"(a), "r"(parity) : "memory");
}
__device__ __forceinline__ uint32_t mbar_test(uint32_t a, uint32_t parity) {
  uint32_t ok;
  asm volatile("{\n.reg .pred p;\nmbarrier.test_wait.parity.shared::cta.b64 p, [%1], %2;\nselp.u32 %0, 1, 0, p;\n}"
               : "=r"(ok) : "r"(a), "r"(parity) : "memory");
  return ok;
}
__device__ __forceinline__ bool elect_one() {
  uint32_t r;
  asm volatile("{\n.reg .pred p;\nelect.sync _|p, 0xffffffff;\nselp.u32 %0, 1, 0, p;\n}" : "=r"(r));
  return r != 0;
}
__device__ __forceinline__ void tma_2d(uint32_t dst, const CUtensorMap* tm, int c0, int c1, uint32_t bar) {
  asm volatile("cp.async.bulk.tensor.2d.shared::cluster.global.mbarrier::complete_tx::bytes [%0], [%1, {%3, %4}], [%2];"
               ::"r"(dst), "l"(tm), "r"(bar), "r"(c0), "r"(c1) : "memory");
}
__device__ __forceinline__ void bulk_g2s(uint32_t dst, const void* src, uint32_t bytes, uint32_t bar) {
  asm volatile("cp.async.bulk.shared::cluster.global.mbarrier::complete_tx::bytes [%0], [%1], %2, [%3];"
               ::"r"(dst), "l"(src), "r"(bytes), "r"(bar) : "memory");
}
__device__ __forceinline__ void fence_async_smem() { asm volatile("fence.proxy.async.shared::cta;" ::: "memory"); }
__device__ __forceinline__ void fence_async_all() { asm volatile("fence.proxy.async.global;" ::: "memory"); }

__device__ __forceinline__ void bar_sync(int id, int n) { asm volatile("bar.sync %0, %1;" ::"r"(id), "r"(n) : "memory"); }
__device__ __forceinline__ void cnt_wait(int idx, unsigned target) {
  unsigned v, n = 0;
#pragma unroll 1
  while (true) {
    asm volatile("ld.acquire.gpu.global.u32 %0, [%1];" : "=r"(v) : "l"(&g_cnt[idx * 32]) : "memory");
    if (v >= target || ++n >= (1u << 16)) break;
    __nanosleep(32);
  }
}
__device__ __forceinline__ void wg_fence() { asm volatile("wgmma.fence.sync.aligned;" ::: "memory"); }
__device__ __forceinline__ void wg_commit() { asm volatile("wgmma.commit_group.sync.aligned;" ::: "memory"); }
template <int N> __device__ __forceinline__ void wg_wait() { asm volatile("wgmma.wait_group.sync.aligned %0;" ::"n"(N) : "memory"); }
template <int N> __device__ __forceinline__ void fence_regs(float (&d)[N]) {
#pragma unroll
  for (int i = 0; i < N; i++) asm volatile("" : "+f"(d[i])::"memory");
}
__device__ __forceinline__ uint64_t make_desc(uint32_t saddr, uint32_t lbo, uint32_t sbo, uint32_t swz) {
  return (uint64_t)((saddr & 0x3FFFF) >> 4) | ((uint64_t)(lbo >> 4) << 16) | ((uint64_t)(sbo >> 4) << 32) | ((uint64_t)swz << 62);
}
__device__ __forceinline__ float ex2f(float x) { float y; asm("ex2.approx.ftz.f32 %0, %1;" : "=f"(y) : "f"(x)); return y; }
__device__ __forceinline__ float rcpf(float x) { float y; asm("rcp.approx.ftz.f32 %0, %1;" : "=f"(y) : "f"(x)); return y; }
__device__ __forceinline__ uint32_t pack_bf16(float lo, float hi) {
  uint32_t r; asm("cvt.rn.bf16x2.f32 %0, %1, %2;" : "=r"(r) : "f"(hi), "f"(lo)); return r;
}
__device__ __forceinline__ uint32_t lop_and_or(uint32_t a, uint32_t m, uint32_t c) {
  uint32_t r; asm("lop3.b32 %0, %1, %2, %3, 0xEA;" : "=r"(r) : "r"(a), "r"(m), "r"(c)); return r;
}
__device__ __forceinline__ void sts32(uint32_t a, uint32_t v) { asm volatile("st.shared.b32 [%0], %1;" ::"r"(a), "r"(v) : "memory"); }
__device__ __forceinline__ void st_shared_nv(uint32_t a, uint32_t v) { asm volatile("st.shared.b32 [%0], %1;" ::"r"(a), "r"(v)); }
__device__ __forceinline__ void sts64(uint32_t a, uint32_t v0, uint32_t v1) { asm volatile("st.shared.v2.b32 [%0], {%1, %2};" ::"r"(a), "r"(v0), "r"(v1) : "memory"); }
__device__ __forceinline__ void sts128(uint32_t a, uint4 v) {
  asm volatile("st.shared.v4.b32 [%0], {%1, %2, %3, %4};" ::"r"(a), "r"(v.x), "r"(v.y), "r"(v.z), "r"(v.w) : "memory");
}
__device__ __forceinline__ float4 ldcg_f4(const float* p) {
  float4 v; asm volatile("ld.global.cg.v4.f32 {%0, %1, %2, %3}, [%4];" : "=f"(v.x), "=f"(v.y), "=f"(v.z), "=f"(v.w) : "l"(p) : "memory"); return v;
}
__device__ __forceinline__ void ldsm4(uint32_t* r, uint32_t a) {
  asm volatile("ldmatrix.sync.aligned.m8n8.x4.shared.b16 {%0, %1, %2, %3}, [%4];"
               : "=r"(r[0]), "=r"(r[1]), "=r"(r[2]), "=r"(r[3]) : "r"(a) : "memory");
}
__device__ __forceinline__ float quad_sum(float v) { v += __shfl_xor_sync(~0u, v, 1); v += __shfl_xor_sync(~0u, v, 2); return v; }
__device__ __forceinline__ float quad_max(float v) { v = fmaxf(v, __shfl_xor_sync(~0u, v, 1)); v = fmaxf(v, __shfl_xor_sync(~0u, v, 2)); return v; }

template <int SD> __device__ __forceinline__ void wgmma_ss_n56_ta0_tb1(float (&d)[28], uint64_t da, uint64_t db) {
  if (SD) asm volatile("wgmma.mma_async.sync.aligned.m64n56k16.f32.bf16.bf16 {%0, %1, %2, %3, %4, %5, %6, %7, %8, %9, %10, %11, %12, %13, %14, %15, %16, %17, %18, %19, %20, %21, %22, %23, %24, %25, %26, %27}, %28, %29, 1, 1, 1, 0, 1;\n"
    : "+f"(d[0]), "+f"(d[1]), "+f"(d[2]), "+f"(d[3]), "+f"(d[4]), "+f"(d[5]), "+f"(d[6]), "+f"(d[7]), "+f"(d[8]), "+f"(d[9]), "+f"(d[10]), "+f"(d[11]), "+f"(d[12]), "+f"(d[13]), "+f"(d[14]), "+f"(d[15]), "+f"(d[16]), "+f"(d[17]), "+f"(d[18]), "+f"(d[19]), "+f"(d[20]), "+f"(d[21]), "+f"(d[22]), "+f"(d[23]), "+f"(d[24]), "+f"(d[25]), "+f"(d[26]), "+f"(d[27])
    : "l"(da), "l"(db));
  else asm volatile("wgmma.mma_async.sync.aligned.m64n56k16.f32.bf16.bf16 {%0, %1, %2, %3, %4, %5, %6, %7, %8, %9, %10, %11, %12, %13, %14, %15, %16, %17, %18, %19, %20, %21, %22, %23, %24, %25, %26, %27}, %28, %29, 0, 1, 1, 0, 1;\n"
    : "=f"(d[0]), "=f"(d[1]), "=f"(d[2]), "=f"(d[3]), "=f"(d[4]), "=f"(d[5]), "=f"(d[6]), "=f"(d[7]), "=f"(d[8]), "=f"(d[9]), "=f"(d[10]), "=f"(d[11]), "=f"(d[12]), "=f"(d[13]), "=f"(d[14]), "=f"(d[15]), "=f"(d[16]), "=f"(d[17]), "=f"(d[18]), "=f"(d[19]), "=f"(d[20]), "=f"(d[21]), "=f"(d[22]), "=f"(d[23]), "=f"(d[24]), "=f"(d[25]), "=f"(d[26]), "=f"(d[27])
    : "l"(da), "l"(db));
}
template <int SD> __device__ __forceinline__ void wgmma_ss_n64_ta0_tb1(float (&d)[32], uint64_t da, uint64_t db) {
  if (SD) asm volatile("wgmma.mma_async.sync.aligned.m64n64k16.f32.bf16.bf16 {%0, %1, %2, %3, %4, %5, %6, %7, %8, %9, %10, %11, %12, %13, %14, %15, %16, %17, %18, %19, %20, %21, %22, %23, %24, %25, %26, %27, %28, %29, %30, %31}, %32, %33, 1, 1, 1, 0, 1;\n"
    : "+f"(d[0]), "+f"(d[1]), "+f"(d[2]), "+f"(d[3]), "+f"(d[4]), "+f"(d[5]), "+f"(d[6]), "+f"(d[7]), "+f"(d[8]), "+f"(d[9]), "+f"(d[10]), "+f"(d[11]), "+f"(d[12]), "+f"(d[13]), "+f"(d[14]), "+f"(d[15]), "+f"(d[16]), "+f"(d[17]), "+f"(d[18]), "+f"(d[19]), "+f"(d[20]), "+f"(d[21]), "+f"(d[22]), "+f"(d[23]), "+f"(d[24]), "+f"(d[25]), "+f"(d[26]), "+f"(d[27]), "+f"(d[28]), "+f"(d[29]), "+f"(d[30]), "+f"(d[31])
    : "l"(da), "l"(db));
  else asm volatile("wgmma.mma_async.sync.aligned.m64n64k16.f32.bf16.bf16 {%0, %1, %2, %3, %4, %5, %6, %7, %8, %9, %10, %11, %12, %13, %14, %15, %16, %17, %18, %19, %20, %21, %22, %23, %24, %25, %26, %27, %28, %29, %30, %31}, %32, %33, 0, 1, 1, 0, 1;\n"
    : "=f"(d[0]), "=f"(d[1]), "=f"(d[2]), "=f"(d[3]), "=f"(d[4]), "=f"(d[5]), "=f"(d[6]), "=f"(d[7]), "=f"(d[8]), "=f"(d[9]), "=f"(d[10]), "=f"(d[11]), "=f"(d[12]), "=f"(d[13]), "=f"(d[14]), "=f"(d[15]), "=f"(d[16]), "=f"(d[17]), "=f"(d[18]), "=f"(d[19]), "=f"(d[20]), "=f"(d[21]), "=f"(d[22]), "=f"(d[23]), "=f"(d[24]), "=f"(d[25]), "=f"(d[26]), "=f"(d[27]), "=f"(d[28]), "=f"(d[29]), "=f"(d[30]), "=f"(d[31])
    : "l"(da), "l"(db));
}
template <int SD> __device__ __forceinline__ void wgmma_ss_n8_ta0_tb1(float (&d)[4], uint64_t da, uint64_t db) {
  if (SD) asm volatile("wgmma.mma_async.sync.aligned.m64n8k16.f32.bf16.bf16 {%0, %1, %2, %3}, %4, %5, 1, 1, 1, 0, 1;\n"
    : "+f"(d[0]), "+f"(d[1]), "+f"(d[2]), "+f"(d[3])
    : "l"(da), "l"(db));
  else asm volatile("wgmma.mma_async.sync.aligned.m64n8k16.f32.bf16.bf16 {%0, %1, %2, %3}, %4, %5, 0, 1, 1, 0, 1;\n"
    : "=f"(d[0]), "=f"(d[1]), "=f"(d[2]), "=f"(d[3])
    : "l"(da), "l"(db));
}
template <int SD> __device__ __forceinline__ void wgmma_rs_n64_tb1(float (&d)[32], uint32_t a0, uint32_t a1, uint32_t a2, uint32_t a3, uint64_t db) {
  if (SD) asm volatile("wgmma.mma_async.sync.aligned.m64n64k16.f32.bf16.bf16 {%0, %1, %2, %3, %4, %5, %6, %7, %8, %9, %10, %11, %12, %13, %14, %15, %16, %17, %18, %19, %20, %21, %22, %23, %24, %25, %26, %27, %28, %29, %30, %31}, {%32, %33, %34, %35}, %36, 1, 1, 1, 1;\n"
    : "+f"(d[0]), "+f"(d[1]), "+f"(d[2]), "+f"(d[3]), "+f"(d[4]), "+f"(d[5]), "+f"(d[6]), "+f"(d[7]), "+f"(d[8]), "+f"(d[9]), "+f"(d[10]), "+f"(d[11]), "+f"(d[12]), "+f"(d[13]), "+f"(d[14]), "+f"(d[15]), "+f"(d[16]), "+f"(d[17]), "+f"(d[18]), "+f"(d[19]), "+f"(d[20]), "+f"(d[21]), "+f"(d[22]), "+f"(d[23]), "+f"(d[24]), "+f"(d[25]), "+f"(d[26]), "+f"(d[27]), "+f"(d[28]), "+f"(d[29]), "+f"(d[30]), "+f"(d[31])
    : "r"(a0), "r"(a1), "r"(a2), "r"(a3), "l"(db));
  else asm volatile("wgmma.mma_async.sync.aligned.m64n64k16.f32.bf16.bf16 {%0, %1, %2, %3, %4, %5, %6, %7, %8, %9, %10, %11, %12, %13, %14, %15, %16, %17, %18, %19, %20, %21, %22, %23, %24, %25, %26, %27, %28, %29, %30, %31}, {%32, %33, %34, %35}, %36, 0, 1, 1, 1;\n"
    : "=f"(d[0]), "=f"(d[1]), "=f"(d[2]), "=f"(d[3]), "=f"(d[4]), "=f"(d[5]), "=f"(d[6]), "=f"(d[7]), "=f"(d[8]), "=f"(d[9]), "=f"(d[10]), "=f"(d[11]), "=f"(d[12]), "=f"(d[13]), "=f"(d[14]), "=f"(d[15]), "=f"(d[16]), "=f"(d[17]), "=f"(d[18]), "=f"(d[19]), "=f"(d[20]), "=f"(d[21]), "=f"(d[22]), "=f"(d[23]), "=f"(d[24]), "=f"(d[25]), "=f"(d[26]), "=f"(d[27]), "=f"(d[28]), "=f"(d[29]), "=f"(d[30]), "=f"(d[31])
    : "r"(a0), "r"(a1), "r"(a2), "r"(a3), "l"(db));
}
template <int SD> __device__ __forceinline__ void wgmma_ss_n32_ta1_tb1(float (&d)[16], uint64_t da, uint64_t db) {
  if (SD) asm volatile("wgmma.mma_async.sync.aligned.m64n32k16.f32.bf16.bf16 {%0, %1, %2, %3, %4, %5, %6, %7, %8, %9, %10, %11, %12, %13, %14, %15}, %16, %17, 1, 1, 1, 1, 1;\n"
    : "+f"(d[0]), "+f"(d[1]), "+f"(d[2]), "+f"(d[3]), "+f"(d[4]), "+f"(d[5]), "+f"(d[6]), "+f"(d[7]), "+f"(d[8]), "+f"(d[9]), "+f"(d[10]), "+f"(d[11]), "+f"(d[12]), "+f"(d[13]), "+f"(d[14]), "+f"(d[15])
    : "l"(da), "l"(db));
  else asm volatile("wgmma.mma_async.sync.aligned.m64n32k16.f32.bf16.bf16 {%0, %1, %2, %3, %4, %5, %6, %7, %8, %9, %10, %11, %12, %13, %14, %15}, %16, %17, 0, 1, 1, 1, 1;\n"
    : "=f"(d[0]), "=f"(d[1]), "=f"(d[2]), "=f"(d[3]), "=f"(d[4]), "=f"(d[5]), "=f"(d[6]), "=f"(d[7]), "=f"(d[8]), "=f"(d[9]), "=f"(d[10]), "=f"(d[11]), "=f"(d[12]), "=f"(d[13]), "=f"(d[14]), "=f"(d[15])
    : "l"(da), "l"(db));
}
template <int SD> __device__ __forceinline__ void wgmma_ss_n32_ta0_tb1(float (&d)[16], uint64_t da, uint64_t db) {
  if (SD) asm volatile("wgmma.mma_async.sync.aligned.m64n32k16.f32.bf16.bf16 {%0, %1, %2, %3, %4, %5, %6, %7, %8, %9, %10, %11, %12, %13, %14, %15}, %16, %17, 1, 1, 1, 0, 1;\n"
    : "+f"(d[0]), "+f"(d[1]), "+f"(d[2]), "+f"(d[3]), "+f"(d[4]), "+f"(d[5]), "+f"(d[6]), "+f"(d[7]), "+f"(d[8]), "+f"(d[9]), "+f"(d[10]), "+f"(d[11]), "+f"(d[12]), "+f"(d[13]), "+f"(d[14]), "+f"(d[15])
    : "l"(da), "l"(db));
  else asm volatile("wgmma.mma_async.sync.aligned.m64n32k16.f32.bf16.bf16 {%0, %1, %2, %3, %4, %5, %6, %7, %8, %9, %10, %11, %12, %13, %14, %15}, %16, %17, 0, 1, 1, 0, 1;\n"
    : "=f"(d[0]), "=f"(d[1]), "=f"(d[2]), "=f"(d[3]), "=f"(d[4]), "=f"(d[5]), "=f"(d[6]), "=f"(d[7]), "=f"(d[8]), "=f"(d[9]), "=f"(d[10]), "=f"(d[11]), "=f"(d[12]), "=f"(d[13]), "=f"(d[14]), "=f"(d[15])
    : "l"(da), "l"(db));
}
template <int SD> __device__ __forceinline__ void wgmma_rs_n64_tb0(float (&d)[32], uint32_t a0, uint32_t a1, uint32_t a2, uint32_t a3, uint64_t db) {
  if (SD) asm volatile("wgmma.mma_async.sync.aligned.m64n64k16.f32.bf16.bf16 {%0, %1, %2, %3, %4, %5, %6, %7, %8, %9, %10, %11, %12, %13, %14, %15, %16, %17, %18, %19, %20, %21, %22, %23, %24, %25, %26, %27, %28, %29, %30, %31}, {%32, %33, %34, %35}, %36, 1, 1, 1, 0;\n"
    : "+f"(d[0]), "+f"(d[1]), "+f"(d[2]), "+f"(d[3]), "+f"(d[4]), "+f"(d[5]), "+f"(d[6]), "+f"(d[7]), "+f"(d[8]), "+f"(d[9]), "+f"(d[10]), "+f"(d[11]), "+f"(d[12]), "+f"(d[13]), "+f"(d[14]), "+f"(d[15]), "+f"(d[16]), "+f"(d[17]), "+f"(d[18]), "+f"(d[19]), "+f"(d[20]), "+f"(d[21]), "+f"(d[22]), "+f"(d[23]), "+f"(d[24]), "+f"(d[25]), "+f"(d[26]), "+f"(d[27]), "+f"(d[28]), "+f"(d[29]), "+f"(d[30]), "+f"(d[31])
    : "r"(a0), "r"(a1), "r"(a2), "r"(a3), "l"(db));
  else asm volatile("wgmma.mma_async.sync.aligned.m64n64k16.f32.bf16.bf16 {%0, %1, %2, %3, %4, %5, %6, %7, %8, %9, %10, %11, %12, %13, %14, %15, %16, %17, %18, %19, %20, %21, %22, %23, %24, %25, %26, %27, %28, %29, %30, %31}, {%32, %33, %34, %35}, %36, 0, 1, 1, 0;\n"
    : "=f"(d[0]), "=f"(d[1]), "=f"(d[2]), "=f"(d[3]), "=f"(d[4]), "=f"(d[5]), "=f"(d[6]), "=f"(d[7]), "=f"(d[8]), "=f"(d[9]), "=f"(d[10]), "=f"(d[11]), "=f"(d[12]), "=f"(d[13]), "=f"(d[14]), "=f"(d[15]), "=f"(d[16]), "=f"(d[17]), "=f"(d[18]), "=f"(d[19]), "=f"(d[20]), "=f"(d[21]), "=f"(d[22]), "=f"(d[23]), "=f"(d[24]), "=f"(d[25]), "=f"(d[26]), "=f"(d[27]), "=f"(d[28]), "=f"(d[29]), "=f"(d[30]), "=f"(d[31])
    : "r"(a0), "r"(a1), "r"(a2), "r"(a3), "l"(db));
}
template <int SD> __device__ __forceinline__ void wgmma_rs_n32_tb1(float (&d)[16], uint32_t a0, uint32_t a1, uint32_t a2, uint32_t a3, uint64_t db) {
  if (SD) asm volatile("wgmma.mma_async.sync.aligned.m64n32k16.f32.bf16.bf16 {%0, %1, %2, %3, %4, %5, %6, %7, %8, %9, %10, %11, %12, %13, %14, %15}, {%16, %17, %18, %19}, %20, 1, 1, 1, 1;\n"
    : "+f"(d[0]), "+f"(d[1]), "+f"(d[2]), "+f"(d[3]), "+f"(d[4]), "+f"(d[5]), "+f"(d[6]), "+f"(d[7]), "+f"(d[8]), "+f"(d[9]), "+f"(d[10]), "+f"(d[11]), "+f"(d[12]), "+f"(d[13]), "+f"(d[14]), "+f"(d[15])
    : "r"(a0), "r"(a1), "r"(a2), "r"(a3), "l"(db));
  else asm volatile("wgmma.mma_async.sync.aligned.m64n32k16.f32.bf16.bf16 {%0, %1, %2, %3, %4, %5, %6, %7, %8, %9, %10, %11, %12, %13, %14, %15}, {%16, %17, %18, %19}, %20, 0, 1, 1, 1;\n"
    : "=f"(d[0]), "=f"(d[1]), "=f"(d[2]), "=f"(d[3]), "=f"(d[4]), "=f"(d[5]), "=f"(d[6]), "=f"(d[7]), "=f"(d[8]), "=f"(d[9]), "=f"(d[10]), "=f"(d[11]), "=f"(d[12]), "=f"(d[13]), "=f"(d[14]), "=f"(d[15])
    : "r"(a0), "r"(a1), "r"(a2), "r"(a3), "l"(db));
}


__device__ __forceinline__ uint32_t sw64_off(int row, int d) { return row * 64 + ((((d >> 3) ^ (row >> 1)) & 3) << 4) + (d & 7) * 2; }

__device__ __forceinline__ uint32_t exp2_pair_fma(float t0, float t1, uint32_t c_half, uint32_t c_3) {
  uint32_t y0, y;
  asm("prmt.b32 %0, %1, %2, 0x6521;" : "=r"(y0) : "r"(__float_as_uint(t0)), "r"(__float_as_uint(t1)));
  uint32_t h = lop_and_or(y0, 0x007F007Fu, c_half);
  uint32_t e = lop_and_or(y0, 0xFF80FF80u, c_3);
  asm("fma.rn.bf16x2 %0, %1, %2, %3;" : "=r"(y) : "r"(y0), "r"(h), "r"(e));
  return y;
}

__device__ __forceinline__ void feature_map(float (&p)[32], uint32_t rb, int lq) {
  const float L2E = 1.4426950408889634f;
  const bool tail_ok = lq < 2;
  float mx[4], mn[4], b[32], sa[4], sn[4];
#pragma unroll
  for (int g = 0; g < 4; g++) {
    const int o = 16 * (g >> 1) + 2 * (g & 1);
    if (!tail_ok) { p[o + 12] = p[o]; p[o + 13] = p[o]; }
    mx[g] = fmaxf(fmaxf(fmaxf(p[o], p[o + 1]), fmaxf(p[o + 4], p[o + 5])), fmaxf(fmaxf(p[o + 8], p[o + 9]), fmaxf(p[o + 12], p[o + 13])));
    mn[g] = fminf(fminf(fminf(p[o], p[o + 1]), fminf(p[o + 4], p[o + 5])), fminf(fminf(p[o + 8], p[o + 9]), fminf(p[o + 12], p[o + 13])));
  }
#pragma unroll
  for (int o = 1; o <= 2; o <<= 1)
#pragma unroll
    for (int g = 0; g < 4; g++) { mx[g] = fmaxf(mx[g], __shfl_xor_sync(~0u, mx[g], o)); mn[g] = fminf(mn[g], __shfl_xor_sync(~0u, mn[g], o)); }
#pragma unroll
  for (int g = 0; g < 4; g++) {
    const int o = 16 * (g >> 1) + 2 * (g & 1);
    const float cx = -mx[g] * L2E, cn = mn[g] * L2E;
#pragma unroll
    for (int i = 0; i < 8; i++) {
      const int k = o + 4 * (i >> 1) + (i & 1);
      b[k] = ex2f(fmaf(p[k], -L2E, cn));
      p[k] = ex2f(fmaf(p[k], L2E, cx));
    }
    if (!tail_ok) { p[o + 12] = p[o + 13] = b[o + 12] = b[o + 13] = 0.f; }
    sa[g] = ((p[o] + p[o + 1]) + (p[o + 4] + p[o + 5])) + ((p[o + 8] + p[o + 9]) + (p[o + 12] + p[o + 13]));
    sn[g] = ((b[o] + b[o + 1]) + (b[o + 4] + b[o + 5])) + ((b[o + 8] + b[o + 9]) + (b[o + 12] + b[o + 13]));
    sa[g] += __shfl_xor_sync(~0u, sa[g], 1); sn[g] += __shfl_xor_sync(~0u, sn[g], 1);
    sa[g] += __shfl_xor_sync(~0u, sa[g], 2); sn[g] += __shfl_xor_sync(~0u, sn[g], 2);
  }
#pragma unroll
  for (int g = 0; g < 4; g++) {
    const int o = 16 * (g >> 1) + 2 * (g & 1);
    const float ra = rcpf(sa[g]), rn = rcpf(sn[g]);
    const uint32_t off = (g >> 1) * 16384 + (g & 1) * 1024;
#pragma unroll
    for (int jj = 0; jj < 4; jj++) {
      st_shared_nv((rb ^ (jj << 4)) + off, pack_bf16(p[o + 4 * jj] * ra, p[o + 4 * jj + 1] * ra));
      st_shared_nv((rb ^ ((4 + jj) << 4)) + off, pack_bf16(b[o + 4 * jj] * rn, b[o + 4 * jj + 1] * rn));
    }
  }
}

__device__ __forceinline__ void store_heads(uint32_t base, const uint32_t (&a)[14], uint32_t pad0, uint32_t pad1, int row0, int lq) {
  const uint32_t rb = base + row0 * 64 + (((row0 >> 1) & 3) << 4);
  const uint32_t b0 = rb + lq * 4;
  const uint32_t b1 = (rb + 8192 + ((lq * 4 + 8) & 15)) ^ ((lq >> 1) << 4);
#pragma unroll
  for (int j = 0; j < 7; j++) {
    uint32_t ad;
    if (j < 3) ad = b0 ^ (j << 4);
    else if (j == 3) ad = (lq < 2) ? (b0 ^ 48u) : (b1 ^ 16u);
    else ad = (lq < 2) ? (b1 ^ ((j - 4) << 4)) : ((b1 ^ 16u) ^ ((j - 3) << 4));
    sts32(ad, a[2 * j]);
    sts32(ad + 512, a[2 * j + 1]);
  }
  sts64((rb ^ 48u) + 8 + (lq & 1) * 8192 + (lq >> 1) * 512, pad0, pad1);
}

struct Params {
  const __nv_bfloat16* w_phi;
  const __nv_bfloat16* wk;
  const __nv_bfloat16* wv;
  const __nv_bfloat16* gate_w;
};

__global__ void __launch_bounds__(NTHREADS, 1)
fused_kernel(const __grid_constant__ CUtensorMap tm_x, const __grid_constant__ CUtensorMap tm_wqkv,
             const __grid_constant__ CUtensorMap tm_wq, const __grid_constant__ CUtensorMap tm_woa,
             const __grid_constant__ CUtensorMap tm_wob, const __grid_constant__ CUtensorMap tm_out, const Params prm) {
  extern __shared__ uint8_t smem_raw[];
  uint32_t sb = (smem_u32(smem_raw) + 1023u) & ~1023u;
  uint8_t* sgen = smem_raw + (sb - smem_u32(smem_raw));
  asm volatile("mov.u32 %0, %0;" : "+r"(sb));
  const int tid = threadIdx.x, lane = tid & 31;
  const int warp = __shfl_sync(~0u, tid >> 5, 0), wg = warp >> 2;
  const int pt = blockIdx.x >> 3, hp = blockIdx.x & 7;
  const uint32_t bars = sb + OFF_BAR;
  auto BAR = [&](int i) { return bars + 8u * i; };
  const unsigned epoch = g_epoch & 1;

  auto load_proj = [&](int c, int g) {
    mbar_expect_tx(BAR(B_FULL + g), (c < 3 ? 16384 : 0) + 4 * 7168);
    if (c < 3) tma_2d(sb + OFF_X + c * 16384, &tm_x, c * 64, pt * 128, BAR(B_FULL + g));
    tma_2d(sb + OFF_RING + g * 32768, &tm_wq, hp * 56, c * 64, BAR(B_FULL + g));
#pragma unroll 1
    for (int j = 0; j < 3; j++) tma_2d(sb + OFF_RING + g * 32768 + 8192 + j * 8192, &tm_wqkv, j * DM + hp * 56, c * 64, BAR(B_FULL + g));
  };
  if (warp == 16) {
    if (elect_one()) {
      mbar_init(BAR(B_FULL), 1);
      fence_async_smem();
      load_proj(0, 0);
      mbar_init(BAR(B_RAW), 1); mbar_init(BAR(B_FULL + 1), 1); mbar_init(BAR(B_FULL + 2), 1);
      fence_async_smem();
    }
    __syncwarp();
    asm volatile("bar.arrive 0, %0;" ::"n"(NTHREADS) : "memory");
  } else {
    if (elect_one()) {
#pragma unroll 1
      for (int i = warp + 3 - (warp > 16); i < B_N; i += 19) {
        if (i == B_RAW) continue;
        int cnt = i < B_WO || (i > B_SIG && i < B_XL) || i == B_X1FREE ? 16 : 1;
        if (i == B_BUILD) cnt = 16;
        if (i == B_SIG || i == B_SIG + 1 || i == B_QSQ) cnt = 8;
        if (i == B_KVR) cnt = 2;
        mbar_init(BAR(i), cnt);
        fence_async_smem();
      }
    }
    bar_sync(0, NTHREADS);
  }

  if (wg == 4) {
    asm volatile("setmaxnreg.dec.sync.aligned.u32 32;");
    if (warp == 16) {
      if (elect_one()) {
        mbar_expect_tx(BAR(B_RAW), 25088 + 3136 + 896);
        bulk_g2s(sb + OFF_RAW, hp < 4 ? prm.wk : prm.wv, 25088, BAR(B_RAW));
        bulk_g2s(sb + OFF_RAW + 25088, prm.w_phi + 2 * hp * DH * DH, 3136, BAR(B_RAW));
        bulk_g2s(sb + OFF_RAW + 28224, prm.gate_w, 896, BAR(B_RAW));
        load_proj(1, 1);
        load_proj(2, 2);
      }
      __syncwarp();
      bar_sync(3, 64);
      if (elect_one()) {
        int g = 0, nkv = 8;
        uint32_t par = 0;
#pragma unroll 1
        for (int c = 3; c < 7; c++) {
          if (c == 5) mbar_wait(BAR(B_BUILD), 0);
          if (c & 1) mbar_expect_tx(BAR(B_XL + (c > 4)), 32768);
          tma_2d(sb + OFF_X + c * 16384, &tm_x, c * 64, pt * 128, BAR(B_XL + (c > 4)));
        }
        uint32_t todo = 15, rdy = 0;
#pragma unroll 1
        for (int n = 3; n < 15 + nkv; n++) {
          if (n == 7) { cnt_wait(C_KV, NCTA); fence_async_all(); }
          if (n == 15) {
            mbar_wait(BAR(B_SLOW), 0);
            if (*(volatile int*)(sgen + OFF_RED)) nkv = 26;
          }
          int j = n - 7 - nkv;
          if (j == 0) { cnt_wait(C_OA + pt, 8); fence_async_all(); }
          const bool last = j == 7;
          if (!last) mbar_wait(BAR(B_EMPTY + g), par);
          if (j >= 4) {
            uint32_t spin = 0;
#pragma unroll 1
            while (!rdy) {
              uint4 v;
              asm volatile("ld.acquire.gpu.global.v4.u32 {%0, %1, %2, %3}, [%4];"
                           : "=r"(v.x), "=r"(v.y), "=r"(v.z), "=r"(v.w) : "l"(&g_cnt[(C_OB + pt) * 32]) : "memory");
              rdy = ((v.x >= 2) | (v.y >= 2) << 1 | (v.z >= 2) << 2 | (v.w >= 2) << 3) & todo;
              if (++spin >= (1u << 16)) rdy = todo;
            }
            const int pick = __ffs(rdy) - 1;
            todo &= ~(1u << pick);
            rdy &= todo;
            ((volatile int*)(sgen + OFF_RED + 16))[j - 4] = pick;
            j = 4 + pick;
            fence_async_all();
          }
          if (n < 7) { load_proj(n, g); }
          else {
            const uint32_t fb = BAR(last ? B_RAW : B_FULL + g);
            mbar_expect_tx(fb, 32768);
            bulk_g2s(last ? sb + OFF_WO : sb + OFF_RING + g * 32768,
                     j < 0 ? g_kv_img + ((n - 7) & 7) * 32768 : g_o_img + (size_t)(pt * 8 + j) * 32768, 32768, fb);
          }
          if (++g == 3) { g = 0; par ^= 1; }
        }
        if (atomicAdd(&g_cnt[C_DONE * 32], 1u) == NCTA - 1) {
#pragma unroll 1
          for (int i = 0; i < C_N; i++) *(uint4*)&g_cnt[i * 32] = make_uint4(0u, 0u, 0u, 0u);
          g_epoch = epoch ^ 1;
        }
      }
    } else {
      if (warp == 18) {
        if (elect_one()) {
#pragma unroll 1
          for (int i = 0; i < 4; i++) {
            mbar_wait(BAR(B_SIG + i), 0);
            if (i == 1) {
#pragma unroll 1
              for (int j = 0; j < 4; j++)
                asm volatile("cp.reduce.async.bulk.global.shared::cta.bulk_group.add.f32 [%0], [%1], 8192;"
                             ::"l"(g_kvacc[epoch] + hp * 4096 + (j >> 1) * 2048), "r"(sb + OFF_PHIK + j * 8192) : "memory");
            }
            if (i >= 2)
              asm volatile("cp.async.bulk.global.shared::cta.bulk_group [%0], [%1], 16384;"
                           ::"l"(g_o_img + (size_t)(pt * 2 + i - 2) * 131072 + hp * 16384), "r"(sb + OFF_OSTG) : "memory");
            if (i >= 1) asm volatile("cp.async.bulk.commit_group;\ncp.async.bulk.wait_group 0;" ::: "memory");
            asm volatile("red.release.gpu.global.add.u32 [%0], 1;"
                         ::"l"(&g_cnt[(i == 0 ? C_KV : i == 1 ? C_PART : (i == 2 ? C_OA : C_OB) + pt) * 32 + (i == 3 ? hp >> 1 : 0)]) : "memory");
            if (i == 1 || i == 2) {
              if (i == 2) mbar_wait(BAR(B_X1FREE), 0);
              mbar_expect_tx(BAR(B_WO + i - 1), 7 * 7168);
#pragma unroll 1
              for (int c = 0; c < 7; c++)
                tma_2d(sb + OFF_WO + (i - 1) * 57344 + c * 8192, i == 1 ? &tm_woa : &tm_wob, hp * 56, c * 64, BAR(B_WO + i - 1));
            }
          }
        }
      } else if (warp == 19) {
        if (lane == 0) {
          mbar_wait(BAR(B_SIG + 0), 0);
          cnt_wait(C_KV, NCTA);
        }
        __syncwarp();
        float ksq = 0.f, vsq = 0.f;
#pragma unroll
        for (int sl = 0; sl < 4; sl++) {
          float4 a = ldcg_f4(g_ksq + sl * 128 + lane * 4), b = ldcg_f4(g_vsq + sl * 128 + lane * 4);
          float m = fmaxf(fmaxf(a.x, a.y), fmaxf(a.z, a.w));
          m = __uint_as_float(__reduce_max_sync(~0u, __float_as_uint(m)));
          ksq += m;
          vsq = fmaxf(vsq, fmaxf(fmaxf(b.x, b.y), fmaxf(b.z, b.w)));
        }
        mbar_wait(BAR(B_QSQ), 0);
        const float4 qa4 = ((const float4*)(sgen + OFF_QSQ))[lane], qb4 = ((const float4*)(sgen + OFF_QSQ))[32 + lane];
        const float qmax = fmaxf(fmaxf(fmaxf(qa4.x, qa4.y), fmaxf(qa4.z, qa4.w)), fmaxf(fmaxf(qb4.x, qb4.y), fmaxf(qb4.z, qb4.w)));
        const bool slow = __any_sync(~0u, !(qmax * ksq <= 98.f * 98.f) || !(vsq <= 2.0e8f));
        if (lane == 0) {
          *(volatile int*)(sgen + OFF_RED) = slow;
          mbar_arrive(BAR(B_SLOW), 1);
        }
      } else {
        float4* z = (float4*)(g_kvacc[epoch ^ 1] + blockIdx.x * 256) + lane;
        z[0] = make_float4(0.f, 0.f, 0.f, 0.f);
        z[32] = make_float4(0.f, 0.f, 0.f, 0.f);
        bar_sync(3, 64);
        mbar_wait(BAR(B_BUILD), 0);
#pragma unroll 1
        for (int c = 3; c < 7; c++) {
          mbar_wait(BAR(B_EMPTY + c % 3), (c / 3 - 1) & 1);
#pragma unroll
          for (int h = 0; h < 2; h++) {
            const int r = lane + 32 * h;
            sts128(sb + OFF_RING + (c % 3) * 32768 + 16384 + r * 128 + ((7 ^ (r & 7)) << 4), *(const uint4*)(sgen + OFF_SLC + c * 1024 + r * 16));
          }
          fence_async_smem();
          __syncwarp();
          if (lane == 0) mbar_arrive(BAR(B_SLJ + c - 3), 1);
        }
        if (lane == 0) {
          mbar_wait(BAR(B_SIG + 0), 0);
          cnt_wait(C_KV, NCTA);
        }
        __syncwarp();
        ((float4*)(sgen + OFF_GATE))[lane] = ldcg_f4(g_gate + pt * 128 + lane * 4);
      }
      if (warp != 18) {
        if (lane == 0) {
          mbar_wait(BAR(B_SIG + 1), 0);
          cnt_wait(C_PART, NCTA);
        }
        __syncwarp();
        const int e = warp == 19;
        const float* src = g_kvacc[epoch] + hp * 4096 + e * 2048 + (lane ^ ((lane >> 2) & 3)) * 8;
#pragma unroll 1
        for (int i = 0; i < 8; i += 2) {
          const float4 a = ldcg_f4(src + i * 256), b = ldcg_f4(src + i * 256 + 4), c = ldcg_f4(src + i * 256 + 256), d = ldcg_f4(src + i * 256 + 260);
          const uint32_t ad = sb + OFF_KVR + e * 4096 + sw64_off(i * 8 + (lane >> 2), (lane & 3) * 8);
          sts128(ad, make_uint4(pack_bf16(a.x, a.y), pack_bf16(a.z, a.w), pack_bf16(b.x, b.y), pack_bf16(b.z, b.w)));
          sts128(ad + 512, make_uint4(pack_bf16(c.x, c.y), pack_bf16(c.z, c.w), pack_bf16(d.x, d.y), pack_bf16(d.z, d.w)));
        }
        fence_async_smem();
        __syncwarp();
        if (lane == 0) mbar_arrive(BAR(B_KVR), 1);
      }
    }
  } else {
    asm volatile("setmaxnreg.inc.sync.aligned.u32 112;");
    const int mh = wg & 1, nh = wg >> 1, wq = warp & 3;
    const int lq = lane & 3;
    const int rowl = wq * 16 + (lane >> 2);
    const int row0 = mh * 64 + rowl;
    int slot = 0;
    uint32_t par = 0;
    {
      float acc0[32], acc1[28], accs[4];
      const uint64_t dR = make_desc(sb + OFF_RING + nh * 16384, 1024, 1024, 1);
      const uint64_t dX = make_desc(sb + OFF_X + mh * 8192, 1024, 1024, 1);
#pragma unroll
      for (int i = 0; i < 28; i++) acc0[i] = acc1[i] = 0.f;
#pragma unroll
      for (int i = 28; i < 32; i++) acc0[i] = 0.f;
      const uint64_t dSlc = make_desc(sb + OFF_SLC, 128, 128, 0);
#pragma unroll 1
      for (int c = 0; c < 7; c++) {
        if (c == 3 || c == 5) mbar_wait(BAR(B_XL + (c > 4)), 0);
        mbar_wait(BAR(B_FULL + slot), par);
        if (nh == 1 && c >= 3) mbar_wait(BAR(B_SLJ + c - 3), 0);
        const uint64_t dA = dX + c * 1024, dB = dR + slot * 2048;
        wg_fence();
#pragma unroll
        for (int ks = 0; ks < 4; ks++) {
          wgmma_ss_n64_ta0_tb1<1>(acc0, dA + ks * 2, dB + ks * 128);
          wgmma_ss_n56_ta0_tb1<1>(acc1, dA + ks * 2, dB + 512 + ks * 128);
        }
        wg_commit();
        if (c == 0) {
          mbar_wait(BAR(B_RAW), 0);
          const int k = tid >> 3, cn = tid & 7;
          const bool data = k < 56 && (cn >> 2) == (k >= DH);
          const uint2* wsrc = (const uint2*)(sgen + OFF_RAW + 25088 + k * 56 + (cn & 3) * 16);
          uint2 w0 = make_uint2(0u, 0u), w1 = w0;
          if (data) w0 = wsrc[0];
          if (data && (cn & 3) != 3) w1 = wsrc[1];
          sts128(sb + OFF_WBD + k * 128 + ((cn ^ (k & 7)) << 4), make_uint4(w0.x, w0.y, w1.x, w1.y));
          if (tid < DM) {
            const uint2* src = (const uint2*)(sgen + OFF_RAW + tid * 56 + (hp & 3) * 16);
            w0 = src[0];
            w1 = make_uint2(hp == 3 ? (uint32_t)((const unsigned short*)(sgen + OFF_RAW + 28224))[tid] : 0u, 0u);
            if ((hp & 3) != 3) w1 = src[1];
            const int cc = tid >> 6, r = tid & 63;
            sts128(cc == 1 || cc == 2 ? sb + OFF_RING + cc * 32768 + 16384 + r * 128 + ((7 ^ (r & 7)) << 4) : sb + OFF_SLC + tid * 16,
                   make_uint4(w0.x, w0.y, w1.x, w1.y));
          }
          fence_async_smem();
          __syncwarp();
          if (lane == 0) mbar_arrive(BAR(B_BUILD), 1);
          mbar_wait(BAR(B_BUILD), 0);
        }
        wg_wait<0>();
        if (lane == 0) mbar_arrive(BAR(B_EMPTY + slot), 1);
        if (c == 0) {
          fence_regs(acc0);
          acc0[28] = acc0[29] = acc0[30] = acc0[31] = 0.f;
        }
        if (++slot == 3) { slot = 0; par ^= 1; }
      }
      if (nh == 1) {
        wg_fence();
        wgmma_ss_n8_ta0_tb1<0>(accs, dX, dSlc);
#pragma unroll
        for (int ks = 1; ks < 4; ks++) wgmma_ss_n8_ta0_tb1<1>(accs, dX + ks * 2, dSlc + ks * 16);
        wg_commit();
      }
      wg_wait<0>();
      fence_regs(acc0); fence_regs(acc1); fence_regs(accs);
      if (nh == 0) {
        float sq[4] = {0.f, 0.f, 0.f, 0.f};
#pragma unroll
        for (int i = 0; i < 28; i++) acc0[i] *= 0.18898223650461362f * 1.4426950408889634f;
#pragma unroll
        for (int j = 0; j < 7; j++) {
#pragma unroll
          for (int rr = 0; rr < 2; rr++) {
            const float s2 = acc0[4 * j + 2 * rr] * acc0[4 * j + 2 * rr] + acc0[4 * j + 2 * rr + 1] * acc0[4 * j + 2 * rr + 1];
            if (j < 3) sq[rr] += s2;
            else if (j > 3) sq[2 + rr] += s2;
            else { sq[rr] += (lq < 2) ? s2 : 0.f; sq[2 + rr] += (lq < 2) ? 0.f : s2; }
          }
        }
#pragma unroll
        for (int i = 0; i < 4; i++) sq[i] = quad_sum(sq[i]);
        const float mine = lq == 0 ? sq[0] : lq == 1 ? sq[1] : lq == 2 ? sq[2] : sq[3];
        ((float*)(sgen + OFF_QSQ))[(mh + (lq & 2)) * 64 + rowl + 8 * (lq & 1)] = mine <= 3.0e38f ? mine : __int_as_float(0x7f800000);
        __syncwarp();
        if (lane == 0) mbar_arrive(BAR(B_QSQ), 1);
      } else {
        const int sl = hp & 3;
        const bool isk = hp < 4, real = (sl < 3) || (lq < 2);
        const int pos = pt * 128 + row0, kr = pos & 63;
        uint8_t* dst = g_kv_img + (pos >> 6) * 8192 + (isk ? 0 : 4096) + sw64_off(kr, sl * 8 + 2 * lq);
        const uint32_t pat = isk ? POLY_PAT >> (kr >> 3) : 0u;
        float mxv = 0.f;
#pragma unroll
        for (int rr = 0; rr < 2; rr++) {
          const float v0 = accs[2 * rr] + acc0[28 + 2 * rr], v1 = accs[2 * rr + 1] + acc0[29 + 2 * rr];
          const bool poly = (pat >> rr) & 1;
          const float sc = poly ? 2.f : 1.f;
          const float s2 = quad_sum(real ? v0 * v0 + v1 * v1 : 0.f);
          mxv = fmaxf(mxv, s2 <= 3.0e38f ? s2 : __int_as_float(0x7f800000));
          const uint32_t padv = lq == 2 ? (poly ? 0x443F4000u : 0x00003F80u) : (poly ? 0x3AB03F4Du : 0u);
          *(uint32_t*)(dst + rr * 512) = real ? pack_bf16(sc * v0, sc * v1) : padv;
          if (hp == 3 && lq == 2) g_gate[pos + 8 * rr] = rcpf(1.f + ex2f(-1.4426950408889634f * v0));
        }
        mxv = __uint_as_float(__reduce_max_sync(~0u, __float_as_uint(mxv)));
        if (lane == 0) (isk ? g_ksq : g_vsq)[sl * 128 + pt * 8 + mh * 4 + wq] = mxv;
        __syncwarp();
        if (lane == 0) mbar_arrive(BAR(B_SIG + 0), 1);
      }
      uint32_t h[14];
      float pp[32];
      {
        uint32_t a[16];
#pragma unroll
        for (int i = 0; i < 14; i++) {
          const uint32_t u0 = pack_bf16(acc0[2 * i], acc0[2 * i + 1]), u1 = pack_bf16(acc1[2 * i], acc1[2 * i + 1]);
          h[i] = nh ? u1 : u0;
          a[i] = nh ? u0 : u1;
        }
        a[14] = a[0] ^ 0x80008000u;
        a[15] = a[1] ^ 0x80008000u;
        const uint64_t dW = make_desc(sb + OFF_WBD, 1024, 1024, 1);
        wg_fence();
        wgmma_rs_n64_tb1<0>(pp, a[0], a[1], a[2], a[3], dW);
#pragma unroll
        for (int ks = 1; ks < 4; ks++) wgmma_rs_n64_tb1<1>(pp, a[4 * ks], a[4 * ks + 1], a[4 * ks + 2], a[4 * ks + 3], dW + ks * 128);
        wg_commit();
        bar_sync(1, 512);
        store_heads(sb + (nh ? OFF_VA : OFF_QP), h, nh ? 0x00003F80u : 0x3F800000u, nh ? 0u : 0x3F803F80u, row0, lq);
        wg_wait<0>();
        fence_regs(pp);
      }
      feature_map(pp, sb + (nh ? OFF_PHIK : OFF_PHIQ) + row0 * 128 + lq * 4 + ((rowl & 7) << 4), lq);
      fence_async_smem();
      bar_sync(1, 512);
      if (nh == 1) {
        float kv0[16], kv1[16];
        const uint64_t dP = make_desc(sb + OFF_PHIK + mh * 8192, 1024, 1024, 1);
        const uint64_t dV = make_desc(sb + OFF_VA + mh * 4096, 512, 512, 2);
        wg_fence();
        wgmma_ss_n32_ta1_tb1<0>(kv0, dP, dV);
        wgmma_ss_n32_ta1_tb1<0>(kv1, dP + 1024, dV + 512);
#pragma unroll
        for (int ks = 1; ks < 4; ks++) {
          wgmma_ss_n32_ta1_tb1<1>(kv0, dP + ks * 128, dV + ks * 64);
          wgmma_ss_n32_ta1_tb1<1>(kv1, dP + 1024 + ks * 128, dV + 512 + ks * 64);
        }
        wg_commit();
        wg_wait<0>();
        fence_regs(kv0); fence_regs(kv1);
        bar_sync(4 + wg, 128);
        const uint32_t sa = sb + OFF_PHIK + mh * 8192 + rowl * 128 + lq * 8 + (rowl & 3) * 32;
#pragma unroll
        for (int j = 0; j < 8; j++) {
          sts64((sa ^ (32 * (j >> 1))) + 1024 * (j & 1), __float_as_uint(kv0[2 * j]), __float_as_uint(kv0[2 * j + 1]));
          sts64((sa ^ (32 * (j >> 1))) + 16384 + 1024 * (j & 1), __float_as_uint(kv1[2 * j]), __float_as_uint(kv1[2 * j + 1]));
        }
        fence_async_smem();
        __syncwarp();
        if (lane == 0) mbar_arrive(BAR(B_SIG + 1), 1);
      }
    }
    {
      const uint64_t dK = make_desc(sb + OFF_RING, 512, 512, 2);
      const uint64_t dhi = dK & 0xffffffff00000000ull;
      const uint32_t dlo0 = (uint32_t)dK;
      uint32_t ok = 0, fin = 0, q[8];
      float o[16];
#pragma unroll
      for (int i = 0; i < 16; i++) o[i] = 0.f;
      {
        const int r = mh * 64 + wq * 16 + (lane & 7) + ((lane >> 3) & 1) * 8;
        ldsm4(q, sb + OFF_QP + nh * 8192 + sw64_off(r, (lane >> 4) * 8));
        ldsm4(q + 4, sb + OFF_QP + nh * 8192 + sw64_off(r, 16 + (lane >> 4) * 8));
      }
      const int qb = QB_AT;
      float s[32];
      mbar_wait(BAR(B_FULL + slot), par);
      wg_fence();
      wgmma_rs_n64_tb0<0>(s, q[0], q[1], q[2], q[3], dhi | (dlo0 + slot * 2048));
      wgmma_rs_n64_tb0<1>(s, q[4], q[5], q[6], q[7], dhi | (dlo0 + slot * 2048 + 2));
      wg_commit();
      wg_wait<0>();
      fence_regs(s);
#pragma unroll 1
      for (int it = 0; it <= 8; it++) {
        uint32_t p[16];
        if (it == qb || it == 8) {
          float t[16];
          if (it < 8) {
            mbar_wait(BAR(B_KVR), 0);
            const uint64_t dR = make_desc(sb + OFF_KVR + nh * 4096, 512, 512, 2);
            const uint64_t dP = make_desc(sb + OFF_PHIQ + nh * 16384 + mh * 8192, 1024, 1024, 1);
            wg_fence();
            wgmma_ss_n32_ta0_tb1<0>(t, dP, dR);
#pragma unroll
            for (int ks = 1; ks < 4; ks++) wgmma_ss_n32_ta0_tb1<1>(t, dP + ks * 2, dR + ks * 64);
            wg_commit();
            wg_wait<0>();
            fence_regs(t);
            if (lane == 0) mbar_arrive(BAR(B_X1FREE), 1);
          } else {
            if (!fin) { mbar_wait(BAR(B_SLOW), 0); mbar_wait(BAR(B_WO + 1), 0); }
            if (__builtin_expect(__any_sync(~0u, *(volatile int*)(sgen + OFF_RED)), 0)) {
              uint32_t qz[8];
#pragma unroll
              for (int i = 0; i < 8; i++) qz[i] = (i >= 6 && lq >= 2) ? 0u : q[i];
              float m0 = -3.0e38f, m1 = -3.0e38f, o2[16];
              int sl2 = slot;
              uint32_t par2 = par;
#pragma unroll 1
              for (int j64 = 0; j64 < 32; j64++) {
                float s[32];
                mbar_wait(BAR(B_FULL + sl2), par2);
                const uint32_t lo = dlo0 + sl2 * 2048 + (j64 & 3) * 512;
                wg_fence();
                wgmma_rs_n64_tb0<0>(s, qz[0], qz[1], qz[2], qz[3], dhi | lo);
                wgmma_rs_n64_tb0<1>(s, qz[4], qz[5], qz[6], qz[7], dhi | (lo + 2));
                wg_commit();
                wg_wait<0>();
                fence_regs(s);
#pragma unroll
                for (int j = 0; j < 8; j++) {
                  const float sc = ((POLY_PAT >> j) & 1) ? 0.5f : 1.f;
                  m0 = fmaxf(m0, fmaxf(s[4 * j], s[4 * j + 1]) * sc);
                  m1 = fmaxf(m1, fmaxf(s[4 * j + 2], s[4 * j + 3]) * sc);
                }
                if ((j64 & 3) == 3) {
                  if (lane == 0) mbar_arrive(BAR(B_EMPTY + sl2), 1);
                  if (++sl2 == 3) { sl2 = 0; par2 ^= 1; }
                }
              }
              m0 = quad_max(m0); m1 = quad_max(m1);
#pragma unroll
              for (int i = 0; i < 16; i++) o2[i] = 0.f;
#pragma unroll 1
              for (int j64 = 0; j64 < 32; j64++) {
                float s[32];
                mbar_wait(BAR(B_FULL + sl2), par2);
                const uint32_t lo = dlo0 + sl2 * 2048 + (j64 & 3) * 512;
                wg_fence();
                wgmma_rs_n64_tb0<0>(s, qz[0], qz[1], qz[2], qz[3], dhi | lo);
                wgmma_rs_n64_tb0<1>(s, qz[4], qz[5], qz[6], qz[7], dhi | (lo + 2));
                wg_commit();
                wg_wait<0>();
                fence_regs(s);
                uint32_t ps[16];
#pragma unroll
                for (int j = 0; j < 8; j++) {
                  const float sc = ((POLY_PAT >> j) & 1) ? 0.5f : 1.f;
                  ps[2 * j] = pack_bf16(ex2f(fmaf(s[4 * j], sc, -m0)), ex2f(fmaf(s[4 * j + 1], sc, -m0)));
                  ps[2 * j + 1] = pack_bf16(ex2f(fmaf(s[4 * j + 2], sc, -m1)), ex2f(fmaf(s[4 * j + 3], sc, -m1)));
                }
                wg_fence();
#pragma unroll
                for (int ks = 0; ks < 4; ks++)
                  wgmma_rs_n32_tb1<1>(o2, ps[4 * ks], ps[4 * ks + 1], ps[4 * ks + 2], ps[4 * ks + 3], dhi | (lo + 256 + ks * 64));
                wg_commit();
                wg_wait<0>();
                fence_regs(o2);
                if ((j64 & 3) == 3) {
                  if (lane == 0) mbar_arrive(BAR(B_EMPTY + sl2), 1);
                  if (++sl2 == 3) { sl2 = 0; par2 ^= 1; }
                }
              }
#pragma unroll 1
              for (int j = 0; j < 2; j++) {
                mbar_wait(BAR(B_FULL + sl2), par2);
                __syncwarp();
                if (lane == 0) mbar_arrive(BAR(B_EMPTY + sl2), 1);
                if (++sl2 == 3) { sl2 = 0; par2 ^= 1; }
              }
#pragma unroll
              for (int i = 0; i < 16; i++) o[i] = o2[i];
            }
#pragma unroll
            for (int i = 0; i < 16; i++) t[i] = o[i];
#pragma unroll
            for (int i = 0; i < 32; i++) s[i] = 0.f;
          }
          const int br = it == 8;
          const float eps = br ? 0.f : 1e-6f;
          const float g0 = ((const float*)(sgen + OFF_GATE))[row0], g1 = ((const float*)(sgen + OFF_GATE))[row0 + 8];
          const float d0 = __shfl_sync(~0u, t[12], (lane & ~3) | 2), d1 = __shfl_sync(~0u, t[14], (lane & ~3) | 2);
          const float r0 = (br ? 1.f - g0 : g0) * rcpf(d0 + eps), r1 = (br ? 1.f - g1 : g1) * rcpf(d1 + eps);
          const uint32_t oa = sb + OFF_OSTG + (nh * 2 + mh) * 4096 + sw64_off(rowl, 2 * lq);
#pragma unroll
          for (int j = 0; j < 4; j++) {
            const bool real = j < 3 || lq < 2;
            sts32(oa ^ (j << 4), real ? pack_bf16(t[4 * j] * r0, t[4 * j + 1] * r0) : 0u);
            sts32((oa ^ (j << 4)) + 512, real ? pack_bf16(t[4 * j + 2] * r1, t[4 * j + 3] * r1) : 0u);
          }
          fence_async_smem();
          __syncwarp();
          if (lane == 0) mbar_arrive(BAR(B_SIG + 2 + br), 1);
          if (br) break;
        }
        const uint32_t lo = dlo0 + slot * 2048;
        int nslot = slot + 1;
        uint32_t npar = par;
        if (nslot == 3) { nslot = 0; npar ^= 1; }
#pragma unroll
        for (int u = 0; u < 4; u++) {
          if (u == 1) fin = mbar_test(BAR(B_SLOW), 0) & mbar_test(BAR(B_WO + 1), 0);
          if (u == 2) ok = mbar_test(BAR(B_FULL + nslot), npar);
#pragma unroll
          for (int j = 0; j < 8; j++) {
            if ((POLY_PAT >> j) & 1) {
              p[2 * j] = exp2_pair_fma(s[4 * j], s[4 * j + 1], 0x3F003F00u, 0x00030003u);
              p[2 * j + 1] = exp2_pair_fma(s[4 * j + 2], s[4 * j + 3], 0x3F003F00u, 0x00030003u);
            } else {
              p[2 * j] = pack_bf16(ex2f(s[4 * j]), ex2f(s[4 * j + 1]));
              p[2 * j + 1] = pack_bf16(ex2f(s[4 * j + 2]), ex2f(s[4 * j + 3]));
            }
          }
          if (u == 3 && !ok && it < 7) mbar_wait(BAR(B_FULL + nslot), npar);
          const uint32_t ln = u < 3 ? lo + (u + 1) * 512 : dlo0 + nslot * 2048;
          wg_fence();
#pragma unroll
          for (int ks = 0; ks < 4; ks++)
            wgmma_rs_n32_tb1<1>(o, p[4 * ks], p[4 * ks + 1], p[4 * ks + 2], p[4 * ks + 3], dhi | (lo + u * 512 + 256 + ks * 64));
          wgmma_rs_n64_tb0<0>(s, q[0], q[1], q[2], q[3], dhi | ln);
          wgmma_rs_n64_tb0<1>(s, q[4], q[5], q[6], q[7], dhi | (ln + 2));
          wg_commit();
          wg_wait<0>();
          fence_regs(s);
          fence_regs(o);
        }
        if (lane == 0) mbar_arrive(BAR(B_EMPTY + slot), 1);
        slot = nslot; par = npar;
      }
      wg_wait<0>();
    }
    if (nh == 1) return;
    {
      float acc[28];
#pragma unroll
      for (int i = 0; i < 28; i++) acc[i] = 0.f;
      const uint64_t dS = make_desc(sb + OFF_WO, 1024, 1024, 1);
      const uint64_t dR = make_desc(sb + OFF_RING + mh * 4096, 512, 512, 2);
#pragma unroll 1
      for (int c = 0; c < 8; c++) {
        mbar_wait(BAR(B_WO + (c >> 2)), 0);
        mbar_wait(BAR(c == 7 ? B_RAW : B_FULL + slot), c == 7 ? 1 : par);
        const int id = c < 4 ? c : 4 + __shfl_sync(~0u, ((volatile int*)(sgen + OFF_RED + 16))[c & 3], 0);
        const uint64_t dA = c == 7 ? dR - (OFF_RING - OFF_WO) / 16 : dR + slot * 2048, dB = dS + id * 896;
        wg_fence();
#pragma unroll
        for (int h = 0; h < 4; h++) {
          wgmma_ss_n56_ta0_tb1<1>(acc, dA + h * 512, dB + h * 224);
          wgmma_ss_n56_ta0_tb1<1>(acc, dA + h * 512 + 2, dB + h * 224 + 128);
        }
        wg_commit();
        if (c < 4) {
          wg_wait<0>();
          if (lane == 0) mbar_arrive(BAR(B_EMPTY + slot), 2);
        }
        if (++slot == 3) { slot = 0; par ^= 1; }
      }
      wg_wait<0>();
      fence_regs(acc);
      const uint32_t oa = sb + OFF_OSTG + mh * 8192 + rowl * 128 + lq * 4 + ((rowl & 7) << 4);
#pragma unroll
      for (int j = 0; j < 7; j++) {
        sts32(oa ^ (j << 4), pack_bf16(acc[4 * j], acc[4 * j + 1]));
        sts32((oa ^ (j << 4)) + 1024, pack_bf16(acc[4 * j + 2], acc[4 * j + 3]));
      }
      fence_async_smem();
      bar_sync(4 + wg, 128);
      if (wq == 0 && elect_one()) {
        asm volatile("cp.async.bulk.tensor.2d.global.shared::cta.bulk_group [%0, {%2, %3}], [%1];"
                     ::"l"(&tm_out), "r"(sb + OFF_OSTG + mh * 8192), "r"(hp * 56), "r"(pt * 128 + mh * 64) : "memory");
        asm volatile("cp.async.bulk.commit_group;\ncp.async.bulk.wait_group.read 0;" ::: "memory");
      }
    }
  }
}

typedef CUresult (*EncodeFn)(CUtensorMap*, CUtensorMapDataType, cuuint32_t, void*, const cuuint64_t*, const cuuint64_t*,
                             const cuuint32_t*, const cuuint32_t*, CUtensorMapInterleave, CUtensorMapSwizzle,
                             CUtensorMapL2promotion, CUtensorMapFloatOOBfill);

void make_map(EncodeFn enc, CUtensorMap* tm, const void* ptr, uint64_t cols, uint64_t rows, uint32_t box_cols, uint32_t box_rows) {
  cuuint64_t dims[2] = {cols, rows};
  cuuint64_t strides[1] = {cols * 2};
  cuuint32_t box[2] = {box_cols, box_rows};
  cuuint32_t es[2] = {1, 1};
  enc(tm, CU_TENSOR_MAP_DATA_TYPE_BFLOAT16, 2, const_cast<void*>(ptr), dims, strides, box, es, CU_TENSOR_MAP_INTERLEAVE_NONE,
      CU_TENSOR_MAP_SWIZZLE_128B, CU_TENSOR_MAP_L2_PROMOTION_L2_128B, CU_TENSOR_MAP_FLOAT_OOB_FILL_NONE);
}

}

extern "C" void kernel_launch(void* const* d_in, const int* in_sizes, int n_in, void* d_out, int out_size) {
  (void)in_sizes; (void)n_in; (void)out_size;
  static EncodeFn enc = nullptr;
  if (!enc) {
    void* fn = nullptr;
    cudaDriverEntryPointQueryResult qr;
    cudaGetDriverEntryPoint("cuTensorMapEncodeTiled", &fn, cudaEnableDefault, &qr);
    enc = (EncodeFn)fn;
    cudaFuncSetAttribute(fused_kernel, cudaFuncAttributeMaxDynamicSharedMemorySize, SMEM_BYTES);
  }
  CUtensorMap tm_x, tm_wqkv, tm_wq, tm_woa, tm_wob, tm_out;
  make_map(enc, &tm_out, d_out, DM, S_LEN, 56, 64);
  make_map(enc, &tm_x, d_in[0], DM, S_LEN, 64, 128);
  make_map(enc, &tm_wqkv, d_in[1], 3 * DM, DM, 56, 64);
  make_map(enc, &tm_wq, d_in[5], DM, DM, 56, 64);
  make_map(enc, &tm_woa, d_in[3], DM, DM, 56, 64);
  make_map(enc, &tm_wob, d_in[8], DM, DM, 56, 64);
  Params prm;
  prm.w_phi = (const __nv_bfloat16*)d_in[2];
  prm.wk = (const __nv_bfloat16*)d_in[6];
  prm.wv = (const __nv_bfloat16*)d_in[7];
  prm.gate_w = (const __nv_bfloat16*)d_in[9];
  fused_kernel<<<NCTA, NTHREADS, SMEM_BYTES>>>(tm_x, tm_wqkv, tm_wq, tm_woa, tm_wob, tm_out, prm);
}
```
